```python
import torch

def _softmax(x, axis=-1):
    return torch.softmax(x, dim=axis)
def _gelu(x):
    return torch.nn.functional.gelu(x, approximate="tanh")
def _silu(x):
    return torch.nn.functional.silu(x)
def _sigmoid(x):
    return torch.sigmoid(x)
def _layernorm(x, axis=-1, eps=1e-5):
    m = x.mean(dim=axis, keepdim=True)
    v = x.var(dim=axis, keepdim=True, unbiased=False)
    return (x - m) / torch.sqrt(v + eps)
def _scatter_add(tgt, idx, src, axis=0):
    return tgt.clone().index_add_(axis, idx, src)
def _segment_sum(src, seg, n):
    out = torch.zeros((n,) + src.shape[1:], dtype=src.dtype)
    return out.index_add_(0, seg, src)
def _pad(x, pw):
    flat = tuple(v for pair in reversed(pw) for v in pair)
    return torch.nn.functional.pad(x, flat)

kernel_name = 'parallel_sum__compressed_kv_cla__moe_arch_mod__prompt'

def setup_inputs():

    _w = (lambda a: (lambda t: t.to(torch.bfloat16) if t.is_floating_point() else t)(torch.as_tensor(a)))
    def _A_setup():
        B, H, Sq, Sk, D, M = 1, 32, 2048, 2048, 128, 640
        Dc = 4 * D
        return {
            "x": _w((lambda *s: torch.randn(*s, dtype=torch.bfloat16) * 0.05)(B, Sq, M)),
            "c_kv": _w((lambda *s: torch.randn(*s, dtype=torch.bfloat16) * 1.6)(B, Sk, Dc)),
            "w_q": _w((lambda *s: torch.randn(*s, dtype=torch.bfloat16) * 0.8)(M, H, D) * (M ** -0.5)),
            "w_uk": _w((lambda *s: torch.randn(*s, dtype=torch.bfloat16) * 0.8)(Dc, H, D) * (Dc ** -0.5)),
            "w_uv": _w((lambda *s: torch.randn(*s, dtype=torch.bfloat16) * 1.6)(Dc, H, D) * (Dc ** -0.5)),
            "w_o": _w((lambda *s: torch.randn(*s, dtype=torch.bfloat16) * 1.6)(H, D, M) * ((H * D) ** -0.5)),
        }
    _A_in = _A_setup()

    def _B_setup():
        B, S, D, F, C = 1, 2048, 640, 1728, 8
        return {
            "x": _w((lambda *s: torch.randn(*s, dtype=torch.bfloat16) * 0.05)(B, S, D)),
            "w_r": _w((lambda *s: torch.randn(*s, dtype=torch.bfloat16) * 0.05)(D)),
            "w_gate": _w((lambda *s: torch.randn(*s, dtype=torch.bfloat16) * 0.05)(D, F)),
            "w_up": _w((lambda *s: torch.randn(*s, dtype=torch.bfloat16) * 0.05)(D, F)),
            "w_down": _w((lambda *s: torch.randn(*s, dtype=torch.bfloat16) * 0.05)(F, D)),
        }
    _B_in = _B_setup()

    return {
        "A_x": _A_in["x"],
        "A_c_kv": _A_in["c_kv"],
        "A_w_q": _A_in["w_q"],
        "A_w_uk": _A_in["w_uk"],
        "A_w_uv": _A_in["w_uv"],
        "A_w_o": _A_in["w_o"],
        "B_x": _B_in["x"],
        "B_w_r": _B_in["w_r"],
        "B_w_gate": _B_in["w_gate"],
        "B_w_up": _B_in["w_up"],
        "B_w_down": _B_in["w_down"],
    }

def reference(A_x, A_c_kv, A_w_q, A_w_uk, A_w_uv, A_w_o, B_x, B_w_r, B_w_gate, B_w_up, B_w_down):
    def _A_ref(x, c_kv, w_q, w_uk, w_uv, w_o):
        B, Sq, M = x.shape[0], x.shape[1], x.shape[2]
        Sk = c_kv.shape[1]
        H, D = w_q.shape[1], w_q.shape[2]
        q = torch.einsum("bqm,mhd->bhqd", x, w_q)
        k = torch.einsum("bkc,chd->bhkd", c_kv, w_uk)
        v = torch.einsum("bkc,chd->bhkd", c_kv, w_uv)
        scores = torch.einsum("bhqd,bhkd->bhqk", q, k) * (D ** -0.5)
        off = Sk - Sq
        qi = torch.arange(Sq)[:, None]
        kj = torch.arange(Sk)[None, :]
        cmask = kj <= (qi + off)
        scores = torch.where(cmask[None, None], scores, -1e9)
        p = _softmax(scores, axis=-1)
        ctx = torch.einsum("bhqk,bhkd->bhqd", p, v)
        return torch.einsum("bhqd,hdm->bqm", ctx, w_o)

    def _B_ref(x, w_r, w_gate, w_up, w_down):
        B, S, D = x.shape
        C = 8
        r = x @ w_r
        idx = torch.argsort(-r, axis=-1)[:, :C]
        idx_e = (lambda x, n, axis: torch.repeat_interleave(x, n, dim=axis))(idx.reshape(B, C, 1), D, axis=2)
        x_sel = (lambda x, i, axis: torch.take_along_dim(x, i, dim=axis))(x, idx_e, axis=1)
        g = _silu(x_sel @ w_gate)
        u = x_sel @ w_up
        y = (g * u) @ w_down
        r_sel = _sigmoid((lambda x, i, axis: torch.take_along_dim(x, i, dim=axis))(r, idx, axis=1))
        y = y * r_sel.reshape(B, C, 1)
        b_off = (torch.arange(B) * S).reshape(B, 1)
        flat_idx = (idx + b_off).reshape(B * C)
        zero = (x * 0.0).reshape(B * S, D)
        upd = _scatter_add(zero, flat_idx, y.reshape(B * C, D), axis=0)
        return x + upd.reshape(B, S, D)

    x = A_x
    xn = _layernorm(x, axis=-1)
    return x + _A_ref(xn, A_c_kv, A_w_q, A_w_uk, A_w_uv, A_w_o) + _B_ref(xn, B_w_r, B_w_gate, B_w_up, B_w_down)
```

```cpp
#include <cuda_runtime.h>
#include <cuda_bf16.h>
#include <cuda.h>
#include <stdint.h>

namespace {

constexpr int SEQ = 2048, DM = 640, DC = 512, NH = 32, HD = 128, FF = 1728;
constexpr int NSLOT = 7, SLOT = 32768;
constexpr int NCTA = 132;
constexpr uint32_t DESC_HI = (1024u >> 4) | (1u << 30);
constexpr int SMEM_BYTES = NSLOT * SLOT + 2048;

constexpr int BAR_FULL = 0, BAR_EMPTY = 64, BAR_SIG = 128  , MISC_OFF = 512;

constexpr int F_EXIT = 0, F_LN = 1, F_MOD = 2, F_KV = 4  , F_PART = 36  , F_CTX = 68  , F_NUM = 580;

__device__ __align__(1024) __nv_bfloat16 g_xn[SEQ * DM];
__device__ __align__(1024) __nv_bfloat16 g_kv[NH * 16 * 2 * 128 * 128];
__device__ __align__(1024) __nv_bfloat16 g_ctx[NH * SEQ * HD];
__device__ __align__(1024) float g_part[32 * 4 * 128 * 320];
__device__ __align__(16) float g_r[SEQ];
__device__ __align__(16) float g_ypart[4 * 8 * DM];
__device__ int g_idx[8];
__device__ float g_rsel[8];
__device__ uint32_t g_flags[F_NUM * 8];

struct Params {
    CUtensorMap ckv, wuk, wuv, xn, wq, kv, ctx, wo;
    const __nv_bfloat16 *x, *wr, *wg, *wu, *wd;
    __nv_bfloat16* out;
};

__device__ __forceinline__ uint32_t smem_u32(const void* p) { return (uint32_t)__cvta_generic_to_shared(p); }
__device__ __forceinline__ void mbar_init(uint32_t bar, uint32_t cnt) {
    asm volatile("mbarrier.init.shared::cta.b64 [%0], %1;" ::"r"(bar), "r"(cnt) : "memory");
}
__device__ __forceinline__ void mbar_expect_tx(uint32_t bar, uint32_t bytes) {
    asm volatile("mbarrier.arrive.expect_tx.shared::cta.b64 _, [%0], %1;" ::"r"(bar), "r"(bytes) : "memory");
}
__device__ __forceinline__ void mbar_arrive(uint32_t bar) {
    asm volatile("mbarrier.arrive.shared::cta.b64 _, [%0];" ::"r"(bar) : "memory");
}
__device__ __forceinline__ void mbar_arrive_cluster(uint32_t cluster_addr) {
    asm volatile("mbarrier.arrive.shared::cluster.b64 _, [%0];" ::"r"(cluster_addr) : "memory");
}
__device__ __forceinline__ uint32_t mapa(uint32_t addr, uint32_t cta) {
    uint32_t r;
    asm("mapa.shared::cluster.u32 %0, %1, %2;" : "=r"(r) : "r"(addr), "r"(cta));
    return r;
}
__device__ __forceinline__ void mbar_wait(uint32_t bar, uint32_t parity) {
    asm volatile(
        "{\n.reg .pred p;\n.reg .b32 c;\n"
        "mbarrier.try_wait.parity.shared::cta.b64 p, [%0], %1;\n"
        "@p bra WDONE;\n"
        "mov.b32 c, 0;\n"
        "WLOOP:\n"
        "mbarrier.try_wait.parity.shared::cta.b64 p, [%0], %1;\n"
        "@p bra WDONE;\n"
        "add.u32 c, c, 1;\n"
        "setp.lt.u32 p, c, 0x400000;\n"
        "@p bra WLOOP;\n"
        "trap;\n"
        "WDONE:\n}\n" ::"r"(bar), "r"(parity) : "memory");
}
__device__ __forceinline__ void tma_load(uint32_t dst, const CUtensorMap* m, int c0, int c1, uint32_t bar) {
    asm volatile("cp.async.bulk.tensor.2d.shared::cluster.global.mbarrier::complete_tx::bytes [%0], [%1, {%3, %4}], [%2];"
                 ::"r"(dst), "l"(m), "r"(bar), "r"(c0), "r"(c1) : "memory");
}
__device__ __forceinline__ void tma_load_mc(uint32_t dst, const CUtensorMap* m, int c0, int c1, uint32_t bar) {
    asm volatile("cp.async.bulk.tensor.2d.shared::cluster.global.mbarrier::complete_tx::bytes.multicast::cluster [%0], [%1, {%3, %4}], [%2], %5;"
                 ::"r"(dst), "l"(m), "r"(bar), "r"(c0), "r"(c1), "h"((uint16_t)3) : "memory");
}
__device__ __forceinline__ void prefetch_map(const CUtensorMap* m) {
    asm volatile("prefetch.tensormap [%0];" ::"l"(m) : "memory");
}
__device__ __forceinline__ void cluster_arrive() { asm volatile("barrier.cluster.arrive.release.aligned;" ::: "memory"); }
__device__ __forceinline__ void cluster_wait() { asm volatile("barrier.cluster.wait.acquire.aligned;" ::: "memory"); }
__device__ __forceinline__ void named_sync(int id, int n) { asm volatile("bar.sync %0, %1;" ::"r"(id), "r"(n) : "memory"); }
__device__ __forceinline__ void named_arrive(int id, int n) { asm volatile("bar.arrive %0, %1;" ::"r"(id), "r"(n) : "memory"); }

__device__ __forceinline__ void flag_add(int f) {
    asm volatile("fence.acq_rel.gpu;\nred.relaxed.gpu.global.add.u32 [%0], 1;" ::"l"(g_flags + f * 8) : "memory");
}
__device__ __forceinline__ void flag_wait(int f, uint32_t target) {
    asm volatile(
        "{\n.reg .pred p;\n.reg .b32 c, v;\n"
        "mov.b32 c, 0;\n"
        "FLOOP:\n"
        "ld.acquire.gpu.global.u32 v, [%0];\n"
        "sub.u32 v, v, %1;\n"
        "setp.ge.s32 p, v, 0;\n"
        "@p bra FDONE;\n"
        "nanosleep.u32 40;\n"
        "add.u32 c, c, 1;\n"
        "setp.lt.u32 p, c, 0x400000;\n"
        "@p bra FLOOP;\n"
        "trap;\n"
        "FDONE:\n}\n" ::"l"(g_flags + f * 8), "r"(target) : "memory");
}
__device__ __forceinline__ void fence_proxy_async() { asm volatile("fence.proxy.async;" ::: "memory"); }

__device__ __forceinline__ void wgmma_fence() { asm volatile("wgmma.fence.sync.aligned;" ::: "memory"); }
__device__ __forceinline__ void wgmma_commit() { asm volatile("wgmma.commit_group.sync.aligned;" ::: "memory"); }
template <int N>
__device__ __forceinline__ void wgmma_wait() { asm volatile("wgmma.wait_group.sync.aligned %0;" ::"n"(N) : "memory"); }
template <int N>
__device__ __forceinline__ void fence_regs(float (&d)[N]) {
#pragma unroll
    for (int i = 0; i < N; i++) asm volatile("" : "+f"(d[i])::"memory");
}
template <int N>
__device__ __forceinline__ void fence_regs(uint32_t (&d)[N]) {
#pragma unroll
    for (int i = 0; i < N; i++) asm volatile("" : "+r"(d[i])::"memory");
}
__device__ __forceinline__ uint32_t desc_lo(uint32_t addr, uint32_t lbo) { return ((addr & 0x3FFFF) >> 4) | ((lbo >> 4) << 16); }

template <int TA, int TB>
__device__ __forceinline__ void wgmma_ss_n128(float (&d)[64], uint32_t alo, uint32_t blo, int scale_d) {
    asm volatile("{\n.reg .pred p;\n.reg .b64 da, db;\nsetp.ne.b32 p, %66, 0;\n"
        "mov.b64 da, {%64, %69};\nmov.b64 db, {%65, %69};\n"
        "wgmma.mma_async.sync.aligned.m64n128k16.f32.bf16.bf16 "
        "{%0, %1, %2, %3, %4, %5, %6, %7, %8, %9, %10, %11, %12, %13, %14, %15, %16, %17, %18, %19, %20, %21, %22, %23, %24, %25, %26, %27, %28, %29, %30, %31, %32, %33, %34, %35, %36, %37, %38, %39, %40, %41, %42, %43, %44, %45, %46, %47, %48, %49, %50, %51, %52, %53, %54, %55, %56, %57, %58, %59, %60, %61, %62, %63}, da, db, p, 1, 1, %67, %68;\n}\n"
        :
          "+f"(d[0]), "+f"(d[1]), "+f"(d[2]), "+f"(d[3]), "+f"(d[4]), "+f"(d[5]), "+f"(d[6]), "+f"(d[7]),
          "+f"(d[8]), "+f"(d[9]), "+f"(d[10]), "+f"(d[11]), "+f"(d[12]), "+f"(d[13]), "+f"(d[14]), "+f"(d[15]),
          "+f"(d[16]), "+f"(d[17]), "+f"(d[18]), "+f"(d[19]), "+f"(d[20]), "+f"(d[21]), "+f"(d[22]), "+f"(d[23]),
          "+f"(d[24]), "+f"(d[25]), "+f"(d[26]), "+f"(d[27]), "+f"(d[28]), "+f"(d[29]), "+f"(d[30]), "+f"(d[31]),
          "+f"(d[32]), "+f"(d[33]), "+f"(d[34]), "+f"(d[35]), "+f"(d[36]), "+f"(d[37]), "+f"(d[38]), "+f"(d[39]),
          "+f"(d[40]), "+f"(d[41]), "+f"(d[42]), "+f"(d[43]), "+f"(d[44]), "+f"(d[45]), "+f"(d[46]), "+f"(d[47]),
          "+f"(d[48]), "+f"(d[49]), "+f"(d[50]), "+f"(d[51]), "+f"(d[52]), "+f"(d[53]), "+f"(d[54]), "+f"(d[55]),
          "+f"(d[56]), "+f"(d[57]), "+f"(d[58]), "+f"(d[59]), "+f"(d[60]), "+f"(d[61]), "+f"(d[62]), "+f"(d[63])
        : "r"(alo), "r"(blo), "r"(scale_d), "n"(TA), "n"(TB), "r"(DESC_HI));
}
template <int TA, int TB>
__device__ __forceinline__ void wgmma_ss_n192(float (&d)[96], uint32_t alo, uint32_t blo, int scale_d) {
    asm volatile("{\n.reg .pred p;\n.reg .b64 da, db;\nsetp.ne.b32 p, %98, 0;\n"
        "mov.b64 da, {%96, %101};\nmov.b64 db, {%97, %101};\n"
        "wgmma.mma_async.sync.aligned.m64n192k16.f32.bf16.bf16 "
        "{%0, %1, %2, %3, %4, %5, %6, %7, %8, %9, %10, %11, %12, %13, %14, %15, %16, %17, %18, %19, %20, %21, %22, %23, %24, %25, %26, %27, %28, %29, %30, %31, %32, %33, %34, %35, %36, %37, %38, %39, %40, %41, %42, %43, %44, %45, %46, %47, %48, %49, %50, %51, %52, %53, %54, %55, %56, %57, %58, %59, %60, %61, %62, %63, %64, %65, %66, %67, %68, %69, %70, %71, %72, %73, %74, %75, %76, %77, %78, %79, %80, %81, %82, %83, %84, %85, %86, %87, %88, %89, %90, %91, %92, %93, %94, %95}, da, db, p, 1, 1, %99, %100;\n}\n"
        :
          "+f"(d[0]), "+f"(d[1]), "+f"(d[2]), "+f"(d[3]), "+f"(d[4]), "+f"(d[5]), "+f"(d[6]), "+f"(d[7]),
          "+f"(d[8]), "+f"(d[9]), "+f"(d[10]), "+f"(d[11]), "+f"(d[12]), "+f"(d[13]), "+f"(d[14]), "+f"(d[15]),
          "+f"(d[16]), "+f"(d[17]), "+f"(d[18]), "+f"(d[19]), "+f"(d[20]), "+f"(d[21]), "+f"(d[22]), "+f"(d[23]),
          "+f"(d[24]), "+f"(d[25]), "+f"(d[26]), "+f"(d[27]), "+f"(d[28]), "+f"(d[29]), "+f"(d[30]), "+f"(d[31]),
          "+f"(d[32]), "+f"(d[33]), "+f"(d[34]), "+f"(d[35]), "+f"(d[36]), "+f"(d[37]), "+f"(d[38]), "+f"(d[39]),
          "+f"(d[40]), "+f"(d[41]), "+f"(d[42]), "+f"(d[43]), "+f"(d[44]), "+f"(d[45]), "+f"(d[46]), "+f"(d[47]),
          "+f"(d[48]), "+f"(d[49]), "+f"(d[50]), "+f"(d[51]), "+f"(d[52]), "+f"(d[53]), "+f"(d[54]), "+f"(d[55]),
          "+f"(d[56]), "+f"(d[57]), "+f"(d[58]), "+f"(d[59]), "+f"(d[60]), "+f"(d[61]), "+f"(d[62]), "+f"(d[63]),
          "+f"(d[64]), "+f"(d[65]), "+f"(d[66]), "+f"(d[67]), "+f"(d[68]), "+f"(d[69]), "+f"(d[70]), "+f"(d[71]),
          "+f"(d[72]), "+f"(d[73]), "+f"(d[74]), "+f"(d[75]), "+f"(d[76]), "+f"(d[77]), "+f"(d[78]), "+f"(d[79]),
          "+f"(d[80]), "+f"(d[81]), "+f"(d[82]), "+f"(d[83]), "+f"(d[84]), "+f"(d[85]), "+f"(d[86]), "+f"(d[87]),
          "+f"(d[88]), "+f"(d[89]), "+f"(d[90]), "+f"(d[91]), "+f"(d[92]), "+f"(d[93]), "+f"(d[94]), "+f"(d[95])
        : "r"(alo), "r"(blo), "r"(scale_d), "n"(TA), "n"(TB), "r"(DESC_HI));
}
template <int TB>
__device__ __forceinline__ void wgmma_rs_n128(float (&d)[64], uint32_t a0, uint32_t a1, uint32_t a2, uint32_t a3, uint32_t blo, int scale_d) {
    asm volatile("{\n.reg .pred p;\n.reg .b64 db;\nsetp.ne.b32 p, %69, 0;\n"
        "mov.b64 db, {%68, %71};\n"
        "wgmma.mma_async.sync.aligned.m64n128k16.f32.bf16.bf16 "
        "{%0, %1, %2, %3, %4, %5, %6, %7, %8, %9, %10, %11, %12, %13, %14, %15, %16, %17, %18, %19, %20, %21, %22, %23, %24, %25, %26, %27, %28, %29, %30, %31, %32, %33, %34, %35, %36, %37, %38, %39, %40, %41, %42, %43, %44, %45, %46, %47, %48, %49, %50, %51, %52, %53, %54, %55, %56, %57, %58, %59, %60, %61, %62, %63}, {%64, %65, %66, %67}, db, p, 1, 1, %70;\n}\n"
        :
          "+f"(d[0]), "+f"(d[1]), "+f"(d[2]), "+f"(d[3]), "+f"(d[4]), "+f"(d[5]), "+f"(d[6]), "+f"(d[7]),
          "+f"(d[8]), "+f"(d[9]), "+f"(d[10]), "+f"(d[11]), "+f"(d[12]), "+f"(d[13]), "+f"(d[14]), "+f"(d[15]),
          "+f"(d[16]), "+f"(d[17]), "+f"(d[18]), "+f"(d[19]), "+f"(d[20]), "+f"(d[21]), "+f"(d[22]), "+f"(d[23]),
          "+f"(d[24]), "+f"(d[25]), "+f"(d[26]), "+f"(d[27]), "+f"(d[28]), "+f"(d[29]), "+f"(d[30]), "+f"(d[31]),
          "+f"(d[32]), "+f"(d[33]), "+f"(d[34]), "+f"(d[35]), "+f"(d[36]), "+f"(d[37]), "+f"(d[38]), "+f"(d[39]),
          "+f"(d[40]), "+f"(d[41]), "+f"(d[42]), "+f"(d[43]), "+f"(d[44]), "+f"(d[45]), "+f"(d[46]), "+f"(d[47]),
          "+f"(d[48]), "+f"(d[49]), "+f"(d[50]), "+f"(d[51]), "+f"(d[52]), "+f"(d[53]), "+f"(d[54]), "+f"(d[55]),
          "+f"(d[56]), "+f"(d[57]), "+f"(d[58]), "+f"(d[59]), "+f"(d[60]), "+f"(d[61]), "+f"(d[62]), "+f"(d[63])
        : "r"(a0), "r"(a1), "r"(a2), "r"(a3), "r"(blo), "r"(scale_d), "n"(TB), "r"(DESC_HI));
}

__device__ __forceinline__ uint32_t pack_bf16(float lo, float hi) {
    uint32_t r;
    asm("cvt.rn.bf16x2.f32 %0, %1, %2;" : "=r"(r) : "f"(hi), "f"(lo));
    return r;
}
__device__ __forceinline__ float bf_lo(uint32_t v) { return __uint_as_float(v << 16); }
__device__ __forceinline__ float bf_hi(uint32_t v) { return __uint_as_float(v & 0xffff0000u); }
__device__ __forceinline__ float round_bf16(float v) { return __bfloat162float(__float2bfloat16_rn(v)); }
__device__ __forceinline__ float ex2(float x) {
    float y;
    asm("ex2.approx.ftz.f32 %0, %1;" : "=f"(y) : "f"(x));
    return y;
}
__device__ __forceinline__ void stg128(void* p, uint32_t a, uint32_t b, uint32_t c, uint32_t d) {
    asm volatile("st.global.v4.b32 [%0], {%1, %2, %3, %4};" ::"l"(p), "r"(a), "r"(b), "r"(c), "r"(d) : "memory");
}
__device__ __forceinline__ int perm_row(int t) { return (t & ~255) | (((0x78 >> (((t >> 6) & 3) * 2)) & 3) << 6) | (t & 63); }
__device__ __forceinline__ int unperm_row(int t) { return (t & ~255) | (((0x9C >> (((t >> 6) & 3) * 2)) & 3) << 6) | (t & 63); }

#define PROF(i)
#define PROFG(i)

__device__ __forceinline__ void store_tile(const float (&a)[64], __nv_bfloat16* row0, __nv_bfloat16* row1, float s0, float s1) {
#pragma unroll
    for (int i = 0; i < 4; i++) {
        stg128(row0 + 32 * i, pack_bf16(a[16 * i + 0] * s0, a[16 * i + 1] * s0), pack_bf16(a[16 * i + 4] * s0, a[16 * i + 5] * s0),
               pack_bf16(a[16 * i + 8] * s0, a[16 * i + 9] * s0), pack_bf16(a[16 * i + 12] * s0, a[16 * i + 13] * s0));
        stg128(row1 + 32 * i, pack_bf16(a[16 * i + 2] * s1, a[16 * i + 3] * s1), pack_bf16(a[16 * i + 6] * s1, a[16 * i + 7] * s1),
               pack_bf16(a[16 * i + 10] * s1, a[16 * i + 11] * s1), pack_bf16(a[16 * i + 14] * s1, a[16 * i + 15] * s1));
    }
}

struct Prod {
    uint32_t smem, bars, pe;
    int ring;
    __device__ __forceinline__ uint32_t acquire(int s, uint32_t bytes) {
        mbar_wait(bars + BAR_EMPTY + s * 8, (pe >> s) & 1);
        pe ^= 1u << s;
        mbar_expect_tx(bars + BAR_FULL + s * 8, bytes);
        return bars + BAR_FULL + s * 8;
    }
    __device__ __forceinline__ int next() {
        int s = ring;
        ring = (ring == NSLOT - 1) ? 0 : ring + 1;
        return s;
    }
};

__device__ __forceinline__ int slot_a(int i) { return (0x5310 >> (4 * i)) & 15; }
__device__ __forceinline__ int slot_w(int m) { return (0x264 >> (4 * m)) & 15; }

__device__ __forceinline__ void producer(const Params& P, uint32_t smem, uint32_t bars, uint32_t epoch, int ca, int cb, int rank) {
    Prod pr{smem, bars, 0x7fu, 0};
    {
        const int row0 = (2 * ca + rank) * 128;
        int m = 0;
        for (int u = 0; u < 32; u++) {
            if (u < 4) {
                int s = slot_a(u);
                uint32_t fb = pr.acquire(s, SLOT);
                tma_load(smem + s * SLOT, &P.ckv, u * 128, row0, fb);
                tma_load(smem + s * SLOT + 16384, &P.ckv, u * 128 + 64, row0, fb);
            }
            int s = slot_w(m);
            m = (m == 2) ? 0 : m + 1;
            uint32_t fb = pr.acquire(s, SLOT);
            int h = cb + 8 * (u >> 3);
            tma_load_mc(smem + s * SLOT + rank * 16384, (u & 4) ? &P.wuv : &P.wuk, h * 128 + rank * 64, (u & 3) * 128, fb);
        }
    }
    flag_wait(F_LN, 256u * (epoch + 1));
    fence_proxy_async();
    for (int rd = 0; rd < 4; rd++) {
        const int h = 8 * rd + cb, p = (rd & 1) ? 7 - ca : ca;
        for (int ks = 0; ks < 10; ks++) {
            int s = pr.next();
            uint32_t fb = pr.acquire(s, SLOT);
            tma_load(smem + s * SLOT, &P.xn, ks * 64, 256 * p + 128 * rank, fb);
            tma_load_mc(smem + s * SLOT + 16384 + rank * 8192, &P.wq, h * 128 + rank * 64, ks * 64, fb);
        }
        flag_wait(F_KV + h, 32u * (epoch + 1));
        fence_proxy_async();
        const int n = 2 * p + 2;
        for (int i = 0; i <= n; i++) {
            if (i < n) {
                int s = pr.next();
                uint32_t fb = pr.acquire(s, SLOT);
                tma_load_mc(smem + s * SLOT + rank * 16384, &P.kv, rank * 64, ((h * 16 + (n - 1 - i)) * 2) * 128, fb);
            }
            if (i > 0) {
                int s = pr.next();
                uint32_t fb = pr.acquire(s, SLOT);
                tma_load_mc(smem + s * SLOT + rank * 16384, &P.kv, rank * 64, ((h * 16 + (n - i)) * 2 + 1) * 128, fb);
            }
        }
    }
    {
        const int p = ca, n0 = 320 * (cb & 1), kg = cb >> 1;
        for (int t = 0; t < 16; t++) {
            const int h = 8 * (t >> 2) + 2 * kg + ((t >> 1) & 1), ks = t & 1;
            const int krow = h * 128 + ks * 64 + rank * 32;
            int s = pr.next();
            uint32_t fb = pr.acquire(s, SLOT);
            tma_load_mc(smem + s * SLOT + 16384 + rank * 8192, &P.wo, n0, krow, fb);
            tma_load_mc(smem + s * SLOT + 16384 + rank * 8192 + 4096, &P.wo, n0 + 64, krow, fb);
            if (ks == 0) {
                flag_wait(F_CTX + h * 16 + p * 2 + rank, 2u * (epoch + 1));
                fence_proxy_async();
            }
            tma_load(smem + s * SLOT, &P.ctx, ks * 64, h * SEQ + 256 * p + 128 * rank, fb);
            s = pr.next();
            fb = pr.acquire(s, 24576);
#pragma unroll
            for (int c = 0; c < 3; c++) tma_load_mc(smem + s * SLOT + rank * 12288 + c * 4096, &P.wo, n0 + 128 + 64 * c, krow, fb);
        }
    }
}

struct Cons {
    uint32_t smem, bars, rel, pf;
    int ring;
    bool rel_on;
    __device__ __forceinline__ void wait(int s) {
        mbar_wait(bars + BAR_FULL + s * 8, (pf >> s) & 1);
        pf ^= 1u << s;
    }
    __device__ __forceinline__ void release(int s) {
        if (rel_on) mbar_arrive_cluster(rel + s * 8);
    }
    __device__ __forceinline__ int next() {
        int s = ring;
        ring = (ring == NSLOT - 1) ? 0 : ring + 1;
        return s;
    }
};

__device__ __forceinline__ void layernorm_rows(const Params& P, int cta, int cw  , int lane) {
    const int t = cta * 16 + cw * 2 + (lane >> 4), l = lane & 15;
    const uint4* xr = reinterpret_cast<const uint4*>(P.x + (size_t)t * DM);
    const uint4* wr = reinterpret_cast<const uint4*>(P.wr);
    uint4 xv[5], wv[5];
#pragma unroll
    for (int i = 0; i < 5; i++) xv[i] = __ldg(xr + l + 16 * i);
#pragma unroll
    for (int i = 0; i < 5; i++) wv[i] = __ldg(wr + l + 16 * i);
    float v[40];
#pragma unroll
    for (int i = 0; i < 5; i++) {
        v[8 * i + 0] = bf_lo(xv[i].x); v[8 * i + 1] = bf_hi(xv[i].x); v[8 * i + 2] = bf_lo(xv[i].y); v[8 * i + 3] = bf_hi(xv[i].y);
        v[8 * i + 4] = bf_lo(xv[i].z); v[8 * i + 5] = bf_hi(xv[i].z); v[8 * i + 6] = bf_lo(xv[i].w); v[8 * i + 7] = bf_hi(xv[i].w);
    }
    float sum = 0.f;
#pragma unroll
    for (int i = 0; i < 40; i++) sum += v[i];
#pragma unroll
    for (int o = 8; o > 0; o >>= 1) sum += __shfl_xor_sync(0xffffffffu, sum, o);
    const float mean = __fdiv_rn(sum, (float)DM);
    float sq = 0.f;
#pragma unroll
    for (int i = 0; i < 40; i++) { float d = v[i] - mean; sq += d * d; }
#pragma unroll
    for (int o = 8; o > 0; o >>= 1) sq += __shfl_xor_sync(0xffffffffu, sq, o);
    const float mb = round_bf16(mean);
    const float sd = round_bf16(__fsqrt_rn(round_bf16(round_bf16(__fdiv_rn(sq, (float)DM)) + 1e-5f)));
    uint4* dst = reinterpret_cast<uint4*>(g_xn + (size_t)perm_row(t) * DM);
    float r = 0.f;
#pragma unroll
    for (int i = 0; i < 5; i++) {
        uint32_t o[4];
        const uint32_t w[4] = {wv[i].x, wv[i].y, wv[i].z, wv[i].w};
#pragma unroll
        for (int j = 0; j < 4; j++) {
            o[j] = pack_bf16(__fdiv_rn(round_bf16(v[8 * i + 2 * j] - mb), sd), __fdiv_rn(round_bf16(v[8 * i + 2 * j + 1] - mb), sd));
            r += bf_lo(o[j]) * bf_lo(w[j]);
            r += bf_hi(o[j]) * bf_hi(w[j]);
        }
        dst[l + 16 * i] = make_uint4(o[0], o[1], o[2], o[3]);
    }
#pragma unroll
    for (int o = 8; o > 0; o >>= 1) r += __shfl_xor_sync(0xffffffffu, r, o);
    if (l == 0) g_r[t] = round_bf16(r);
}

constexpr float SM_SCALE = 0.08838834764831845f * 1.4426950408889634f;

__device__ __forceinline__ void row_max(const float (&s)[64], float& mx0, float& mx1) {
    float a0 = fmaxf(s[0], s[1]), a1 = fmaxf(s[4], s[5]), b0 = fmaxf(s[2], s[3]), b1 = fmaxf(s[6], s[7]);
#pragma unroll
    for (int j = 2; j < 16; j += 2) {
        a0 = fmaxf(a0, fmaxf(s[4 * j], s[4 * j + 1]));
        a1 = fmaxf(a1, fmaxf(s[4 * j + 4], s[4 * j + 5]));
        b0 = fmaxf(b0, fmaxf(s[4 * j + 2], s[4 * j + 3]));
        b1 = fmaxf(b1, fmaxf(s[4 * j + 6], s[4 * j + 7]));
    }
    mx0 = fmaxf(a0, a1);
    mx1 = fmaxf(b0, b1);
    mx0 = fmaxf(mx0, __shfl_xor_sync(0xffffffffu, mx0, 1));
    mx1 = fmaxf(mx1, __shfl_xor_sync(0xffffffffu, mx1, 1));
    mx0 = fmaxf(mx0, __shfl_xor_sync(0xffffffffu, mx0, 2));
    mx1 = fmaxf(mx1, __shfl_xor_sync(0xffffffffu, mx1, 2));
}
__device__ __forceinline__ void exp_tile(float (&s)[64], float m0, float m1, float& r0, float& r1) {
    const float n0 = -m0 * SM_SCALE, n1 = -m1 * SM_SCALE;
    float a0 = 0.f, a1 = 0.f, b0 = 0.f, b1 = 0.f;
#pragma unroll
    for (int j = 0; j < 16; j++) {
        s[4 * j + 0] = ex2(fmaf(s[4 * j + 0], SM_SCALE, n0));
        s[4 * j + 1] = ex2(fmaf(s[4 * j + 1], SM_SCALE, n0));
        s[4 * j + 2] = ex2(fmaf(s[4 * j + 2], SM_SCALE, n1));
        s[4 * j + 3] = ex2(fmaf(s[4 * j + 3], SM_SCALE, n1));
        a0 += s[4 * j + 0]; a1 += s[4 * j + 1]; b0 += s[4 * j + 2]; b1 += s[4 * j + 3];
    }
    r0 = a0 + a1;
    r1 = b0 + b1;
}
__device__ __forceinline__ void pack_tile(const float (&s)[64], uint32_t (&p)[32]) {
#pragma unroll
    for (int i = 0; i < 32; i++) p[i] = pack_bf16(s[2 * i], s[2 * i + 1]);
}
__device__ __forceinline__ void gemm_rs(float (&d)[64], const uint32_t (&a)[32], uint32_t slot_addr, int acc_first) {
    const uint32_t b = desc_lo(slot_addr, 16384);
#pragma unroll
    for (int k = 0; k < 8; k++) wgmma_rs_n128<1>(d, a[4 * k], a[4 * k + 1], a[4 * k + 2], a[4 * k + 3], b + k * 128, k ? 1 : acc_first);
}
__device__ __forceinline__ void gemm_q(float (&d)[64], uint32_t slot_addr, int role, int acc_first) {
    const uint32_t a = desc_lo(slot_addr + role * 8192, 16), b = desc_lo(slot_addr + 16384, 8192);
#pragma unroll
    for (int k = 0; k < 4; k++) wgmma_ss_n128<0, 1>(d, a + k * 2, b + k * 128, k ? 1 : acc_first);
}

__device__ __forceinline__ void signal(uint32_t bars, int wg, int e, int lane) {
    __syncwarp();
    if (lane == 0) mbar_arrive(bars + BAR_SIG + (wg * 9 + e) * 8);
}

__device__ __forceinline__ void consumer(const Params& P, uint32_t smem, uint32_t bars, uint32_t epoch, int ca, int cb, int rank, int wg) {
    const int lane = threadIdx.x & 31, w = (threadIdx.x >> 5) & 3, q = lane & 3, lr = lane >> 2;
    layernorm_rows(P, blockIdx.x, wg * 4 + w, lane);
    signal(bars, wg, 0, lane);
    cluster_wait();
    Cons c{smem, bars, mapa(bars + BAR_EMPTY, lane & 1), 0u, 0, lane < 2};
    PROF(1);
    {
        float ak[64], av[64];
        const int j = 2 * ca + rank;
        const int krow = 64 * wg + 16 * w + lr;
        const int vrow = 64 * wg + 32 * (w >> 1) + 8 * (lr >> 1) + 4 * (w & 1) + (lr & 1);
        int m = 0, prev = -1;
        for (int hh = 0; hh < 4; hh++) {
#pragma unroll
            for (int kc = 0; kc < 4; kc++) {
                const int sa = slot_a(kc), sw = slot_w(m);
                m = (m == 2) ? 0 : m + 1;
                if (hh == 0) c.wait(sa);
                c.wait(sw);
                const uint32_t da = desc_lo(smem + sw * SLOT + wg * 16384, 16), db = desc_lo(smem + sa * SLOT, 16);
                wgmma_fence();
#pragma unroll
                for (int k = 0; k < 8; k++) wgmma_ss_n128<1, 0>(ak, da + k * 128, db + (k >> 2) * 1024 + (k & 3) * 2, (kc | k) ? 1 : 0);
                wgmma_commit();
                wgmma_wait<1>();
                if (prev >= 0) c.release(prev);
                prev = sw;
                if (kc == 0 && hh > 0) {
                    fence_regs(av);
                    __nv_bfloat16* base = g_kv + (size_t)(((cb + 8 * (hh - 1)) * 16 + j) * 2 + 1) * 16384 + 8 * q;
                    store_tile(av, base + vrow * 128, base + (vrow + 2) * 128, 1.f, 1.f);
                    signal(bars, wg, hh, lane);
                }
            }
#pragma unroll
            for (int kc = 0; kc < 4; kc++) {
                const int sa = slot_a(kc), sw = slot_w(m);
                m = (m == 2) ? 0 : m + 1;
                c.wait(sw);
                const uint32_t da = desc_lo(smem + sa * SLOT + wg * 8192, 16), db = desc_lo(smem + sw * SLOT, 16384);
                wgmma_fence();
#pragma unroll
                for (int k = 0; k < 8; k++) wgmma_ss_n128<0, 1>(av, da + (k >> 2) * 1024 + (k & 3) * 2, db + k * 128, (kc | k) ? 1 : 0);
                wgmma_commit();
                wgmma_wait<1>();
                c.release(prev);
                if (hh == 3 && kc > 0) c.release(slot_a(kc - 1));
                prev = sw;
                if (kc == 0) {
                    fence_regs(ak);
                    __nv_bfloat16* base = g_kv + (size_t)(((cb + 8 * hh) * 16 + j) * 2) * 16384 + 8 * q;
                    store_tile(ak, base + krow * 128, base + (krow + 8) * 128, 1.f, 1.f);
                }
            }
        }
        wgmma_wait<0>();
        c.release(slot_a(3));
        c.release(prev);
        fence_regs(av);
        __nv_bfloat16* base = g_kv + (size_t)(((cb + 24) * 16 + j) * 2 + 1) * 16384 + 8 * q;
        store_tile(av, base + vrow * 128, base + (vrow + 2) * 128, 1.f, 1.f);
        signal(bars, wg, 4, lane);
    }
    PROF(2);
    {
        float o[64], s[64];
        uint32_t pf[32], qf[32];
        for (int rd = 0; rd < 4; rd++) {
            const int h = 8 * rd + cb, p = (rd & 1) ? 7 - ca : ca;
            const int role = wg ^ (rd & 1);
            {
                int prev = -1;
                for (int ks = 0; ks < 10; ks++) {
                    const int sl = c.next();
                    c.wait(sl);
                    wgmma_fence();
                    gemm_q(s, smem + sl * SLOT, role, ks);
                    wgmma_commit();
                    wgmma_wait<1>();
                    if (prev >= 0) c.release(prev);
                    prev = sl;
                }
                wgmma_wait<0>();
                c.release(prev);
                fence_regs(s);
                pack_tile(s, qf);
            }
            PROF(8 + rd * 4);
            int nrest = 2 * p + role;
            if (!role) { const int sl = c.next(); c.wait(sl); c.release(sl); }
            {
                const int sl = c.next();
                c.wait(sl);
                fence_regs(qf);
                wgmma_fence();
                gemm_rs(s, qf, smem + sl * SLOT, 0);
                wgmma_commit();
                if (!role) { const int s2 = c.next(); c.wait(s2); c.release(s2); }
                wgmma_wait<0>();
                c.release(sl);
                fence_regs(s);
            }
            {
                const int rr = 64 * (role ^ rank) + 16 * w + lr - 8 * q;
#pragma unroll
                for (int j = 0; j < 16; j++) {
                    const int cc = 32 * (j >> 2) + 2 * (j & 3);
                    if (cc > rr) s[4 * j] = -INFINITY;
                    if (cc + 1 > rr) s[4 * j + 1] = -INFINITY;
                    if (cc > rr + 8) s[4 * j + 2] = -INFINITY;
                    if (cc + 1 > rr + 8) s[4 * j + 3] = -INFINITY;
                }
            }
            float m0, m1, l0, l1;
            row_max(s, m0, m1);
            exp_tile(s, m0, m1, l0, l1);
            pack_tile(s, pf);
#pragma unroll
            for (int i = 0; i < 64; i++) o[i] = 0.f;
            PROF(9 + rd * 4);
            for (int it = 0; it < nrest; it++) {
                const int sk = c.next(), sv = c.next();
                c.wait(sk);
                fence_regs(o); fence_regs(pf); fence_regs(s);
                wgmma_fence();
                gemm_rs(s, qf, smem + sk * SLOT, 0);
                wgmma_commit();
                c.wait(sv);
                wgmma_fence();
                gemm_rs(o, pf, smem + sv * SLOT, 1);
                wgmma_commit();
                wgmma_wait<1>();
                c.release(sk);
                fence_regs(s);
                float x0, x1, r0, r1;
                row_max(s, x0, x1);
                x0 = fmaxf(x0, m0); x1 = fmaxf(x1, m1);
                const float a0 = ex2((m0 - x0) * SM_SCALE), a1 = ex2((m1 - x1) * SM_SCALE);
                m0 = x0; m1 = x1;
                exp_tile(s, m0, m1, r0, r1);
                l0 = l0 * a0 + r0; l1 = l1 * a1 + r1;
                wgmma_wait<0>();
                c.release(sv);
                fence_regs(o); fence_regs(pf);
#pragma unroll
                for (int j = 0; j < 16; j++) { o[4 * j] *= a0; o[4 * j + 1] *= a0; o[4 * j + 2] *= a1; o[4 * j + 3] *= a1; }
                pack_tile(s, pf);
            }
            PROF(10 + rd * 4);
            {
                const int sv = c.next();
                c.wait(sv);
                fence_regs(o); fence_regs(pf);
                wgmma_fence();
                gemm_rs(o, pf, smem + sv * SLOT, 1);
                wgmma_commit();
                l0 += __shfl_xor_sync(0xffffffffu, l0, 1); l1 += __shfl_xor_sync(0xffffffffu, l1, 1);
                l0 += __shfl_xor_sync(0xffffffffu, l0, 2); l1 += __shfl_xor_sync(0xffffffffu, l1, 2);
                wgmma_wait<0>();
                c.release(sv);
                fence_regs(o); fence_regs(pf);
                __nv_bfloat16* base = g_ctx + (size_t)(h * SEQ + 256 * p + 128 * rank + 64 * role + 16 * w + lr) * HD + 8 * q;
                store_tile(o, base, base + 8 * HD, __frcp_rn(l0), __frcp_rn(l1));
                signal(bars, wg, 5 + rd, lane);
            }
            PROF(11 + rd * 4);
        }
    }
    PROF(3);
    {
        float a1[64], a2[96];
        int px = -1, py = -1;
        for (int t = 0; t < 16; t++) {
            const int sx = c.next(), sy = c.next();
            c.wait(sx);
            const uint32_t da = desc_lo(smem + sx * SLOT + wg * 8192, 16);
            const uint32_t b1 = desc_lo(smem + sx * SLOT + 16384, 4096), b2 = desc_lo(smem + sy * SLOT, 4096);
            wgmma_fence();
#pragma unroll
            for (int k = 0; k < 4; k++) wgmma_ss_n128<0, 1>(a1, da + k * 2, b1 + (k >> 1) * 512 + (k & 1) * 128, k ? 1 : t);
            c.wait(sy);
            wgmma_fence();
#pragma unroll
            for (int k = 0; k < 4; k++) wgmma_ss_n192<0, 1>(a2, da + k * 2, b2 + (k >> 1) * 768 + (k & 1) * 128, k ? 1 : t);
            wgmma_commit();
            wgmma_wait<1>();
            if (px >= 0) { c.release(px); c.release(py); }
            px = sx; py = sy;
        }
        wgmma_wait<0>();
        fence_regs(a1); fence_regs(a2);
        PROF(4);
        const int nh = cb & 1, kg = cb >> 1, tile = (ca * 2 + rank) * 2 + nh;
        float* dst = g_part + ((size_t)(tile * 4 + kg) * 128 + 64 * wg + 16 * w + lr) * 320 + 2 * q;
#pragma unroll
        for (int j = 0; j < 16; j++) {
            *reinterpret_cast<float2*>(dst + 8 * j) = make_float2(a1[4 * j], a1[4 * j + 1]);
            *reinterpret_cast<float2*>(dst + 8 * 320 + 8 * j) = make_float2(a1[4 * j + 2], a1[4 * j + 3]);
        }
#pragma unroll
        for (int j = 0; j < 24; j++) {
            *reinterpret_cast<float2*>(dst + 128 + 8 * j) = make_float2(a2[4 * j], a2[4 * j + 1]);
            *reinterpret_cast<float2*>(dst + 8 * 320 + 128 + 8 * j) = make_float2(a2[4 * j + 2], a2[4 * j + 3]);
        }
        const int tid = threadIdx.x - 128;
        named_sync(1, 256);
        if (tid == 0) {
            flag_add(F_PART + tile);
            flag_wait(F_PART + tile, 4u * (epoch + 1));
            flag_wait(F_MOD, 4u * (epoch + 1));
        }
        named_sync(1, 256);
        PROF(5);
        const int lrow = 32 * kg + (tid >> 3);
        const int prow = 256 * ca + 128 * rank + lrow, trow = unperm_row(prow);
        int sel = -1;
#pragma unroll
        for (int i = 0; i < 8; i++) if (__ldcg(g_idx + i) == trow) sel = i;
#pragma unroll
        for (int i = 0; i < 5; i++) {
            const int col = 8 * ((tid & 7) + 8 * i), gcol = 320 * nh + col;
            float v[8];
            const uint4 xv = __ldg(reinterpret_cast<const uint4*>(P.x + (size_t)trow * DM + gcol));
            const uint4 nv = __ldcg(reinterpret_cast<const uint4*>(g_xn + (size_t)prow * DM + gcol));
            v[0] = bf_lo(xv.x) + bf_lo(nv.x); v[1] = bf_hi(xv.x) + bf_hi(nv.x); v[2] = bf_lo(xv.y) + bf_lo(nv.y); v[3] = bf_hi(xv.y) + bf_hi(nv.y);
            v[4] = bf_lo(xv.z) + bf_lo(nv.z); v[5] = bf_hi(xv.z) + bf_hi(nv.z); v[6] = bf_lo(xv.w) + bf_lo(nv.w); v[7] = bf_hi(xv.w) + bf_hi(nv.w);
#pragma unroll
            for (int k = 0; k < 4; k++) {
                const float4* src = reinterpret_cast<const float4*>(g_part + ((size_t)(tile * 4 + k) * 128 + lrow) * 320 + col);
                const float4 u0 = __ldcg(src), u1 = __ldcg(src + 1);
                v[0] += u0.x; v[1] += u0.y; v[2] += u0.z; v[3] += u0.w; v[4] += u1.x; v[5] += u1.y; v[6] += u1.z; v[7] += u1.w;
            }
            if (sel >= 0) {
                const float rs = __ldcg(g_rsel + sel);
#pragma unroll
                for (int e = 0; e < 8; e++) {
                    float y = 0.f;
#pragma unroll
                    for (int k = 0; k < 4; k++) y += __ldcg(g_ypart + (k * 8 + sel) * DM + gcol + e);
                    v[e] += round_bf16(round_bf16(y) * rs);
                }
            }
            stg128(P.out + (size_t)trow * DM + gcol, pack_bf16(v[0], v[1]), pack_bf16(v[2], v[3]), pack_bf16(v[4], v[5]), pack_bf16(v[6], v[7]));
        }
    }
    PROF(6);
}

__device__ __forceinline__ void mma16816(float (&d)[4], uint32_t a0, uint32_t a2, uint32_t b0, uint32_t b1) {
    asm volatile("mma.sync.aligned.m16n8k16.row.col.f32.bf16.bf16.f32 {%0,%1,%2,%3}, {%4,%5,%6,%5}, {%7,%8}, {%0,%1,%2,%3};"
                 : "+f"(d[0]), "+f"(d[1]), "+f"(d[2]), "+f"(d[3]) : "r"(a0), "r"(0u), "r"(a2), "r"(b0), "r"(b1));
}
__device__ __forceinline__ void mma_rows(float (&acc)[8][4], uint32_t a0, uint32_t a2, const uint4& w0, const uint4& w1, const uint4& w2, const uint4& w3) {
    const uint32_t r0[4] = {w0.x, w0.y, w0.z, w0.w}, r1[4] = {w1.x, w1.y, w1.z, w1.w};
    const uint32_t r2[4] = {w2.x, w2.y, w2.z, w2.w}, r3[4] = {w3.x, w3.y, w3.z, w3.w};
#pragma unroll
    for (int i = 0; i < 4; i++) {
        mma16816(acc[2 * i], a0, a2, __byte_perm(r0[i], r1[i], 0x5410), __byte_perm(r2[i], r3[i], 0x5410));
        mma16816(acc[2 * i + 1], a0, a2, __byte_perm(r0[i], r1[i], 0x7632), __byte_perm(r2[i], r3[i], 0x7632));
    }
}

__device__ __forceinline__ void mod_ffn(const Params& P, uint8_t* sm, uint32_t epoch, int mc  ) {
    const int tid = threadIdx.x - 128, lane = tid & 31, cw = tid >> 5, q = lane & 3, lr = lane >> 2;
    float* red = reinterpret_cast<float*>(sm);
    uint32_t* xs = reinterpret_cast<uint32_t*>(sm + 8 * 8 * DM * 4);
    uint32_t* wmax = xs + 8 * 324;
    int* sidx = reinterpret_cast<int*>(wmax + 16);
    if (tid == 0) flag_wait(F_LN, 256u * (epoch + 1));
    named_sync(1, 256);
    uint32_t key[8];
#pragma unroll
    for (int i = 0; i < 8; i++) {
        const int t = tid + 256 * i;
        uint32_t b = __float_as_uint(__ldcg(g_r + t) + 0.f) >> 16;
        b = (b & 0x8000u) ? (~b & 0xffffu) : (b | 0x8000u);
        key[i] = (b << 16) | (uint32_t)(0xffff - t);
    }
    for (int rnd = 0; rnd < 8; rnd++) {
        uint32_t mx = key[0];
#pragma unroll
        for (int i = 1; i < 8; i++) mx = max(mx, key[i]);
        mx = __reduce_max_sync(0xffffffffu, mx);
        if (lane == 0) wmax[(rnd & 1) * 8 + cw] = mx;
        named_sync(1, 256);
        mx = __reduce_max_sync(0xffffffffu, wmax[(rnd & 1) * 8 + (lane & 7)]);
#pragma unroll
        for (int i = 0; i < 8; i++) if (key[i] == mx) key[i] = 0;
        if (tid == 0) sidx[rnd] = 0xffff - (int)(mx & 0xffffu);
    }
    named_sync(1, 256);
    if (mc == 0 && tid < 8) {
        const int t = sidx[tid];
        g_idx[tid] = t;
        g_rsel[tid] = round_bf16(1.0f / (1.0f + __expf(-__ldcg(g_r + t))));
    }
    {
        const uint32_t* src = reinterpret_cast<const uint32_t*>(g_xn + (size_t)perm_row(sidx[cw]) * DM);
        for (int i = lane; i < 320; i += 32) xs[cw * 324 + i] = __ldcg(src + i);
    }
    named_sync(1, 256);
    const int fg = cw * 4 + mc;
    float* myred = red + cw * 8 * DM + lr * DM + 16 * q;
    if (fg < 27) {
        float g[8][4], u[8][4];
#pragma unroll
        for (int i = 0; i < 8; i++)
#pragma unroll
            for (int e = 0; e < 4; e++) { g[i][e] = 0.f; u[i][e] = 0.f; }
        const __nv_bfloat16* wg = P.wg + (size_t)(2 * q) * FF + fg * 64 + 8 * lr;
        const __nv_bfloat16* wu = P.wu + (size_t)(2 * q) * FF + fg * 64 + 8 * lr;
#pragma unroll 1
        for (int k0 = 0; k0 < 40; k0 += 4) {
            uint4 a[4][4], b[4][4];
#pragma unroll
            for (int kk = 0; kk < 4; kk++)
#pragma unroll
                for (int r = 0; r < 4; r++) {
                    const size_t off = (size_t)((k0 + kk) * 16 + (r & 1) + 8 * (r >> 1)) * FF;
                    a[kk][r] = __ldg(reinterpret_cast<const uint4*>(wg + off));
                    b[kk][r] = __ldg(reinterpret_cast<const uint4*>(wu + off));
                }
#pragma unroll
            for (int kk = 0; kk < 4; kk++) {
                const uint32_t a0 = xs[lr * 324 + (k0 + kk) * 8 + q], a2 = xs[lr * 324 + (k0 + kk) * 8 + 4 + q];
                mma_rows(g, a0, a2, a[kk][0], a[kk][1], a[kk][2], a[kk][3]);
                mma_rows(u, a0, a2, b[kk][0], b[kk][1], b[kk][2], b[kk][3]);
            }
        }
        float hv[16];
#pragma unroll
        for (int i = 0; i < 8; i++)
#pragma unroll
            for (int e = 0; e < 2; e++) {
                const float gp = round_bf16(g[i][e]);
                const float sg = round_bf16(gp / (1.0f + __expf(-gp)));
                hv[8 * e + i] = sg * round_bf16(u[i][e]);
            }
        uint32_t hp[8];
#pragma unroll
        for (int i = 0; i < 8; i++) hp[i] = pack_bf16(hv[2 * i], hv[2 * i + 1]);
        const __nv_bfloat16* wd = P.wd + (size_t)(fg * 64 + 16 * q) * DM + 8 * lr;
#pragma unroll 1
        for (int dg = 0; dg < 10; dg += 2) {
            uint4 a[2][16];
#pragma unroll
            for (int z = 0; z < 2; z++)
#pragma unroll
                for (int r = 0; r < 16; r++) a[z][r] = __ldg(reinterpret_cast<const uint4*>(wd + (size_t)r * DM + (dg + z) * 64));
#pragma unroll
            for (int z = 0; z < 2; z++) {
                float y[8][4];
#pragma unroll
                for (int i = 0; i < 8; i++)
#pragma unroll
                    for (int e = 0; e < 4; e++) y[i][e] = 0.f;
#pragma unroll
                for (int kk = 0; kk < 4; kk++) mma_rows(y, hp[2 * kk], hp[2 * kk + 1], a[z][4 * kk], a[z][4 * kk + 1], a[z][4 * kk + 2], a[z][4 * kk + 3]);
#pragma unroll
                for (int i = 0; i < 8; i++) { myred[(dg + z) * 64 + i] = y[i][0]; myred[(dg + z) * 64 + 8 + i] = y[i][1]; }
            }
        }
    } else {
        for (int dg = 0; dg < 10; dg++)
#pragma unroll
            for (int i = 0; i < 16; i++) myred[dg * 64 + i] = 0.f;
    }
    named_sync(1, 256);
    for (int i = tid; i < 8 * DM; i += 256) {
        float y = 0.f;
#pragma unroll
        for (int k = 0; k < 8; k++) y += red[k * 8 * DM + i];
        g_ypart[mc * 8 * DM + i] = y;
    }
    named_sync(1, 256);
    if (tid == 0) flag_add(F_MOD);
}

__global__ void __cluster_dims__(2, 1, 1) __launch_bounds__(384, 1) fused_kernel(const __grid_constant__ Params P) {
    extern __shared__ __align__(1024) uint8_t smem_raw[];
    const uint32_t smem = (smem_u32(smem_raw) + 1023u) & ~1023u;
    uint8_t* smem_gen = smem_raw + (smem - smem_u32(smem_raw));
    const uint32_t bars = smem + NSLOT * SLOT;
    volatile uint32_t* misc = reinterpret_cast<volatile uint32_t*>(smem_gen + NSLOT * SLOT + MISC_OFF);
    const int wgi = __shfl_sync(0xffffffffu, threadIdx.x >> 7, 0);
    const int cl = blockIdx.x >> 1, rank = blockIdx.x & 1, ca = cl & 7, cb = cl >> 3;
    PROFG(30);
    PROF(0);
    if (threadIdx.x == 0) {
        for (int s = 0; s < NSLOT; s++) { mbar_init(bars + BAR_FULL + s * 8, 1); mbar_init(bars + BAR_EMPTY + s * 8, 16); }
        for (int s = 0; s < 18; s++) mbar_init(bars + BAR_SIG + s * 8, 4);
        asm volatile("fence.mbarrier_init.release.cluster;" ::: "memory");
        uint32_t e;
        asm volatile("ld.relaxed.gpu.global.u32 %0, [%1];" : "=r"(e) : "l"(g_flags + F_EXIT * 8) : "memory");
        misc[0] = e / NCTA;
    }
    __syncthreads();
    cluster_arrive();
    const uint32_t epoch = misc[0];
    if (wgi == 0) {
        asm volatile("setmaxnreg.dec.sync.aligned.u32 40;");
        const int w = threadIdx.x >> 5, lane = threadIdx.x & 31;
        cluster_wait();
        if (cl < 64) {
            if (w == 0) {
                if (lane == 0) {
                    prefetch_map(&P.ckv); prefetch_map(&P.wuk); prefetch_map(&P.wuv); prefetch_map(&P.xn);
                    prefetch_map(&P.wq); prefetch_map(&P.kv); prefetch_map(&P.ctx); prefetch_map(&P.wo);
                    producer(P, smem, bars, epoch, ca, cb, rank);
                }
            } else if (w < 3 && lane == 0) {
                const int wg = w - 1;
                for (int e = 0; e < 9; e++) {
                    mbar_wait(bars + BAR_SIG + (wg * 9 + e) * 8, 0);
                    int f;
                    if (e == 0) f = F_LN;
                    else if (e < 5) f = F_KV + cb + 8 * (e - 1);
                    else { const int rd = e - 5; f = F_CTX + (8 * rd + cb) * 16 + ((rd & 1) ? 7 - ca : ca) * 2 + rank; }
                    flag_add(f);
                }
            }
        }
        __syncwarp();
        cluster_arrive();
        cluster_wait();
        if (threadIdx.x == 0) atomicAdd(g_flags + F_EXIT * 8, 1u);
        PROFG(31);
    } else {
        asm volatile("setmaxnreg.inc.sync.aligned.u32 232;");
        if (cl < 64) {
            consumer(P, smem, bars, epoch, ca, cb, rank, wgi - 1);
        } else {
            cluster_wait();
            mod_ffn(P, smem_gen, epoch, blockIdx.x - 128);
        }
        cluster_arrive();
        PROFG(31);
    }
}

typedef CUresult (*EncodeFn)(CUtensorMap*, CUtensorMapDataType, cuuint32_t, void*, const cuuint64_t*, const cuuint64_t*, const cuuint32_t*,
                             const cuuint32_t*, CUtensorMapInterleave, CUtensorMapSwizzle, CUtensorMapL2promotion, CUtensorMapFloatOOBfill);

void make_map(EncodeFn fn, CUtensorMap* m, const void* ptr, uint64_t rows, uint64_t cols, uint32_t box_rows) {
    cuuint64_t dims[2] = {cols, rows};
    cuuint64_t strides[1] = {cols * 2};
    cuuint32_t box[2] = {64, box_rows};
    cuuint32_t es[2] = {1, 1};
    fn(m, CU_TENSOR_MAP_DATA_TYPE_BFLOAT16, 2, const_cast<void*>(ptr), dims, strides, box, es, CU_TENSOR_MAP_INTERLEAVE_NONE,
       CU_TENSOR_MAP_SWIZZLE_128B, CU_TENSOR_MAP_L2_PROMOTION_L2_128B, CU_TENSOR_MAP_FLOAT_OOB_FILL_NONE);
}

}

extern "C" void kernel_launch(void* const* d_in, const int* in_sizes, int n_in, void* d_out, int out_size) {
    (void)in_sizes; (void)n_in; (void)out_size;
    void* fnp = nullptr;
    cudaDriverEntryPointQueryResult qr;
    cudaGetDriverEntryPoint("cuTensorMapEncodeTiled", &fnp, cudaEnableDefault, &qr);
    EncodeFn fn = (EncodeFn)fnp;
    void *xn, *kv, *ctx;
    cudaGetSymbolAddress(&xn, g_xn);
    cudaGetSymbolAddress(&kv, g_kv);
    cudaGetSymbolAddress(&ctx, g_ctx);
    Params P;
    make_map(fn, &P.ckv, d_in[1], SEQ, DC, 128);
    make_map(fn, &P.wq, d_in[2], DM, NH * HD, 64);
    make_map(fn, &P.wuk, d_in[3], DC, NH * HD, 128);
    make_map(fn, &P.wuv, d_in[4], DC, NH * HD, 128);
    make_map(fn, &P.wo, d_in[5], NH * HD, DM, 32);
    make_map(fn, &P.xn, xn, SEQ, DM, 128);
    make_map(fn, &P.kv, kv, NH * 16 * 2 * 128, 128, 128);
    make_map(fn, &P.ctx, ctx, NH * SEQ, HD, 128);
    P.x = (const __nv_bfloat16*)d_in[0];
    P.wr = (const __nv_bfloat16*)d_in[7];
    P.wg = (const __nv_bfloat16*)d_in[8];
    P.wu = (const __nv_bfloat16*)d_in[9];
    P.wd = (const __nv_bfloat16*)d_in[10];
    P.out = (__nv_bfloat16*)d_out;
    cudaFuncSetAttribute(fused_kernel, cudaFuncAttributeMaxDynamicSharedMemorySize, SMEM_BYTES);
    fused_kernel<<<NCTA, 384, SMEM_BYTES>>>(P);
}
```

```cpp
#include <cuda_runtime.h>
#include <cuda_bf16.h>
#include <cuda.h>
#include <stdint.h>

namespace {

constexpr int SEQ = 2048, DM = 640, DC = 512, NH = 32, HD = 128, FF = 1728;
constexpr int NSLOT = 7, SLOT = 32768;
constexpr int NCTA = 132;
#define PINGPONG 1
#define KVROW(x) (x)
#define SPLITJ 8
constexpr uint32_t DESC_HI = (1024u >> 4) | (1u << 30);
constexpr int SMEM_BYTES = NSLOT * SLOT + 2048;

constexpr int BAR_FULL = 0, BAR_EMPTY = 64, BAR_SIG = 128  , MISC_OFF = 512;

constexpr int F_EXIT = 0, F_LN = 1, F_MOD = 2, F_KV = 4  , F_PART = 36  , F_CTX = 68  , F_NUM = 580;

__device__ __align__(1024) __nv_bfloat16 g_xn[SEQ * DM];
__device__ __align__(1024) __nv_bfloat16 g_kv[NH * 16 * 2 * 128 * 128];
__device__ __align__(1024) __nv_bfloat16 g_ctx[NH * SEQ * HD];
__device__ __align__(1024) float g_part[32 * 4 * 128 * 320];
__device__ __align__(16) float g_r[SEQ];
__device__ __align__(16) float g_ypart[4 * 8 * DM];
__device__ int g_idx[8];
__device__ float g_rsel[8];
__device__ uint32_t g_flags[F_NUM * 8];

struct Params {
    CUtensorMap ckv, wuk, wuv, xn, wq, kv, ctx, wo;
    const __nv_bfloat16 *x, *wr, *wg, *wu, *wd;
    __nv_bfloat16* out;
};

__device__ __forceinline__ uint32_t smem_u32(const void* p) { return (uint32_t)__cvta_generic_to_shared(p); }
__device__ __forceinline__ void mbar_init(uint32_t bar, uint32_t cnt) {
    asm volatile("mbarrier.init.shared::cta.b64 [%0], %1;" ::"r"(bar), "r"(cnt) : "memory");
}
__device__ __forceinline__ void mbar_expect_tx(uint32_t bar, uint32_t bytes) {
    asm volatile("mbarrier.arrive.expect_tx.shared::cta.b64 _, [%0], %1;" ::"r"(bar), "r"(bytes) : "memory");
}
__device__ __forceinline__ void mbar_arrive(uint32_t bar) {
    asm volatile("mbarrier.arrive.shared::cta.b64 _, [%0];" ::"r"(bar) : "memory");
}
__device__ __forceinline__ void mbar_arrive_cluster(uint32_t cluster_addr) {
    asm volatile("mbarrier.arrive.shared::cluster.b64 _, [%0];" ::"r"(cluster_addr) : "memory");
}
__device__ __forceinline__ uint32_t mapa(uint32_t addr, uint32_t cta) {
    uint32_t r;
    asm("mapa.shared::cluster.u32 %0, %1, %2;" : "=r"(r) : "r"(addr), "r"(cta));
    return r;
}
__device__ __forceinline__ void mbar_wait(uint32_t bar, uint32_t parity) {
    asm volatile(
        "{\n.reg .pred p;\n.reg .b32 c;\n"
        "mbarrier.try_wait.parity.shared::cta.b64 p, [%0], %1;\n"
        "@p bra.uni WDONE;\n"
        "mov.b32 c, 0;\n"
        "WLOOP:\n"
        "mbarrier.try_wait.parity.shared::cta.b64 p, [%0], %1;\n"
        "@p bra.uni WDONE;\n"
        "add.u32 c, c, 1;\n"
        "setp.lt.u32 p, c, 0x400000;\n"
        "@p bra.uni WLOOP;\n"
        "trap;\n"
        "WDONE:\n}\n" ::"r"(bar), "r"(parity) : "memory");
}
__device__ __forceinline__ void tma_load(uint32_t dst, const CUtensorMap* m, int c0, int c1, uint32_t bar) {
    asm volatile("cp.async.bulk.tensor.2d.shared::cluster.global.mbarrier::complete_tx::bytes [%0], [%1, {%3, %4}], [%2];"
                 ::"r"(dst), "l"(m), "r"(bar), "r"(c0), "r"(c1) : "memory");
}
__device__ __forceinline__ void tma_load_mc(uint32_t dst, const CUtensorMap* m, int c0, int c1, uint32_t bar) {
    asm volatile("cp.async.bulk.tensor.2d.shared::cluster.global.mbarrier::complete_tx::bytes.multicast::cluster [%0], [%1, {%3, %4}], [%2], %5;"
                 ::"r"(dst), "l"(m), "r"(bar), "r"(c0), "r"(c1), "h"((uint16_t)3) : "memory");
}
__device__ __forceinline__ void prefetch_map(const CUtensorMap* m) {
    asm volatile("prefetch.tensormap [%0];" ::"l"(m) : "memory");
}
__device__ __forceinline__ void cluster_arrive() { asm volatile("barrier.cluster.arrive.release.aligned;" ::: "memory"); }
__device__ __forceinline__ void cluster_wait() { asm volatile("barrier.cluster.wait.acquire.aligned;" ::: "memory"); }
__device__ __forceinline__ void named_sync(int id, int n) { asm volatile("bar.sync %0, %1;" ::"r"(id), "r"(n) : "memory"); }
__device__ __forceinline__ void named_arrive(int id, int n) { asm volatile("bar.arrive %0, %1;" ::"r"(id), "r"(n) : "memory"); }

__device__ __forceinline__ void flag_add(int f) {
    asm volatile("fence.acq_rel.gpu;\nred.relaxed.gpu.global.add.u32 [%0], 1;" ::"l"(g_flags + f * 8) : "memory");
}
__device__ __forceinline__ void flag_wait(int f, uint32_t target) {
    asm volatile(
        "{\n.reg .pred p;\n.reg .b32 c, v;\n"
        "mov.b32 c, 0;\n"
        "FLOOP:\n"
        "ld.acquire.gpu.global.u32 v, [%0];\n"
        "sub.u32 v, v, %1;\n"
        "setp.ge.s32 p, v, 0;\n"
        "@p bra FDONE;\n"
        "nanosleep.u32 40;\n"
        "add.u32 c, c, 1;\n"
        "setp.lt.u32 p, c, 0x400000;\n"
        "@p bra FLOOP;\n"
        "trap;\n"
        "FDONE:\n}\n" ::"l"(g_flags + f * 8), "r"(target) : "memory");
}
__device__ __forceinline__ void fence_proxy_async() { asm volatile("fence.proxy.async;" ::: "memory"); }

__device__ __forceinline__ void wgmma_fence() { asm volatile("wgmma.fence.sync.aligned;" ::: "memory"); }
__device__ __forceinline__ void wgmma_commit() { asm volatile("wgmma.commit_group.sync.aligned;" ::: "memory"); }
template <int N>
__device__ __forceinline__ void wgmma_wait() { asm volatile("wgmma.wait_group.sync.aligned %0;" ::"n"(N) : "memory"); }
template <int N>
__device__ __forceinline__ void fence_regs(float (&d)[N]) {
#pragma unroll
    for (int i = 0; i < N; i++) asm volatile("" : "+f"(d[i])::"memory");
}
template <int N>
__device__ __forceinline__ void fence_regs(uint32_t (&d)[N]) {
#pragma unroll
    for (int i = 0; i < N; i++) asm volatile("" : "+r"(d[i])::"memory");
}
__device__ __forceinline__ uint32_t desc_lo(uint32_t addr, uint32_t lbo) { return ((addr & 0x3FFFF) >> 4) | ((lbo >> 4) << 16); }

template <int TA, int TB>
__device__ __forceinline__ void wgmma_ss_n128(float (&d)[64], uint32_t alo, uint32_t blo, int scale_d) {
    asm volatile("{\n.reg .pred p;\n.reg .b64 da, db;\nsetp.ne.b32 p, %66, 0;\n"
        "mov.b64 da, {%64, %69};\nmov.b64 db, {%65, %69};\n"
        "wgmma.mma_async.sync.aligned.m64n128k16.f32.bf16.bf16 "
        "{%0, %1, %2, %3, %4, %5, %6, %7, %8, %9, %10, %11, %12, %13, %14, %15, %16, %17, %18, %19, %20, %21, %22, %23, %24, %25, %26, %27, %28, %29, %30, %31, %32, %33, %34, %35, %36, %37, %38, %39, %40, %41, %42, %43, %44, %45, %46, %47, %48, %49, %50, %51, %52, %53, %54, %55, %56, %57, %58, %59, %60, %61, %62, %63}, da, db, p, 1, 1, %67, %68;\n}\n"
        :
          "+f"(d[0]), "+f"(d[1]), "+f"(d[2]), "+f"(d[3]), "+f"(d[4]), "+f"(d[5]), "+f"(d[6]), "+f"(d[7]),
          "+f"(d[8]), "+f"(d[9]), "+f"(d[10]), "+f"(d[11]), "+f"(d[12]), "+f"(d[13]), "+f"(d[14]), "+f"(d[15]),
          "+f"(d[16]), "+f"(d[17]), "+f"(d[18]), "+f"(d[19]), "+f"(d[20]), "+f"(d[21]), "+f"(d[22]), "+f"(d[23]),
          "+f"(d[24]), "+f"(d[25]), "+f"(d[26]), "+f"(d[27]), "+f"(d[28]), "+f"(d[29]), "+f"(d[30]), "+f"(d[31]),
          "+f"(d[32]), "+f"(d[33]), "+f"(d[34]), "+f"(d[35]), "+f"(d[36]), "+f"(d[37]), "+f"(d[38]), "+f"(d[39]),
          "+f"(d[40]), "+f"(d[41]), "+f"(d[42]), "+f"(d[43]), "+f"(d[44]), "+f"(d[45]), "+f"(d[46]), "+f"(d[47]),
          "+f"(d[48]), "+f"(d[49]), "+f"(d[50]), "+f"(d[51]), "+f"(d[52]), "+f"(d[53]), "+f"(d[54]), "+f"(d[55]),
          "+f"(d[56]), "+f"(d[57]), "+f"(d[58]), "+f"(d[59]), "+f"(d[60]), "+f"(d[61]), "+f"(d[62]), "+f"(d[63])
        : "r"(alo), "r"(blo), "r"(scale_d), "n"(TA), "n"(TB), "r"(DESC_HI));
}
template <int TA, int TB>
__device__ __forceinline__ void wgmma_ss_n192(float (&d)[96], uint32_t alo, uint32_t blo, int scale_d) {
    asm volatile("{\n.reg .pred p;\n.reg .b64 da, db;\nsetp.ne.b32 p, %98, 0;\n"
        "mov.b64 da, {%96, %101};\nmov.b64 db, {%97, %101};\n"
        "wgmma.mma_async.sync.aligned.m64n192k16.f32.bf16.bf16 "
        "{%0, %1, %2, %3, %4, %5, %6, %7, %8, %9, %10, %11, %12, %13, %14, %15, %16, %17, %18, %19, %20, %21, %22, %23, %24, %25, %26, %27, %28, %29, %30, %31, %32, %33, %34, %35, %36, %37, %38, %39, %40, %41, %42, %43, %44, %45, %46, %47, %48, %49, %50, %51, %52, %53, %54, %55, %56, %57, %58, %59, %60, %61, %62, %63, %64, %65, %66, %67, %68, %69, %70, %71, %72, %73, %74, %75, %76, %77, %78, %79, %80, %81, %82, %83, %84, %85, %86, %87, %88, %89, %90, %91, %92, %93, %94, %95}, da, db, p, 1, 1, %99, %100;\n}\n"
        :
          "+f"(d[0]), "+f"(d[1]), "+f"(d[2]), "+f"(d[3]), "+f"(d[4]), "+f"(d[5]), "+f"(d[6]), "+f"(d[7]),
          "+f"(d[8]), "+f"(d[9]), "+f"(d[10]), "+f"(d[11]), "+f"(d[12]), "+f"(d[13]), "+f"(d[14]), "+f"(d[15]),
          "+f"(d[16]), "+f"(d[17]), "+f"(d[18]), "+f"(d[19]), "+f"(d[20]), "+f"(d[21]), "+f"(d[22]), "+f"(d[23]),
          "+f"(d[24]), "+f"(d[25]), "+f"(d[26]), "+f"(d[27]), "+f"(d[28]), "+f"(d[29]), "+f"(d[30]), "+f"(d[31]),
          "+f"(d[32]), "+f"(d[33]), "+f"(d[34]), "+f"(d[35]), "+f"(d[36]), "+f"(d[37]), "+f"(d[38]), "+f"(d[39]),
          "+f"(d[40]), "+f"(d[41]), "+f"(d[42]), "+f"(d[43]), "+f"(d[44]), "+f"(d[45]), "+f"(d[46]), "+f"(d[47]),
          "+f"(d[48]), "+f"(d[49]), "+f"(d[50]), "+f"(d[51]), "+f"(d[52]), "+f"(d[53]), "+f"(d[54]), "+f"(d[55]),
          "+f"(d[56]), "+f"(d[57]), "+f"(d[58]), "+f"(d[59]), "+f"(d[60]), "+f"(d[61]), "+f"(d[62]), "+f"(d[63]),
          "+f"(d[64]), "+f"(d[65]), "+f"(d[66]), "+f"(d[67]), "+f"(d[68]), "+f"(d[69]), "+f"(d[70]), "+f"(d[71]),
          "+f"(d[72]), "+f"(d[73]), "+f"(d[74]), "+f"(d[75]), "+f"(d[76]), "+f"(d[77]), "+f"(d[78]), "+f"(d[79]),
          "+f"(d[80]), "+f"(d[81]), "+f"(d[82]), "+f"(d[83]), "+f"(d[84]), "+f"(d[85]), "+f"(d[86]), "+f"(d[87]),
          "+f"(d[88]), "+f"(d[89]), "+f"(d[90]), "+f"(d[91]), "+f"(d[92]), "+f"(d[93]), "+f"(d[94]), "+f"(d[95])
        : "r"(alo), "r"(blo), "r"(scale_d), "n"(TA), "n"(TB), "r"(DESC_HI));
}
template <int TB>
__device__ __forceinline__ void wgmma_rs_n128(float (&d)[64], uint32_t a0, uint32_t a1, uint32_t a2, uint32_t a3, uint32_t blo, int scale_d) {
    asm volatile("{\n.reg .pred p;\n.reg .b64 db;\nsetp.ne.b32 p, %69, 0;\n"
        "mov.b64 db, {%68, %71};\n"
        "wgmma.mma_async.sync.aligned.m64n128k16.f32.bf16.bf16 "
        "{%0, %1, %2, %3, %4, %5, %6, %7, %8, %9, %10, %11, %12, %13, %14, %15, %16, %17, %18, %19, %20, %21, %22, %23, %24, %25, %26, %27, %28, %29, %30, %31, %32, %33, %34, %35, %36, %37, %38, %39, %40, %41, %42, %43, %44, %45, %46, %47, %48, %49, %50, %51, %52, %53, %54, %55, %56, %57, %58, %59, %60, %61, %62, %63}, {%64, %65, %66, %67}, db, p, 1, 1, %70;\n}\n"
        :
          "+f"(d[0]), "+f"(d[1]), "+f"(d[2]), "+f"(d[3]), "+f"(d[4]), "+f"(d[5]), "+f"(d[6]), "+f"(d[7]),
          "+f"(d[8]), "+f"(d[9]), "+f"(d[10]), "+f"(d[11]), "+f"(d[12]), "+f"(d[13]), "+f"(d[14]), "+f"(d[15]),
          "+f"(d[16]), "+f"(d[17]), "+f"(d[18]), "+f"(d[19]), "+f"(d[20]), "+f"(d[21]), "+f"(d[22]), "+f"(d[23]),
          "+f"(d[24]), "+f"(d[25]), "+f"(d[26]), "+f"(d[27]), "+f"(d[28]), "+f"(d[29]), "+f"(d[30]), "+f"(d[31]),
          "+f"(d[32]), "+f"(d[33]), "+f"(d[34]), "+f"(d[35]), "+f"(d[36]), "+f"(d[37]), "+f"(d[38]), "+f"(d[39]),
          "+f"(d[40]), "+f"(d[41]), "+f"(d[42]), "+f"(d[43]), "+f"(d[44]), "+f"(d[45]), "+f"(d[46]), "+f"(d[47]),
          "+f"(d[48]), "+f"(d[49]), "+f"(d[50]), "+f"(d[51]), "+f"(d[52]), "+f"(d[53]), "+f"(d[54]), "+f"(d[55]),
          "+f"(d[56]), "+f"(d[57]), "+f"(d[58]), "+f"(d[59]), "+f"(d[60]), "+f"(d[61]), "+f"(d[62]), "+f"(d[63])
        : "r"(a0), "r"(a1), "r"(a2), "r"(a3), "r"(blo), "r"(scale_d), "n"(TB), "r"(DESC_HI));
}
template <int TB>
__device__ __forceinline__ void wgmma_rs_n128_z(float (&d)[64], uint32_t a0, uint32_t a1, uint32_t a2, uint32_t a3, uint32_t blo) {
    asm volatile("{\n.reg .pred p;\n.reg .b64 db;\nsetp.ne.b32 p, %69, 0;\n"
        "mov.b64 db, {%68, %71};\n"
        "wgmma.mma_async.sync.aligned.m64n128k16.f32.bf16.bf16 "
        "{%0, %1, %2, %3, %4, %5, %6, %7, %8, %9, %10, %11, %12, %13, %14, %15, %16, %17, %18, %19, %20, %21, %22, %23, %24, %25, %26, %27, %28, %29, %30, %31, %32, %33, %34, %35, %36, %37, %38, %39, %40, %41, %42, %43, %44, %45, %46, %47, %48, %49, %50, %51, %52, %53, %54, %55, %56, %57, %58, %59, %60, %61, %62, %63}, {%64, %65, %66, %67}, db, p, 1, 1, %70;\n}\n"
        :
          "=f"(d[0]), "=f"(d[1]), "=f"(d[2]), "=f"(d[3]), "=f"(d[4]), "=f"(d[5]), "=f"(d[6]), "=f"(d[7]),
          "=f"(d[8]), "=f"(d[9]), "=f"(d[10]), "=f"(d[11]), "=f"(d[12]), "=f"(d[13]), "=f"(d[14]), "=f"(d[15]),
          "=f"(d[16]), "=f"(d[17]), "=f"(d[18]), "=f"(d[19]), "=f"(d[20]), "=f"(d[21]), "=f"(d[22]), "=f"(d[23]),
          "=f"(d[24]), "=f"(d[25]), "=f"(d[26]), "=f"(d[27]), "=f"(d[28]), "=f"(d[29]), "=f"(d[30]), "=f"(d[31]),
          "=f"(d[32]), "=f"(d[33]), "=f"(d[34]), "=f"(d[35]), "=f"(d[36]), "=f"(d[37]), "=f"(d[38]), "=f"(d[39]),
          "=f"(d[40]), "=f"(d[41]), "=f"(d[42]), "=f"(d[43]), "=f"(d[44]), "=f"(d[45]), "=f"(d[46]), "=f"(d[47]),
          "=f"(d[48]), "=f"(d[49]), "=f"(d[50]), "=f"(d[51]), "=f"(d[52]), "=f"(d[53]), "=f"(d[54]), "=f"(d[55]),
          "=f"(d[56]), "=f"(d[57]), "=f"(d[58]), "=f"(d[59]), "=f"(d[60]), "=f"(d[61]), "=f"(d[62]), "=f"(d[63])
        : "r"(a0), "r"(a1), "r"(a2), "r"(a3), "r"(blo), "n"(0), "n"(TB), "r"(DESC_HI));
}
template <int TA, int TB>
__device__ __forceinline__ void wgmma_ss_n128_z(float (&d)[64], uint32_t alo, uint32_t blo) {
    asm volatile("{\n.reg .pred p;\n.reg .b64 da, db;\nsetp.ne.b32 p, %66, 0;\n"
        "mov.b64 da, {%64, %69};\nmov.b64 db, {%65, %69};\n"
        "wgmma.mma_async.sync.aligned.m64n128k16.f32.bf16.bf16 "
        "{%0, %1, %2, %3, %4, %5, %6, %7, %8, %9, %10, %11, %12, %13, %14, %15, %16, %17, %18, %19, %20, %21, %22, %23, %24, %25, %26, %27, %28, %29, %30, %31, %32, %33, %34, %35, %36, %37, %38, %39, %40, %41, %42, %43, %44, %45, %46, %47, %48, %49, %50, %51, %52, %53, %54, %55, %56, %57, %58, %59, %60, %61, %62, %63}, da, db, p, 1, 1, %67, %68;\n}\n"
        :
          "=f"(d[0]), "=f"(d[1]), "=f"(d[2]), "=f"(d[3]), "=f"(d[4]), "=f"(d[5]), "=f"(d[6]), "=f"(d[7]),
          "=f"(d[8]), "=f"(d[9]), "=f"(d[10]), "=f"(d[11]), "=f"(d[12]), "=f"(d[13]), "=f"(d[14]), "=f"(d[15]),
          "=f"(d[16]), "=f"(d[17]), "=f"(d[18]), "=f"(d[19]), "=f"(d[20]), "=f"(d[21]), "=f"(d[22]), "=f"(d[23]),
          "=f"(d[24]), "=f"(d[25]), "=f"(d[26]), "=f"(d[27]), "=f"(d[28]), "=f"(d[29]), "=f"(d[30]), "=f"(d[31]),
          "=f"(d[32]), "=f"(d[33]), "=f"(d[34]), "=f"(d[35]), "=f"(d[36]), "=f"(d[37]), "=f"(d[38]), "=f"(d[39]),
          "=f"(d[40]), "=f"(d[41]), "=f"(d[42]), "=f"(d[43]), "=f"(d[44]), "=f"(d[45]), "=f"(d[46]), "=f"(d[47]),
          "=f"(d[48]), "=f"(d[49]), "=f"(d[50]), "=f"(d[51]), "=f"(d[52]), "=f"(d[53]), "=f"(d[54]), "=f"(d[55]),
          "=f"(d[56]), "=f"(d[57]), "=f"(d[58]), "=f"(d[59]), "=f"(d[60]), "=f"(d[61]), "=f"(d[62]), "=f"(d[63])
        : "r"(alo), "r"(blo), "n"(0), "n"(TA), "n"(TB), "r"(DESC_HI));
}

__device__ __forceinline__ uint32_t pack_bf16(float lo, float hi) {
    uint32_t r;
    asm("cvt.rn.bf16x2.f32 %0, %1, %2;" : "=r"(r) : "f"(hi), "f"(lo));
    return r;
}
__device__ __forceinline__ float bf_lo(uint32_t v) { return __uint_as_float(v << 16); }
__device__ __forceinline__ float bf_hi(uint32_t v) { return __uint_as_float(v & 0xffff0000u); }
__device__ __forceinline__ float round_bf16(float v) { return __bfloat162float(__float2bfloat16_rn(v)); }
__device__ __forceinline__ float ex2(float x) {
    float y;
    asm("ex2.approx.ftz.f32 %0, %1;" : "=f"(y) : "f"(x));
    return y;
}
__device__ __forceinline__ float rcp(float x) {
    float y;
    asm("rcp.approx.ftz.f32 %0, %1;" : "=f"(y) : "f"(x));
    return y;
}
__device__ __forceinline__ void stg128(void* p, uint32_t a, uint32_t b, uint32_t c, uint32_t d) {
    asm volatile("st.global.v4.b32 [%0], {%1, %2, %3, %4};" ::"l"(p), "r"(a), "r"(b), "r"(c), "r"(d) : "memory");
}
__device__ __forceinline__ int perm_row(int t) { return (t & ~255) | (((0x78 >> (((t >> 6) & 3) * 2)) & 3) << 6) | (t & 63); }
__device__ __forceinline__ int unperm_row(int t) { return (t & ~255) | (((0x9C >> (((t >> 6) & 3) * 2)) & 3) << 6) | (t & 63); }

#define PROF(i)
#define PROFG(i)
#define LP(i)

__device__ __forceinline__ void store_tile(const float (&a)[64], __nv_bfloat16* row0, __nv_bfloat16* row1, float s0, float s1) {
#pragma unroll
    for (int i = 0; i < 4; i++) {
        stg128(row0 + 32 * i, pack_bf16(a[16 * i + 0] * s0, a[16 * i + 1] * s0), pack_bf16(a[16 * i + 4] * s0, a[16 * i + 5] * s0),
               pack_bf16(a[16 * i + 8] * s0, a[16 * i + 9] * s0), pack_bf16(a[16 * i + 12] * s0, a[16 * i + 13] * s0));
        stg128(row1 + 32 * i, pack_bf16(a[16 * i + 2] * s1, a[16 * i + 3] * s1), pack_bf16(a[16 * i + 6] * s1, a[16 * i + 7] * s1),
               pack_bf16(a[16 * i + 10] * s1, a[16 * i + 11] * s1), pack_bf16(a[16 * i + 14] * s1, a[16 * i + 15] * s1));
    }
}

struct Prod {
    uint32_t smem, bars, pe;
    int ring;
    __device__ __forceinline__ uint32_t acquire(int s, uint32_t bytes) {
        mbar_wait(bars + BAR_EMPTY + s * 8, (pe >> s) & 1);
        pe ^= 1u << s;
        mbar_expect_tx(bars + BAR_FULL + s * 8, bytes);
        return bars + BAR_FULL + s * 8;
    }
    __device__ __forceinline__ int next() {
        int s = ring;
        ring = (ring == NSLOT - 1) ? 0 : ring + 1;
        return s;
    }
};

__device__ __forceinline__ int slot_a(int i) { return (0x5310 >> (4 * i)) & 15; }
__device__ __forceinline__ int slot_w(int m) { return (0x264 >> (4 * m)) & 15; }

__device__ __forceinline__ void producer(const Params& P, uint32_t smem, uint32_t bars, uint32_t epoch, int ca, int cb, int rank) {
    Prod pr{smem, bars, 0x7fu, 0};
    {
        const int row0 = (2 * ca + rank) * 128;
        int m = 0;
        for (int u = 0; u < 32; u++) {
            if (u < 4) {
                int s = slot_a(u);
                uint32_t fb = pr.acquire(s, SLOT);
                tma_load(smem + s * SLOT, &P.ckv, u * 128, row0, fb);
                tma_load(smem + s * SLOT + 16384, &P.ckv, u * 128 + 64, row0, fb);
            }
            int s = slot_w(m);
            m = (m == 2) ? 0 : m + 1;
            uint32_t fb = pr.acquire(s, SLOT);
            int h = cb + 8 * (u >> 3);
            tma_load_mc(smem + s * SLOT + rank * 16384, (u & 4) ? &P.wuv : &P.wuk, h * 128 + rank * 64, (u & 3) * 128, fb);
        }
    }
    PROF(1);
    flag_wait(F_LN, 256u * (epoch + 1));
    fence_proxy_async();
    PROF(2);
    for (int rd = 0; rd < 4; rd++) {
        const int h = 8 * rd + cb, p = (rd & 1) ? 7 - ca : ca;
        for (int ks = 0; ks < 10; ks++) {
            int s = pr.next();
            uint32_t fb = pr.acquire(s, SLOT);
            tma_load(smem + s * SLOT, &P.xn, ks * 64, 256 * p + 128 * rank, fb);
            tma_load_mc(smem + s * SLOT + 16384 + rank * 8192, &P.wq, h * 128 + rank * 64, ks * 64, fb);
        }
        PROF(8 + rd * 4);
        flag_wait(F_KV + h, 32u * (epoch + 1));
        PROF(9 + rd * 4);
        fence_proxy_async();
        PROF(10 + rd * 4);
        const int n = 2 * p + 2;
        for (int i = 0; i <= n; i++) {
            if (i < n) {
                int s = pr.next();
                uint32_t fb = pr.acquire(s, SLOT);
                tma_load_mc(smem + s * SLOT + rank * 16384, &P.kv, rank * 64, KVROW(((h * 16 + (n - 1 - i)) * 2) * 128), fb);
            }
            if (i > 0) {
                int s = pr.next();
                uint32_t fb = pr.acquire(s, SLOT);
                tma_load_mc(smem + s * SLOT + rank * 16384, &P.kv, rank * 64, KVROW(((h * 16 + (n - i)) * 2 + 1) * 128), fb);
            }
        }
    }
    {
        const int p = ca, n0 = 320 * (cb & 1), kg = cb >> 1;
        for (int t = 0; t < 16; t++) {
            const int h = 8 * (t >> 2) + 2 * kg + ((t >> 1) & 1), ks = t & 1;
            const int krow = h * 128 + ks * 64 + rank * 32;
            int s = pr.next();
            uint32_t fb = pr.acquire(s, SLOT);
            tma_load_mc(smem + s * SLOT + 16384 + rank * 8192, &P.wo, n0, krow, fb);
            tma_load_mc(smem + s * SLOT + 16384 + rank * 8192 + 4096, &P.wo, n0 + 64, krow, fb);
            if (ks == 0) {
                flag_wait(F_CTX + h * 16 + p * 2 + rank, 2u * (epoch + 1));
                fence_proxy_async();
            }
            tma_load(smem + s * SLOT, &P.ctx, ks * 64, h * SEQ + 256 * p + 128 * rank, fb);
            s = pr.next();
            fb = pr.acquire(s, 24576);
#pragma unroll
            for (int c = 0; c < 3; c++) tma_load_mc(smem + s * SLOT + rank * 12288 + c * 4096, &P.wo, n0 + 128 + 64 * c, krow, fb);
        }
    }
}

struct Cons {
    uint32_t smem, bars, rel, pf;
    int ring;
    bool rel_on;
    __device__ __forceinline__ void wait(int s) {
        mbar_wait(bars + BAR_FULL + s * 8, (pf >> s) & 1);
        pf ^= 1u << s;
    }
    __device__ __forceinline__ void release(int s) {
        if (rel_on) mbar_arrive_cluster(rel + s * 8);
    }
    __device__ __forceinline__ int next() {
        int s = ring;
        ring = (ring == NSLOT - 1) ? 0 : ring + 1;
        return s;
    }
};

__device__ __forceinline__ void layernorm_rows(const Params& P, int cta, int cw  , int lane) {
    const int t = cta * 16 + cw * 2 + (lane >> 4), l = lane & 15;
    const uint4* xr = reinterpret_cast<const uint4*>(P.x + (size_t)t * DM);
    const uint4* wr = reinterpret_cast<const uint4*>(P.wr);
    uint4 xv[5], wv[5];
#pragma unroll
    for (int i = 0; i < 5; i++) xv[i] = __ldg(xr + l + 16 * i);
#pragma unroll
    for (int i = 0; i < 5; i++) wv[i] = __ldg(wr + l + 16 * i);
    float v[40];
#pragma unroll
    for (int i = 0; i < 5; i++) {
        v[8 * i + 0] = bf_lo(xv[i].x); v[8 * i + 1] = bf_hi(xv[i].x); v[8 * i + 2] = bf_lo(xv[i].y); v[8 * i + 3] = bf_hi(xv[i].y);
        v[8 * i + 4] = bf_lo(xv[i].z); v[8 * i + 5] = bf_hi(xv[i].z); v[8 * i + 6] = bf_lo(xv[i].w); v[8 * i + 7] = bf_hi(xv[i].w);
    }
    float sum = 0.f;
#pragma unroll
    for (int i = 0; i < 40; i++) sum += v[i];
#pragma unroll
    for (int o = 8; o > 0; o >>= 1) sum += __shfl_xor_sync(0xffffffffu, sum, o);
    const float mean = __fdiv_rn(sum, (float)DM);
    float sq = 0.f;
#pragma unroll
    for (int i = 0; i < 40; i++) { float d = v[i] - mean; sq += d * d; }
#pragma unroll
    for (int o = 8; o > 0; o >>= 1) sq += __shfl_xor_sync(0xffffffffu, sq, o);
    const float mb = round_bf16(mean);
    const float sd = round_bf16(__fsqrt_rn(round_bf16(round_bf16(__fdiv_rn(sq, (float)DM)) + 1e-5f)));
    uint4* dst = reinterpret_cast<uint4*>(g_xn + (size_t)perm_row(t) * DM);
    float r = 0.f;
#pragma unroll
    for (int i = 0; i < 5; i++) {
        uint32_t o[4];
        const uint32_t w[4] = {wv[i].x, wv[i].y, wv[i].z, wv[i].w};
#pragma unroll
        for (int j = 0; j < 4; j++) {
            o[j] = pack_bf16(__fdiv_rn(round_bf16(v[8 * i + 2 * j] - mb), sd), __fdiv_rn(round_bf16(v[8 * i + 2 * j + 1] - mb), sd));
            r += bf_lo(o[j]) * bf_lo(w[j]);
            r += bf_hi(o[j]) * bf_hi(w[j]);
        }
        dst[l + 16 * i] = make_uint4(o[0], o[1], o[2], o[3]);
    }
#pragma unroll
    for (int o = 8; o > 0; o >>= 1) r += __shfl_xor_sync(0xffffffffu, r, o);
    if (l == 0) g_r[t] = round_bf16(r);
}

constexpr float SM_SCALE = 0.08838834764831845f * 1.4426950408889634f;

__device__ __forceinline__ void row_max(const float (&s)[64], float& mx0, float& mx1) {
    float a0 = fmaxf(s[0], s[1]), a1 = fmaxf(s[4], s[5]), b0 = fmaxf(s[2], s[3]), b1 = fmaxf(s[6], s[7]);
#pragma unroll
    for (int j = 2; j < 16; j += 2) {
        a0 = fmaxf(a0, fmaxf(s[4 * j], s[4 * j + 1]));
        a1 = fmaxf(a1, fmaxf(s[4 * j + 4], s[4 * j + 5]));
        b0 = fmaxf(b0, fmaxf(s[4 * j + 2], s[4 * j + 3]));
        b1 = fmaxf(b1, fmaxf(s[4 * j + 6], s[4 * j + 7]));
    }
    mx0 = fmaxf(a0, a1);
    mx1 = fmaxf(b0, b1);
    mx0 = fmaxf(mx0, __shfl_xor_sync(0xffffffffu, mx0, 1));
    mx1 = fmaxf(mx1, __shfl_xor_sync(0xffffffffu, mx1, 1));
    mx0 = fmaxf(mx0, __shfl_xor_sync(0xffffffffu, mx0, 2));
    mx1 = fmaxf(mx1, __shfl_xor_sync(0xffffffffu, mx1, 2));
}
template <int J0, int J1>
__device__ __forceinline__ void exp_part(float (&s)[64], float n0, float n1, float& r0, float& r1) {
    float a1 = 0.f, b1 = 0.f;
#pragma unroll
    for (int j = J0; j < J1; j++) {
        s[4 * j + 0] = ex2(fmaf(s[4 * j + 0], SM_SCALE, n0));
        s[4 * j + 1] = ex2(fmaf(s[4 * j + 1], SM_SCALE, n0));
        s[4 * j + 2] = ex2(fmaf(s[4 * j + 2], SM_SCALE, n1));
        s[4 * j + 3] = ex2(fmaf(s[4 * j + 3], SM_SCALE, n1));
        r0 += s[4 * j + 0]; a1 += s[4 * j + 1]; r1 += s[4 * j + 2]; b1 += s[4 * j + 3];
    }
    r0 += a1;
    r1 += b1;
}
__device__ __forceinline__ void sched_barrier(float x, float y, uint32_t scratch) {
    asm volatile("{\n.reg .pred p;\nsetp.lt.f32 p, %0, 0f00000000;\n@p st.shared.f32 [%2], %1;\n}\n" ::"f"(x), "f"(y), "r"(scratch) : "memory");
}
__device__ __forceinline__ void pack_tile(const float (&s)[64], uint32_t (&p)[32]) {
#pragma unroll
    for (int i = 0; i < 32; i++) p[i] = pack_bf16(s[2 * i], s[2 * i + 1]);
}
template <bool ZERO>
__device__ __forceinline__ void gemm_rs(float (&d)[64], const uint32_t (&a)[32], uint32_t slot_addr) {
    const uint32_t b = __shfl_sync(0xffffffffu, desc_lo(slot_addr, 16384), 0);
    if (ZERO) wgmma_rs_n128_z<1>(d, a[0], a[1], a[2], a[3], b);
#pragma unroll
    for (int k = ZERO ? 1 : 0; k < 8; k++) wgmma_rs_n128<1>(d, a[4 * k], a[4 * k + 1], a[4 * k + 2], a[4 * k + 3], b + k * 128, 1);
}
template <bool ZERO>
__device__ __forceinline__ void gemm_q(float (&d)[64], uint32_t slot_addr, int role) {
    const uint32_t a = desc_lo(slot_addr + role * 8192, 16), b = desc_lo(slot_addr + 16384, 8192);
    if (ZERO) wgmma_ss_n128_z<0, 1>(d, a, b);
#pragma unroll
    for (int k = ZERO ? 1 : 0; k < 4; k++) wgmma_ss_n128<0, 1>(d, a + k * 2, b + k * 128, 1);
}

__device__ __forceinline__ void signal(uint32_t bars, int wg, int e, int lane) {
    __syncwarp();
    if (lane == 0) mbar_arrive(bars + BAR_SIG + (wg * 9 + e) * 8);
}

__device__ __forceinline__ void consumer(const Params& P, uint32_t smem, uint32_t bars, uint32_t epoch, int ca, int cb, int rank, int wg) {
    const int lane = threadIdx.x & 31, w = (threadIdx.x >> 5) & 3, q = lane & 3, lr = lane >> 2;
    layernorm_rows(P, blockIdx.x, wg * 4 + w, lane);
    signal(bars, wg, 0, lane);
    cluster_wait();
    Cons c{smem, bars, mapa(bars + BAR_EMPTY, lane & 1), 0u, 0, lane < 2};
    PROF(1);
    float o[64], s[64];
    int pend0, pend1;
    __nv_bfloat16* ep_ptr;
    int ep_step;
    {
        const int j = 2 * ca + rank;
        const int krow = 64 * wg + 16 * w + lr;
        const int vrow = 64 * wg + 32 * (w >> 1) + 8 * (lr >> 1) + 4 * (w & 1) + (lr & 1);
        int m = 0, prev = -1;
        for (int hh = 0; hh < 4; hh++) {
#pragma unroll
            for (int kc = 0; kc < 4; kc++) {
                const int sa = slot_a(kc), sw = slot_w(m);
                m = (m == 2) ? 0 : m + 1;
                if (hh == 0) c.wait(sa);
                c.wait(sw);
                const uint32_t da = desc_lo(smem + sw * SLOT + wg * 16384, 16), db = desc_lo(smem + sa * SLOT, 16);
                wgmma_fence();
#pragma unroll
                for (int k = 0; k < 8; k++) wgmma_ss_n128<1, 0>(s, da + k * 128, db + (k >> 2) * 1024 + (k & 3) * 2, (kc | k) ? 1 : 0);
                wgmma_commit();
                wgmma_wait<1>();
                if (prev >= 0) c.release(prev);
                prev = sw;
                if (kc == 0 && hh > 0) {
                    fence_regs(o);
                    __nv_bfloat16* base = g_kv + (size_t)(((cb + 8 * (hh - 1)) * 16 + j) * 2 + 1) * 16384 + 8 * q;
                    store_tile(o, base + vrow * 128, base + (vrow + 2) * 128, 1.f, 1.f);
                    signal(bars, wg, hh, lane);
                }
            }
#pragma unroll
            for (int kc = 0; kc < 4; kc++) {
                const int sa = slot_a(kc), sw = slot_w(m);
                m = (m == 2) ? 0 : m + 1;
                c.wait(sw);
                const uint32_t da = desc_lo(smem + sa * SLOT + wg * 8192, 16), db = desc_lo(smem + sw * SLOT, 16384);
                wgmma_fence();
#pragma unroll
                for (int k = 0; k < 8; k++) wgmma_ss_n128<0, 1>(o, da + (k >> 2) * 1024 + (k & 3) * 2, db + k * 128, (kc | k) ? 1 : 0);
                wgmma_commit();
                wgmma_wait<1>();
                c.release(prev);
                if (hh == 3 && kc > 0) c.release(slot_a(kc - 1));
                prev = sw;
                if (kc == 0) {
                    fence_regs(s);
                    __nv_bfloat16* base = g_kv + (size_t)(((cb + 8 * hh) * 16 + j) * 2) * 16384 + 8 * q;
                    store_tile(s, base + krow * 128, base + (krow + 8) * 128, 1.f, 1.f);
                }
            }
        }
        pend0 = slot_a(3); pend1 = prev;
        ep_ptr = g_kv + (size_t)(((cb + 24) * 16 + j) * 2 + 1) * 16384 + 8 * q + vrow * 128;
        ep_step = 2 * 128;
    }
    PROF(2);
    {
        uint32_t pf[32], qf[32];
        float l0 = 1.f, l1 = 1.f;
        const int bar_me = 2 + wg, bar_other = 3 - wg;
        for (int rd = 0; rd < 4; rd++) {
            const int h = 8 * rd + cb, p = (rd & 1) ? 7 - ca : ca;
            const int role = wg ^ (rd & 1);
            {
                const int s0 = c.next(), s1 = c.next();
                c.wait(s0);
                wgmma_fence();
                gemm_q<true>(s, smem + s0 * SLOT, role);
                c.wait(s1);
                wgmma_fence();
                gemm_q<false>(s, smem + s1 * SLOT, role);
                wgmma_commit();
                wgmma_wait<1>();
                c.release(pend0);
                if (pend1 >= 0) c.release(pend1);
                fence_regs(o);
                store_tile(o, ep_ptr, ep_ptr + ep_step, rcp(l0), rcp(l1));
                signal(bars, wg, 4 + rd, lane);
                PROF(11 + rd * 4);
                int prev = -1;
                for (int ks = 2; ks < 10; ks++) {
                    const int sl = c.next();
                    c.wait(sl);
                    wgmma_fence();
                    gemm_q<false>(s, smem + sl * SLOT, role);
                    wgmma_commit();
                    wgmma_wait<1>();
                    if (prev >= 0) c.release(prev);
                    else { c.release(s0); c.release(s1); }
                    prev = sl;
                }
                wgmma_wait<0>();
                c.release(prev);
                fence_regs(s);
                pack_tile(s, qf);
            }
            PROF(8 + rd * 4);
            const int nrest = 2 * p + role;
            if (!role) { const int sl = c.next(); c.wait(sl); c.release(sl); }
            {
                const int sl = c.next();
                c.wait(sl);
                fence_regs(qf);
                if (PINGPONG && !role) named_sync(bar_me, 256);
                wgmma_fence();
                gemm_rs<true>(s, qf, smem + sl * SLOT);
                wgmma_commit();
                if (PINGPONG) named_arrive(bar_other, 256);
                if (!role) { const int s2 = c.next(); c.wait(s2); c.release(s2); }
                wgmma_wait<0>();
                c.release(sl);
                fence_regs(s);
            }
            {
                const int rr = 64 * (role ^ rank) + 16 * w + lr - 8 * q;
#pragma unroll
                for (int j = 0; j < 16; j++) {
                    const int cc = 32 * (j >> 2) + 2 * (j & 3);
                    if (cc > rr) s[4 * j] = -INFINITY;
                    if (cc + 1 > rr) s[4 * j + 1] = -INFINITY;
                    if (cc > rr + 8) s[4 * j + 2] = -INFINITY;
                    if (cc + 1 > rr + 8) s[4 * j + 3] = -INFINITY;
                }
            }
            float m0, m1;
            row_max(s, m0, m1);
            l0 = 0.f; l1 = 0.f;
            exp_part<0, 16>(s, -m0 * SM_SCALE, -m1 * SM_SCALE, l0, l1);
            pack_tile(s, pf);
#pragma unroll
            for (int i = 0; i < 64; i++) o[i] = 0.f;
            PROF(9 + rd * 4);
            for (int it = 0; it < nrest; it++) {
                const int sk = c.next(), sv = c.next();
                LP(0);
                c.wait(sk);
                c.wait(sv);
                fence_regs(o); fence_regs(pf);
                LP(1);
                if (PINGPONG) named_sync(bar_me, 256);
                LP(2);
                wgmma_fence();
                gemm_rs<true>(s, qf, smem + sk * SLOT);
                wgmma_commit();
                gemm_rs<false>(o, pf, smem + sv * SLOT);
                wgmma_commit();
                if (PINGPONG) named_arrive(bar_other, 256);
                LP(3);
                wgmma_wait<1>();
                LP(4);
                c.release(sk);
                fence_regs(s);
                float x0, x1;
                row_max(s, x0, x1);
                x0 = fmaxf(x0, m0); x1 = fmaxf(x1, m1);
                const float a0 = ex2((m0 - x0) * SM_SCALE), a1 = ex2((m1 - x1) * SM_SCALE);
                m0 = x0; m1 = x1;
                const float n0 = -m0 * SM_SCALE, n1 = -m1 * SM_SCALE;
                l0 *= a0; l1 *= a1;
                exp_part<0, SPLITJ>(s, n0, n1, l0, l1);
                sched_barrier(l0, l1, bars + MISC_OFF + 16);
                LP(5);
                wgmma_wait<0>();
                LP(6);
                c.release(sv);
                fence_regs(o); fence_regs(pf);
                exp_part<SPLITJ, 16>(s, n0, n1, l0, l1);
#pragma unroll
                for (int j = 0; j < 16; j++) { o[4 * j] *= a0; o[4 * j + 1] *= a0; o[4 * j + 2] *= a1; o[4 * j + 3] *= a1; }
                pack_tile(s, pf);
            }
            PROF(10 + rd * 4);
            {
                const int sv = c.next();
                c.wait(sv);
                fence_regs(o); fence_regs(pf);
                if (PINGPONG && !role) named_sync(bar_me, 256);
                wgmma_fence();
                gemm_rs<false>(o, pf, smem + sv * SLOT);
                wgmma_commit();
                l0 += __shfl_xor_sync(0xffffffffu, l0, 1); l1 += __shfl_xor_sync(0xffffffffu, l1, 1);
                l0 += __shfl_xor_sync(0xffffffffu, l0, 2); l1 += __shfl_xor_sync(0xffffffffu, l1, 2);
                pend0 = sv; pend1 = -1;
                ep_ptr = g_ctx + (size_t)(h * SEQ + 256 * p + 128 * rank + 64 * role + 16 * w + lr) * HD + 8 * q;
                ep_step = 8 * HD;
            }
        }
        wgmma_wait<0>();
        c.release(pend0);
        fence_regs(o); fence_regs(pf);
        store_tile(o, ep_ptr, ep_ptr + ep_step, rcp(l0), rcp(l1));
        signal(bars, wg, 8, lane);
    }
    PROF(3);
    {
        float a1[64], a2[96];
        int px = -1, py = -1;
        for (int t = 0; t < 16; t++) {
            const int sx = c.next(), sy = c.next();
            c.wait(sx);
            const uint32_t da = desc_lo(smem + sx * SLOT + wg * 8192, 16);
            const uint32_t b1 = desc_lo(smem + sx * SLOT + 16384, 4096), b2 = desc_lo(smem + sy * SLOT, 4096);
            wgmma_fence();
#pragma unroll
            for (int k = 0; k < 4; k++) wgmma_ss_n128<0, 1>(a1, da + k * 2, b1 + (k >> 1) * 512 + (k & 1) * 128, k ? 1 : t);
            c.wait(sy);
            wgmma_fence();
#pragma unroll
            for (int k = 0; k < 4; k++) wgmma_ss_n192<0, 1>(a2, da + k * 2, b2 + (k >> 1) * 768 + (k & 1) * 128, k ? 1 : t);
            wgmma_commit();
            wgmma_wait<1>();
            if (px >= 0) { c.release(px); c.release(py); }
            px = sx; py = sy;
        }
        wgmma_wait<0>();
        fence_regs(a1); fence_regs(a2);
        PROF(4);
        const int nh = cb & 1, kg = cb >> 1, tile = (ca * 2 + rank) * 2 + nh;
        float* dst = g_part + ((size_t)(tile * 4 + kg) * 128 + 64 * wg + 16 * w + lr) * 320 + 2 * q;
#pragma unroll
        for (int j = 0; j < 16; j++) {
            *reinterpret_cast<float2*>(dst + 8 * j) = make_float2(a1[4 * j], a1[4 * j + 1]);
            *reinterpret_cast<float2*>(dst + 8 * 320 + 8 * j) = make_float2(a1[4 * j + 2], a1[4 * j + 3]);
        }
#pragma unroll
        for (int j = 0; j < 24; j++) {
            *reinterpret_cast<float2*>(dst + 128 + 8 * j) = make_float2(a2[4 * j], a2[4 * j + 1]);
            *reinterpret_cast<float2*>(dst + 8 * 320 + 128 + 8 * j) = make_float2(a2[4 * j + 2], a2[4 * j + 3]);
        }
        const int tid = threadIdx.x - 128;
        named_sync(1, 256);
        if (tid == 0) {
            flag_add(F_PART + tile);
            flag_wait(F_PART + tile, 4u * (epoch + 1));
            flag_wait(F_MOD, 4u * (epoch + 1));
        }
        named_sync(1, 256);
        PROF(5);
        const int lrow = 32 * kg + (tid >> 3);
        const int prow = 256 * ca + 128 * rank + lrow, trow = unperm_row(prow);
        int sel = -1;
#pragma unroll
        for (int i = 0; i < 8; i++) if (__ldcg(g_idx + i) == trow) sel = i;
#pragma unroll
        for (int i = 0; i < 5; i++) {
            const int col = 8 * ((tid & 7) + 8 * i), gcol = 320 * nh + col;
            float v[8];
            const uint4 xv = __ldg(reinterpret_cast<const uint4*>(P.x + (size_t)trow * DM + gcol));
            const uint4 nv = __ldcg(reinterpret_cast<const uint4*>(g_xn + (size_t)prow * DM + gcol));
            v[0] = bf_lo(xv.x) + bf_lo(nv.x); v[1] = bf_hi(xv.x) + bf_hi(nv.x); v[2] = bf_lo(xv.y) + bf_lo(nv.y); v[3] = bf_hi(xv.y) + bf_hi(nv.y);
            v[4] = bf_lo(xv.z) + bf_lo(nv.z); v[5] = bf_hi(xv.z) + bf_hi(nv.z); v[6] = bf_lo(xv.w) + bf_lo(nv.w); v[7] = bf_hi(xv.w) + bf_hi(nv.w);
#pragma unroll
            for (int k = 0; k < 4; k++) {
                const float4* src = reinterpret_cast<const float4*>(g_part + ((size_t)(tile * 4 + k) * 128 + lrow) * 320 + col);
                const float4 u0 = __ldcg(src), u1 = __ldcg(src + 1);
                v[0] += u0.x; v[1] += u0.y; v[2] += u0.z; v[3] += u0.w; v[4] += u1.x; v[5] += u1.y; v[6] += u1.z; v[7] += u1.w;
            }
            if (sel >= 0) {
                const float rs = __ldcg(g_rsel + sel);
#pragma unroll
                for (int e = 0; e < 8; e++) {
                    float y = 0.f;
#pragma unroll
                    for (int k = 0; k < 4; k++) y += __ldcg(g_ypart + (k * 8 + sel) * DM + gcol + e);
                    v[e] += round_bf16(round_bf16(y) * rs);
                }
            }
            stg128(P.out + (size_t)trow * DM + gcol, pack_bf16(v[0], v[1]), pack_bf16(v[2], v[3]), pack_bf16(v[4], v[5]), pack_bf16(v[6], v[7]));
        }
    }
    PROF(6);
}

__device__ __forceinline__ void mma16816(float (&d)[4], uint32_t a0, uint32_t a2, uint32_t b0, uint32_t b1) {
    asm volatile("mma.sync.aligned.m16n8k16.row.col.f32.bf16.bf16.f32 {%0,%1,%2,%3}, {%4,%5,%6,%5}, {%7,%8}, {%0,%1,%2,%3};"
                 : "+f"(d[0]), "+f"(d[1]), "+f"(d[2]), "+f"(d[3]) : "r"(a0), "r"(0u), "r"(a2), "r"(b0), "r"(b1));
}
__device__ __forceinline__ void mma_rows(float (&acc)[8][4], uint32_t a0, uint32_t a2, const uint4& w0, const uint4& w1, const uint4& w2, const uint4& w3) {
    const uint32_t r0[4] = {w0.x, w0.y, w0.z, w0.w}, r1[4] = {w1.x, w1.y, w1.z, w1.w};
    const uint32_t r2[4] = {w2.x, w2.y, w2.z, w2.w}, r3[4] = {w3.x, w3.y, w3.z, w3.w};
#pragma unroll
    for (int i = 0; i < 4; i++) {
        mma16816(acc[2 * i], a0, a2, __byte_perm(r0[i], r1[i], 0x5410), __byte_perm(r2[i], r3[i], 0x5410));
        mma16816(acc[2 * i + 1], a0, a2, __byte_perm(r0[i], r1[i], 0x7632), __byte_perm(r2[i], r3[i], 0x7632));
    }
}

__device__ __forceinline__ void mod_ffn(const Params& P, uint8_t* sm, uint32_t epoch, int mc  ) {
    const int tid = threadIdx.x - 128, lane = tid & 31, cw = tid >> 5, q = lane & 3, lr = lane >> 2;
    float* red = reinterpret_cast<float*>(sm);
    uint32_t* xs = reinterpret_cast<uint32_t*>(sm + 8 * 8 * DM * 4);
    uint32_t* wmax = xs + 8 * 324;
    int* sidx = reinterpret_cast<int*>(wmax + 16);
    if (tid == 0) flag_wait(F_LN, 256u * (epoch + 1));
    named_sync(1, 256);
    uint32_t key[8];
#pragma unroll
    for (int i = 0; i < 8; i++) {
        const int t = tid + 256 * i;
        uint32_t b = __float_as_uint(__ldcg(g_r + t) + 0.f) >> 16;
        b = (b & 0x8000u) ? (~b & 0xffffu) : (b | 0x8000u);
        key[i] = (b << 16) | (uint32_t)(0xffff - t);
    }
    for (int rnd = 0; rnd < 8; rnd++) {
        uint32_t mx = key[0];
#pragma unroll
        for (int i = 1; i < 8; i++) mx = max(mx, key[i]);
        mx = __reduce_max_sync(0xffffffffu, mx);
        if (lane == 0) wmax[(rnd & 1) * 8 + cw] = mx;
        named_sync(1, 256);
        mx = __reduce_max_sync(0xffffffffu, wmax[(rnd & 1) * 8 + (lane & 7)]);
#pragma unroll
        for (int i = 0; i < 8; i++) if (key[i] == mx) key[i] = 0;
        if (tid == 0) sidx[rnd] = 0xffff - (int)(mx & 0xffffu);
    }
    named_sync(1, 256);
    if (mc == 0 && tid < 8) {
        const int t = sidx[tid];
        g_idx[tid] = t;
        g_rsel[tid] = round_bf16(1.0f / (1.0f + __expf(-__ldcg(g_r + t))));
    }
    {
        const uint32_t* src = reinterpret_cast<const uint32_t*>(g_xn + (size_t)perm_row(sidx[cw]) * DM);
        for (int i = lane; i < 320; i += 32) xs[cw * 324 + i] = __ldcg(src + i);
    }
    named_sync(1, 256);
    const int fg = cw * 4 + mc;
    float* myred = red + cw * 8 * DM + lr * DM + 16 * q;
    if (fg < 27) {
        float g[8][4], u[8][4];
#pragma unroll
        for (int i = 0; i < 8; i++)
#pragma unroll
            for (int e = 0; e < 4; e++) { g[i][e] = 0.f; u[i][e] = 0.f; }
        const __nv_bfloat16* wg = P.wg + (size_t)(2 * q) * FF + fg * 64 + 8 * lr;
        const __nv_bfloat16* wu = P.wu + (size_t)(2 * q) * FF + fg * 64 + 8 * lr;
#pragma unroll 1
        for (int k0 = 0; k0 < 40; k0 += 4) {
            uint4 a[4][4], b[4][4];
#pragma unroll
            for (int kk = 0; kk < 4; kk++)
#pragma unroll
                for (int r = 0; r < 4; r++) {
                    const size_t off = (size_t)((k0 + kk) * 16 + (r & 1) + 8 * (r >> 1)) * FF;
                    a[kk][r] = __ldg(reinterpret_cast<const uint4*>(wg + off));
                    b[kk][r] = __ldg(reinterpret_cast<const uint4*>(wu + off));
                }
#pragma unroll
            for (int kk = 0; kk < 4; kk++) {
                const uint32_t a0 = xs[lr * 324 + (k0 + kk) * 8 + q], a2 = xs[lr * 324 + (k0 + kk) * 8 + 4 + q];
                mma_rows(g, a0, a2, a[kk][0], a[kk][1], a[kk][2], a[kk][3]);
                mma_rows(u, a0, a2, b[kk][0], b[kk][1], b[kk][2], b[kk][3]);
            }
        }
        float hv[16];
#pragma unroll
        for (int i = 0; i < 8; i++)
#pragma unroll
            for (int e = 0; e < 2; e++) {
                const float gp = round_bf16(g[i][e]);
                const float sg = round_bf16(gp / (1.0f + __expf(-gp)));
                hv[8 * e + i] = sg * round_bf16(u[i][e]);
            }
        uint32_t hp[8];
#pragma unroll
        for (int i = 0; i < 8; i++) hp[i] = pack_bf16(hv[2 * i], hv[2 * i + 1]);
        const __nv_bfloat16* wd = P.wd + (size_t)(fg * 64 + 16 * q) * DM + 8 * lr;
#pragma unroll 1
        for (int dg = 0; dg < 10; dg += 2) {
            uint4 a[2][16];
#pragma unroll
            for (int z = 0; z < 2; z++)
#pragma unroll
                for (int r = 0; r < 16; r++) a[z][r] = __ldg(reinterpret_cast<const uint4*>(wd + (size_t)r * DM + (dg + z) * 64));
#pragma unroll
            for (int z = 0; z < 2; z++) {
                float y[8][4];
#pragma unroll
                for (int i = 0; i < 8; i++)
#pragma unroll
                    for (int e = 0; e < 4; e++) y[i][e] = 0.f;
#pragma unroll
                for (int kk = 0; kk < 4; kk++) mma_rows(y, hp[2 * kk], hp[2 * kk + 1], a[z][4 * kk], a[z][4 * kk + 1], a[z][4 * kk + 2], a[z][4 * kk + 3]);
#pragma unroll
                for (int i = 0; i < 8; i++) { myred[(dg + z) * 64 + i] = y[i][0]; myred[(dg + z) * 64 + 8 + i] = y[i][1]; }
            }
        }
    } else {
        for (int dg = 0; dg < 10; dg++)
#pragma unroll
            for (int i = 0; i < 16; i++) myred[dg * 64 + i] = 0.f;
    }
    named_sync(1, 256);
    for (int i = tid; i < 8 * DM; i += 256) {
        float y = 0.f;
#pragma unroll
        for (int k = 0; k < 8; k++) y += red[k * 8 * DM + i];
        g_ypart[mc * 8 * DM + i] = y;
    }
    named_sync(1, 256);
    if (tid == 0) flag_add(F_MOD);
}

__global__ void __cluster_dims__(2, 1, 1) __launch_bounds__(384, 1) fused_kernel(const __grid_constant__ Params P) {
    extern __shared__ __align__(1024) uint8_t smem_raw[];
    const uint32_t smem = (smem_u32(smem_raw) + 1023u) & ~1023u;
    uint8_t* smem_gen = smem_raw + (smem - smem_u32(smem_raw));
    const uint32_t bars = smem + NSLOT * SLOT;
    volatile uint32_t* misc = reinterpret_cast<volatile uint32_t*>(smem_gen + NSLOT * SLOT + MISC_OFF);
    const int wgi = __shfl_sync(0xffffffffu, threadIdx.x >> 7, 0);
    const int cl = blockIdx.x >> 1, rank = blockIdx.x & 1, ca = cl & 7, cb = cl >> 3;
    PROFG(30);
    PROF(0);
    if (threadIdx.x == 0) {
        for (int s = 0; s < NSLOT; s++) { mbar_init(bars + BAR_FULL + s * 8, 1); mbar_init(bars + BAR_EMPTY + s * 8, 16); }
        for (int s = 0; s < 18; s++) mbar_init(bars + BAR_SIG + s * 8, 4);
        asm volatile("fence.mbarrier_init.release.cluster;" ::: "memory");
        uint32_t e;
        asm volatile("ld.relaxed.gpu.global.u32 %0, [%1];" : "=r"(e) : "l"(g_flags + F_EXIT * 8) : "memory");
        misc[0] = e / NCTA;
    }
    __syncthreads();
    cluster_arrive();
    const uint32_t epoch = misc[0];
    if (wgi == 0) {
        asm volatile("setmaxnreg.dec.sync.aligned.u32 40;");
        const int w = threadIdx.x >> 5, lane = threadIdx.x & 31;
        cluster_wait();
        if (cl < 64) {
            if (w == 0) {
                if (lane == 0) {
                    prefetch_map(&P.ckv); prefetch_map(&P.wuk); prefetch_map(&P.wuv); prefetch_map(&P.xn);
                    prefetch_map(&P.wq); prefetch_map(&P.kv); prefetch_map(&P.ctx); prefetch_map(&P.wo);
                    producer(P, smem, bars, epoch, ca, cb, rank);
                }
            } else if (w < 3 && lane == 0) {
                const int wg = w - 1;
                for (int e = 0; e < 9; e++) {
                    mbar_wait(bars + BAR_SIG + (wg * 9 + e) * 8, 0);
                    int f;
                    if (e == 0) f = F_LN;
                    else if (e < 5) f = F_KV + cb + 8 * (e - 1);
                    else { const int rd = e - 5; f = F_CTX + (8 * rd + cb) * 16 + ((rd & 1) ? 7 - ca : ca) * 2 + rank; }
                    flag_add(f);
                }
            }
        }
        __syncwarp();
        cluster_arrive();
        cluster_wait();
        if (threadIdx.x == 0) atomicAdd(g_flags + F_EXIT * 8, 1u);
        PROFG(31);
    } else {
        asm volatile("setmaxnreg.inc.sync.aligned.u32 232;");
        if (cl < 64) {
            consumer(P, smem, bars, epoch, ca, cb, rank, wgi - 1);
        } else {
            cluster_wait();
            mod_ffn(P, smem_gen, epoch, blockIdx.x - 128);
        }
        cluster_arrive();
        PROFG(31);
    }
}

typedef CUresult (*EncodeFn)(CUtensorMap*, CUtensorMapDataType, cuuint32_t, void*, const cuuint64_t*, const cuuint64_t*, const cuuint32_t*,
                             const cuuint32_t*, CUtensorMapInterleave, CUtensorMapSwizzle, CUtensorMapL2promotion, CUtensorMapFloatOOBfill);

void make_map(EncodeFn fn, CUtensorMap* m, const void* ptr, uint64_t rows, uint64_t cols, uint32_t box_rows) {
    cuuint64_t dims[2] = {cols, rows};
    cuuint64_t strides[1] = {cols * 2};
    cuuint32_t box[2] = {64, box_rows};
    cuuint32_t es[2] = {1, 1};
    fn(m, CU_TENSOR_MAP_DATA_TYPE_BFLOAT16, 2, const_cast<void*>(ptr), dims, strides, box, es, CU_TENSOR_MAP_INTERLEAVE_NONE,
       CU_TENSOR_MAP_SWIZZLE_128B, CU_TENSOR_MAP_L2_PROMOTION_L2_128B, CU_TENSOR_MAP_FLOAT_OOB_FILL_NONE);
}

}

extern "C" void kernel_launch(void* const* d_in, const int* in_sizes, int n_in, void* d_out, int out_size) {
    (void)in_sizes; (void)n_in; (void)out_size;
    void* fnp = nullptr;
    cudaDriverEntryPointQueryResult qr;
    cudaGetDriverEntryPoint("cuTensorMapEncodeTiled", &fnp, cudaEnableDefault, &qr);
    EncodeFn fn = (EncodeFn)fnp;
    void *xn, *kv, *ctx;
    cudaGetSymbolAddress(&xn, g_xn);
    cudaGetSymbolAddress(&kv, g_kv);
    cudaGetSymbolAddress(&ctx, g_ctx);
    Params P;
    make_map(fn, &P.ckv, d_in[1], SEQ, DC, 128);
    make_map(fn, &P.wq, d_in[2], DM, NH * HD, 64);
    make_map(fn, &P.wuk, d_in[3], DC, NH * HD, 128);
    make_map(fn, &P.wuv, d_in[4], DC, NH * HD, 128);
    make_map(fn, &P.wo, d_in[5], NH * HD, DM, 32);
    make_map(fn, &P.xn, xn, SEQ, DM, 128);
    make_map(fn, &P.kv, kv, NH * 16 * 2 * 128, 128, 128);
    make_map(fn, &P.ctx, ctx, NH * SEQ, HD, 128);
    P.x = (const __nv_bfloat16*)d_in[0];
    P.wr = (const __nv_bfloat16*)d_in[7];
    P.wg = (const __nv_bfloat16*)d_in[8];
    P.wu = (const __nv_bfloat16*)d_in[9];
    P.wd = (const __nv_bfloat16*)d_in[10];
    P.out = (__nv_bfloat16*)d_out;
    cudaFuncSetAttribute(fused_kernel, cudaFuncAttributeMaxDynamicSharedMemorySize, SMEM_BYTES);
    fused_kernel<<<NCTA, 384, SMEM_BYTES>>>(P);
}
```

```cpp
#include <cuda_runtime.h>
#include <cuda_bf16.h>
#include <cuda.h>
#include <stdint.h>

namespace {

constexpr int SEQ = 2048, DM = 640, DC = 512, NH = 32, HD = 128, FF = 1728;
constexpr int NSLOT = 7, SLOT = 32768;
constexpr int NCTA = 132;
#define PINGPONG 1
#define KVROW(x) (x)
#define PREFETCH_W 1
#define LN_LATE 1
#define PACE 4
#define PACE_LAG 2
#define SPLITJ 8
constexpr uint32_t DESC_HI = (1024u >> 4) | (1u << 30);
constexpr int SMEM_BYTES = NSLOT * SLOT + 3072;

constexpr int BAR_FULL = 0, BAR_EMPTY = 64, BAR_SIG = 128  , BAR_DEP = 320  , MISC_OFF = 512;

constexpr int F_EXIT = 0, F_LN = 1, F_MOD = 2, F_MODP = 3, F_KV = 4  , F_PART = 36  , F_CTX = 292  , F_NUM = 804;

__device__ __align__(1024) __nv_bfloat16 g_xn[SEQ * DM];
__device__ __align__(1024) __nv_bfloat16 g_kv[NH * 16 * 2 * 128 * 128];
__device__ __align__(1024) __nv_bfloat16 g_ctx[NH * SEQ * HD];
__device__ __align__(1024) __nv_bfloat16 g_res[SEQ * DM];
__device__ __align__(1024) uint4 g_part[32 * 4 * 4 * 5 * 256];
__device__ __align__(16) float g_r[SEQ];
__device__ __align__(16) float g_ypart[27 * 8 * DM];
__device__ uint32_t g_flags[F_NUM * 8];

struct TrueT { static constexpr bool value = true; };
struct FalseT { static constexpr bool value = false; };

struct Params {
    CUtensorMap ckv, wuk, wuv, xn, wq, kv, ctx, wo, wg, wu, wd;
    const __nv_bfloat16 *x, *wr, *ckv_ptr, *wuk_ptr;
    __nv_bfloat16* out;
};

__device__ __forceinline__ uint32_t smem_u32(const void* p) { return (uint32_t)__cvta_generic_to_shared(p); }
__device__ __forceinline__ void mbar_init(uint32_t bar, uint32_t cnt) {
    asm volatile("mbarrier.init.shared::cta.b64 [%0], %1;" ::"r"(bar), "r"(cnt) : "memory");
}
__device__ __forceinline__ void mbar_expect_tx(uint32_t bar, uint32_t bytes) {
    asm volatile("mbarrier.arrive.expect_tx.shared::cta.b64 _, [%0], %1;" ::"r"(bar), "r"(bytes) : "memory");
}
__device__ __forceinline__ void mbar_arrive(uint32_t bar) {
    asm volatile("mbarrier.arrive.shared::cta.b64 _, [%0];" ::"r"(bar) : "memory");
}
__device__ __forceinline__ void mbar_arrive_cluster(uint32_t cluster_addr) {
    asm volatile("mbarrier.arrive.shared::cluster.b64 _, [%0];" ::"r"(cluster_addr) : "memory");
}
__device__ __forceinline__ uint32_t mapa(uint32_t addr, uint32_t cta) {
    uint32_t r;
    asm("mapa.shared::cluster.u32 %0, %1, %2;" : "=r"(r) : "r"(addr), "r"(cta));
    return r;
}
__device__ __forceinline__ void mbar_wait(uint32_t bar, uint32_t parity) {
    asm volatile(
        "{\n.reg .pred p;\n.reg .b32 c;\n"
        "mov.b32 c, 0;\n"
        "WLOOP:\n"
        "mbarrier.try_wait.parity.shared::cta.b64 p, [%0], %1;\n"
        "@p bra.uni WDONE;\n"
        "add.u32 c, c, 1;\n"
        "setp.lt.u32 p, c, 0x400000;\n"
        "@p bra.uni WLOOP;\n"
        "trap;\n"
        "WDONE:\n}\n" ::"r"(bar), "r"(parity) : "memory");
}
__device__ __forceinline__ void tma_load(uint32_t dst, const CUtensorMap* m, int c0, int c1, uint32_t bar) {
    asm volatile("cp.async.bulk.tensor.2d.shared::cluster.global.mbarrier::complete_tx::bytes [%0], [%1, {%3, %4}], [%2];"
                 ::"r"(dst), "l"(m), "r"(bar), "r"(c0), "r"(c1) : "memory");
}
__device__ __forceinline__ void tma_load_mc(uint32_t dst, const CUtensorMap* m, int c0, int c1, uint32_t bar) {
    asm volatile("cp.async.bulk.tensor.2d.shared::cluster.global.mbarrier::complete_tx::bytes.multicast::cluster [%0], [%1, {%3, %4}], [%2], %5;"
                 ::"r"(dst), "l"(m), "r"(bar), "r"(c0), "r"(c1), "h"((uint16_t)3) : "memory");
}
__device__ __forceinline__ void prefetch_map(const CUtensorMap* m) {
    asm volatile("prefetch.tensormap [%0];" ::"l"(m) : "memory");
}
__device__ __forceinline__ void cluster_arrive() { asm volatile("barrier.cluster.arrive.relaxed.aligned;" ::: "memory"); }
__device__ __forceinline__ void cluster_wait() { asm volatile("barrier.cluster.wait.aligned;" ::: "memory"); }
__device__ __forceinline__ void named_sync(int id, int n) { asm volatile("bar.sync %0, %1;" ::"r"(id), "r"(n) : "memory"); }
__device__ __forceinline__ void named_arrive(int id, int n) { asm volatile("bar.arrive %0, %1;" ::"r"(id), "r"(n) : "memory"); }

__device__ __forceinline__ void flag_add(int f) {
    asm volatile("fence.acq_rel.gpu;\nred.relaxed.gpu.global.add.u32 [%0], 1;" ::"l"(g_flags + f * 8) : "memory");
}
template <int SLEEP>
__device__ __forceinline__ void flag_wait(int f, uint32_t target) {
    asm volatile(
        "{\n.reg .pred p;\n.reg .b32 c, v;\n"
        "mov.b32 c, 0;\n"
        "FLOOP:\n"
        "ld.acquire.gpu.global.u32 v, [%0];\n"
        "sub.u32 v, v, %1;\n"
        "setp.ge.s32 p, v, 0;\n"
        "@p bra FDONE;\n"
        "nanosleep.u32 %2;\n"
        "add.u32 c, c, 1;\n"
        "setp.lt.u32 p, c, 0x400000;\n"
        "@p bra FLOOP;\n"
        "trap;\n"
        "FDONE:\n}\n" ::"l"(g_flags + f * 8), "r"(target), "n"(SLEEP) : "memory");
}
__device__ __forceinline__ uint32_t read_epoch() {
    uint32_t e;
    asm volatile("ld.relaxed.gpu.global.u32 %0, [%1];" : "=r"(e) : "l"(g_flags + F_EXIT * 8) : "memory");
    return e / NCTA;
}
__device__ __forceinline__ void tma_prefetch(const CUtensorMap* m, int c0, int c1) {
    asm volatile("cp.async.bulk.prefetch.tensor.2d.L2.global [%0, {%1, %2}];" ::"l"(m), "r"(c0), "r"(c1) : "memory");
}
__device__ __forceinline__ void fence_proxy_async() { asm volatile("fence.proxy.async;" ::: "memory"); }

__device__ __forceinline__ void wgmma_fence() { asm volatile("wgmma.fence.sync.aligned;" ::: "memory"); }
__device__ __forceinline__ void wgmma_commit() { asm volatile("wgmma.commit_group.sync.aligned;" ::: "memory"); }
template <int N>
__device__ __forceinline__ void wgmma_wait() { asm volatile("wgmma.wait_group.sync.aligned %0;" ::"n"(N) : "memory"); }
template <int N>
__device__ __forceinline__ void fence_regs(float (&d)[N]) {
#pragma unroll
    for (int i = 0; i < N; i++) asm volatile("" : "+f"(d[i])::"memory");
}
template <int N>
__device__ __forceinline__ void fence_regs(uint32_t (&d)[N]) {
#pragma unroll
    for (int i = 0; i < N; i++) asm volatile("" : "+r"(d[i])::"memory");
}
__device__ __forceinline__ uint32_t desc_lo(uint32_t addr, uint32_t lbo) { return ((addr & 0x3FFFF) >> 4) | ((lbo >> 4) << 16); }

template <int TA, int TB>
__device__ __forceinline__ void wgmma_ss_n128(float (&d)[64], uint32_t alo, uint32_t blo, int scale_d) {
    asm volatile("{\n.reg .pred p;\n.reg .b64 da, db;\nsetp.ne.b32 p, %66, 0;\n"
        "mov.b64 da, {%64, %69};\nmov.b64 db, {%65, %69};\n"
        "wgmma.mma_async.sync.aligned.m64n128k16.f32.bf16.bf16 "
        "{%0, %1, %2, %3, %4, %5, %6, %7, %8, %9, %10, %11, %12, %13, %14, %15, %16, %17, %18, %19, %20, %21, %22, %23, %24, %25, %26, %27, %28, %29, %30, %31, %32, %33, %34, %35, %36, %37, %38, %39, %40, %41, %42, %43, %44, %45, %46, %47, %48, %49, %50, %51, %52, %53, %54, %55, %56, %57, %58, %59, %60, %61, %62, %63}, da, db, p, 1, 1, %67, %68;\n}\n"
        :
          "+f"(d[0]), "+f"(d[1]), "+f"(d[2]), "+f"(d[3]), "+f"(d[4]), "+f"(d[5]), "+f"(d[6]), "+f"(d[7]),
          "+f"(d[8]), "+f"(d[9]), "+f"(d[10]), "+f"(d[11]), "+f"(d[12]), "+f"(d[13]), "+f"(d[14]), "+f"(d[15]),
          "+f"(d[16]), "+f"(d[17]), "+f"(d[18]), "+f"(d[19]), "+f"(d[20]), "+f"(d[21]), "+f"(d[22]), "+f"(d[23]),
          "+f"(d[24]), "+f"(d[25]), "+f"(d[26]), "+f"(d[27]), "+f"(d[28]), "+f"(d[29]), "+f"(d[30]), "+f"(d[31]),
          "+f"(d[32]), "+f"(d[33]), "+f"(d[34]), "+f"(d[35]), "+f"(d[36]), "+f"(d[37]), "+f"(d[38]), "+f"(d[39]),
          "+f"(d[40]), "+f"(d[41]), "+f"(d[42]), "+f"(d[43]), "+f"(d[44]), "+f"(d[45]), "+f"(d[46]), "+f"(d[47]),
          "+f"(d[48]), "+f"(d[49]), "+f"(d[50]), "+f"(d[51]), "+f"(d[52]), "+f"(d[53]), "+f"(d[54]), "+f"(d[55]),
          "+f"(d[56]), "+f"(d[57]), "+f"(d[58]), "+f"(d[59]), "+f"(d[60]), "+f"(d[61]), "+f"(d[62]), "+f"(d[63])
        : "r"(alo), "r"(blo), "r"(scale_d), "n"(TA), "n"(TB), "r"(DESC_HI));
}
template <int TA, int TB>
__device__ __forceinline__ void wgmma_ss_n192(float (&d)[96], uint32_t alo, uint32_t blo, int scale_d) {
    asm volatile("{\n.reg .pred p;\n.reg .b64 da, db;\nsetp.ne.b32 p, %98, 0;\n"
        "mov.b64 da, {%96, %101};\nmov.b64 db, {%97, %101};\n"
        "wgmma.mma_async.sync.aligned.m64n192k16.f32.bf16.bf16 "
        "{%0, %1, %2, %3, %4, %5, %6, %7, %8, %9, %10, %11, %12, %13, %14, %15, %16, %17, %18, %19, %20, %21, %22, %23, %24, %25, %26, %27, %28, %29, %30, %31, %32, %33, %34, %35, %36, %37, %38, %39, %40, %41, %42, %43, %44, %45, %46, %47, %48, %49, %50, %51, %52, %53, %54, %55, %56, %57, %58, %59, %60, %61, %62, %63, %64, %65, %66, %67, %68, %69, %70, %71, %72, %73, %74, %75, %76, %77, %78, %79, %80, %81, %82, %83, %84, %85, %86, %87, %88, %89, %90, %91, %92, %93, %94, %95}, da, db, p, 1, 1, %99, %100;\n}\n"
        :
          "+f"(d[0]), "+f"(d[1]), "+f"(d[2]), "+f"(d[3]), "+f"(d[4]), "+f"(d[5]), "+f"(d[6]), "+f"(d[7]),
          "+f"(d[8]), "+f"(d[9]), "+f"(d[10]), "+f"(d[11]), "+f"(d[12]), "+f"(d[13]), "+f"(d[14]), "+f"(d[15]),
          "+f"(d[16]), "+f"(d[17]), "+f"(d[18]), "+f"(d[19]), "+f"(d[20]), "+f"(d[21]), "+f"(d[22]), "+f"(d[23]),
          "+f"(d[24]), "+f"(d[25]), "+f"(d[26]), "+f"(d[27]), "+f"(d[28]), "+f"(d[29]), "+f"(d[30]), "+f"(d[31]),
          "+f"(d[32]), "+f"(d[33]), "+f"(d[34]), "+f"(d[35]), "+f"(d[36]), "+f"(d[37]), "+f"(d[38]), "+f"(d[39]),
          "+f"(d[40]), "+f"(d[41]), "+f"(d[42]), "+f"(d[43]), "+f"(d[44]), "+f"(d[45]), "+f"(d[46]), "+f"(d[47]),
          "+f"(d[48]), "+f"(d[49]), "+f"(d[50]), "+f"(d[51]), "+f"(d[52]), "+f"(d[53]), "+f"(d[54]), "+f"(d[55]),
          "+f"(d[56]), "+f"(d[57]), "+f"(d[58]), "+f"(d[59]), "+f"(d[60]), "+f"(d[61]), "+f"(d[62]), "+f"(d[63]),
          "+f"(d[64]), "+f"(d[65]), "+f"(d[66]), "+f"(d[67]), "+f"(d[68]), "+f"(d[69]), "+f"(d[70]), "+f"(d[71]),
          "+f"(d[72]), "+f"(d[73]), "+f"(d[74]), "+f"(d[75]), "+f"(d[76]), "+f"(d[77]), "+f"(d[78]), "+f"(d[79]),
          "+f"(d[80]), "+f"(d[81]), "+f"(d[82]), "+f"(d[83]), "+f"(d[84]), "+f"(d[85]), "+f"(d[86]), "+f"(d[87]),
          "+f"(d[88]), "+f"(d[89]), "+f"(d[90]), "+f"(d[91]), "+f"(d[92]), "+f"(d[93]), "+f"(d[94]), "+f"(d[95])
        : "r"(alo), "r"(blo), "r"(scale_d), "n"(TA), "n"(TB), "r"(DESC_HI));
}
template <int TB>
__device__ __forceinline__ void wgmma_rs_n128(float (&d)[64], uint32_t a0, uint32_t a1, uint32_t a2, uint32_t a3, uint32_t blo, int scale_d) {
    asm volatile("{\n.reg .pred p;\n.reg .b64 db;\nsetp.ne.b32 p, %69, 0;\n"
        "mov.b64 db, {%68, %71};\n"
        "wgmma.mma_async.sync.aligned.m64n128k16.f32.bf16.bf16 "
        "{%0, %1, %2, %3, %4, %5, %6, %7, %8, %9, %10, %11, %12, %13, %14, %15, %16, %17, %18, %19, %20, %21, %22, %23, %24, %25, %26, %27, %28, %29, %30, %31, %32, %33, %34, %35, %36, %37, %38, %39, %40, %41, %42, %43, %44, %45, %46, %47, %48, %49, %50, %51, %52, %53, %54, %55, %56, %57, %58, %59, %60, %61, %62, %63}, {%64, %65, %66, %67}, db, p, 1, 1, %70;\n}\n"
        :
          "+f"(d[0]), "+f"(d[1]), "+f"(d[2]), "+f"(d[3]), "+f"(d[4]), "+f"(d[5]), "+f"(d[6]), "+f"(d[7]),
          "+f"(d[8]), "+f"(d[9]), "+f"(d[10]), "+f"(d[11]), "+f"(d[12]), "+f"(d[13]), "+f"(d[14]), "+f"(d[15]),
          "+f"(d[16]), "+f"(d[17]), "+f"(d[18]), "+f"(d[19]), "+f"(d[20]), "+f"(d[21]), "+f"(d[22]), "+f"(d[23]),
          "+f"(d[24]), "+f"(d[25]), "+f"(d[26]), "+f"(d[27]), "+f"(d[28]), "+f"(d[29]), "+f"(d[30]), "+f"(d[31]),
          "+f"(d[32]), "+f"(d[33]), "+f"(d[34]), "+f"(d[35]), "+f"(d[36]), "+f"(d[37]), "+f"(d[38]), "+f"(d[39]),
          "+f"(d[40]), "+f"(d[41]), "+f"(d[42]), "+f"(d[43]), "+f"(d[44]), "+f"(d[45]), "+f"(d[46]), "+f"(d[47]),
          "+f"(d[48]), "+f"(d[49]), "+f"(d[50]), "+f"(d[51]), "+f"(d[52]), "+f"(d[53]), "+f"(d[54]), "+f"(d[55]),
          "+f"(d[56]), "+f"(d[57]), "+f"(d[58]), "+f"(d[59]), "+f"(d[60]), "+f"(d[61]), "+f"(d[62]), "+f"(d[63])
        : "r"(a0), "r"(a1), "r"(a2), "r"(a3), "r"(blo), "r"(scale_d), "n"(TB), "r"(DESC_HI));
}
template <int TB>
__device__ __forceinline__ void wgmma_rs_n128_z(float (&d)[64], uint32_t a0, uint32_t a1, uint32_t a2, uint32_t a3, uint32_t blo) {
    asm volatile("{\n.reg .pred p;\n.reg .b64 db;\nsetp.ne.b32 p, %69, 0;\n"
        "mov.b64 db, {%68, %71};\n"
        "wgmma.mma_async.sync.aligned.m64n128k16.f32.bf16.bf16 "
        "{%0, %1, %2, %3, %4, %5, %6, %7, %8, %9, %10, %11, %12, %13, %14, %15, %16, %17, %18, %19, %20, %21, %22, %23, %24, %25, %26, %27, %28, %29, %30, %31, %32, %33, %34, %35, %36, %37, %38, %39, %40, %41, %42, %43, %44, %45, %46, %47, %48, %49, %50, %51, %52, %53, %54, %55, %56, %57, %58, %59, %60, %61, %62, %63}, {%64, %65, %66, %67}, db, p, 1, 1, %70;\n}\n"
        :
          "=f"(d[0]), "=f"(d[1]), "=f"(d[2]), "=f"(d[3]), "=f"(d[4]), "=f"(d[5]), "=f"(d[6]), "=f"(d[7]),
          "=f"(d[8]), "=f"(d[9]), "=f"(d[10]), "=f"(d[11]), "=f"(d[12]), "=f"(d[13]), "=f"(d[14]), "=f"(d[15]),
          "=f"(d[16]), "=f"(d[17]), "=f"(d[18]), "=f"(d[19]), "=f"(d[20]), "=f"(d[21]), "=f"(d[22]), "=f"(d[23]),
          "=f"(d[24]), "=f"(d[25]), "=f"(d[26]), "=f"(d[27]), "=f"(d[28]), "=f"(d[29]), "=f"(d[30]), "=f"(d[31]),
          "=f"(d[32]), "=f"(d[33]), "=f"(d[34]), "=f"(d[35]), "=f"(d[36]), "=f"(d[37]), "=f"(d[38]), "=f"(d[39]),
          "=f"(d[40]), "=f"(d[41]), "=f"(d[42]), "=f"(d[43]), "=f"(d[44]), "=f"(d[45]), "=f"(d[46]), "=f"(d[47]),
          "=f"(d[48]), "=f"(d[49]), "=f"(d[50]), "=f"(d[51]), "=f"(d[52]), "=f"(d[53]), "=f"(d[54]), "=f"(d[55]),
          "=f"(d[56]), "=f"(d[57]), "=f"(d[58]), "=f"(d[59]), "=f"(d[60]), "=f"(d[61]), "=f"(d[62]), "=f"(d[63])
        : "r"(a0), "r"(a1), "r"(a2), "r"(a3), "r"(blo), "n"(0), "n"(TB), "r"(DESC_HI));
}
template <int TA, int TB>
__device__ __forceinline__ void wgmma_ss_n128_z(float (&d)[64], uint32_t alo, uint32_t blo) {
    asm volatile("{\n.reg .pred p;\n.reg .b64 da, db;\nsetp.ne.b32 p, %66, 0;\n"
        "mov.b64 da, {%64, %69};\nmov.b64 db, {%65, %69};\n"
        "wgmma.mma_async.sync.aligned.m64n128k16.f32.bf16.bf16 "
        "{%0, %1, %2, %3, %4, %5, %6, %7, %8, %9, %10, %11, %12, %13, %14, %15, %16, %17, %18, %19, %20, %21, %22, %23, %24, %25, %26, %27, %28, %29, %30, %31, %32, %33, %34, %35, %36, %37, %38, %39, %40, %41, %42, %43, %44, %45, %46, %47, %48, %49, %50, %51, %52, %53, %54, %55, %56, %57, %58, %59, %60, %61, %62, %63}, da, db, p, 1, 1, %67, %68;\n}\n"
        :
          "=f"(d[0]), "=f"(d[1]), "=f"(d[2]), "=f"(d[3]), "=f"(d[4]), "=f"(d[5]), "=f"(d[6]), "=f"(d[7]),
          "=f"(d[8]), "=f"(d[9]), "=f"(d[10]), "=f"(d[11]), "=f"(d[12]), "=f"(d[13]), "=f"(d[14]), "=f"(d[15]),
          "=f"(d[16]), "=f"(d[17]), "=f"(d[18]), "=f"(d[19]), "=f"(d[20]), "=f"(d[21]), "=f"(d[22]), "=f"(d[23]),
          "=f"(d[24]), "=f"(d[25]), "=f"(d[26]), "=f"(d[27]), "=f"(d[28]), "=f"(d[29]), "=f"(d[30]), "=f"(d[31]),
          "=f"(d[32]), "=f"(d[33]), "=f"(d[34]), "=f"(d[35]), "=f"(d[36]), "=f"(d[37]), "=f"(d[38]), "=f"(d[39]),
          "=f"(d[40]), "=f"(d[41]), "=f"(d[42]), "=f"(d[43]), "=f"(d[44]), "=f"(d[45]), "=f"(d[46]), "=f"(d[47]),
          "=f"(d[48]), "=f"(d[49]), "=f"(d[50]), "=f"(d[51]), "=f"(d[52]), "=f"(d[53]), "=f"(d[54]), "=f"(d[55]),
          "=f"(d[56]), "=f"(d[57]), "=f"(d[58]), "=f"(d[59]), "=f"(d[60]), "=f"(d[61]), "=f"(d[62]), "=f"(d[63])
        : "r"(alo), "r"(blo), "n"(0), "n"(TA), "n"(TB), "r"(DESC_HI));
}

__device__ __forceinline__ uint32_t pack_bf16(float lo, float hi) {
    uint32_t r;
    asm("cvt.rn.bf16x2.f32 %0, %1, %2;" : "=r"(r) : "f"(hi), "f"(lo));
    return r;
}
__device__ __forceinline__ uint32_t add_bf16x2(uint32_t a, uint32_t b) {
    uint32_t r;
    asm("add.rn.bf16x2 %0, %1, %2;" : "=r"(r) : "r"(a), "r"(b));
    return r;
}
__device__ __forceinline__ float bf_lo(uint32_t v) { return __uint_as_float(v << 16); }
__device__ __forceinline__ float bf_hi(uint32_t v) { return __uint_as_float(v & 0xffff0000u); }
__device__ __forceinline__ float round_bf16(float v) { return __bfloat162float(__float2bfloat16_rn(v)); }
__device__ __forceinline__ float ex2(float x) {
    float y;
    asm("ex2.approx.ftz.f32 %0, %1;" : "=f"(y) : "f"(x));
    return y;
}
__device__ __forceinline__ float rcp(float x) {
    float y;
    asm("rcp.approx.ftz.f32 %0, %1;" : "=f"(y) : "f"(x));
    return y;
}
__device__ __forceinline__ void stg128(void* p, uint32_t a, uint32_t b, uint32_t c, uint32_t d) {
    asm volatile("st.global.v4.b32 [%0], {%1, %2, %3, %4};" ::"l"(p), "r"(a), "r"(b), "r"(c), "r"(d) : "memory");
}
__device__ __forceinline__ int perm_row(int t) { return (t & ~255) | (((0x78 >> (((t >> 6) & 3) * 2)) & 3) << 6) | (t & 63); }
__device__ __forceinline__ int unperm_row(int t) { return (t & ~255) | (((0x9C >> (((t >> 6) & 3) * 2)) & 3) << 6) | (t & 63); }

#define PROF(i)
#define PROFG(i)
#define PROFDUMP()
#define TR(i)
#define LP(i)

template <int I>
__device__ __forceinline__ void store_chunk(const float (&a)[64], __nv_bfloat16* row0, __nv_bfloat16* row1, float s0, float s1) {
    stg128(row0 + 32 * I, pack_bf16(a[16 * I + 0] * s0, a[16 * I + 1] * s0), pack_bf16(a[16 * I + 4] * s0, a[16 * I + 5] * s0),
           pack_bf16(a[16 * I + 8] * s0, a[16 * I + 9] * s0), pack_bf16(a[16 * I + 12] * s0, a[16 * I + 13] * s0));
    stg128(row1 + 32 * I, pack_bf16(a[16 * I + 2] * s1, a[16 * I + 3] * s1), pack_bf16(a[16 * I + 6] * s1, a[16 * I + 7] * s1),
           pack_bf16(a[16 * I + 10] * s1, a[16 * I + 11] * s1), pack_bf16(a[16 * I + 14] * s1, a[16 * I + 15] * s1));
}
template <int I>
struct IntT { static constexpr int value = I; };
template <class F>
__device__ __forceinline__ void for4(F f) { f(IntT<0>{}); f(IntT<1>{}); f(IntT<2>{}); f(IntT<3>{}); }

struct Prod {
    uint32_t smem, bars, pe;
    int ring;
    __device__ __forceinline__ uint32_t acquire(int s, uint32_t bytes) {
        mbar_wait(bars + BAR_EMPTY + s * 8, (pe >> s) & 1);
        pe ^= 1u << s;
        mbar_expect_tx(bars + BAR_FULL + s * 8, bytes);
        return bars + BAR_FULL + s * 8;
    }
    __device__ __forceinline__ int next() {
        int s = ring;
        ring = (ring == NSLOT - 1) ? 0 : ring + 1;
        return s;
    }
};

__device__ __forceinline__ int slot_a(int i) { return (0x5310 >> (4 * i)) & 15; }
__device__ __forceinline__ int slot_w(int m) { return (0x264 >> (4 * m)) & 15; }

__device__ __forceinline__ void producer(const Params& P, uint32_t smem, uint32_t bars, int ca, int cb, int rank) {
    Prod pr{smem, bars, 0x54u, 0};
    {
        int m = 0;
#pragma unroll 1
        for (int u = 0; u < 32; u++) {
            if (u >= 3) {
                const int v = (u == 3) ? 4 + ca : u + 8;
                if (v < 32 && (u == 3 || (v & 7) == ca)) tma_prefetch((v & 4) ? &P.wuv : &P.wuk, (cb + 8 * (v >> 3)) * 128 + rank * 64, (v & 3) * 128);
                if (u == 24) {
                    tma_prefetch(&P.wq, cb * 128 + rank * 64, ca * 64);
                    if (ca < 2) tma_prefetch(&P.wq, cb * 128 + rank * 64, (ca + 8) * 64);
                }
            }
            int s = slot_w(m);
            m = (m == 2) ? 0 : m + 1;
            uint32_t fb = pr.acquire(s, SLOT);
            int h = cb + 8 * (u >> 3);
            TR(1 + u);
            tma_load_mc(smem + s * SLOT + rank * 16384, (u & 4) ? &P.wuv : &P.wuk, h * 128 + rank * 64, (u & 3) * 128, fb);
            if (u < 3) {
                s = slot_a(u + 1);
                fb = bars + BAR_FULL + s * 8;
                mbar_expect_tx(fb, SLOT);
                tma_load(smem + s * SLOT, &P.ckv, u * 128 + 128, (2 * ca + rank) * 128, fb);
                tma_load(smem + s * SLOT + 16384, &P.ckv, u * 128 + 192, (2 * ca + rank) * 128, fb);
            }
        }
    }
    PROF(1);
    mbar_wait(bars + BAR_DEP, 0);
#pragma unroll 1
    for (int rd = 0; rd < 4; rd++) {
        const int h = 8 * rd + cb, p = (rd & 1) ? 7 - ca : ca;
#pragma unroll 1
        for (int ks = 0; ks < 10; ks++) {
            int s = pr.next();
            uint32_t fb = pr.acquire(s, SLOT);
            tma_load(smem + s * SLOT, &P.xn, ks * 64, 256 * p + 128 * rank, fb);
            tma_load_mc(smem + s * SLOT + 16384 + rank * 8192, &P.wq, h * 128 + rank * 64, ks * 64, fb);
        }
        PROF(8 + rd * 4);
        mbar_wait(bars + BAR_DEP + (1 + rd) * 8, 0);
        if (rd < 3) {
            tma_prefetch(&P.wq, (h + 8) * 128 + rank * 64, ca * 64);
            if (ca < 2) tma_prefetch(&P.wq, (h + 8) * 128 + rank * 64, (ca + 8) * 64);
        } else {
#pragma unroll 1
            for (int i = 0; i < 10; i++) {
                const int t = ca + (i >= 5 ? 8 : 0);
                tma_prefetch(&P.wo, 320 * (cb & 1) + 64 * (i >= 5 ? i - 5 : i), (8 * (t >> 2) + (cb & 6) + ((t >> 1) & 1)) * 128 + (t & 1) * 64 + rank * 32);
            }
        }
        const int last = 4 * p + 3, top = h * 32 + last;
#pragma unroll 1
        for (int i = 0; i <= last; i++) {
            const int t = (i == 0) ? top - 1 : (i == last) ? h * 32 + 1 : (i & 1) ? top - 2 - i : top + 2 - i;
            int s = pr.next();
            uint32_t fb = pr.acquire(s, SLOT);
            tma_load_mc(smem + s * SLOT + rank * 16384, &P.kv, rank * 64, KVROW(t * 128), fb);
        }
        PROF(9 + rd * 4);
    }
    {
        const int n0 = 320 * (cb & 1), kg = cb >> 1;
#pragma unroll 1
        for (int t = 0; t < 16; t++) {
            const int h = 8 * (t >> 2) + 2 * kg + ((t >> 1) & 1), ks = t & 1;
            const int krow = h * 128 + ks * 64 + rank * 32;
            int s = pr.next();
            uint32_t fb = pr.acquire(s, SLOT);
            tma_load_mc(smem + s * SLOT + 16384 + rank * 8192, &P.wo, n0, krow, fb);
            tma_load_mc(smem + s * SLOT + 16384 + rank * 8192 + 4096, &P.wo, n0 + 64, krow, fb);
            mbar_wait(bars + BAR_DEP + (5 + (t >> 1)) * 8, 0);
            tma_load(smem + s * SLOT, &P.ctx, ks * 64, h * SEQ + 256 * ca + 128 * rank, fb);
            s = pr.next();
            fb = pr.acquire(s, 24576);
#pragma unroll
            for (int c = 0; c < 3; c++) tma_load_mc(smem + s * SLOT + rank * 12288 + c * 4096, &P.wo, n0 + 128 + 64 * c, krow, fb);
        }
    }
}

struct Cons {
    uint32_t bars, rel;
    uint32_t st;
    bool rel_on;
    __device__ __forceinline__ void uni() { st = __reduce_or_sync(0xffffffffu, st); }
    __device__ __forceinline__ void wait(int s) {
        mbar_wait(bars + BAR_FULL + s * 8, (st >> s) & 1);
        st ^= 1u << s;
    }
    __device__ __forceinline__ void release(int s) {
        if (rel_on) mbar_arrive_cluster(rel + s * 8);
    }
    template <int N = NSLOT>
    __device__ __forceinline__ int next() {
        const int s = st >> 8;
        st = (s == N - 1) ? (st & 255u) : st + 256u;
        return s;
    }
};

__device__ __forceinline__ float div640(float x) {
    const float q = x * (1.0f / DM);
    return fmaf(fmaf(-q, (float)DM, x), 1.0f / DM, q);
}
__device__ __forceinline__ float sqrt_approx(float x) {
    float y;
    asm("sqrt.approx.ftz.f32 %0, %1;" : "=f"(y) : "f"(x));
    return y;
}
struct LayerNorm {
    uint4 xv[5], wv[5];
    uint32_t nmb;
    float inv, r;
    __device__ __forceinline__ void stats() {
        float v[40];
#pragma unroll
        for (int i = 0; i < 20; i++) { const uint32_t u = (&xv[i >> 2].x)[i & 3]; v[2 * i] = bf_lo(u); v[2 * i + 1] = bf_hi(u); }
        float sum = 0.f, sq = 0.f;
#pragma unroll
        for (int i = 0; i < 40; i += 4) sum += (v[i] + v[i + 1]) + (v[i + 2] + v[i + 3]);
#pragma unroll
        for (int o = 8; o > 0; o >>= 1) sum += __shfl_xor_sync(0xffffffffu, sum, o);
        const float mean = div640(sum);
#pragma unroll
        for (int i = 0; i < 40; i += 2) { const float d0 = v[i] - mean, d1 = v[i + 1] - mean; sq += fmaf(d0, d0, d1 * d1); }
#pragma unroll
        for (int o = 8; o > 0; o >>= 1) sq += __shfl_xor_sync(0xffffffffu, sq, o);
        nmb = pack_bf16(-mean, -mean);
        inv = rcp(round_bf16(sqrt_approx(round_bf16(round_bf16(div640(sq)) + 1e-5f))));
        r = 0.f;
    }
    template <int I>
    __device__ __forceinline__ void piece(int t, int l) {
        uint32_t o[4], z[4];
#pragma unroll
        for (int j = 0; j < 4; j++) {
            const uint32_t u = (&xv[I].x)[j], w = (&wv[I].x)[j];
            const uint32_t d = add_bf16x2(u, nmb);
            o[j] = pack_bf16(bf_lo(d) * inv, bf_hi(d) * inv);
            const float n0 = bf_lo(o[j]), n1 = bf_hi(o[j]);
            z[j] = add_bf16x2(u, o[j]);
            r = fmaf(n1, bf_hi(w), fmaf(n0, bf_lo(w), r));
        }
        stg128(g_xn + (size_t)perm_row(t) * DM + 8 * (l + 16 * I), o[0], o[1], o[2], o[3]);
        stg128(g_res + (size_t)t * DM + 8 * (l + 16 * I), z[0], z[1], z[2], z[3]);
        if (I == 4) {
#pragma unroll
            for (int k = 8; k > 0; k >>= 1) r += __shfl_xor_sync(0xffffffffu, r, k);
            if (l == 0) g_r[t] = round_bf16(r);
        }
    }
};

constexpr float SM_SCALE = 0.08838834764831845f * 1.4426950408889634f;

__device__ __forceinline__ void row_max(const float (&s)[64], float& mx0, float& mx1) {
    float a0 = fmaxf(s[0], s[1]), a1 = fmaxf(s[4], s[5]), b0 = fmaxf(s[2], s[3]), b1 = fmaxf(s[6], s[7]);
#pragma unroll
    for (int j = 2; j < 16; j += 2) {
        a0 = fmaxf(a0, fmaxf(s[4 * j], s[4 * j + 1]));
        a1 = fmaxf(a1, fmaxf(s[4 * j + 4], s[4 * j + 5]));
        b0 = fmaxf(b0, fmaxf(s[4 * j + 2], s[4 * j + 3]));
        b1 = fmaxf(b1, fmaxf(s[4 * j + 6], s[4 * j + 7]));
    }
    mx0 = fmaxf(a0, a1);
    mx1 = fmaxf(b0, b1);
    mx0 = fmaxf(mx0, __shfl_xor_sync(0xffffffffu, mx0, 1));
    mx1 = fmaxf(mx1, __shfl_xor_sync(0xffffffffu, mx1, 1));
    mx0 = fmaxf(mx0, __shfl_xor_sync(0xffffffffu, mx0, 2));
    mx1 = fmaxf(mx1, __shfl_xor_sync(0xffffffffu, mx1, 2));
}
template <int J0, int J1, int SEG = 0>
__device__ __forceinline__ void exp_part(float (&s)[64], float n0, float n1, float& r0, float& r1) {
    float a1 = 0.f, b1 = 0.f;
#pragma unroll
    for (int j = J0; j < J1; j++) {
        if (SEG > 0 && j >= SEG && j % (SEG > 0 ? SEG : 1) == 0) {
            n0 = fmaf(s[4 * (j - PACE_LAG)], 0.f, n0);
            n1 = fmaf(s[4 * (j - PACE_LAG)], 0.f, n1);
        }
        s[4 * j + 0] = ex2(fmaf(s[4 * j + 0], SM_SCALE, n0));
        s[4 * j + 1] = ex2(fmaf(s[4 * j + 1], SM_SCALE, n0));
        s[4 * j + 2] = ex2(fmaf(s[4 * j + 2], SM_SCALE, n1));
        s[4 * j + 3] = ex2(fmaf(s[4 * j + 3], SM_SCALE, n1));
        r0 += s[4 * j + 0]; r1 += s[4 * j + 2];
        if (j == J0) { a1 = s[4 * j + 1]; b1 = s[4 * j + 3]; } else { a1 += s[4 * j + 1]; b1 += s[4 * j + 3]; }
    }
    r0 += a1;
    r1 += b1;
}
__device__ __forceinline__ void sched_barrier(float x, float y, uint32_t scratch) {
    asm volatile("{\n.reg .pred p;\nsetp.lt.f32 p, %0, 0f00000000;\n@p st.shared.f32 [%2], %1;\n}\n" ::"f"(x), "f"(y), "r"(scratch) : "memory");
}
__device__ __forceinline__ void pack_tile(const float (&s)[64], uint32_t (&p)[32]) {
#pragma unroll
    for (int i = 0; i < 32; i++) p[i] = pack_bf16(s[2 * i], s[2 * i + 1]);
}
template <bool ZERO>
__device__ __forceinline__ void gemm_rs(float (&d)[64], const uint32_t (&a)[32], uint32_t slot_addr, int acc = 1) {
    const uint32_t b = desc_lo(slot_addr, 16384);
    if (ZERO) wgmma_rs_n128_z<1>(d, a[0], a[1], a[2], a[3], b);
#pragma unroll
    for (int k = ZERO ? 1 : 0; k < 8; k++) wgmma_rs_n128<1>(d, a[4 * k], a[4 * k + 1], a[4 * k + 2], a[4 * k + 3], b + k * 128, k ? 1 : acc);
}
template <int ZERO>
__device__ __forceinline__ void gemm_q(float (&d)[64], uint32_t slot_addr, int role) {
    const uint32_t a = desc_lo(slot_addr + role * 8192, 16), b = desc_lo(slot_addr + 16384, 8192);
    if (ZERO) wgmma_ss_n128_z<0, 1>(d, a, b);
#pragma unroll
    for (int k = ZERO ? 1 : 0; k < 4; k++) wgmma_ss_n128<0, 1>(d, a + k * 2, b + k * 128, 1);
}
template <bool KT, bool ZERO>
__device__ __forceinline__ void gemm_kv(float (&d)[64], uint32_t ckv_addr, uint32_t w_addr, int wg) {
    if (KT) {
        const uint32_t a = desc_lo(w_addr + wg * 16384, 16), b = desc_lo(ckv_addr, 16);
        if (ZERO) wgmma_ss_n128_z<1, 0>(d, a, b);
#pragma unroll
        for (int k = ZERO ? 1 : 0; k < 8; k++) wgmma_ss_n128<1, 0>(d, a + k * 128, b + (k >> 2) * 1024 + (k & 3) * 2, 1);
    } else {
        const uint32_t a = desc_lo(ckv_addr + wg * 8192, 16), b = desc_lo(w_addr, 16384);
        if (ZERO) wgmma_ss_n128_z<0, 1>(d, a, b);
#pragma unroll
        for (int k = ZERO ? 1 : 0; k < 8; k++) wgmma_ss_n128<0, 1>(d, a + (k >> 2) * 1024 + (k & 3) * 2, b + k * 128, 1);
    }
}
__device__ __forceinline__ void mma16816(float& d0, float& d1, float& d2, float& d3, uint32_t a0, uint32_t a1, uint32_t a2, uint32_t a3, uint32_t b0, uint32_t b1) {
    asm volatile("mma.sync.aligned.m16n8k16.row.col.f32.bf16.bf16.f32 {%0,%1,%2,%3}, {%4,%5,%6,%7}, {%8,%9}, {%0,%1,%2,%3};"
                 : "+f"(d0), "+f"(d1), "+f"(d2), "+f"(d3) : "r"(a0), "r"(a1), "r"(a2), "r"(a3), "r"(b0), "r"(b1));
}
__device__ __forceinline__ uint32_t ld_pair(const __nv_bfloat16* p) {
    const unsigned short* u = reinterpret_cast<const unsigned short*>(p);
    return (uint32_t)__ldcg(u) | ((uint32_t)__ldcg(u + 128) << 16);
}
__device__ __forceinline__ void attention_exact(float (&o)[64], const uint32_t (&qf)[32], float& l0, float& l1, int h, int nblk, int rr, int lane) {
    const int q = lane & 3, lr = lane >> 2;
    float m0 = -INFINITY, m1 = -INFINITY;
    l0 = 0.f; l1 = 0.f;
#pragma unroll
    for (int i = 0; i < 64; i++) o[i] = 0.f;
#pragma unroll 1
    for (int cidx = 0; cidx < nblk * 8; cidx++) {
        const int kc = cidx & 7;
        const __nv_bfloat16* kt = g_kv + (size_t)((h * 16 + (cidx >> 3)) * 2) * 16384;
        float sc[8];
#pragma unroll
        for (int i = 0; i < 8; i++) sc[i] = 0.f;
#pragma unroll
        for (int kk = 0; kk < 8; kk++)
#pragma unroll
            for (int nt = 0; nt < 2; nt++) {
                const __nv_bfloat16* b = kt + (16 * kk + 2 * q) * 128 + 16 * kc + 8 * nt + lr;
                mma16816(sc[4 * nt], sc[4 * nt + 1], sc[4 * nt + 2], sc[4 * nt + 3], qf[4 * kk], qf[4 * kk + 1], qf[4 * kk + 2], qf[4 * kk + 3],
                         ld_pair(b), ld_pair(b + 8 * 128));
            }
        const int lim = rr + ((nblk - 1) - (cidx >> 3)) * 128 - 32 * (kc >> 1) - 4 * (kc & 1);
#pragma unroll
        for (int i = 0; i < 8; i++)
            if (2 * (i >> 2) + (i & 1) > lim + 4 * (i & 2)) sc[i] = -INFINITY;
        float x0 = fmaxf(fmaxf(sc[0], sc[1]), fmaxf(sc[4], sc[5])), x1 = fmaxf(fmaxf(sc[2], sc[3]), fmaxf(sc[6], sc[7]));
        x0 = fmaxf(x0, __shfl_xor_sync(0xffffffffu, x0, 1)); x1 = fmaxf(x1, __shfl_xor_sync(0xffffffffu, x1, 1));
        x0 = fmaxf(x0, __shfl_xor_sync(0xffffffffu, x0, 2)); x1 = fmaxf(x1, __shfl_xor_sync(0xffffffffu, x1, 2));
        x0 = fmaxf(x0, m0); x1 = fmaxf(x1, m1);
        const float a0 = ex2((m0 - x0) * SM_SCALE), a1 = ex2((m1 - x1) * SM_SCALE);
        m0 = x0; m1 = x1;
#pragma unroll
        for (int i = 0; i < 8; i++) sc[i] = ex2((sc[i] - ((i & 2) ? m1 : m0)) * SM_SCALE);
        l0 = l0 * a0 + (sc[0] + sc[1]) + (sc[4] + sc[5]);
        l1 = l1 * a1 + (sc[2] + sc[3]) + (sc[6] + sc[7]);
        const uint32_t p0 = pack_bf16(sc[0], sc[1]), p1 = pack_bf16(sc[2], sc[3]), p2 = pack_bf16(sc[4], sc[5]), p3 = pack_bf16(sc[6], sc[7]);
        const __nv_bfloat16* vb = kt + 16384 + (16 * kc + 2 * q) * 128 + lr;
#pragma unroll
        for (int nt = 0; nt < 16; nt++) {
            o[4 * nt] *= a0; o[4 * nt + 1] *= a0; o[4 * nt + 2] *= a1; o[4 * nt + 3] *= a1;
            mma16816(o[4 * nt], o[4 * nt + 1], o[4 * nt + 2], o[4 * nt + 3], p0, p1, p2, p3, ld_pair(vb + 8 * nt), ld_pair(vb + 8 * nt + 8 * 128));
        }
    }
    l0 += __shfl_xor_sync(0xffffffffu, l0, 1); l1 += __shfl_xor_sync(0xffffffffu, l1, 1);
    l0 += __shfl_xor_sync(0xffffffffu, l0, 2); l1 += __shfl_xor_sync(0xffffffffu, l1, 2);
}

__device__ __forceinline__ void signal(uint32_t bars, int wg, int e, int lane) {
    __syncwarp();
    if (lane == 0) mbar_arrive(bars + BAR_SIG + (wg * 9 + e) * 8);
}

__device__ __forceinline__ void consumer(const Params& P, uint32_t smem, uint32_t bars, int ca, int cb, int rank, int wg, LayerNorm& ln) {
    const int lane = threadIdx.x & 31, w = (threadIdx.x >> 5) & 3, q = lane & 3, lr = lane >> 2;
    PROF(7);
    const int ln_t = blockIdx.x * 16 + wg * 8 + w * 2 + (lane >> 4);
    ln.stats();
    ln.piece<0>(ln_t, lane & 15);
    cluster_wait();
    Cons c{bars, mapa(bars + BAR_EMPTY, lane & 1), 0u, lane < 2};
    PROF(1);
    float o[64], s[64];
    int pend;
    __nv_bfloat16* ep_ptr;
    int ep_step;
    {
        const int krow = 64 * wg + 16 * w + lr;
        const int vrow = 64 * wg + 32 * (w >> 1) + 8 * (lr >> 1) + 4 * (w & 1) + (lr & 1);
        __nv_bfloat16* base = g_kv + (size_t)((cb * 16 + 2 * ca + rank) * 2) * 16384 + 8 * q;
        ep_step = 2 * 128;
        pend = -1;
        auto step = [&](auto kt, auto kc, float (&d)[64], int hh) {
            c.uni();
            const int sa = slot_a(kc.value), sw = slot_w(c.next<3>());
            TR(1 + (hh * 8 + (kt.value ? 0 : 4) + kc.value) * 2);
            if (kt.value && hh == 0) c.wait(sa);
            c.wait(sw);
            TR(2 + (hh * 8 + (kt.value ? 0 : 4) + kc.value) * 2);
            wgmma_fence();
            gemm_kv<kt.value, kc.value == 0>(d, smem + sa * SLOT, smem + sw * SLOT, wg);
            wgmma_commit();
            wgmma_wait<1>();
            if (pend >= 0) c.release(pend);
            if (!kt.value && kc.value > 0 && hh == 3) c.release(slot_a(kc.value - 1));
            pend = sw;
        };
#pragma unroll 1
        for (int hh = 0; hh < 4; hh++) {
            for4([&](auto kc) {
                step(TrueT{}, kc, s, hh);
                if (hh > 0) {
                    if (kc.value == 0) fence_regs(o);
                    store_chunk<kc.value>(o, ep_ptr, ep_ptr + ep_step, 1.f, 1.f);
                } else {
                    ln.template piece<kc.value + 1>(ln_t, lane & 15);
                }
            });
            signal(bars, wg, hh, lane);
            for4([&](auto kc) {
                step(FalseT{}, kc, o, hh);
                if (kc.value == 0) fence_regs(s);
                store_chunk<kc.value>(s, base + krow * 128, base + (krow + 8) * 128, 1.f, 1.f);
            });
            PROF(24 + hh);
            ep_ptr = base + 16384 + vrow * 128;
            base += 8 * 32 * 16384;
        }
        c.st &= 255u;
    }
    PROF(2);
    {
        uint32_t pf[32], qf[32];
        float l0 = 1.f, l1 = 1.f;
        const int bar_me = 2 + wg, bar_other = 3 - wg;
#pragma unroll 1
        for (int rd = 0; rd < 4; rd++) {
            const int h = 8 * rd + cb, p = (rd & 1) ? 7 - ca : ca;
            const int role = __reduce_or_sync(0xffffffffu, wg ^ (rd & 1));
            {
                auto qstep = [&](auto zero) {
                    c.uni();
                    const int sl = c.next();
                    c.wait(sl);
                    wgmma_fence();
                    gemm_q<zero.value>(s, smem + sl * SLOT, role);
                    wgmma_commit();
                    wgmma_wait<1>();
                    c.release(pend);
                    pend = sl;
                };
                l0 = rcp(l0); l1 = rcp(l1);
                for4([&](auto i) {
                    qstep(IntT<i.value == 0>{});
                    if (i.value == 0) {
                        if (rd == 0) c.release(slot_a(3));
                        fence_regs(o);
                    }
                    store_chunk<i.value>(o, ep_ptr, ep_ptr + ep_step, l0, l1);
                });
                signal(bars, wg, 4 + rd, lane);
                PROF(11 + rd * 4);
#pragma unroll 1
                for (int ks = 4; ks < 10; ks++) qstep(FalseT{});
                wgmma_wait<0>();
                c.release(pend);
                fence_regs(s);
                pack_tile(s, qf);
            }
            PROF(8 + rd * 4);
            const int nrest = 2 * p + role;
            if (!role) { const int sl = c.next(); c.wait(sl); c.release(sl); }
            {
                c.uni();
                const int sl = c.next();
                c.wait(sl);
                fence_regs(qf);
                if (PINGPONG && !role) named_sync(bar_me, 256);
                wgmma_fence();
                gemm_rs<true>(s, qf, smem + sl * SLOT);
                wgmma_commit();
                if (PINGPONG) named_arrive(bar_other, 256);
                if (!role) { const int s2 = c.next(); c.wait(s2); c.release(s2); }
                wgmma_wait<0>();
                c.release(sl);
                fence_regs(s);
            }
            const int rr = 64 * (role ^ rank) + 16 * w + lr - 8 * q;
#pragma unroll
            for (int j = 0; j < 16; j++) {
                const int cc = 32 * (j >> 2) + 2 * (j & 3);
                if (cc > rr) s[4 * j] = -INFINITY;
                if (cc + 1 > rr) s[4 * j + 1] = -INFINITY;
                if (cc > rr + 8) s[4 * j + 2] = -INFINITY;
                if (cc + 1 > rr + 8) s[4 * j + 3] = -INFINITY;
            }
            float n0, n1;
            row_max(s, n0, n1);
            n0 *= -SM_SCALE; n1 *= -SM_SCALE;
            l0 = 0.f; l1 = 0.f;
            exp_part<0, 16>(s, n0, n1, l0, l1);
            pack_tile(s, pf);
            PROF(9 + rd * 4);
#pragma unroll 1
            for (int it = 0; it < nrest; it++) {
                c.uni();
                const int sk = c.next(), sv = c.next();
                LP(0);
                c.wait(sk);
                c.wait(sv);
                fence_regs(o); fence_regs(pf);
                LP(1);
                if (PINGPONG) named_sync(bar_me, 256);
                LP(2);
                wgmma_fence();
                gemm_rs<true>(s, qf, smem + sk * SLOT);
                wgmma_commit();
                gemm_rs<false>(o, pf, smem + sv * SLOT, it);
                wgmma_commit();
                if (PINGPONG) named_arrive(bar_other, 256);
                LP(3);
                wgmma_wait<1>();
                LP(4);
                c.release(sk);
                fence_regs(s);
                exp_part<0, SPLITJ, PACE>(s, n0, n1, l0, l1);
                sched_barrier(l0, l1, bars + MISC_OFF + 16);
                LP(5);
                wgmma_wait<0>();
                LP(6);
                c.release(sv);
                fence_regs(o); fence_regs(pf);
                exp_part<SPLITJ, 16, PACE>(s, n0, n1, l0, l1);
                pack_tile(s, pf);
            }
            PROF(10 + rd * 4);
            l0 += __shfl_xor_sync(0xffffffffu, l0, 1); l1 += __shfl_xor_sync(0xffffffffu, l1, 1);
            l0 += __shfl_xor_sync(0xffffffffu, l0, 2); l1 += __shfl_xor_sync(0xffffffffu, l1, 2);
            if (__builtin_expect(nrest > 0 && __any_sync(0xffffffffu, !(l0 < 0x1p60f && l1 < 0x1p60f)), 0)) {
                attention_exact(o, qf, l0, l1, h, nrest + 1, rr, lane);
#pragma unroll
                for (int i = 0; i < 32; i++) pf[i] = 0u;
            }
            {
                c.uni();
                const int sv = c.next();
                c.wait(sv);
                fence_regs(o); fence_regs(pf);
                if (PINGPONG && !role) named_sync(bar_me, 256);
                wgmma_fence();
                gemm_rs<false>(o, pf, smem + sv * SLOT, nrest);
                wgmma_commit();
                pend = sv;
                ep_ptr = g_ctx + (size_t)(h * SEQ + 256 * p + 128 * rank + 64 * role + 16 * w + lr) * HD + 8 * q;
                ep_step = 8 * HD;
            }
        }
        wgmma_wait<0>();
        c.release(pend);
        fence_regs(o); fence_regs(pf);
        l0 = rcp(l0); l1 = rcp(l1);
        for4([&](auto i) { store_chunk<i.value>(o, ep_ptr, ep_ptr + ep_step, l0, l1); });
        signal(bars, wg, 8, lane);
    }
    PROF(3);
    {
        float a1[64], a2[96];
        int px = -1, py = -1;
#pragma unroll 1
        for (int t = 0; t < 16; t++) {
            c.uni();
            const int sx = c.next(), sy = c.next();
            c.wait(sx);
            const uint32_t da = desc_lo(smem + sx * SLOT + wg * 8192, 16);
            const uint32_t b1 = desc_lo(smem + sx * SLOT + 16384, 4096), b2 = desc_lo(smem + sy * SLOT, 4096);
            wgmma_fence();
#pragma unroll
            for (int k = 0; k < 4; k++) wgmma_ss_n128<0, 1>(a1, da + k * 2, b1 + (k >> 1) * 512 + (k & 1) * 128, k ? 1 : t);
            c.wait(sy);
            wgmma_fence();
#pragma unroll
            for (int k = 0; k < 4; k++) wgmma_ss_n192<0, 1>(a2, da + k * 2, b2 + (k >> 1) * 768 + (k & 1) * 128, k ? 1 : t);
            wgmma_commit();
            wgmma_wait<1>();
            if (px >= 0) { c.release(px); c.release(py); }
            px = sx; py = sy;
        }
        const int nh = cb & 1, kg = cb >> 1, tile = (ca * 2 + rank) * 2 + nh, tid = threadIdx.x - 128;
        const int goff = (unperm_row(256 * ca + 128 * rank + 64 * wg) + 16 * w + 8 * (kg >> 1)) * (DM / 8) + 40 * nh + 20 * (kg & 1) + lane;
        const uint32_t epoch = read_epoch();
        mbar_wait(bars + BAR_DEP + 13 * 8, 0);
        uint4 rv[5];
#pragma unroll
        for (int i = 0; i < 5; i++) {
            const int r = ((lane + 32 * i) * 205) >> 12;
            rv[i] = __ldcg(reinterpret_cast<const uint4*>(g_res) + (goff + 32 * i + 60 * r));
        }
        wgmma_wait<0>();
        fence_regs(a1); fence_regs(a2);
        PROF(4);
        uint32_t own[20];
#pragma unroll
        for (int g = 0; g < 4; g++) {
            uint32_t pk[20];
#pragma unroll
            for (int i = 0; i < 20; i++) {
                const int j = 20 * (g & 1) + i, e = 2 * (g >> 1);
                pk[i] = (j < 16) ? pack_bf16(a1[4 * (j & 15) + e], a1[4 * (j & 15) + e + 1]) : pack_bf16(a2[4 * (j < 16 ? 0 : j - 16) + e], a2[4 * (j < 16 ? 0 : j - 16) + e + 1]);
                if (g == 0 || g == kg) own[i] = pk[i];
            }
            if (g != kg) {
                uint4* dst = g_part + ((tile * 4 + g) * 4 + kg) * 5 * 256 + tid;
#pragma unroll
                for (int i = 0; i < 5; i++) stg128(dst + i * 256, pk[4 * i], pk[4 * i + 1], pk[4 * i + 2], pk[4 * i + 3]);
            }
        }
        __syncwarp();
        if (lane == 0) {
            flag_add(F_PART + tile * 8 + wg * 4 + w);
            flag_wait<20>(F_PART + tile * 8 + wg * 4 + w, 4u * (epoch + 1));
        }
        __syncwarp();
        PROF(5);
        uint4 in[3][5];
#pragma unroll
        for (int k = 0; k < 3; k++)
#pragma unroll
            for (int i = 0; i < 5; i++) in[k][i] = __ldcg(g_part + ((tile * 4 + kg) * 4 + ((kg + 1 + k) & 3)) * 5 * 256 + i * 256 + tid);
        const uint32_t stage = smem + (c.st >> 8) * SLOT + (wg * 4 + w) * 2688;
#pragma unroll
        for (int i = 0; i < 5; i++) {
            uint32_t r[4];
#pragma unroll
            for (int e = 0; e < 4; e++) {
                const uint32_t u0 = (&in[0][i].x)[e], u1 = (&in[1][i].x)[e], u2 = (&in[2][i].x)[e], u3 = own[4 * i + e];
                r[e] = pack_bf16((bf_lo(u0) + bf_lo(u1)) + (bf_lo(u2) + bf_lo(u3)), (bf_hi(u0) + bf_hi(u1)) + (bf_hi(u2) + bf_hi(u3)));
            }
            asm volatile("stmatrix.sync.aligned.m8n8.x4.shared.b16 [%0], {%1, %2, %3, %4};"
                         ::"r"(stage + (lane & 7) * 336 + (4 * i + (lane >> 3)) * 16), "r"(r[0]), "r"(r[1]), "r"(r[2]), "r"(r[3]) : "memory");
        }
        __syncwarp();
#pragma unroll
        for (int i = 0; i < 5; i++) {
            const int r = ((lane + 32 * i) * 205) >> 12;
            uint4 v;
            asm volatile("ld.shared.v4.b32 {%0, %1, %2, %3}, [%4];" : "=r"(v.x), "=r"(v.y), "=r"(v.z), "=r"(v.w) : "r"(stage + (lane + 32 * i + r) * 16) : "memory");
            stg128(reinterpret_cast<uint4*>(P.out) + (goff + 32 * i + 60 * r), add_bf16x2(v.x, rv[i].x), add_bf16x2(v.y, rv[i].y), add_bf16x2(v.z, rv[i].z), add_bf16x2(v.w, rv[i].w));
        }
    }
    PROF(6);
}

__device__ __forceinline__ void mma_rows(float (&acc)[8][4], uint32_t a0, uint32_t a2, const uint4& w0, const uint4& w1, const uint4& w2, const uint4& w3) {
    const uint32_t r0[4] = {w0.x, w0.y, w0.z, w0.w}, r1[4] = {w1.x, w1.y, w1.z, w1.w};
    const uint32_t r2[4] = {w2.x, w2.y, w2.z, w2.w}, r3[4] = {w3.x, w3.y, w3.z, w3.w};
#pragma unroll
    for (int i = 0; i < 4; i++) {
        mma16816(acc[2 * i][0], acc[2 * i][1], acc[2 * i][2], acc[2 * i][3], a0, 0u, a2, 0u, __byte_perm(r0[i], r1[i], 0x5410), __byte_perm(r2[i], r3[i], 0x5410));
        mma16816(acc[2 * i + 1][0], acc[2 * i + 1][1], acc[2 * i + 1][2], acc[2 * i + 1][3], a0, 0u, a2, 0u, __byte_perm(r0[i], r1[i], 0x7632), __byte_perm(r2[i], r3[i], 0x7632));
    }
}

__device__ __forceinline__ void mod_ffn(const Params& P, uint8_t* sm, int mc  ) {
    const uint32_t epoch = read_epoch();
    const int tid = threadIdx.x - 128, lane = tid & 31, cw = tid >> 5, q = lane & 3, lr = lane >> 2;
    uint32_t* xs = reinterpret_cast<uint32_t*>(sm);
    uint32_t* wmax = xs + 8 * 324;
    int* sidx = reinterpret_cast<int*>(wmax + 16);
    const int fg = cw * 4 + mc;
    const uint32_t ring = smem_u32(sm) + 16384 + cw * 24576, rbar = smem_u32(sm) + 12288 + cw * 32;
    auto issue = [&](int u, int st) {
        if (lane == 0 && u < 30) {
            mbar_expect_tx(rbar + st * 8, 8192);
            if (u < 20) {
                tma_load(ring + st * 8192, &P.wg, fg * 64, u * 32, rbar + st * 8);
                tma_load(ring + st * 8192 + 4096, &P.wu, fg * 64, u * 32, rbar + st * 8);
            } else {
                tma_load(ring + st * 8192, &P.wd, (u - 20) * 64, fg * 64, rbar + st * 8);
            }
        }
    };
    if (lane == 0) {
        mbar_init(rbar, 1); mbar_init(rbar + 8, 1); mbar_init(rbar + 16, 1);
        asm volatile("fence.mbarrier_init.release.cluster;" ::: "memory");
    }
    if (tid == 0) flag_wait<100>(F_LN, 256u * (epoch + 1));
    named_sync(1, 256);
    PROF(1);
    if (fg < 27) {
#pragma unroll 1
        for (int u = 0; u < 3; u++) issue(u, u);
    }
    PROF(2);
    uint32_t key[8];
#pragma unroll
    for (int i = 0; i < 8; i++) {
        const int t = tid + 256 * i;
        uint32_t b = __float_as_uint(__ldcg(g_r + t) + 0.f) >> 16;
        b = (b & 0x8000u) ? (~b & 0xffffu) : (b | 0x8000u);
        key[i] = (b << 16) | (uint32_t)(0xffff - t);
    }
#pragma unroll 1
    for (int rnd = 0; rnd < 8; rnd++) {
        uint32_t mx = key[0];
#pragma unroll
        for (int i = 1; i < 8; i++) mx = max(mx, key[i]);
        mx = __reduce_max_sync(0xffffffffu, mx);
        if (lane == 0) wmax[(rnd & 1) * 8 + cw] = mx;
        named_sync(1, 256);
        mx = __reduce_max_sync(0xffffffffu, wmax[(rnd & 1) * 8 + (lane & 7)]);
#pragma unroll
        for (int i = 0; i < 8; i++) if (key[i] == mx) key[i] = 0;
        if (tid == 0) sidx[rnd] = 0xffff - (int)(mx & 0xffffu);
    }
    named_sync(1, 256);
    {
        const uint32_t* src = reinterpret_cast<const uint32_t*>(g_xn + (size_t)perm_row(sidx[cw]) * DM);
#pragma unroll 2
        for (int i = lane; i < 320; i += 32) xs[cw * 324 + i] = __ldcg(src + i);
    }
    named_sync(1, 256);
    PROF(3);
    if (fg < 27) {
        float g[8][4], v[8][4];
        uint32_t hp[8];
#pragma unroll
        for (int i = 0; i < 8; i++)
#pragma unroll
            for (int e = 0; e < 4; e++) { g[i][e] = 0.f; v[i][e] = 0.f; }
        int st = 0, ph = 0;
#pragma unroll 1
        for (int u = 0; u < 60; u++) {
            if (!(u & 1)) mbar_wait(rbar + st * 8, ph);
            uint4 a[8];
#pragma unroll
            for (int r = 0; r < 8; r++) {
                const int row = (u < 40) ? 32 * (r >> 2) + 16 * (u & 1) + 2 * q + (r & 1) + 4 * (r & 2) : 16 * q + 8 * (u & 1) + r;
                asm volatile("ld.shared.v4.b32 {%0, %1, %2, %3}, [%4];" : "=r"(a[r].x), "=r"(a[r].y), "=r"(a[r].z), "=r"(a[r].w)
                             : "r"(ring + st * 8192 + row * 128 + ((lr ^ row) & 7) * 16) : "memory");
            }
            uint32_t f0, f1, f2, f3;
            if (u < 40) { f0 = f2 = xs[lr * 324 + u * 8 + q]; f1 = f3 = xs[lr * 324 + u * 8 + 4 + q]; }
            else if (u & 1) { f0 = hp[4]; f1 = hp[5]; f2 = hp[6]; f3 = hp[7]; }
            else { f0 = hp[0]; f1 = hp[1]; f2 = hp[2]; f3 = hp[3]; }
            mma_rows(g, f0, f1, a[0], a[1], a[2], a[3]);
            mma_rows(v, f2, f3, a[4], a[5], a[6], a[7]);
            if (u & 1) {
                __syncwarp();
                issue((u >> 1) + 3, st);
                if (++st == 3) { st = 0; ph ^= 1; }
                if (u >= 39) {
                    if (u == 39) {
                        float hv[16];
#pragma unroll
                        for (int i = 0; i < 16; i++) {
                            const float gp = round_bf16(g[i & 7][i >> 3]);
                            hv[i] = round_bf16(__fdividef(gp, 1.0f + __expf(fminf(-gp, 80.f)))) * round_bf16(v[i & 7][i >> 3]);
                        }
#pragma unroll
                        for (int i = 0; i < 8; i++) hp[i] = pack_bf16(hv[2 * i], hv[2 * i + 1]);
                    } else {
                        float4* dst = reinterpret_cast<float4*>(g_ypart + (fg * 8 + lr) * DM + ((u - 40) >> 1) * 64 + 16 * q);
#pragma unroll
                        for (int i = 0; i < 4; i++) {
                            const int j = 4 * (i & 1), e = i >> 1;
                            dst[i] = make_float4(g[j][e] + v[j][e], g[j + 1][e] + v[j + 1][e], g[j + 2][e] + v[j + 2][e], g[j + 3][e] + v[j + 3][e]);
                        }
                    }
#pragma unroll
                    for (int i = 0; i < 8; i++) { g[i][0] = 0.f; g[i][1] = 0.f; v[i][0] = 0.f; v[i][1] = 0.f; }
                }
            }
        }
    }
    PROF(5);
    named_sync(1, 256);
    if (tid == 0) {
        flag_add(F_MODP);
        flag_wait<100>(F_MODP, 4u * (epoch + 1));
    }
    named_sync(1, 256);
    PROF(6);
#pragma unroll 1
    for (int i = tid; i < 2 * DM; i += 256) {
        const int c = 2 * mc + (i >= DM), col = i - (i >= DM) * DM, t = sidx[c];
        float y = 0.f;
#pragma unroll 9
        for (int k = 0; k < 27; k++) y += __ldcg(g_ypart + (k * 8 + c) * DM + col);
        const float rs = round_bf16(__fdividef(1.0f, 1.0f + __expf(fminf(-__ldcg(g_r + t), 80.f))));
        const float xn = __bfloat162float(reinterpret_cast<const __nv_bfloat16*>(xs + c * 324)[col]);
        g_res[(size_t)t * DM + col] = __float2bfloat16_rn(__bfloat162float(P.x[(size_t)t * DM + col]) + round_bf16(xn + round_bf16(round_bf16(y) * rs)));
    }
    named_sync(1, 256);
    if (tid == 0) flag_add(F_MOD);
    PROF(7);
}

__global__ void __cluster_dims__(2, 1, 1) __launch_bounds__(384, 1) fused_kernel(const __grid_constant__ Params P) {
    extern __shared__ __align__(1024) uint8_t smem_raw[];
    const uint32_t smem = (smem_u32(smem_raw) + 1023u) & ~1023u;
    uint8_t* smem_gen = smem_raw + (smem - smem_u32(smem_raw));
    const uint32_t bars = smem + NSLOT * SLOT;
    const int wgi = __shfl_sync(0xffffffffu, threadIdx.x >> 7, 0);
    const int cl = blockIdx.x >> 1, rank = blockIdx.x & 1, ca = cl & 7, cb = cl >> 3;
    PROFG(30);
    PROF(0);
    LayerNorm ln;
    if (wgi != 0) {
        const uint4* xr = reinterpret_cast<const uint4*>(P.x + (size_t)((blockIdx.x & 127) * 16 + ((threadIdx.x - 128) >> 4)) * DM) + (threadIdx.x & 15);
        const uint4* wr = reinterpret_cast<const uint4*>(P.wr) + (threadIdx.x & 15);
#pragma unroll
        for (int i = 0; i < 5; i++) { ln.xv[i] = __ldg(xr + 16 * i); ln.wv[i] = __ldg(wr + 16 * i); }
        PROF(28);
    } else if (threadIdx.x == 0) {
#pragma unroll
        for (int i = 0; i < NSLOT; i++) { mbar_init(bars + BAR_FULL + i * 8, 1); mbar_init(bars + BAR_EMPTY + i * 8, 16); }
        asm volatile("fence.mbarrier_init.release.cluster;" ::: "memory");
        PROF(24);
    } else if (threadIdx.x == 32) {
#pragma unroll
        for (int i = 0; i < 18; i++) mbar_init(bars + BAR_SIG + i * 8, 4);
#pragma unroll
        for (int i = 0; i < 14; i++) mbar_init(bars + BAR_DEP + i * 8, 1);
    } else if (threadIdx.x >= 64 && cl < 64) {
        const int i = threadIdx.x - 64;
        if (i == 0) { prefetch_map(&P.ckv); prefetch_map(&P.wuk); }
        const char* a = reinterpret_cast<const char*>(P.ckv_ptr) + ((2 * ca + rank) * 128 + cb * 16) * (DC * 2) + i * 256;
        asm volatile("prefetch.global.L2 [%0];" ::"l"(a));
        asm volatile("prefetch.global.L2 [%0];" ::"l"(a + 128));
        asm volatile("prefetch.global.L2 [%0];" ::"l"(P.wuk_ptr + (size_t)(i * 8 + ca) * (NH * HD) + cb * 128 + rank * 64));
    }
    __syncthreads();
    PROF(29);
    cluster_arrive();
    if (wgi > 0) {
        asm volatile("setmaxnreg.inc.sync.aligned.u32 232;");
        if (cl >= 64) {
            cluster_wait();
            mod_ffn(P, smem_gen, blockIdx.x - 128);
        } else {
            consumer(P, smem, bars, ca, cb, rank, wgi - 1, ln);
        }
        cluster_arrive();
        PROFG(31);
        PROFDUMP();
    } else {
        asm volatile("setmaxnreg.dec.sync.aligned.u32 40;");
        const int w = threadIdx.x >> 5, lane = threadIdx.x & 31;
        if (threadIdx.x == 32 && cl < 64) {
            mbar_expect_tx(bars + BAR_FULL, SLOT);
            tma_load(smem, &P.ckv, 0, (2 * ca + rank) * 128, bars + BAR_FULL);
            tma_load(smem + 16384, &P.ckv, 64, (2 * ca + rank) * 128, bars + BAR_FULL);
        }
        if (threadIdx.x == 64) {
            prefetch_map(&P.wuv); prefetch_map(&P.xn); prefetch_map(&P.wq); prefetch_map(&P.kv); prefetch_map(&P.ctx); prefetch_map(&P.wo);
        }
        __syncwarp();
        cluster_wait();
        PROF(27);
        if (cl < 64) {
            if (w == 0) {
                if (lane == 0) producer(P, smem, bars, ca, cb, rank);
            } else if (w < 3 && lane == 0) {
                const int wg = w - 1;
#pragma unroll 1
                for (int e = 0; e < 9; e++) {
                    mbar_wait(bars + BAR_SIG + (wg * 9 + e) * 8, 0);
                    int f;
                    if (e == 0) f = F_LN;
                    else if (e < 5) f = F_KV + cb + 8 * (e - 1);
                    else { const int rd = e - 5; f = F_CTX + (8 * rd + cb) * 16 + ((rd & 1) ? 7 - ca : ca) * 2 + rank; }
                    flag_add(f);
                }
            } else if (lane == 0) {
                const uint32_t epoch = read_epoch();
#pragma unroll 1
                for (int i = 0; i < 14; i++) {
                    const int e = (i < 11) ? i : (i == 11) ? 13 : i - 1;
                    int f;
                    uint32_t n;
                    if (e == 0) { f = F_LN; n = 256; }
                    else if (e < 5) { f = F_KV + cb + 8 * (e - 1); n = 32; }
                    else if (e < 13) { f = F_CTX + (8 * ((e - 5) >> 1) + (cb & 6) + ((e - 5) & 1)) * 16 + ca * 2 + rank; n = 2; }
                    else { f = F_MOD; n = 4; }
                    flag_wait<100>(f, n * (epoch + 1));
                    fence_proxy_async();
                    mbar_arrive(bars + BAR_DEP + e * 8);
                }
            }
        }
        __syncwarp();
        cluster_arrive();
        cluster_wait();
        if (threadIdx.x == 0) atomicAdd(g_flags + F_EXIT * 8, 1u);
        PROFG(31);
        PROFDUMP();
    }
}

typedef CUresult (*EncodeFn)(CUtensorMap*, CUtensorMapDataType, cuuint32_t, void*, const cuuint64_t*, const cuuint64_t*, const cuuint32_t*,
                             const cuuint32_t*, CUtensorMapInterleave, CUtensorMapSwizzle, CUtensorMapL2promotion, CUtensorMapFloatOOBfill);

void make_map(EncodeFn fn, CUtensorMap* m, const void* ptr, uint64_t rows, uint64_t cols, uint32_t box_rows) {
    cuuint64_t dims[2] = {cols, rows};
    cuuint64_t strides[1] = {cols * 2};
    cuuint32_t box[2] = {64, box_rows};
    cuuint32_t es[2] = {1, 1};
    fn(m, CU_TENSOR_MAP_DATA_TYPE_BFLOAT16, 2, const_cast<void*>(ptr), dims, strides, box, es, CU_TENSOR_MAP_INTERLEAVE_NONE,
       CU_TENSOR_MAP_SWIZZLE_128B, CU_TENSOR_MAP_L2_PROMOTION_L2_128B, CU_TENSOR_MAP_FLOAT_OOB_FILL_NONE);
}

}

extern "C" void kernel_launch(void* const* d_in, const int* in_sizes, int n_in, void* d_out, int out_size) {
    (void)in_sizes; (void)n_in; (void)out_size;
    void* fnp = nullptr;
    cudaDriverEntryPointQueryResult qr;
    cudaGetDriverEntryPoint("cuTensorMapEncodeTiled", &fnp, cudaEnableDefault, &qr);
    EncodeFn fn = (EncodeFn)fnp;
    void *xn, *kv, *ctx;
    cudaGetSymbolAddress(&xn, g_xn);
    cudaGetSymbolAddress(&kv, g_kv);
    cudaGetSymbolAddress(&ctx, g_ctx);
    Params P;
    make_map(fn, &P.ckv, d_in[1], SEQ, DC, 128);
    make_map(fn, &P.wq, d_in[2], DM, NH * HD, 64);
    make_map(fn, &P.wuk, d_in[3], DC, NH * HD, 128);
    make_map(fn, &P.wuv, d_in[4], DC, NH * HD, 128);
    make_map(fn, &P.wo, d_in[5], NH * HD, DM, 32);
    make_map(fn, &P.xn, xn, SEQ, DM, 128);
    make_map(fn, &P.kv, kv, NH * 16 * 2 * 128, 128, 128);
    make_map(fn, &P.ctx, ctx, NH * SEQ, HD, 128);
    P.x = (const __nv_bfloat16*)d_in[0];
    P.wr = (const __nv_bfloat16*)d_in[7];
    make_map(fn, &P.wg, d_in[8], DM, FF, 32);
    make_map(fn, &P.wu, d_in[9], DM, FF, 32);
    make_map(fn, &P.wd, d_in[10], FF, DM, 64);
    P.ckv_ptr = (const __nv_bfloat16*)d_in[1];
    P.wuk_ptr = (const __nv_bfloat16*)d_in[3];
    P.out = (__nv_bfloat16*)d_out;
    cudaFuncSetAttribute(fused_kernel, cudaFuncAttributeMaxDynamicSharedMemorySize, SMEM_BYTES);
    fused_kernel<<<NCTA, 384, SMEM_BYTES>>>(P);
}
```

```cpp
#include <cuda_runtime.h>
#include <cuda_bf16.h>
#include <cuda.h>
#include <stdint.h>

namespace {

constexpr int SEQ = 2048, DM = 640, DC = 512, NH = 32, HD = 128, FF = 1728;
constexpr int NSLOT = 7, SLOT = 32768;
constexpr int NCTA = 132;
#define PINGPONG 1
#define PREFETCH_W 1
#define PACE 2
#define PACE_LAG 2
#define SIGMA 1
#define KVORDER 0x1023
#define PREFETCH_XN 0
#define KVSPLIT 2
#define EF 1
#define QST 4
#define SPLITJ 8
constexpr uint32_t DESC_HI = (1024u >> 4) | (1u << 30);
constexpr int SMEM_BYTES = NSLOT * SLOT + 3072;

constexpr int BAR_FULL = 0, BAR_EMPTY = 64, BAR_SIG = 128  , BAR_DEP = 320  , MISC_OFF = 512;

constexpr int F_EXIT = 0, F_LN = 1, F_MOD = 2, F_MODP = 3, F_KV = 4  , F_PART = 36  , F_CTX = 292  , F_NUM = 804;

__device__ __align__(1024) __nv_bfloat16 g_xn[SEQ * DM];
__device__ __align__(1024) __nv_bfloat16 g_kv[NH * 16 * 2 * 128 * 128];
__device__ __align__(1024) __nv_bfloat16 g_ctx[NH * SEQ * HD];
__device__ __align__(1024) __nv_bfloat16 g_res[SEQ * DM];
__device__ __align__(1024) uint4 g_part[32 * 4 * 4 * 5 * 256];
__device__ __align__(16) float g_r[SEQ];
__device__ __align__(16) float g_ypart[27 * 8 * DM];
__device__ uint32_t g_flags[F_NUM * 8];

struct TrueT { static constexpr bool value = true; };
struct FalseT { static constexpr bool value = false; };

struct Params {
    CUtensorMap ckv, wuk, wuv, xn, wq, kv, ctx, wo, wg, wu, wd;
    const __nv_bfloat16 *x, *wr, *ckv_ptr, *wuk_ptr;
    __nv_bfloat16* out;
};

__device__ __forceinline__ uint32_t smem_u32(const void* p) { return (uint32_t)__cvta_generic_to_shared(p); }
__device__ __forceinline__ void mbar_init(uint32_t bar, uint32_t cnt) {
    asm volatile("mbarrier.init.shared::cta.b64 [%0], %1;" ::"r"(bar), "r"(cnt) : "memory");
}
__device__ __forceinline__ void mbar_expect_tx(uint32_t bar, uint32_t bytes) {
    asm volatile("mbarrier.arrive.expect_tx.shared::cta.b64 _, [%0], %1;" ::"r"(bar), "r"(bytes) : "memory");
}
__device__ __forceinline__ void mbar_arrive(uint32_t bar) {
    asm volatile("mbarrier.arrive.shared::cta.b64 _, [%0];" ::"r"(bar) : "memory");
}
__device__ __forceinline__ uint32_t mapa(uint32_t addr, uint32_t cta) {
    uint32_t r;
    asm("mapa.shared::cluster.u32 %0, %1, %2;" : "=r"(r) : "r"(addr), "r"(cta));
    return r;
}
__device__ __forceinline__ void mbar_wait(uint32_t bar, uint32_t parity) {
    asm volatile(
        "{\n.reg .pred p;\n.reg .b32 c;\n"
        "mov.b32 c, 0;\n"
        "WLOOP:\n"
        "mbarrier.try_wait.parity.shared::cta.b64 p, [%0], %1;\n"
        "@p bra.uni WDONE;\n"
        "add.u32 c, c, 1;\n"
        "setp.lt.u32 p, c, 0x400000;\n"
        "@p bra.uni WLOOP;\n"
        "trap;\n"
        "WDONE:\n}\n" ::"r"(bar), "r"(parity) : "memory");
}
__device__ __forceinline__ void tma_load(uint32_t dst, const CUtensorMap* m, int c0, int c1, uint32_t bar) {
    asm volatile("cp.async.bulk.tensor.2d.shared::cluster.global.mbarrier::complete_tx::bytes [%0], [%1, {%3, %4}], [%2];"
                 ::"r"(dst), "l"(m), "r"(bar), "r"(c0), "r"(c1) : "memory");
}
__device__ __forceinline__ void tma_load_mc(uint32_t dst, const CUtensorMap* m, int c0, int c1, uint32_t bar) {
    asm volatile("cp.async.bulk.tensor.2d.shared::cluster.global.mbarrier::complete_tx::bytes.multicast::cluster [%0], [%1, {%3, %4}], [%2], %5;"
                 ::"r"(dst), "l"(m), "r"(bar), "r"(c0), "r"(c1), "h"((uint16_t)3) : "memory");
}
__device__ __forceinline__ uint64_t policy_evict_first() {
    uint64_t p;
    asm("createpolicy.fractional.L2::evict_first.b64 %0, 1.0;" : "=l"(p));
    return p;
}
__device__ __forceinline__ void tma_load_stream(uint32_t dst, const CUtensorMap* m, int c0, int c1, uint32_t bar) {
    asm volatile("cp.async.bulk.tensor.2d.shared::cluster.global.mbarrier::complete_tx::bytes.L2::cache_hint [%0], [%1, {%3, %4}], [%2], %5;"
                 ::"r"(dst), "l"(m), "r"(bar), "r"(c0), "r"(c1), "l"(policy_evict_first()) : "memory");
}
__device__ __forceinline__ uint4 ldg_stream(const void* p) {
    uint4 v;
    asm volatile("ld.global.nc.L2::cache_hint.v4.b32 {%0, %1, %2, %3}, [%4], %5;" : "=r"(v.x), "=r"(v.y), "=r"(v.z), "=r"(v.w) : "l"(p), "l"(policy_evict_first()));
    return v;
}
__device__ __forceinline__ void prefetch_map(const CUtensorMap* m) {
    asm volatile("prefetch.tensormap [%0];" ::"l"(m) : "memory");
}
__device__ __forceinline__ void cluster_arrive() { asm volatile("barrier.cluster.arrive.relaxed.aligned;" ::: "memory"); }
__device__ __forceinline__ void cluster_wait() { asm volatile("barrier.cluster.wait.aligned;" ::: "memory"); }
__device__ __forceinline__ void named_sync(int id, int n) { asm volatile("bar.sync %0, %1;" ::"r"(id), "r"(n) : "memory"); }
__device__ __forceinline__ void named_arrive(int id, int n) { asm volatile("bar.arrive %0, %1;" ::"r"(id), "r"(n) : "memory"); }

__device__ __forceinline__ void flag_add(int f) {
    asm volatile("fence.acq_rel.gpu;\nred.relaxed.gpu.global.add.u32 [%0], 1;" ::"l"(g_flags + f * 8) : "memory");
}
template <int SLEEP>
__device__ __forceinline__ void flag_wait(int f, uint32_t target) {
    asm volatile(
        "{\n.reg .pred p;\n.reg .b32 c, v;\n"
        "mov.b32 c, 0;\n"
        "FLOOP:\n"
        "ld.acquire.gpu.global.u32 v, [%0];\n"
        "sub.u32 v, v, %1;\n"
        "setp.ge.s32 p, v, 0;\n"
        "@p bra FDONE;\n"
        "nanosleep.u32 %2;\n"
        "add.u32 c, c, 1;\n"
        "setp.lt.u32 p, c, 0x400000;\n"
        "@p bra FLOOP;\n"
        "trap;\n"
        "FDONE:\n}\n" ::"l"(g_flags + f * 8), "r"(target), "n"(SLEEP) : "memory");
}
__device__ __forceinline__ uint32_t read_epoch() {
    uint32_t e;
    asm volatile("ld.relaxed.gpu.global.u32 %0, [%1];" : "=r"(e) : "l"(g_flags + F_EXIT * 8) : "memory");
    return e / NCTA;
}
__device__ __forceinline__ void tma_prefetch(const CUtensorMap* m, int c0, int c1) {
    asm volatile("cp.async.bulk.prefetch.tensor.2d.L2.global [%0, {%1, %2}];" ::"l"(m), "r"(c0), "r"(c1) : "memory");
}
__device__ __forceinline__ void fence_proxy_async() { asm volatile("fence.proxy.async;" ::: "memory"); }

__device__ __forceinline__ void wgmma_fence() { asm volatile("wgmma.fence.sync.aligned;" ::: "memory"); }
__device__ __forceinline__ void wgmma_commit() { asm volatile("wgmma.commit_group.sync.aligned;" ::: "memory"); }
template <int N>
__device__ __forceinline__ void wgmma_wait() { asm volatile("wgmma.wait_group.sync.aligned %0;" ::"n"(N) : "memory"); }
template <int N>
__device__ __forceinline__ void fence_regs(float (&d)[N]) {
#pragma unroll
    for (int i = 0; i < N; i++) asm volatile("" : "+f"(d[i])::"memory");
}
template <int N>
__device__ __forceinline__ void fence_regs(uint32_t (&d)[N]) {
#pragma unroll
    for (int i = 0; i < N; i++) asm volatile("" : "+r"(d[i])::"memory");
}

template <int TA, int TB>
__device__ __forceinline__ void wgmma_ss_n128(float (&d)[64], uint32_t alo, uint32_t blo, int scale_d) {
    asm volatile("{\n.reg .pred p;\n.reg .b64 da, db;\nsetp.ne.b32 p, %66, 0;\n"
        "mov.b64 da, {%64, %69};\nmov.b64 db, {%65, %69};\n"
        "wgmma.mma_async.sync.aligned.m64n128k16.f32.bf16.bf16 "
        "{%0, %1, %2, %3, %4, %5, %6, %7, %8, %9, %10, %11, %12, %13, %14, %15, %16, %17, %18, %19, %20, %21, %22, %23, %24, %25, %26, %27, %28, %29, %30, %31, %32, %33, %34, %35, %36, %37, %38, %39, %40, %41, %42, %43, %44, %45, %46, %47, %48, %49, %50, %51, %52, %53, %54, %55, %56, %57, %58, %59, %60, %61, %62, %63}, da, db, p, 1, 1, %67, %68;\n}\n"
        :
          "+f"(d[0]), "+f"(d[1]), "+f"(d[2]), "+f"(d[3]), "+f"(d[4]), "+f"(d[5]), "+f"(d[6]), "+f"(d[7]),
          "+f"(d[8]), "+f"(d[9]), "+f"(d[10]), "+f"(d[11]), "+f"(d[12]), "+f"(d[13]), "+f"(d[14]), "+f"(d[15]),
          "+f"(d[16]), "+f"(d[17]), "+f"(d[18]), "+f"(d[19]), "+f"(d[20]), "+f"(d[21]), "+f"(d[22]), "+f"(d[23]),
          "+f"(d[24]), "+f"(d[25]), "+f"(d[26]), "+f"(d[27]), "+f"(d[28]), "+f"(d[29]), "+f"(d[30]), "+f"(d[31]),
          "+f"(d[32]), "+f"(d[33]), "+f"(d[34]), "+f"(d[35]), "+f"(d[36]), "+f"(d[37]), "+f"(d[38]), "+f"(d[39]),
          "+f"(d[40]), "+f"(d[41]), "+f"(d[42]), "+f"(d[43]), "+f"(d[44]), "+f"(d[45]), "+f"(d[46]), "+f"(d[47]),
          "+f"(d[48]), "+f"(d[49]), "+f"(d[50]), "+f"(d[51]), "+f"(d[52]), "+f"(d[53]), "+f"(d[54]), "+f"(d[55]),
          "+f"(d[56]), "+f"(d[57]), "+f"(d[58]), "+f"(d[59]), "+f"(d[60]), "+f"(d[61]), "+f"(d[62]), "+f"(d[63])
        : "r"(alo), "r"(blo), "r"(scale_d), "n"(TA), "n"(TB), "r"(DESC_HI));
}
template <int TA, int TB>
__device__ __forceinline__ void wgmma_ss_n192(float (&d)[96], uint32_t alo, uint32_t blo, int scale_d) {
    asm volatile("{\n.reg .pred p;\n.reg .b64 da, db;\nsetp.ne.b32 p, %98, 0;\n"
        "mov.b64 da, {%96, %101};\nmov.b64 db, {%97, %101};\n"
        "wgmma.mma_async.sync.aligned.m64n192k16.f32.bf16.bf16 "
        "{%0, %1, %2, %3, %4, %5, %6, %7, %8, %9, %10, %11, %12, %13, %14, %15, %16, %17, %18, %19, %20, %21, %22, %23, %24, %25, %26, %27, %28, %29, %30, %31, %32, %33, %34, %35, %36, %37, %38, %39, %40, %41, %42, %43, %44, %45, %46, %47, %48, %49, %50, %51, %52, %53, %54, %55, %56, %57, %58, %59, %60, %61, %62, %63, %64, %65, %66, %67, %68, %69, %70, %71, %72, %73, %74, %75, %76, %77, %78, %79, %80, %81, %82, %83, %84, %85, %86, %87, %88, %89, %90, %91, %92, %93, %94, %95}, da, db, p, 1, 1, %99, %100;\n}\n"
        :
          "+f"(d[0]), "+f"(d[1]), "+f"(d[2]), "+f"(d[3]), "+f"(d[4]), "+f"(d[5]), "+f"(d[6]), "+f"(d[7]),
          "+f"(d[8]), "+f"(d[9]), "+f"(d[10]), "+f"(d[11]), "+f"(d[12]), "+f"(d[13]), "+f"(d[14]), "+f"(d[15]),
          "+f"(d[16]), "+f"(d[17]), "+f"(d[18]), "+f"(d[19]), "+f"(d[20]), "+f"(d[21]), "+f"(d[22]), "+f"(d[23]),
          "+f"(d[24]), "+f"(d[25]), "+f"(d[26]), "+f"(d[27]), "+f"(d[28]), "+f"(d[29]), "+f"(d[30]), "+f"(d[31]),
          "+f"(d[32]), "+f"(d[33]), "+f"(d[34]), "+f"(d[35]), "+f"(d[36]), "+f"(d[37]), "+f"(d[38]), "+f"(d[39]),
          "+f"(d[40]), "+f"(d[41]), "+f"(d[42]), "+f"(d[43]), "+f"(d[44]), "+f"(d[45]), "+f"(d[46]), "+f"(d[47]),
          "+f"(d[48]), "+f"(d[49]), "+f"(d[50]), "+f"(d[51]), "+f"(d[52]), "+f"(d[53]), "+f"(d[54]), "+f"(d[55]),
          "+f"(d[56]), "+f"(d[57]), "+f"(d[58]), "+f"(d[59]), "+f"(d[60]), "+f"(d[61]), "+f"(d[62]), "+f"(d[63]),
          "+f"(d[64]), "+f"(d[65]), "+f"(d[66]), "+f"(d[67]), "+f"(d[68]), "+f"(d[69]), "+f"(d[70]), "+f"(d[71]),
          "+f"(d[72]), "+f"(d[73]), "+f"(d[74]), "+f"(d[75]), "+f"(d[76]), "+f"(d[77]), "+f"(d[78]), "+f"(d[79]),
          "+f"(d[80]), "+f"(d[81]), "+f"(d[82]), "+f"(d[83]), "+f"(d[84]), "+f"(d[85]), "+f"(d[86]), "+f"(d[87]),
          "+f"(d[88]), "+f"(d[89]), "+f"(d[90]), "+f"(d[91]), "+f"(d[92]), "+f"(d[93]), "+f"(d[94]), "+f"(d[95])
        : "r"(alo), "r"(blo), "r"(scale_d), "n"(TA), "n"(TB), "r"(DESC_HI));
}
template <int TB>
__device__ __forceinline__ void wgmma_rs_n128(float (&d)[64], uint32_t a0, uint32_t a1, uint32_t a2, uint32_t a3, uint32_t blo, int scale_d) {
    asm volatile("{\n.reg .pred p;\n.reg .b64 db;\nsetp.ne.b32 p, %69, 0;\n"
        "mov.b64 db, {%68, %71};\n"
        "wgmma.mma_async.sync.aligned.m64n128k16.f32.bf16.bf16 "
        "{%0, %1, %2, %3, %4, %5, %6, %7, %8, %9, %10, %11, %12, %13, %14, %15, %16, %17, %18, %19, %20, %21, %22, %23, %24, %25, %26, %27, %28, %29, %30, %31, %32, %33, %34, %35, %36, %37, %38, %39, %40, %41, %42, %43, %44, %45, %46, %47, %48, %49, %50, %51, %52, %53, %54, %55, %56, %57, %58, %59, %60, %61, %62, %63}, {%64, %65, %66, %67}, db, p, 1, 1, %70;\n}\n"
        :
          "+f"(d[0]), "+f"(d[1]), "+f"(d[2]), "+f"(d[3]), "+f"(d[4]), "+f"(d[5]), "+f"(d[6]), "+f"(d[7]),
          "+f"(d[8]), "+f"(d[9]), "+f"(d[10]), "+f"(d[11]), "+f"(d[12]), "+f"(d[13]), "+f"(d[14]), "+f"(d[15]),
          "+f"(d[16]), "+f"(d[17]), "+f"(d[18]), "+f"(d[19]), "+f"(d[20]), "+f"(d[21]), "+f"(d[22]), "+f"(d[23]),
          "+f"(d[24]), "+f"(d[25]), "+f"(d[26]), "+f"(d[27]), "+f"(d[28]), "+f"(d[29]), "+f"(d[30]), "+f"(d[31]),
          "+f"(d[32]), "+f"(d[33]), "+f"(d[34]), "+f"(d[35]), "+f"(d[36]), "+f"(d[37]), "+f"(d[38]), "+f"(d[39]),
          "+f"(d[40]), "+f"(d[41]), "+f"(d[42]), "+f"(d[43]), "+f"(d[44]), "+f"(d[45]), "+f"(d[46]), "+f"(d[47]),
          "+f"(d[48]), "+f"(d[49]), "+f"(d[50]), "+f"(d[51]), "+f"(d[52]), "+f"(d[53]), "+f"(d[54]), "+f"(d[55]),
          "+f"(d[56]), "+f"(d[57]), "+f"(d[58]), "+f"(d[59]), "+f"(d[60]), "+f"(d[61]), "+f"(d[62]), "+f"(d[63])
        : "r"(a0), "r"(a1), "r"(a2), "r"(a3), "r"(blo), "r"(scale_d), "n"(TB), "r"(DESC_HI));
}
template <int TB>
__device__ __forceinline__ void wgmma_rs_n128_z(float (&d)[64], uint32_t a0, uint32_t a1, uint32_t a2, uint32_t a3, uint32_t blo) {
    asm volatile("{\n.reg .pred p;\n.reg .b64 db;\nsetp.ne.b32 p, %69, 0;\n"
        "mov.b64 db, {%68, %71};\n"
        "wgmma.mma_async.sync.aligned.m64n128k16.f32.bf16.bf16 "
        "{%0, %1, %2, %3, %4, %5, %6, %7, %8, %9, %10, %11, %12, %13, %14, %15, %16, %17, %18, %19, %20, %21, %22, %23, %24, %25, %26, %27, %28, %29, %30, %31, %32, %33, %34, %35, %36, %37, %38, %39, %40, %41, %42, %43, %44, %45, %46, %47, %48, %49, %50, %51, %52, %53, %54, %55, %56, %57, %58, %59, %60, %61, %62, %63}, {%64, %65, %66, %67}, db, p, 1, 1, %70;\n}\n"
        :
          "=f"(d[0]), "=f"(d[1]), "=f"(d[2]), "=f"(d[3]), "=f"(d[4]), "=f"(d[5]), "=f"(d[6]), "=f"(d[7]),
          "=f"(d[8]), "=f"(d[9]), "=f"(d[10]), "=f"(d[11]), "=f"(d[12]), "=f"(d[13]), "=f"(d[14]), "=f"(d[15]),
          "=f"(d[16]), "=f"(d[17]), "=f"(d[18]), "=f"(d[19]), "=f"(d[20]), "=f"(d[21]), "=f"(d[22]), "=f"(d[23]),
          "=f"(d[24]), "=f"(d[25]), "=f"(d[26]), "=f"(d[27]), "=f"(d[28]), "=f"(d[29]), "=f"(d[30]), "=f"(d[31]),
          "=f"(d[32]), "=f"(d[33]), "=f"(d[34]), "=f"(d[35]), "=f"(d[36]), "=f"(d[37]), "=f"(d[38]), "=f"(d[39]),
          "=f"(d[40]), "=f"(d[41]), "=f"(d[42]), "=f"(d[43]), "=f"(d[44]), "=f"(d[45]), "=f"(d[46]), "=f"(d[47]),
          "=f"(d[48]), "=f"(d[49]), "=f"(d[50]), "=f"(d[51]), "=f"(d[52]), "=f"(d[53]), "=f"(d[54]), "=f"(d[55]),
          "=f"(d[56]), "=f"(d[57]), "=f"(d[58]), "=f"(d[59]), "=f"(d[60]), "=f"(d[61]), "=f"(d[62]), "=f"(d[63])
        : "r"(a0), "r"(a1), "r"(a2), "r"(a3), "r"(blo), "n"(0), "n"(TB), "r"(DESC_HI));
}
template <int TA, int TB>
__device__ __forceinline__ void wgmma_ss_n128_z(float (&d)[64], uint32_t alo, uint32_t blo) {
    asm volatile("{\n.reg .pred p;\n.reg .b64 da, db;\nsetp.ne.b32 p, %66, 0;\n"
        "mov.b64 da, {%64, %69};\nmov.b64 db, {%65, %69};\n"
        "wgmma.mma_async.sync.aligned.m64n128k16.f32.bf16.bf16 "
        "{%0, %1, %2, %3, %4, %5, %6, %7, %8, %9, %10, %11, %12, %13, %14, %15, %16, %17, %18, %19, %20, %21, %22, %23, %24, %25, %26, %27, %28, %29, %30, %31, %32, %33, %34, %35, %36, %37, %38, %39, %40, %41, %42, %43, %44, %45, %46, %47, %48, %49, %50, %51, %52, %53, %54, %55, %56, %57, %58, %59, %60, %61, %62, %63}, da, db, p, 1, 1, %67, %68;\n}\n"
        :
          "=f"(d[0]), "=f"(d[1]), "=f"(d[2]), "=f"(d[3]), "=f"(d[4]), "=f"(d[5]), "=f"(d[6]), "=f"(d[7]),
          "=f"(d[8]), "=f"(d[9]), "=f"(d[10]), "=f"(d[11]), "=f"(d[12]), "=f"(d[13]), "=f"(d[14]), "=f"(d[15]),
          "=f"(d[16]), "=f"(d[17]), "=f"(d[18]), "=f"(d[19]), "=f"(d[20]), "=f"(d[21]), "=f"(d[22]), "=f"(d[23]),
          "=f"(d[24]), "=f"(d[25]), "=f"(d[26]), "=f"(d[27]), "=f"(d[28]), "=f"(d[29]), "=f"(d[30]), "=f"(d[31]),
          "=f"(d[32]), "=f"(d[33]), "=f"(d[34]), "=f"(d[35]), "=f"(d[36]), "=f"(d[37]), "=f"(d[38]), "=f"(d[39]),
          "=f"(d[40]), "=f"(d[41]), "=f"(d[42]), "=f"(d[43]), "=f"(d[44]), "=f"(d[45]), "=f"(d[46]), "=f"(d[47]),
          "=f"(d[48]), "=f"(d[49]), "=f"(d[50]), "=f"(d[51]), "=f"(d[52]), "=f"(d[53]), "=f"(d[54]), "=f"(d[55]),
          "=f"(d[56]), "=f"(d[57]), "=f"(d[58]), "=f"(d[59]), "=f"(d[60]), "=f"(d[61]), "=f"(d[62]), "=f"(d[63])
        : "r"(alo), "r"(blo), "n"(0), "n"(TA), "n"(TB), "r"(DESC_HI));
}

__device__ __forceinline__ uint32_t pack_bf16(float lo, float hi) {
    uint32_t r;
    asm("cvt.rn.bf16x2.f32 %0, %1, %2;" : "=r"(r) : "f"(hi), "f"(lo));
    return r;
}
__device__ __forceinline__ uint32_t add_bf16x2(uint32_t a, uint32_t b) {
    uint32_t r;
    asm("add.rn.bf16x2 %0, %1, %2;" : "=r"(r) : "r"(a), "r"(b));
    return r;
}
__device__ __forceinline__ float bf_lo(uint32_t v) { return __uint_as_float(v << 16); }
__device__ __forceinline__ float bf_hi(uint32_t v) { return __uint_as_float(v & 0xffff0000u); }
__device__ __forceinline__ float round_bf16(float v) { return __bfloat162float(__float2bfloat16_rn(v)); }
__device__ __forceinline__ float ex2(float x) {
    float y;
    asm("ex2.approx.ftz.f32 %0, %1;" : "=f"(y) : "f"(x));
    return y;
}
__device__ __forceinline__ float rcp(float x) {
    float y;
    asm("rcp.approx.ftz.f32 %0, %1;" : "=f"(y) : "f"(x));
    return y;
}
__device__ __forceinline__ void stg128(void* p, uint32_t a, uint32_t b, uint32_t c, uint32_t d) {
    asm volatile("st.global.v4.b32 [%0], {%1, %2, %3, %4};" ::"l"(p), "r"(a), "r"(b), "r"(c), "r"(d) : "memory");
}
__device__ __forceinline__ int perm_row(int t) { return (t & ~255) | (((0x78 >> (((t >> 6) & 3) * 2)) & 3) << 6) | (t & 63); }
__device__ __forceinline__ int unperm_row(int t) { return (t & ~255) | (((0x9C >> (((t >> 6) & 3) * 2)) & 3) << 6) | (t & 63); }

#define PROF(i)
#define PROFG(i)
#define PROFDUMP()
#define TR(i)
#define BP(r, i)
#define LP(i)

template <int I>
__device__ __forceinline__ void store_chunk(const float (&a)[64], __nv_bfloat16* row0, __nv_bfloat16* row1, float s0, float s1) {
    stg128(row0 + 32 * I, pack_bf16(a[16 * I + 0] * s0, a[16 * I + 1] * s0), pack_bf16(a[16 * I + 4] * s0, a[16 * I + 5] * s0),
           pack_bf16(a[16 * I + 8] * s0, a[16 * I + 9] * s0), pack_bf16(a[16 * I + 12] * s0, a[16 * I + 13] * s0));
    stg128(row1 + 32 * I, pack_bf16(a[16 * I + 2] * s1, a[16 * I + 3] * s1), pack_bf16(a[16 * I + 6] * s1, a[16 * I + 7] * s1),
           pack_bf16(a[16 * I + 10] * s1, a[16 * I + 11] * s1), pack_bf16(a[16 * I + 14] * s1, a[16 * I + 15] * s1));
}
template <int I>
struct IntT { static constexpr int value = I; };
template <class F>
__device__ __forceinline__ void for4(F f) { f(IntT<0>{}); f(IntT<1>{}); f(IntT<2>{}); f(IntT<3>{}); }

struct Prod {
    uint32_t smem, bars, pe;
    int ring;
    __device__ __forceinline__ uint32_t acquire(int s, uint32_t bytes) {
        mbar_wait(bars + BAR_EMPTY + s * 8, (pe >> s) & 1);
        pe ^= 1u << s;
        mbar_expect_tx(bars + BAR_FULL + s * 8, bytes);
        return bars + BAR_FULL + s * 8;
    }
    __device__ __forceinline__ int next() {
        int s = ring;
        ring = (ring == NSLOT - 1) ? 0 : ring + 1;
        return s;
    }
};

__device__ __forceinline__ int item_p(int ca, int rd) {
    const int v = (rd & 1) ? (ca + 4) & 7 : ca;
    return (rd & 2) ? 7 - v : v;
}
__device__ __forceinline__ int kv_round(int i) { return (KVORDER >> (4 * i)) & 3; }
__device__ __forceinline__ int slot_a(int i) { return (0x5310 >> (4 * i)) & 15; }
__device__ __forceinline__ int slot_w(int m) { return (0x264 >> (4 * m)) & 15; }

__device__ __forceinline__ void producer(const Params& P, uint32_t smem, uint32_t bars, int ca, int cb, int rank) {
    Prod pr{smem, bars, 0x50u, 0};
    {
        int m = 0;
#pragma unroll 1
        for (int u = 0; u < 32; u++) {
            if (u >= 3) {
                const int v = (u == 3) ? 4 + ca : u + 8;
                if (v < 32 && (u == 3 || (v & 7) == ca)) tma_prefetch((v & 4) ? &P.wuv : &P.wuk, (cb + 8 * kv_round(v >> 3)) * 128 + rank * 64, (v & 3) * 128);
                if (u == 24) {
                    tma_prefetch(&P.wq, cb * 128 + rank * 64, ca * 64);
                    if (ca < 2) tma_prefetch(&P.wq, cb * 128 + rank * 64, (ca + 8) * 64);
                }
            }
            int s = slot_w(m);
            m = (m == 2) ? 0 : m + 1;
            uint32_t fb = pr.acquire(s, SLOT);
            int h = cb + 8 * kv_round(u >> 3);
            TR(1 + u);
            tma_load_mc(smem + s * SLOT + rank * 16384, (u & 4) ? &P.wuv : &P.wuk, h * 128 + rank * 64, (u & 3) * 128, fb);
            if (u < 3) {
                s = slot_a(u + 1);
                fb = bars + BAR_FULL + s * 8;
                mbar_expect_tx(fb, SLOT);
                tma_load(smem + s * SLOT, &P.ckv, u * 128 + 128, (2 * ca + rank) * 128, fb);
                tma_load(smem + s * SLOT + 16384, &P.ckv, u * 128 + 192, (2 * ca + rank) * 128, fb);
            }
        }
    }
    PROF(1);
    mbar_wait(bars + BAR_DEP, 0);
#pragma unroll 1
    for (int rd = 0; rd < 4; rd++) {
        const int h = 8 * rd + cb, p = item_p(ca, rd);
#pragma unroll 1
        for (int ks = 0; ks < 10; ks++) {
            int s = pr.next();
            uint32_t fb = pr.acquire(s, SLOT);
            tma_load(smem + s * SLOT, &P.xn, ks * 64, 256 * p + 128 * rank, fb);
            tma_load_mc(smem + s * SLOT + 16384 + rank * 8192, &P.wq, h * 128 + rank * 64, ks * 64, fb);
        }
        PROF(8 + rd * 4);
        mbar_wait(bars + BAR_DEP + (1 + rd) * 8, 0);
        if (rd < 3) {
            tma_prefetch(&P.wq, (h + 8) * 128 + rank * 64, ca * 64);
            if (ca < 2) tma_prefetch(&P.wq, (h + 8) * 128 + rank * 64, (ca + 8) * 64);
        } else {
#pragma unroll 1
            for (int i = 0; i < 10; i++) {
                const int t = ca + (i >= 5 ? 8 : 0);
                tma_prefetch(&P.wo, 320 * (cb & 1) + 64 * (i >= 5 ? i - 5 : i), (8 * (t >> 2) + (cb & 6) + ((t >> 1) & 1)) * 128 + (t & 1) * 64 + rank * 32);
            }
        }
        const int last = 4 * p + 3, top = h * 32 + last;
#pragma unroll 1
        for (int i = 0; i <= last; i++) {
            const int t = (i == 0) ? top - 1 : (i == last) ? h * 32 + 1 : (i & 1) ? top - 2 - i : top + 2 - i;
            int s = pr.next();
            uint32_t fb = pr.acquire(s, SLOT);
            tma_load_mc(smem + s * SLOT + rank * 16384, &P.kv, rank * 64, t * 128, fb);
        }
        PROF(9 + rd * 4);
    }
    {
        const int n0 = 320 * (cb & 1), kg = cb >> 1;
#pragma unroll 1
        for (int t = 0; t < 16; t++) {
            const int h = 8 * (t >> 2) + 2 * kg + ((t >> 1) & 1), ks = t & 1;
            const int krow = h * 128 + ks * 64 + rank * 32;
            int s = pr.next();
            uint32_t fb = pr.acquire(s, SLOT);
            tma_load_mc(smem + s * SLOT + 16384 + rank * 8192, &P.wo, n0, krow, fb);
            tma_load_mc(smem + s * SLOT + 16384 + rank * 8192 + 4096, &P.wo, n0 + 64, krow, fb);
            mbar_wait(bars + BAR_DEP + (5 + (t >> 1)) * 8, 0);
            tma_load(smem + s * SLOT, &P.ctx, ks * 64, h * SEQ + 256 * ca + 128 * rank, fb);
            s = pr.next();
            fb = pr.acquire(s, 24576);
#pragma unroll
            for (int c = 0; c < 3; c++) tma_load_mc(smem + s * SLOT + rank * 12288 + c * 4096, &P.wo, n0 + 128 + 64 * c, krow, fb);
        }
    }
}

struct Slot {
    uint32_t bo, dl, par;
};
struct Cons {
    uint32_t bars, rel;
    uint32_t dl0;
    uint32_t lane;
    Slot cur;
    __device__ __forceinline__ Slot slot(int s, uint32_t par) const { return Slot{(uint32_t)s * 8, dl0 + (uint32_t)s * (SLOT >> 4), par}; }
    __device__ __forceinline__ void wait(const Slot& s) const { mbar_wait(bars + BAR_FULL + s.bo, s.par); }
    __device__ __forceinline__ void release(uint32_t bo) const {
        asm volatile("{\n.reg .pred p;\nsetp.lt.u32 p, %1, 2;\n@p mbarrier.arrive.shared::cluster.b64 _, [%0];\n}\n" ::"r"(rel + bo), "r"(lane) : "memory");
    }
    __device__ __forceinline__ Slot next() {
        const Slot s = cur;
        const bool wrap = s.bo == (NSLOT - 1) * 8;
        cur.bo = wrap ? 0u : s.bo + 8;
        cur.dl = wrap ? dl0 : s.dl + (SLOT >> 4);
        cur.par = s.par ^ (wrap ? 1u : 0u);
        return s;
    }
};
__host__ __device__ constexpr uint32_t lbo(uint32_t bytes) { return (bytes >> 4) << 16; }

__device__ __forceinline__ float div640(float x) {
    const float q = x * (1.0f / DM);
    return fmaf(fmaf(-q, (float)DM, x), 1.0f / DM, q);
}
__device__ __forceinline__ float sqrt_approx(float x) {
    float y;
    asm("sqrt.approx.ftz.f32 %0, %1;" : "=f"(y) : "f"(x));
    return y;
}
struct LayerNorm {
    uint4 xv[5], wv[5];
    uint32_t nmb;
    float inv, r;
    __device__ __forceinline__ void stats() {
        float v[40];
#pragma unroll
        for (int i = 0; i < 20; i++) { const uint32_t u = (&xv[i >> 2].x)[i & 3]; v[2 * i] = bf_lo(u); v[2 * i + 1] = bf_hi(u); }
        float sum = 0.f, sq = 0.f;
#pragma unroll
        for (int i = 0; i < 40; i += 4) sum += (v[i] + v[i + 1]) + (v[i + 2] + v[i + 3]);
#pragma unroll
        for (int o = 8; o > 0; o >>= 1) sum += __shfl_xor_sync(0xffffffffu, sum, o);
        const float mean = div640(sum);
#pragma unroll
        for (int i = 0; i < 40; i += 2) { const float d0 = v[i] - mean, d1 = v[i + 1] - mean; sq += fmaf(d0, d0, d1 * d1); }
#pragma unroll
        for (int o = 8; o > 0; o >>= 1) sq += __shfl_xor_sync(0xffffffffu, sq, o);
        nmb = pack_bf16(-mean, -mean);
        inv = rcp(round_bf16(sqrt_approx(round_bf16(round_bf16(div640(sq)) + 1e-5f))));
        r = 0.f;
    }
    template <int I>
    __device__ __forceinline__ void piece(int t, int l) {
        uint32_t o[4], z[4];
#pragma unroll
        for (int j = 0; j < 4; j++) {
            const uint32_t u = (&xv[I].x)[j], w = (&wv[I].x)[j];
            const uint32_t d = add_bf16x2(u, nmb);
            o[j] = pack_bf16(bf_lo(d) * inv, bf_hi(d) * inv);
            const float n0 = bf_lo(o[j]), n1 = bf_hi(o[j]);
            z[j] = add_bf16x2(u, o[j]);
            r = fmaf(n1, bf_hi(w), fmaf(n0, bf_lo(w), r));
        }
        stg128(g_xn + (size_t)perm_row(t) * DM + 8 * (l + 16 * I), o[0], o[1], o[2], o[3]);
        stg128(g_res + (size_t)t * DM + 8 * (l + 16 * I), z[0], z[1], z[2], z[3]);
        if (I == 4) {
#pragma unroll
            for (int k = 8; k > 0; k >>= 1) r += __shfl_xor_sync(0xffffffffu, r, k);
            if (l == 0) g_r[t] = round_bf16(r);
        }
    }
};

constexpr float SM_SCALE = 0.08838834764831845f * 1.4426950408889634f;

template <int J0, int J1, int SEG = 0>
__device__ __forceinline__ void exp_part(float (&s)[64], float n0, float n1, float& r0, float& r1) {
    float a1 = 0.f, b1 = 0.f;
#pragma unroll
    for (int j = J0; j < J1; j++) {
        if (SEG > 0 && j >= SEG && j % (SEG > 0 ? SEG : 1) == 0) {
            n0 = fmaf(s[4 * (j - PACE_LAG)], 0.f, n0);
            n1 = fmaf(s[4 * (j - PACE_LAG)], 0.f, n1);
        }
        s[4 * j + 0] = ex2(fmaf(s[4 * j + 0], SM_SCALE, n0));
        s[4 * j + 1] = ex2(fmaf(s[4 * j + 1], SM_SCALE, n0));
        s[4 * j + 2] = ex2(fmaf(s[4 * j + 2], SM_SCALE, n1));
        s[4 * j + 3] = ex2(fmaf(s[4 * j + 3], SM_SCALE, n1));
        r0 += s[4 * j + 0]; r1 += s[4 * j + 2];
        if (j == J0) { a1 = s[4 * j + 1]; b1 = s[4 * j + 3]; } else { a1 += s[4 * j + 1]; b1 += s[4 * j + 3]; }
    }
    r0 += a1;
    r1 += b1;
}
__device__ __forceinline__ void sched_barrier(float x, float y, uint32_t scratch) {
    asm volatile("{\n.reg .pred p;\nsetp.lt.f32 p, %0, 0f00000000;\n@p st.shared.f32 [%2], %1;\n}\n" ::"f"(x), "f"(y), "r"(scratch) : "memory");
}
__device__ __forceinline__ void pack_tile(const float (&s)[64], uint32_t (&p)[32]) {
#pragma unroll
    for (int i = 0; i < 32; i++) p[i] = pack_bf16(s[2 * i], s[2 * i + 1]);
}
template <bool ZERO>
__device__ __forceinline__ void gemm_rs(float (&d)[64], const uint32_t (&a)[32], uint32_t dl, int acc = 1) {
    const uint32_t b = dl + lbo(16384);
    if (ZERO) wgmma_rs_n128_z<1>(d, a[0], a[1], a[2], a[3], b);
#pragma unroll
    for (int k = ZERO ? 1 : 0; k < 8; k++) wgmma_rs_n128<1>(d, a[4 * k], a[4 * k + 1], a[4 * k + 2], a[4 * k + 3], b + k * 128, k ? 1 : acc);
}
template <int ZERO>
__device__ __forceinline__ void gemm_q(float (&d)[64], uint32_t dl, int role) {
    const uint32_t a = dl + role * 512 + lbo(16), b = dl + 1024 + lbo(8192);
    if (ZERO) wgmma_ss_n128_z<0, 1>(d, a, b);
#pragma unroll
    for (int k = ZERO ? 1 : 0; k < 4; k++) wgmma_ss_n128<0, 1>(d, a + k * 2, b + k * 128, 1);
}
template <bool KT, bool ZERO, int K0, int K1>
__device__ __forceinline__ void gemm_kv(float (&d)[64], uint32_t ckv, uint32_t wt, int wg) {
    if (KT) {
        const uint32_t a = wt + wg * 1024 + lbo(16), b = ckv + lbo(16);
        if (ZERO) wgmma_ss_n128_z<1, 0>(d, a, b);
#pragma unroll
        for (int k = ZERO ? 1 : K0; k < K1; k++) wgmma_ss_n128<1, 0>(d, a + k * 128, b + (k >> 2) * 1024 + (k & 3) * 2, 1);
    } else {
        const uint32_t a = ckv + wg * 512 + lbo(16), b = wt + lbo(16384);
        if (ZERO) wgmma_ss_n128_z<0, 1>(d, a, b);
#pragma unroll
        for (int k = ZERO ? 1 : K0; k < K1; k++) wgmma_ss_n128<0, 1>(d, a + (k >> 2) * 1024 + (k & 3) * 2, b + k * 128, 1);
    }
}
__device__ __forceinline__ void mma16816(float& d0, float& d1, float& d2, float& d3, uint32_t a0, uint32_t a1, uint32_t a2, uint32_t a3, uint32_t b0, uint32_t b1) {
    asm volatile("mma.sync.aligned.m16n8k16.row.col.f32.bf16.bf16.f32 {%0,%1,%2,%3}, {%4,%5,%6,%7}, {%8,%9}, {%0,%1,%2,%3};"
                 : "+f"(d0), "+f"(d1), "+f"(d2), "+f"(d3) : "r"(a0), "r"(a1), "r"(a2), "r"(a3), "r"(b0), "r"(b1));
}
__device__ __forceinline__ uint32_t ld_pair(const __nv_bfloat16* p) {
    const unsigned short* u = reinterpret_cast<const unsigned short*>(p);
    return (uint32_t)__ldcg(u) | ((uint32_t)__ldcg(u + 128) << 16);
}
__device__ __forceinline__ void attention_exact(float (&o)[64], const uint32_t (&qf)[32], float& l0, float& l1, int h, int nblk, int rr, int lane) {
    const int q = lane & 3, lr = lane >> 2;
    float m0 = -INFINITY, m1 = -INFINITY;
    l0 = 0.f; l1 = 0.f;
#pragma unroll
    for (int i = 0; i < 64; i++) o[i] = 0.f;
#pragma unroll 1
    for (int cidx = 0; cidx < nblk * 8; cidx++) {
        const int kc = cidx & 7;
        const __nv_bfloat16* kt = g_kv + (size_t)((h * 16 + (cidx >> 3)) * 2) * 16384;
        float sc[8];
#pragma unroll
        for (int i = 0; i < 8; i++) sc[i] = 0.f;
#pragma unroll
        for (int kk = 0; kk < 8; kk++)
#pragma unroll
            for (int nt = 0; nt < 2; nt++) {
                const __nv_bfloat16* b = kt + (16 * kk + 2 * q) * 128 + 16 * kc + 8 * nt + lr;
                mma16816(sc[4 * nt], sc[4 * nt + 1], sc[4 * nt + 2], sc[4 * nt + 3], qf[4 * kk], qf[4 * kk + 1], qf[4 * kk + 2], qf[4 * kk + 3],
                         ld_pair(b), ld_pair(b + 8 * 128));
            }
        const int lim = rr + ((nblk - 1) - (cidx >> 3)) * 128 - 32 * (kc >> 1) - 4 * (kc & 1);
#pragma unroll
        for (int i = 0; i < 8; i++)
            if (2 * (i >> 2) + (i & 1) > lim + 4 * (i & 2)) sc[i] = -INFINITY;
        float x0 = fmaxf(fmaxf(sc[0], sc[1]), fmaxf(sc[4], sc[5])), x1 = fmaxf(fmaxf(sc[2], sc[3]), fmaxf(sc[6], sc[7]));
        x0 = fmaxf(x0, __shfl_xor_sync(0xffffffffu, x0, 1)); x1 = fmaxf(x1, __shfl_xor_sync(0xffffffffu, x1, 1));
        x0 = fmaxf(x0, __shfl_xor_sync(0xffffffffu, x0, 2)); x1 = fmaxf(x1, __shfl_xor_sync(0xffffffffu, x1, 2));
        x0 = fmaxf(x0, m0); x1 = fmaxf(x1, m1);
        const float a0 = ex2((m0 - x0) * SM_SCALE), a1 = ex2((m1 - x1) * SM_SCALE);
        m0 = x0; m1 = x1;
#pragma unroll
        for (int i = 0; i < 8; i++) sc[i] = ex2((sc[i] - ((i & 2) ? m1 : m0)) * SM_SCALE);
        l0 = l0 * a0 + (sc[0] + sc[1]) + (sc[4] + sc[5]);
        l1 = l1 * a1 + (sc[2] + sc[3]) + (sc[6] + sc[7]);
        const uint32_t p0 = pack_bf16(sc[0], sc[1]), p1 = pack_bf16(sc[2], sc[3]), p2 = pack_bf16(sc[4], sc[5]), p3 = pack_bf16(sc[6], sc[7]);
        const __nv_bfloat16* vb = kt + 16384 + (16 * kc + 2 * q) * 128 + lr;
#pragma unroll
        for (int nt = 0; nt < 16; nt++) {
            o[4 * nt] *= a0; o[4 * nt + 1] *= a0; o[4 * nt + 2] *= a1; o[4 * nt + 3] *= a1;
            mma16816(o[4 * nt], o[4 * nt + 1], o[4 * nt + 2], o[4 * nt + 3], p0, p1, p2, p3, ld_pair(vb + 8 * nt), ld_pair(vb + 8 * nt + 8 * 128));
        }
    }
}

__device__ __forceinline__ void signal(uint32_t bars, int wg, int e, int lane) {
    __syncwarp();
    asm volatile("{\n.reg .pred p;\nsetp.eq.u32 p, %1, 0;\n@p mbarrier.arrive.shared::cta.b64 _, [%0];\n}\n" ::"r"(bars + BAR_SIG + (wg * 9 + e) * 8), "r"(lane) : "memory");
}

__device__ __forceinline__ void consumer(const Params& P, uint32_t smem, uint32_t bars, int ca, int cb, int rank, int wg, LayerNorm& ln) {
    const int lane = threadIdx.x & 31, w = (threadIdx.x >> 5) & 3, q = lane & 3, lr = lane >> 2;
    PROF(7);
    const int ln_t = blockIdx.x * 16 + wg * 8 + w * 2 + (lane >> 4);
    ln.stats();
    ln.piece<0>(ln_t, lane & 15);
    cluster_wait();
    Cons c{bars, mapa(bars + BAR_EMPTY, lane & 1), (smem & 0x3FFFF) >> 4, (uint32_t)lane, Slot{0u, (smem & 0x3FFFF) >> 4, 1u}};
    PROFG(180);
    PROF(1);
    float o[64], s[64];
    uint32_t pend;
    __nv_bfloat16* ep_ptr;
    int ep_step;
    {
        const int krow = 64 * wg + 16 * w + lr;
        const int vrow = 64 * wg + 32 * (w >> 1) + 8 * (lr >> 1) + 4 * (w & 1) + (lr & 1);
        ep_step = 2 * 128;
        int m = 0;
        uint32_t lap = 0;
        auto step = [&](auto kt, auto kc, float (&d)[64], int hh) {
            const Slot sa = c.slot(slot_a(kc.value), 0), sw = c.slot(slot_w(m), lap ^ (m >> 1));
            lap ^= m >> 1;
            m = (m == 2) ? 0 : m + 1;
            TR(1 + (hh * 8 + (kt.value ? 0 : 4) + kc.value) * 2);
            if (kt.value && hh == 0) c.wait(sa);
            c.wait(sw);
            TR(2 + (hh * 8 + (kt.value ? 0 : 4) + kc.value) * 2);
            wgmma_fence();
            gemm_kv<kt.value, kc.value == 0, 0, KVSPLIT>(d, sa.dl, sw.dl, wg);
            wgmma_commit();
            wgmma_wait<1>();
            if (!(kt.value && kc.value == 0 && hh == 0)) c.release(pend);
            if (!kt.value && kc.value > 0 && hh == 3) c.release(slot_a(kc.value - 1) * 8);
            pend = sw.bo;
            wgmma_fence();
            gemm_kv<kt.value, false, KVSPLIT, 8>(d, sa.dl, sw.dl, wg);
            wgmma_commit();
        };
#pragma unroll 1
        for (int hh = 0; hh < 4; hh++) {
            __nv_bfloat16* base = g_kv + (size_t)(((cb + 8 * kv_round(hh)) * 16 + 2 * ca + rank) * 2) * 16384 + 8 * q;
            for4([&](auto kc) {
                step(TrueT{}, kc, s, hh);
                if (hh > 0) {
                    if (kc.value == 0) fence_regs(o);
                    store_chunk<kc.value>(o, ep_ptr, ep_ptr + ep_step, 1.f, 1.f);
                } else {
                    ln.template piece<kc.value + 1>(ln_t, lane & 15);
                }
            });
            signal(bars, wg, hh, lane);
            for4([&](auto kc) {
                step(FalseT{}, kc, o, hh);
                if (kc.value == 0) fence_regs(s);
                store_chunk<kc.value>(s, base + krow * 128, base + (krow + 8) * 128, 1.f, 1.f);
            });
            PROF(24 + hh);
            if (hh == 1) PROFG(181);
            ep_ptr = base + 16384 + vrow * 128;
        }
    }
    PROFG(182);
    PROF(2);
    {
        uint32_t pf[32], qf[32];
        float l0 = 0.25f, l1 = 0.25f;
        const int bar_me = 2 + wg, bar_other = 3 - wg;
#pragma unroll 1
        for (int rd = 0; rd < 4; rd++) {
            const int h = 8 * rd + cb, p = item_p(ca, rd);
            const int role = wg ^ (rd & 1);
            const int nrest = 2 * p + role;
            Slot kfirst;
            {
                auto qstep = [&](auto zero, int ks) {
                    const Slot sl = c.next();
                    BP(2, 4 + 3 * ks);
                    c.wait(sl);
                    BP(2, 5 + 3 * ks);
                    wgmma_fence();
                    gemm_q<zero.value>(s, sl.dl, role);
                    wgmma_commit();
                    wgmma_wait<1>();
                    BP(2, 6 + 3 * ks);
                    c.release(pend);
                    pend = sl.bo;
                };
                qstep(TrueT{}, 0);
                if (rd == 0) c.release(slot_a(3) * 8);
                fence_regs(o);
#pragma unroll 1
                for (int ks = 1; ks < QST; ks++) qstep(FalseT{}, ks);
                for4([&](auto i) {
                    qstep(FalseT{}, QST + i.value);
                    if (i.value == 0) {
                        l0 += __shfl_xor_sync(0xffffffffu, l0, 1); l1 += __shfl_xor_sync(0xffffffffu, l1, 1);
                        l0 += __shfl_xor_sync(0xffffffffu, l0, 2); l1 += __shfl_xor_sync(0xffffffffu, l1, 2);
                        l0 = rcp(l0); l1 = rcp(l1);
                    }
                    store_chunk<i.value>(o, ep_ptr, ep_ptr + ep_step, l0, l1);
                });
                signal(bars, wg, 4 + rd, lane);
                PROF(11 + rd * 4);
#pragma unroll 1
                for (int ks = QST + 4; ks < 10; ks++) qstep(FalseT{}, ks);
                if (!role) { const Slot sl = c.next(); c.wait(sl); c.release(sl.bo); }
                kfirst = c.next();
                c.wait(kfirst);
                wgmma_wait<0>();
                BP(2, 34);
                c.release(pend);
                fence_regs(s);
                pack_tile(s, qf);
            }
            PROF(8 + rd * 4);
            fence_regs(qf);
            BP(2, 35);
            if (PINGPONG && !role) named_sync(bar_me, 256);
            BP(2, 36);
            wgmma_fence();
            gemm_rs<true>(s, qf, kfirst.dl);
            wgmma_commit();
            if (PINGPONG) named_arrive(bar_other, 256);
            BP(2, 37);
            if (!role) { const Slot sl = c.next(); c.wait(sl); c.release(sl.bo); }
            const int dg = __reduce_or_sync(0xffffffffu, 2 * (role ^ rank) + (w >> 1));
            wgmma_wait<0>();
            BP(2, 38);
            fence_regs(s);
            c.release(kfirst.bo);
            float n0, n1;
            l0 = 0.f; l1 = 0.f;
            for4([&](auto a) {
                constexpr int B = 16 * a.value;
                if (a.value == dg) {
                    const int lim = 16 * (w & 1) + lr - 8 * q;
#pragma unroll
                    for (int i = 0; i < 16; i++)
                        if (2 * (i >> 2) + (i & 1) > lim + 4 * (i & 2)) s[B + i] = -INFINITY;
                }
                if (a.value == 0) {
                    n0 = fmaxf(fmaxf(fmaxf(s[0], s[1]), fmaxf(s[4], s[5])), fmaxf(fmaxf(s[8], s[9]), fmaxf(s[12], s[13])));
                    n1 = fmaxf(fmaxf(fmaxf(s[2], s[3]), fmaxf(s[6], s[7])), fmaxf(fmaxf(s[10], s[11]), fmaxf(s[14], s[15])));
                    n0 = fmaxf(n0, __shfl_xor_sync(0xffffffffu, n0, 1)); n1 = fmaxf(n1, __shfl_xor_sync(0xffffffffu, n1, 1));
                    n0 = fmaxf(n0, __shfl_xor_sync(0xffffffffu, n0, 2)); n1 = fmaxf(n1, __shfl_xor_sync(0xffffffffu, n1, 2));
                    n0 *= -SM_SCALE; n1 *= -SM_SCALE;
                }
                if (a.value <= dg) {
                    exp_part<4 * a.value, 4 * a.value + 4>(s, n0, n1, l0, l1);
#pragma unroll
                    for (int i = 0; i < 8; i++) pf[8 * a.value + i] = pack_bf16(s[B + 2 * i], s[B + 2 * i + 1]);
                } else {
#pragma unroll
                    for (int i = 0; i < 8; i++) pf[8 * a.value + i] = 0u;
                }
            });
            PROF(9 + rd * 4);
#pragma unroll 1
            for (int it = 0; it < nrest; it++) {
                const Slot sk = c.next(), sv = c.next();
                LP(0);
                if (it < 3) BP(2, 40 + 4 * it);
                if (it >= nrest - 2) BP(1, 60 + 4 * (it - nrest + 2));
                c.wait(sk);
                c.wait(sv);
                fence_regs(o); fence_regs(pf);
                LP(1);
                if (it < 3) BP(2, 41 + 4 * it);
                if (it >= nrest - 2) BP(1, 61 + 4 * (it - nrest + 2));
                if (PINGPONG) named_sync(bar_me, 256);
                LP(2);
                if (it < 3) BP(2, 42 + 4 * it);
                if (it >= nrest - 2) BP(1, 62 + 4 * (it - nrest + 2));
                wgmma_fence();
                gemm_rs<true>(s, qf, sk.dl);
                wgmma_commit();
                gemm_rs<false>(o, pf, sv.dl, it);
                wgmma_commit();
                if (PINGPONG) named_arrive(bar_other, 256);
                LP(3);
                if (it < 3) BP(2, 43 + 4 * it);
                if (it >= nrest - 2) BP(1, 63 + 4 * (it - nrest + 2));
                wgmma_wait<1>();
                LP(4);
                c.release(sk.bo);
                fence_regs(s);
                exp_part<0, SPLITJ, PACE>(s, n0, n1, l0, l1);
                sched_barrier(l0, l1, bars + MISC_OFF + 16);
                LP(5);
                wgmma_wait<0>();
                LP(6);
                c.release(sv.bo);
                fence_regs(o); fence_regs(pf);
                exp_part<SPLITJ, 16, PACE>(s, n0, n1, l0, l1);
                pack_tile(s, pf);
            }
            PROF(10 + rd * 4);
            PROFG(183 + rd);
            const Slot sv = c.next();
            BP(1, 0);
            c.wait(sv);
            if (nrest == 0) {
#pragma unroll
                for (int i = 0; i < 64; i++) o[i] = 0.f;
            }
            if (__builtin_expect(__any_sync(0xffffffffu, !(l0 < 0x1p60f && l1 < 0x1p60f)), 0)) {
                attention_exact(o, qf, l0, l1, h, nrest + 1, 64 * (role ^ rank) + 16 * w + lr - 8 * q, lane);
#pragma unroll
                for (int i = 0; i < 32; i++) pf[i] = 0u;
            }
            fence_regs(o); fence_regs(pf);
            BP(1, 1);
            if (PINGPONG && !role) named_sync(bar_me, 256);
            BP(1, 2);
            wgmma_fence();
            gemm_rs<false>(o, pf, sv.dl);
            wgmma_commit();
            BP(1, 3);
            pend = sv.bo;
            ep_ptr = g_ctx + (size_t)(h * SEQ + 256 * p + 128 * rank + 64 * role + 16 * w + lr) * HD + 8 * q;
            ep_step = 8 * HD;
        }
        l0 += __shfl_xor_sync(0xffffffffu, l0, 1); l1 += __shfl_xor_sync(0xffffffffu, l1, 1);
        l0 += __shfl_xor_sync(0xffffffffu, l0, 2); l1 += __shfl_xor_sync(0xffffffffu, l1, 2);
        l0 = rcp(l0); l1 = rcp(l1);
        wgmma_wait<0>();
        c.release(pend);
        fence_regs(o); fence_regs(pf);
        for4([&](auto i) { store_chunk<i.value>(o, ep_ptr, ep_ptr + ep_step, l0, l1); });
        signal(bars, wg, 8, lane);
    }
    PROFG(187);
    PROF(3);
    {
        float a1[64], a2[96];
        uint32_t px = 0, py = 0;
#pragma unroll 1
        for (int t = 0; t < 16; t++) {
            const Slot sx = c.next(), sy = c.next();
            c.wait(sx);
            const uint32_t da = sx.dl + wg * 512 + lbo(16), b1 = sx.dl + 1024 + lbo(4096), b2 = sy.dl + lbo(4096);
            wgmma_fence();
#pragma unroll
            for (int k = 0; k < 4; k++) wgmma_ss_n128<0, 1>(a1, da + k * 2, b1 + (k >> 1) * 512 + (k & 1) * 128, k ? 1 : t);
            wgmma_commit();
            wgmma_wait<1>();
            if (t > 0) { c.release(px); c.release(py); }
            px = sx.bo; py = sy.bo;
            c.wait(sy);
            wgmma_fence();
#pragma unroll
            for (int k = 0; k < 4; k++) wgmma_ss_n192<0, 1>(a2, da + k * 2, b2 + (k >> 1) * 768 + (k & 1) * 128, k ? 1 : t);
            wgmma_commit();
        }
        const int nh = cb & 1, kg = cb >> 1, tile = (ca * 2 + rank) * 2 + nh, tid = threadIdx.x - 128;
        const int goff = (unperm_row(256 * ca + 128 * rank + 64 * wg) + 16 * w + 8 * (kg >> 1)) * (DM / 8) + 40 * nh + 20 * (kg & 1) + lane;
        const uint32_t epoch = read_epoch();
        mbar_wait(bars + BAR_DEP + 13 * 8, 0);
        uint4 rv[5];
#pragma unroll
        for (int i = 0; i < 5; i++) {
            const int r = ((lane + 32 * i) * 205) >> 12;
            rv[i] = __ldcg(reinterpret_cast<const uint4*>(g_res) + (goff + 32 * i + 60 * r));
        }
        wgmma_wait<0>();
        fence_regs(a1); fence_regs(a2);
    PROFG(188);
        PROF(4);
        uint32_t own[20];
#pragma unroll
        for (int g = 0; g < 4; g++) {
            uint32_t pk[20];
#pragma unroll
            for (int i = 0; i < 20; i++) {
                const int j = 20 * (g & 1) + i, e = 2 * (g >> 1);
                pk[i] = (j < 16) ? pack_bf16(a1[4 * (j & 15) + e], a1[4 * (j & 15) + e + 1]) : pack_bf16(a2[4 * (j < 16 ? 0 : j - 16) + e], a2[4 * (j < 16 ? 0 : j - 16) + e + 1]);
                if (g == 0 || g == kg) own[i] = pk[i];
            }
            if (g != kg) {
                uint4* dst = g_part + ((tile * 4 + g) * 4 + kg) * 5 * 256 + tid;
#pragma unroll
                for (int i = 0; i < 5; i++) stg128(dst + i * 256, pk[4 * i], pk[4 * i + 1], pk[4 * i + 2], pk[4 * i + 3]);
            }
        }
        __syncwarp();
        if (lane == 0) {
            flag_add(F_PART + tile * 8 + wg * 4 + w);
            flag_wait<20>(F_PART + tile * 8 + wg * 4 + w, 4u * (epoch + 1));
        }
        __syncwarp();
        PROF(5);
        uint4 in[3][5];
#pragma unroll
        for (int k = 0; k < 3; k++)
#pragma unroll
            for (int i = 0; i < 5; i++) in[k][i] = __ldcg(g_part + ((tile * 4 + kg) * 4 + ((kg + 1 + k) & 3)) * 5 * 256 + i * 256 + tid);
        const uint32_t stage = smem + c.cur.bo * (SLOT / 8) + (wg * 4 + w) * 2688;
#pragma unroll
        for (int i = 0; i < 5; i++) {
            uint32_t r[4];
#pragma unroll
            for (int e = 0; e < 4; e++) {
                const uint32_t u0 = (&in[0][i].x)[e], u1 = (&in[1][i].x)[e], u2 = (&in[2][i].x)[e], u3 = own[4 * i + e];
                r[e] = pack_bf16((bf_lo(u0) + bf_lo(u1)) + (bf_lo(u2) + bf_lo(u3)), (bf_hi(u0) + bf_hi(u1)) + (bf_hi(u2) + bf_hi(u3)));
            }
            asm volatile("stmatrix.sync.aligned.m8n8.x4.shared.b16 [%0], {%1, %2, %3, %4};"
                         ::"r"(stage + (lane & 7) * 336 + (4 * i + (lane >> 3)) * 16), "r"(r[0]), "r"(r[1]), "r"(r[2]), "r"(r[3]) : "memory");
        }
        __syncwarp();
#pragma unroll
        for (int i = 0; i < 5; i++) {
            const int r = ((lane + 32 * i) * 205) >> 12;
            uint4 v;
            asm volatile("ld.shared.v4.b32 {%0, %1, %2, %3}, [%4];" : "=r"(v.x), "=r"(v.y), "=r"(v.z), "=r"(v.w) : "r"(stage + (lane + 32 * i + r) * 16) : "memory");
            stg128(reinterpret_cast<uint4*>(P.out) + (goff + 32 * i + 60 * r), add_bf16x2(v.x, rv[i].x), add_bf16x2(v.y, rv[i].y), add_bf16x2(v.z, rv[i].z), add_bf16x2(v.w, rv[i].w));
        }
    }
    PROF(6);
}

__device__ __forceinline__ void mma_rows(float (&acc)[8][4], uint32_t a0, uint32_t a2, const uint4& w0, const uint4& w1, const uint4& w2, const uint4& w3) {
    const uint32_t r0[4] = {w0.x, w0.y, w0.z, w0.w}, r1[4] = {w1.x, w1.y, w1.z, w1.w};
    const uint32_t r2[4] = {w2.x, w2.y, w2.z, w2.w}, r3[4] = {w3.x, w3.y, w3.z, w3.w};
#pragma unroll
    for (int i = 0; i < 4; i++) {
        mma16816(acc[2 * i][0], acc[2 * i][1], acc[2 * i][2], acc[2 * i][3], a0, 0u, a2, 0u, __byte_perm(r0[i], r1[i], 0x5410), __byte_perm(r2[i], r3[i], 0x5410));
        mma16816(acc[2 * i + 1][0], acc[2 * i + 1][1], acc[2 * i + 1][2], acc[2 * i + 1][3], a0, 0u, a2, 0u, __byte_perm(r0[i], r1[i], 0x7632), __byte_perm(r2[i], r3[i], 0x7632));
    }
}

__device__ __forceinline__ void mod_ffn(const Params& P, uint8_t* sm, int mc  ) {
    const uint32_t epoch = read_epoch();
    const int tid = threadIdx.x - 128, lane = tid & 31, cw = tid >> 5, q = lane & 3, lr = lane >> 2;
    uint32_t* xs = reinterpret_cast<uint32_t*>(sm);
    uint32_t* wmax = xs + 8 * 324;
    int* sidx = reinterpret_cast<int*>(wmax + 16);
    const int fg = cw * 4 + mc;
    const uint32_t ring = smem_u32(sm) + 16384 + cw * 24576, rbar = smem_u32(sm) + 12288 + cw * 32;
    auto issue = [&](int u, int st) {
        if (lane == 0 && u < 30) {
            mbar_expect_tx(rbar + st * 8, 8192);
            if (u < 20) {
                tma_load_stream(ring + st * 8192, &P.wg, fg * 64, u * 32, rbar + st * 8);
                tma_load_stream(ring + st * 8192 + 4096, &P.wu, fg * 64, u * 32, rbar + st * 8);
            } else {
                tma_load_stream(ring + st * 8192, &P.wd, (u - 20) * 64, fg * 64, rbar + st * 8);
            }
        }
    };
    if (lane == 0) {
        mbar_init(rbar, 1); mbar_init(rbar + 8, 1); mbar_init(rbar + 16, 1);
        asm volatile("fence.mbarrier_init.release.cluster;" ::: "memory");
    }
    if (tid == 0) flag_wait<100>(F_LN, 256u * (epoch + 1));
    named_sync(1, 256);
    PROF(1);
    if (fg < 27) {
#pragma unroll 1
        for (int u = 0; u < 3; u++) issue(u, u);
    }
    PROF(2);
    uint32_t key[8];
#pragma unroll
    for (int i = 0; i < 8; i++) {
        const int t = tid + 256 * i;
        uint32_t b = __float_as_uint(__ldcg(g_r + t) + 0.f) >> 16;
        b = (b & 0x8000u) ? (~b & 0xffffu) : (b | 0x8000u);
        key[i] = (b << 16) | (uint32_t)(0xffff - t);
    }
#pragma unroll 1
    for (int rnd = 0; rnd < 8; rnd++) {
        uint32_t mx = key[0];
#pragma unroll
        for (int i = 1; i < 8; i++) mx = max(mx, key[i]);
        mx = __reduce_max_sync(0xffffffffu, mx);
        if (lane == 0) wmax[(rnd & 1) * 8 + cw] = mx;
        named_sync(1, 256);
        mx = __reduce_max_sync(0xffffffffu, wmax[(rnd & 1) * 8 + (lane & 7)]);
#pragma unroll
        for (int i = 0; i < 8; i++) if (key[i] == mx) key[i] = 0;
        if (tid == 0) sidx[rnd] = 0xffff - (int)(mx & 0xffffu);
    }
    named_sync(1, 256);
    {
        const uint32_t* src = reinterpret_cast<const uint32_t*>(g_xn + (size_t)perm_row(sidx[cw]) * DM);
#pragma unroll 2
        for (int i = lane; i < 320; i += 32) xs[cw * 324 + i] = __ldcg(src + i);
    }
    named_sync(1, 256);
    PROF(3);
    if (fg < 27) {
        float g[8][4], v[8][4];
        uint32_t hp[8];
#pragma unroll
        for (int i = 0; i < 8; i++)
#pragma unroll
            for (int e = 0; e < 4; e++) { g[i][e] = 0.f; v[i][e] = 0.f; }
        int st = 0, ph = 0;
#pragma unroll 1
        for (int u = 0; u < 60; u++) {
            if (!(u & 1)) mbar_wait(rbar + st * 8, ph);
            uint4 a[8];
#pragma unroll
            for (int r = 0; r < 8; r++) {
                const int row = (u < 40) ? 32 * (r >> 2) + 16 * (u & 1) + 2 * q + (r & 1) + 4 * (r & 2) : 16 * q + 8 * (u & 1) + r;
                asm volatile("ld.shared.v4.b32 {%0, %1, %2, %3}, [%4];" : "=r"(a[r].x), "=r"(a[r].y), "=r"(a[r].z), "=r"(a[r].w)
                             : "r"(ring + st * 8192 + row * 128 + ((lr ^ row) & 7) * 16) : "memory");
            }
            uint32_t f0, f1, f2, f3;
            if (u < 40) { f0 = f2 = xs[lr * 324 + u * 8 + q]; f1 = f3 = xs[lr * 324 + u * 8 + 4 + q]; }
            else if (u & 1) { f0 = hp[4]; f1 = hp[5]; f2 = hp[6]; f3 = hp[7]; }
            else { f0 = hp[0]; f1 = hp[1]; f2 = hp[2]; f3 = hp[3]; }
            mma_rows(g, f0, f1, a[0], a[1], a[2], a[3]);
            mma_rows(v, f2, f3, a[4], a[5], a[6], a[7]);
            if (u & 1) {
                __syncwarp();
                issue((u >> 1) + 3, st);
                if (++st == 3) { st = 0; ph ^= 1; }
                if (u >= 39) {
                    if (u == 39) {
                        float hv[16];
#pragma unroll
                        for (int i = 0; i < 16; i++) {
                            const float gp = round_bf16(g[i & 7][i >> 3]);
                            hv[i] = round_bf16(__fdividef(gp, 1.0f + __expf(fminf(-gp, 80.f)))) * round_bf16(v[i & 7][i >> 3]);
                        }
#pragma unroll
                        for (int i = 0; i < 8; i++) hp[i] = pack_bf16(hv[2 * i], hv[2 * i + 1]);
                    } else {
                        float4* dst = reinterpret_cast<float4*>(g_ypart + (fg * 8 + lr) * DM + ((u - 40) >> 1) * 64 + 16 * q);
#pragma unroll
                        for (int i = 0; i < 4; i++) {
                            const int j = 4 * (i & 1), e = i >> 1;
                            dst[i] = make_float4(g[j][e] + v[j][e], g[j + 1][e] + v[j + 1][e], g[j + 2][e] + v[j + 2][e], g[j + 3][e] + v[j + 3][e]);
                        }
                    }
#pragma unroll
                    for (int i = 0; i < 8; i++) { g[i][0] = 0.f; g[i][1] = 0.f; v[i][0] = 0.f; v[i][1] = 0.f; }
                }
            }
        }
    }
    PROF(5);
    named_sync(1, 256);
    if (tid == 0) {
        flag_add(F_MODP);
        flag_wait<100>(F_MODP, 4u * (epoch + 1));
    }
    named_sync(1, 256);
    PROF(6);
#pragma unroll 1
    for (int i = tid; i < 2 * DM; i += 256) {
        const int c = 2 * mc + (i >= DM), col = i - (i >= DM) * DM, t = sidx[c];
        float y = 0.f;
#pragma unroll 9
        for (int k = 0; k < 27; k++) y += __ldcg(g_ypart + (k * 8 + c) * DM + col);
        const float rs = round_bf16(__fdividef(1.0f, 1.0f + __expf(fminf(-__ldcg(g_r + t), 80.f))));
        const float xn = __bfloat162float(reinterpret_cast<const __nv_bfloat16*>(xs + c * 324)[col]);
        g_res[(size_t)t * DM + col] = __float2bfloat16_rn(__bfloat162float(P.x[(size_t)t * DM + col]) + round_bf16(xn + round_bf16(round_bf16(y) * rs)));
    }
    named_sync(1, 256);
    if (tid == 0) flag_add(F_MOD);
    PROF(7);
}

__global__ void __cluster_dims__(2, 1, 1) __launch_bounds__(384, 1) fused_kernel(const __grid_constant__ Params P) {
    extern __shared__ __align__(1024) uint8_t smem_raw[];
    const uint32_t smem = (smem_u32(smem_raw) + 1023u) & ~1023u;
    uint8_t* smem_gen = smem_raw + (smem - smem_u32(smem_raw));
    const uint32_t bars = smem + NSLOT * SLOT;
    const int wgi = __reduce_or_sync(0xffffffffu, threadIdx.x >> 7);
    const int cl = blockIdx.x >> 1, rank = blockIdx.x & 1, ca = cl & 7, cb = cl >> 3;
    PROFG(30);
    PROF(0);
    LayerNorm ln;
    if (wgi != 0) {
        const uint4* xr = reinterpret_cast<const uint4*>(P.x + (size_t)((blockIdx.x & 127) * 16 + ((threadIdx.x - 128) >> 4)) * DM) + (threadIdx.x & 15);
        const uint4* wr = reinterpret_cast<const uint4*>(P.wr) + (threadIdx.x & 15);
#pragma unroll
        for (int i = 0; i < 5; i++) { ln.xv[i] = ldg_stream(xr + 16 * i); ln.wv[i] = __ldg(wr + 16 * i); }
        PROF(28);
    } else if (threadIdx.x == 0) {
#pragma unroll
        for (int i = 0; i < NSLOT; i++) { mbar_init(bars + BAR_FULL + i * 8, 1); mbar_init(bars + BAR_EMPTY + i * 8, 16); }
        mbar_arrive(bars + BAR_FULL + 16);
        asm volatile("mbarrier.arrive.shared::cta.b64 _, [%0], 16;" ::"r"(bars + BAR_EMPTY + 16) : "memory");
        asm volatile("fence.mbarrier_init.release.cluster;" ::: "memory");
        PROF(24);
    } else if (threadIdx.x == 32) {
#pragma unroll
        for (int i = 0; i < 18; i++) mbar_init(bars + BAR_SIG + i * 8, 4);
#pragma unroll
        for (int i = 0; i < 14; i++) mbar_init(bars + BAR_DEP + i * 8, 1);
    } else if (threadIdx.x >= 64 && cl < 64) {
        const int i = threadIdx.x - 64;
        if (i == 0) { prefetch_map(&P.ckv); prefetch_map(&P.wuk); }
        const char* a = reinterpret_cast<const char*>(P.ckv_ptr) + ((2 * ca + rank) * 128 + cb * 16) * (DC * 2) + i * 256;
        asm volatile("prefetch.global.L2 [%0];" ::"l"(a));
        asm volatile("prefetch.global.L2 [%0];" ::"l"(a + 128));
        asm volatile("prefetch.global.L2 [%0];" ::"l"(P.wuk_ptr + (size_t)(i * 8 + ca) * (NH * HD) + (cb + 8 * kv_round(0)) * 128 + rank * 64));
    }
    __syncthreads();
    PROF(29);
    cluster_arrive();
    if (wgi > 0) {
        asm volatile("setmaxnreg.inc.sync.aligned.u32 232;");
        if (cl >= 64) {
            cluster_wait();
            mod_ffn(P, smem_gen, blockIdx.x - 128);
        } else {
            consumer(P, smem, bars, ca, cb, rank, wgi - 1, ln);
        }
        cluster_arrive();
        PROFG(31);
        PROFDUMP();
    } else {
        asm volatile("setmaxnreg.dec.sync.aligned.u32 40;");
        const int w = threadIdx.x >> 5, lane = threadIdx.x & 31;
        if (threadIdx.x == 32 && cl < 64) {
            mbar_expect_tx(bars + BAR_FULL, SLOT);
            tma_load(smem, &P.ckv, 0, (2 * ca + rank) * 128, bars + BAR_FULL);
            tma_load(smem + 16384, &P.ckv, 64, (2 * ca + rank) * 128, bars + BAR_FULL);
        }
        if (threadIdx.x == 64) {
            prefetch_map(&P.wuv); prefetch_map(&P.xn); prefetch_map(&P.wq); prefetch_map(&P.kv); prefetch_map(&P.ctx); prefetch_map(&P.wo);
        }
        __syncwarp();
        cluster_wait();
        PROF(27);
        if (cl < 64) {
            if (w == 0) {
                if (lane == 0) producer(P, smem, bars, ca, cb, rank);
            } else if (w < 3 && lane == 0) {
                const int wg = w - 1;
#pragma unroll 1
                for (int e = 0; e < 9; e++) {
                    mbar_wait(bars + BAR_SIG + (wg * 9 + e) * 8, 0);
                    int f;
                    if (e == 0) f = F_LN;
                    else if (e < 5) f = F_KV + cb + 8 * kv_round(e - 1);
                    else { const int rd = e - 5; f = F_CTX + (8 * rd + cb) * 16 + item_p(ca, rd) * 2 + rank; }
                    flag_add(f);
                }
            } else if (lane == 0) {
                const uint32_t epoch = read_epoch();
#pragma unroll 1
                for (int i = 0; i < 14; i++) {
                    const int e = (i < 11) ? i : (i == 11) ? 13 : i - 1;
                    int f;
                    uint32_t n;
                    if (e == 0) { f = F_LN; n = 256; }
                    else if (e < 5) { f = F_KV + cb + 8 * (e - 1); n = 32; }
                    else if (e < 13) { f = F_CTX + (8 * ((e - 5) >> 1) + (cb & 6) + ((e - 5) & 1)) * 16 + ca * 2 + rank; n = 2; }
                    else { f = F_MOD; n = 4; }
                    flag_wait<100>(f, n * (epoch + 1));
                    fence_proxy_async();
                    mbar_arrive(bars + BAR_DEP + e * 8);
                }
            }
        }
        __syncwarp();
        cluster_arrive();
        cluster_wait();
        if (threadIdx.x == 0) atomicAdd(g_flags + F_EXIT * 8, 1u);
        PROFG(31);
        PROFDUMP();
    }
}

typedef CUresult (*EncodeFn)(CUtensorMap*, CUtensorMapDataType, cuuint32_t, void*, const cuuint64_t*, const cuuint64_t*, const cuuint32_t*,
                             const cuuint32_t*, CUtensorMapInterleave, CUtensorMapSwizzle, CUtensorMapL2promotion, CUtensorMapFloatOOBfill);

void make_map(EncodeFn fn, CUtensorMap* m, const void* ptr, uint64_t rows, uint64_t cols, uint32_t box_rows) {
    cuuint64_t dims[2] = {cols, rows};
    cuuint64_t strides[1] = {cols * 2};
    cuuint32_t box[2] = {64, box_rows};
    cuuint32_t es[2] = {1, 1};
    fn(m, CU_TENSOR_MAP_DATA_TYPE_BFLOAT16, 2, const_cast<void*>(ptr), dims, strides, box, es, CU_TENSOR_MAP_INTERLEAVE_NONE,
       CU_TENSOR_MAP_SWIZZLE_128B, CU_TENSOR_MAP_L2_PROMOTION_L2_128B, CU_TENSOR_MAP_FLOAT_OOB_FILL_NONE);
}

}

extern "C" void kernel_launch(void* const* d_in, const int* in_sizes, int n_in, void* d_out, int out_size) {
    (void)in_sizes; (void)n_in; (void)out_size;
    void* fnp = nullptr;
    cudaDriverEntryPointQueryResult qr;
    cudaGetDriverEntryPoint("cuTensorMapEncodeTiled", &fnp, cudaEnableDefault, &qr);
    EncodeFn fn = (EncodeFn)fnp;
    void *xn, *kv, *ctx;
    cudaGetSymbolAddress(&xn, g_xn);
    cudaGetSymbolAddress(&kv, g_kv);
    cudaGetSymbolAddress(&ctx, g_ctx);
    Params P;
    make_map(fn, &P.ckv, d_in[1], SEQ, DC, 128);
    make_map(fn, &P.wq, d_in[2], DM, NH * HD, 64);
    make_map(fn, &P.wuk, d_in[3], DC, NH * HD, 128);
    make_map(fn, &P.wuv, d_in[4], DC, NH * HD, 128);
    make_map(fn, &P.wo, d_in[5], NH * HD, DM, 32);
    make_map(fn, &P.xn, xn, SEQ, DM, 128);
    make_map(fn, &P.kv, kv, NH * 16 * 2 * 128, 128, 128);
    make_map(fn, &P.ctx, ctx, NH * SEQ, HD, 128);
    P.x = (const __nv_bfloat16*)d_in[0];
    P.wr = (const __nv_bfloat16*)d_in[7];
    make_map(fn, &P.wg, d_in[8], DM, FF, 32);
    make_map(fn, &P.wu, d_in[9], DM, FF, 32);
    make_map(fn, &P.wd, d_in[10], FF, DM, 64);
    P.ckv_ptr = (const __nv_bfloat16*)d_in[1];
    P.wuk_ptr = (const __nv_bfloat16*)d_in[3];
    P.out = (__nv_bfloat16*)d_out;
    cudaFuncSetAttribute(fused_kernel, cudaFuncAttributeMaxDynamicSharedMemorySize, SMEM_BYTES);
    fused_kernel<<<NCTA, 384, SMEM_BYTES>>>(P);
}
```

```cpp
#include <cuda_runtime.h>
#include <cuda_bf16.h>
#include <cuda.h>
#include <stdint.h>

namespace {

constexpr int SEQ = 2048, DM = 640, DC = 512, NH = 32, HD = 128, FF = 1728;
constexpr int NSLOT = 7, SLOT = 32768;
constexpr int NCTA = 132;
#define PINGPONG 1
#define PACE 2
#define PACE_LAG 2
#define SIGMA 1
#define KVORDER 0x1023
#define KVSPLIT 2
#define EF 1
#define QST 4
#define WAIT_HINT
#define SPLITJ 8
constexpr uint32_t DESC_HI = (1024u >> 4) | (1u << 30);
constexpr int SMEM_BYTES = NSLOT * SLOT + 3072;

constexpr int BAR_FULL = 0, BAR_EMPTY = 64, BAR_SIG = 128  , BAR_DEP = 320  , MISC_OFF = 512;

constexpr int F_EXIT = 0, F_LN = 1, F_MOD = 2, F_MODP = 3, F_KV = 4  , F_PART = 36  , F_CTX = 292  , F_NUM = 804;

__device__ __align__(1024) __nv_bfloat16 g_xn[SEQ * DM];
__device__ __align__(1024) __nv_bfloat16 g_kv[NH * 16 * 2 * 128 * 128];
__device__ __align__(1024) __nv_bfloat16 g_ctx[NH * SEQ * HD];
__device__ __align__(1024) __nv_bfloat16 g_res[SEQ * DM];
__device__ __align__(1024) uint4 g_part[32 * 4 * 4 * 5 * 256];
__device__ __align__(16) float g_r[SEQ];
__device__ __align__(16) float g_ypart[27 * 8 * DM];
__device__ uint32_t g_flags[F_NUM * 8];

struct TrueT { static constexpr bool value = true; };
struct FalseT { static constexpr bool value = false; };

struct Params {
    CUtensorMap ckv, wuk, wuv, xn, wq, kv, ctx, wo, wg, wu, wd;
    const __nv_bfloat16 *x, *wr, *ckv_ptr, *wuk_ptr;
    __nv_bfloat16* out;
};

__device__ __forceinline__ uint32_t smem_u32(const void* p) { return (uint32_t)__cvta_generic_to_shared(p); }
__device__ __forceinline__ void mbar_init(uint32_t bar, uint32_t cnt) {
    asm volatile("mbarrier.init.shared::cta.b64 [%0], %1;" ::"r"(bar), "r"(cnt) : "memory");
}
__device__ __forceinline__ void mbar_expect_tx(uint32_t bar, uint32_t bytes) {
    asm volatile("mbarrier.arrive.expect_tx.shared::cta.b64 _, [%0], %1;" ::"r"(bar), "r"(bytes) : "memory");
}
__device__ __forceinline__ void mbar_arrive(uint32_t bar) {
    asm volatile("mbarrier.arrive.shared::cta.b64 _, [%0];" ::"r"(bar) : "memory");
}
__device__ __forceinline__ uint32_t mapa(uint32_t addr, uint32_t cta) {
    uint32_t r;
    asm("mapa.shared::cluster.u32 %0, %1, %2;" : "=r"(r) : "r"(addr), "r"(cta));
    return r;
}
__device__ __forceinline__ void mbar_wait(uint32_t bar, uint32_t parity) {
    asm volatile(
        "{\n.reg .pred p;\n.reg .b32 c;\n"
        "mov.b32 c, 0;\n"
        "WLOOP:\n"
        "mbarrier.try_wait.parity.shared::cta.b64 p, [%0], %1" WAIT_HINT ";\n"
        "@p bra.uni WDONE;\n"
        "add.u32 c, c, 1;\n"
        "setp.lt.u32 p, c, 0x400000;\n"
        "@p bra.uni WLOOP;\n"
        "trap;\n"
        "WDONE:\n}\n" ::"r"(bar), "r"(parity) : "memory");
}
__device__ __forceinline__ void tma_load(uint32_t dst, const CUtensorMap* m, int c0, int c1, uint32_t bar) {
    asm volatile("cp.async.bulk.tensor.2d.shared::cluster.global.mbarrier::complete_tx::bytes [%0], [%1, {%3, %4}], [%2];"
                 ::"r"(dst), "l"(m), "r"(bar), "r"(c0), "r"(c1) : "memory");
}
#define ELECT "{\n.reg .pred e;\nelect.sync _|e, 0xffffffff;\n@e "
__device__ __forceinline__ void w_expect_tx(uint32_t bar, uint32_t bytes) {
    asm volatile(ELECT "mbarrier.arrive.expect_tx.shared::cta.b64 _, [%0], %1;\n}\n" ::"r"(bar), "r"(bytes) : "memory");
}
__device__ __forceinline__ void w_tma_load(uint32_t dst, const CUtensorMap* m, int c0, int c1, uint32_t bar) {
    asm volatile(ELECT "cp.async.bulk.tensor.2d.shared::cluster.global.mbarrier::complete_tx::bytes [%0], [%1, {%3, %4}], [%2];\n}\n"
                 ::"r"(dst), "l"(m), "r"(bar), "r"(c0), "r"(c1) : "memory");
}
__device__ __forceinline__ void w_tma_load_mc(uint32_t dst, const CUtensorMap* m, int c0, int c1, uint32_t bar) {
    asm volatile(ELECT "cp.async.bulk.tensor.2d.shared::cluster.global.mbarrier::complete_tx::bytes.multicast::cluster [%0], [%1, {%3, %4}], [%2], %5;\n}\n"
                 ::"r"(dst), "l"(m), "r"(bar), "r"(c0), "r"(c1), "h"((uint16_t)3) : "memory");
}
__device__ __forceinline__ void w_tma_prefetch(const CUtensorMap* m, int c0, int c1) {
    asm volatile(ELECT "cp.async.bulk.prefetch.tensor.2d.L2.global [%0, {%1, %2}];\n}\n" ::"l"(m), "r"(c0), "r"(c1) : "memory");
}
__device__ __forceinline__ uint64_t policy_evict_first() {
    uint64_t p;
    asm("createpolicy.fractional.L2::evict_first.b64 %0, 1.0;" : "=l"(p));
    return p;
}
__device__ __forceinline__ void tma_load_stream(uint32_t dst, const CUtensorMap* m, int c0, int c1, uint32_t bar) {
    asm volatile("cp.async.bulk.tensor.2d.shared::cluster.global.mbarrier::complete_tx::bytes.L2::cache_hint [%0], [%1, {%3, %4}], [%2], %5;"
                 ::"r"(dst), "l"(m), "r"(bar), "r"(c0), "r"(c1), "l"(policy_evict_first()) : "memory");
}
__device__ __forceinline__ uint4 ldg_stream(const void* p) {
    uint4 v;
    asm volatile("ld.global.nc.L2::cache_hint.v4.b32 {%0, %1, %2, %3}, [%4], %5;" : "=r"(v.x), "=r"(v.y), "=r"(v.z), "=r"(v.w) : "l"(p), "l"(policy_evict_first()));
    return v;
}
__device__ __forceinline__ void prefetch_map(const CUtensorMap* m) {
    asm volatile("prefetch.tensormap [%0];" ::"l"(m) : "memory");
}
__device__ __forceinline__ void cluster_arrive() { asm volatile("barrier.cluster.arrive.relaxed.aligned;" ::: "memory"); }
__device__ __forceinline__ void cluster_wait() { asm volatile("barrier.cluster.wait.aligned;" ::: "memory"); }
__device__ __forceinline__ void named_sync(int id, int n) { asm volatile("bar.sync %0, %1;" ::"r"(id), "r"(n) : "memory"); }
__device__ __forceinline__ void named_arrive(int id, int n) { asm volatile("bar.arrive %0, %1;" ::"r"(id), "r"(n) : "memory"); }

__device__ __forceinline__ void flag_add(int f) {
    asm volatile("fence.acq_rel.gpu;\nred.relaxed.gpu.global.add.u32 [%0], 1;" ::"l"(g_flags + f * 8) : "memory");
}
template <int SLEEP>
__device__ __forceinline__ void flag_wait(int f, uint32_t target) {
    asm volatile(
        "{\n.reg .pred p;\n.reg .b32 c, v;\n"
        "mov.b32 c, 0;\n"
        "FLOOP:\n"
        "ld.acquire.gpu.global.u32 v, [%0];\n"
        "sub.u32 v, v, %1;\n"
        "setp.ge.s32 p, v, 0;\n"
        "@p bra FDONE;\n"
        "nanosleep.u32 %2;\n"
        "add.u32 c, c, 1;\n"
        "setp.lt.u32 p, c, 0x400000;\n"
        "@p bra FLOOP;\n"
        "trap;\n"
        "FDONE:\n}\n" ::"l"(g_flags + f * 8), "r"(target), "n"(SLEEP) : "memory");
}
__device__ __forceinline__ uint32_t read_epoch() {
    uint32_t e;
    asm volatile("ld.relaxed.gpu.global.u32 %0, [%1];" : "=r"(e) : "l"(g_flags + F_EXIT * 8) : "memory");
    return e / NCTA;
}
__device__ __forceinline__ void fence_proxy_async() { asm volatile("fence.proxy.async;" ::: "memory"); }

__device__ __forceinline__ void wgmma_fence() { asm volatile("wgmma.fence.sync.aligned;" ::: "memory"); }
__device__ __forceinline__ void wgmma_commit() { asm volatile("wgmma.commit_group.sync.aligned;" ::: "memory"); }
template <int N>
__device__ __forceinline__ void wgmma_wait() { asm volatile("wgmma.wait_group.sync.aligned %0;" ::"n"(N) : "memory"); }
template <int N>
__device__ __forceinline__ void fence_regs(float (&d)[N]) {
#pragma unroll
    for (int i = 0; i < N; i++) asm volatile("" : "+f"(d[i])::"memory");
}
template <int N>
__device__ __forceinline__ void fence_regs(uint32_t (&d)[N]) {
#pragma unroll
    for (int i = 0; i < N; i++) asm volatile("" : "+r"(d[i])::"memory");
}

template <int TA, int TB>
__device__ __forceinline__ void wgmma_ss_n128(float (&d)[64], uint32_t alo, uint32_t blo, int scale_d) {
    asm volatile("{\n.reg .pred p;\n.reg .b64 da, db;\nsetp.ne.b32 p, %66, 0;\n"
        "mov.b64 da, {%64, %69};\nmov.b64 db, {%65, %69};\n"
        "wgmma.mma_async.sync.aligned.m64n128k16.f32.bf16.bf16 "
        "{%0, %1, %2, %3, %4, %5, %6, %7, %8, %9, %10, %11, %12, %13, %14, %15, %16, %17, %18, %19, %20, %21, %22, %23, %24, %25, %26, %27, %28, %29, %30, %31, %32, %33, %34, %35, %36, %37, %38, %39, %40, %41, %42, %43, %44, %45, %46, %47, %48, %49, %50, %51, %52, %53, %54, %55, %56, %57, %58, %59, %60, %61, %62, %63}, da, db, p, 1, 1, %67, %68;\n}\n"
        :
          "+f"(d[0]), "+f"(d[1]), "+f"(d[2]), "+f"(d[3]), "+f"(d[4]), "+f"(d[5]), "+f"(d[6]), "+f"(d[7]),
          "+f"(d[8]), "+f"(d[9]), "+f"(d[10]), "+f"(d[11]), "+f"(d[12]), "+f"(d[13]), "+f"(d[14]), "+f"(d[15]),
          "+f"(d[16]), "+f"(d[17]), "+f"(d[18]), "+f"(d[19]), "+f"(d[20]), "+f"(d[21]), "+f"(d[22]), "+f"(d[23]),
          "+f"(d[24]), "+f"(d[25]), "+f"(d[26]), "+f"(d[27]), "+f"(d[28]), "+f"(d[29]), "+f"(d[30]), "+f"(d[31]),
          "+f"(d[32]), "+f"(d[33]), "+f"(d[34]), "+f"(d[35]), "+f"(d[36]), "+f"(d[37]), "+f"(d[38]), "+f"(d[39]),
          "+f"(d[40]), "+f"(d[41]), "+f"(d[42]), "+f"(d[43]), "+f"(d[44]), "+f"(d[45]), "+f"(d[46]), "+f"(d[47]),
          "+f"(d[48]), "+f"(d[49]), "+f"(d[50]), "+f"(d[51]), "+f"(d[52]), "+f"(d[53]), "+f"(d[54]), "+f"(d[55]),
          "+f"(d[56]), "+f"(d[57]), "+f"(d[58]), "+f"(d[59]), "+f"(d[60]), "+f"(d[61]), "+f"(d[62]), "+f"(d[63])
        : "r"(alo), "r"(blo), "r"(scale_d), "n"(TA), "n"(TB), "r"(DESC_HI));
}
template <int TA, int TB>
__device__ __forceinline__ void wgmma_ss_n192(float (&d)[96], uint32_t alo, uint32_t blo, int scale_d) {
    asm volatile("{\n.reg .pred p;\n.reg .b64 da, db;\nsetp.ne.b32 p, %98, 0;\n"
        "mov.b64 da, {%96, %101};\nmov.b64 db, {%97, %101};\n"
        "wgmma.mma_async.sync.aligned.m64n192k16.f32.bf16.bf16 "
        "{%0, %1, %2, %3, %4, %5, %6, %7, %8, %9, %10, %11, %12, %13, %14, %15, %16, %17, %18, %19, %20, %21, %22, %23, %24, %25, %26, %27, %28, %29, %30, %31, %32, %33, %34, %35, %36, %37, %38, %39, %40, %41, %42, %43, %44, %45, %46, %47, %48, %49, %50, %51, %52, %53, %54, %55, %56, %57, %58, %59, %60, %61, %62, %63, %64, %65, %66, %67, %68, %69, %70, %71, %72, %73, %74, %75, %76, %77, %78, %79, %80, %81, %82, %83, %84, %85, %86, %87, %88, %89, %90, %91, %92, %93, %94, %95}, da, db, p, 1, 1, %99, %100;\n}\n"
        :
          "+f"(d[0]), "+f"(d[1]), "+f"(d[2]), "+f"(d[3]), "+f"(d[4]), "+f"(d[5]), "+f"(d[6]), "+f"(d[7]),
          "+f"(d[8]), "+f"(d[9]), "+f"(d[10]), "+f"(d[11]), "+f"(d[12]), "+f"(d[13]), "+f"(d[14]), "+f"(d[15]),
          "+f"(d[16]), "+f"(d[17]), "+f"(d[18]), "+f"(d[19]), "+f"(d[20]), "+f"(d[21]), "+f"(d[22]), "+f"(d[23]),
          "+f"(d[24]), "+f"(d[25]), "+f"(d[26]), "+f"(d[27]), "+f"(d[28]), "+f"(d[29]), "+f"(d[30]), "+f"(d[31]),
          "+f"(d[32]), "+f"(d[33]), "+f"(d[34]), "+f"(d[35]), "+f"(d[36]), "+f"(d[37]), "+f"(d[38]), "+f"(d[39]),
          "+f"(d[40]), "+f"(d[41]), "+f"(d[42]), "+f"(d[43]), "+f"(d[44]), "+f"(d[45]), "+f"(d[46]), "+f"(d[47]),
          "+f"(d[48]), "+f"(d[49]), "+f"(d[50]), "+f"(d[51]), "+f"(d[52]), "+f"(d[53]), "+f"(d[54]), "+f"(d[55]),
          "+f"(d[56]), "+f"(d[57]), "+f"(d[58]), "+f"(d[59]), "+f"(d[60]), "+f"(d[61]), "+f"(d[62]), "+f"(d[63]),
          "+f"(d[64]), "+f"(d[65]), "+f"(d[66]), "+f"(d[67]), "+f"(d[68]), "+f"(d[69]), "+f"(d[70]), "+f"(d[71]),
          "+f"(d[72]), "+f"(d[73]), "+f"(d[74]), "+f"(d[75]), "+f"(d[76]), "+f"(d[77]), "+f"(d[78]), "+f"(d[79]),
          "+f"(d[80]), "+f"(d[81]), "+f"(d[82]), "+f"(d[83]), "+f"(d[84]), "+f"(d[85]), "+f"(d[86]), "+f"(d[87]),
          "+f"(d[88]), "+f"(d[89]), "+f"(d[90]), "+f"(d[91]), "+f"(d[92]), "+f"(d[93]), "+f"(d[94]), "+f"(d[95])
        : "r"(alo), "r"(blo), "r"(scale_d), "n"(TA), "n"(TB), "r"(DESC_HI));
}
template <int TB>
__device__ __forceinline__ void wgmma_rs_n128(float (&d)[64], uint32_t a0, uint32_t a1, uint32_t a2, uint32_t a3, uint32_t blo, int scale_d) {
    asm volatile("{\n.reg .pred p;\n.reg .b64 db;\nsetp.ne.b32 p, %69, 0;\n"
        "mov.b64 db, {%68, %71};\n"
        "wgmma.mma_async.sync.aligned.m64n128k16.f32.bf16.bf16 "
        "{%0, %1, %2, %3, %4, %5, %6, %7, %8, %9, %10, %11, %12, %13, %14, %15, %16, %17, %18, %19, %20, %21, %22, %23, %24, %25, %26, %27, %28, %29, %30, %31, %32, %33, %34, %35, %36, %37, %38, %39, %40, %41, %42, %43, %44, %45, %46, %47, %48, %49, %50, %51, %52, %53, %54, %55, %56, %57, %58, %59, %60, %61, %62, %63}, {%64, %65, %66, %67}, db, p, 1, 1, %70;\n}\n"
        :
          "+f"(d[0]), "+f"(d[1]), "+f"(d[2]), "+f"(d[3]), "+f"(d[4]), "+f"(d[5]), "+f"(d[6]), "+f"(d[7]),
          "+f"(d[8]), "+f"(d[9]), "+f"(d[10]), "+f"(d[11]), "+f"(d[12]), "+f"(d[13]), "+f"(d[14]), "+f"(d[15]),
          "+f"(d[16]), "+f"(d[17]), "+f"(d[18]), "+f"(d[19]), "+f"(d[20]), "+f"(d[21]), "+f"(d[22]), "+f"(d[23]),
          "+f"(d[24]), "+f"(d[25]), "+f"(d[26]), "+f"(d[27]), "+f"(d[28]), "+f"(d[29]), "+f"(d[30]), "+f"(d[31]),
          "+f"(d[32]), "+f"(d[33]), "+f"(d[34]), "+f"(d[35]), "+f"(d[36]), "+f"(d[37]), "+f"(d[38]), "+f"(d[39]),
          "+f"(d[40]), "+f"(d[41]), "+f"(d[42]), "+f"(d[43]), "+f"(d[44]), "+f"(d[45]), "+f"(d[46]), "+f"(d[47]),
          "+f"(d[48]), "+f"(d[49]), "+f"(d[50]), "+f"(d[51]), "+f"(d[52]), "+f"(d[53]), "+f"(d[54]), "+f"(d[55]),
          "+f"(d[56]), "+f"(d[57]), "+f"(d[58]), "+f"(d[59]), "+f"(d[60]), "+f"(d[61]), "+f"(d[62]), "+f"(d[63])
        : "r"(a0), "r"(a1), "r"(a2), "r"(a3), "r"(blo), "r"(scale_d), "n"(TB), "r"(DESC_HI));
}
template <int TB>
__device__ __forceinline__ void wgmma_rs_n128_z(float (&d)[64], uint32_t a0, uint32_t a1, uint32_t a2, uint32_t a3, uint32_t blo) {
    asm volatile("{\n.reg .pred p;\n.reg .b64 db;\nsetp.ne.b32 p, %69, 0;\n"
        "mov.b64 db, {%68, %71};\n"
        "wgmma.mma_async.sync.aligned.m64n128k16.f32.bf16.bf16 "
        "{%0, %1, %2, %3, %4, %5, %6, %7, %8, %9, %10, %11, %12, %13, %14, %15, %16, %17, %18, %19, %20, %21, %22, %23, %24, %25, %26, %27, %28, %29, %30, %31, %32, %33, %34, %35, %36, %37, %38, %39, %40, %41, %42, %43, %44, %45, %46, %47, %48, %49, %50, %51, %52, %53, %54, %55, %56, %57, %58, %59, %60, %61, %62, %63}, {%64, %65, %66, %67}, db, p, 1, 1, %70;\n}\n"
        :
          "=f"(d[0]), "=f"(d[1]), "=f"(d[2]), "=f"(d[3]), "=f"(d[4]), "=f"(d[5]), "=f"(d[6]), "=f"(d[7]),
          "=f"(d[8]), "=f"(d[9]), "=f"(d[10]), "=f"(d[11]), "=f"(d[12]), "=f"(d[13]), "=f"(d[14]), "=f"(d[15]),
          "=f"(d[16]), "=f"(d[17]), "=f"(d[18]), "=f"(d[19]), "=f"(d[20]), "=f"(d[21]), "=f"(d[22]), "=f"(d[23]),
          "=f"(d[24]), "=f"(d[25]), "=f"(d[26]), "=f"(d[27]), "=f"(d[28]), "=f"(d[29]), "=f"(d[30]), "=f"(d[31]),
          "=f"(d[32]), "=f"(d[33]), "=f"(d[34]), "=f"(d[35]), "=f"(d[36]), "=f"(d[37]), "=f"(d[38]), "=f"(d[39]),
          "=f"(d[40]), "=f"(d[41]), "=f"(d[42]), "=f"(d[43]), "=f"(d[44]), "=f"(d[45]), "=f"(d[46]), "=f"(d[47]),
          "=f"(d[48]), "=f"(d[49]), "=f"(d[50]), "=f"(d[51]), "=f"(d[52]), "=f"(d[53]), "=f"(d[54]), "=f"(d[55]),
          "=f"(d[56]), "=f"(d[57]), "=f"(d[58]), "=f"(d[59]), "=f"(d[60]), "=f"(d[61]), "=f"(d[62]), "=f"(d[63])
        : "r"(a0), "r"(a1), "r"(a2), "r"(a3), "r"(blo), "n"(0), "n"(TB), "r"(DESC_HI));
}
template <int TA, int TB>
__device__ __forceinline__ void wgmma_ss_n128_z(float (&d)[64], uint32_t alo, uint32_t blo) {
    asm volatile("{\n.reg .pred p;\n.reg .b64 da, db;\nsetp.ne.b32 p, %66, 0;\n"
        "mov.b64 da, {%64, %69};\nmov.b64 db, {%65, %69};\n"
        "wgmma.mma_async.sync.aligned.m64n128k16.f32.bf16.bf16 "
        "{%0, %1, %2, %3, %4, %5, %6, %7, %8, %9, %10, %11, %12, %13, %14, %15, %16, %17, %18, %19, %20, %21, %22, %23, %24, %25, %26, %27, %28, %29, %30, %31, %32, %33, %34, %35, %36, %37, %38, %39, %40, %41, %42, %43, %44, %45, %46, %47, %48, %49, %50, %51, %52, %53, %54, %55, %56, %57, %58, %59, %60, %61, %62, %63}, da, db, p, 1, 1, %67, %68;\n}\n"
        :
          "=f"(d[0]), "=f"(d[1]), "=f"(d[2]), "=f"(d[3]), "=f"(d[4]), "=f"(d[5]), "=f"(d[6]), "=f"(d[7]),
          "=f"(d[8]), "=f"(d[9]), "=f"(d[10]), "=f"(d[11]), "=f"(d[12]), "=f"(d[13]), "=f"(d[14]), "=f"(d[15]),
          "=f"(d[16]), "=f"(d[17]), "=f"(d[18]), "=f"(d[19]), "=f"(d[20]), "=f"(d[21]), "=f"(d[22]), "=f"(d[23]),
          "=f"(d[24]), "=f"(d[25]), "=f"(d[26]), "=f"(d[27]), "=f"(d[28]), "=f"(d[29]), "=f"(d[30]), "=f"(d[31]),
          "=f"(d[32]), "=f"(d[33]), "=f"(d[34]), "=f"(d[35]), "=f"(d[36]), "=f"(d[37]), "=f"(d[38]), "=f"(d[39]),
          "=f"(d[40]), "=f"(d[41]), "=f"(d[42]), "=f"(d[43]), "=f"(d[44]), "=f"(d[45]), "=f"(d[46]), "=f"(d[47]),
          "=f"(d[48]), "=f"(d[49]), "=f"(d[50]), "=f"(d[51]), "=f"(d[52]), "=f"(d[53]), "=f"(d[54]), "=f"(d[55]),
          "=f"(d[56]), "=f"(d[57]), "=f"(d[58]), "=f"(d[59]), "=f"(d[60]), "=f"(d[61]), "=f"(d[62]), "=f"(d[63])
        : "r"(alo), "r"(blo), "n"(0), "n"(TA), "n"(TB), "r"(DESC_HI));
}

__device__ __forceinline__ uint32_t pack_bf16(float lo, float hi) {
    uint32_t r;
    asm("cvt.rn.bf16x2.f32 %0, %1, %2;" : "=r"(r) : "f"(hi), "f"(lo));
    return r;
}
__device__ __forceinline__ uint32_t add_bf16x2(uint32_t a, uint32_t b) {
    uint32_t r;
    asm("add.rn.bf16x2 %0, %1, %2;" : "=r"(r) : "r"(a), "r"(b));
    return r;
}
__device__ __forceinline__ float bf_lo(uint32_t v) { return __uint_as_float(v << 16); }
__device__ __forceinline__ float bf_hi(uint32_t v) { return __uint_as_float(v & 0xffff0000u); }
__device__ __forceinline__ float round_bf16(float v) { return __bfloat162float(__float2bfloat16_rn(v)); }
__device__ __forceinline__ float ex2(float x) {
    float y;
    asm("ex2.approx.ftz.f32 %0, %1;" : "=f"(y) : "f"(x));
    return y;
}
__device__ __forceinline__ float rcp(float x) {
    float y;
    asm("rcp.approx.ftz.f32 %0, %1;" : "=f"(y) : "f"(x));
    return y;
}
__device__ __forceinline__ void stg128(void* p, uint32_t a, uint32_t b, uint32_t c, uint32_t d) {
    asm volatile("st.global.v4.b32 [%0], {%1, %2, %3, %4};" ::"l"(p), "r"(a), "r"(b), "r"(c), "r"(d) : "memory");
}
__device__ __forceinline__ int perm_row(int t) { return (t & ~255) | (((0x78 >> (((t >> 6) & 3) * 2)) & 3) << 6) | (t & 63); }
__device__ __forceinline__ int unperm_row(int t) { return (t & ~255) | (((0x9C >> (((t >> 6) & 3) * 2)) & 3) << 6) | (t & 63); }

#define PROF(i)
#define PROFG(i)
#define PROFDUMP()
#define TR(i)
#define BP(r, i)
#define LP(i)

template <int I>
__device__ __forceinline__ void store_chunk(const float (&a)[64], __nv_bfloat16* row0, __nv_bfloat16* row1, float s0, float s1) {
    stg128(row0 + 32 * I, pack_bf16(a[16 * I + 0] * s0, a[16 * I + 1] * s0), pack_bf16(a[16 * I + 4] * s0, a[16 * I + 5] * s0),
           pack_bf16(a[16 * I + 8] * s0, a[16 * I + 9] * s0), pack_bf16(a[16 * I + 12] * s0, a[16 * I + 13] * s0));
    stg128(row1 + 32 * I, pack_bf16(a[16 * I + 2] * s1, a[16 * I + 3] * s1), pack_bf16(a[16 * I + 6] * s1, a[16 * I + 7] * s1),
           pack_bf16(a[16 * I + 10] * s1, a[16 * I + 11] * s1), pack_bf16(a[16 * I + 14] * s1, a[16 * I + 15] * s1));
}
template <int I>
struct IntT { static constexpr int value = I; };
template <class F>
__device__ __forceinline__ void for4(F f) { f(IntT<0>{}); f(IntT<1>{}); f(IntT<2>{}); f(IntT<3>{}); }

struct Prod {
    uint32_t smem, bars;
    uint32_t bo, par;
    uint32_t dst, fb;
    __device__ __forceinline__ void acquire(uint32_t o, uint32_t parity, uint32_t bytes) {
        mbar_wait(bars + BAR_EMPTY + o, parity);
        fb = bars + BAR_FULL + o;
        dst = smem + o * (SLOT / 8);
        w_expect_tx(fb, bytes);
    }
    __device__ __forceinline__ void next(uint32_t bytes) {
        acquire(bo, par, bytes);
        const bool wrap = bo == (NSLOT - 1) * 8;
        bo = wrap ? 0u : bo + 8;
        par ^= wrap ? 1u : 0u;
    }
};

__device__ __forceinline__ int item_p(int ca, int rd) {
    const int v = (rd & 1) ? (ca + 4) & 7 : ca;
    return (rd & 2) ? 7 - v : v;
}
__device__ __forceinline__ int kv_round(int i) { return (KVORDER >> (4 * i)) & 3; }
__device__ __forceinline__ int slot_a(int i) { return (0x5310 >> (4 * i)) & 15; }
__device__ __forceinline__ int slot_w(int m) { return (0x264 >> (4 * m)) & 15; }

__device__ __forceinline__ void producer(const Params& P, uint32_t smem, uint32_t bars, int ca, int cb, int rank) {
    Prod pr{smem, bars, 0u, 0u, 0u, 0u};
    {
        int m = 0;
        uint32_t lap = 1;
#pragma unroll 1
        for (int u = 0; u < 32; u++) {
            if (u >= 3) {
                const int v = (u == 3) ? 4 + ca : u + 8;
                if (v < 32 && (u == 3 || (v & 7) == ca)) w_tma_prefetch((v & 4) ? &P.wuv : &P.wuk, (cb + 8 * kv_round(v >> 3)) * 128 + rank * 64, (v & 3) * 128);
                if (u == 24) {
                    w_tma_prefetch(&P.wq, cb * 128 + rank * 64, ca * 64);
                    if (ca < 2) w_tma_prefetch(&P.wq, cb * 128 + rank * 64, (ca + 8) * 64);
                }
            }
            pr.acquire(slot_w(m) * 8, lap ^ (m >> 1), SLOT);
            lap ^= m >> 1;
            m = (m == 2) ? 0 : m + 1;
            TR(1 + u);
            w_tma_load_mc(pr.dst + rank * 16384, (u & 4) ? &P.wuv : &P.wuk, (cb + 8 * kv_round(u >> 3)) * 128 + rank * 64, (u & 3) * 128, pr.fb);
            if (u < 3) {
                pr.acquire(slot_a(u + 1) * 8, 1, SLOT);
                w_tma_load(pr.dst, &P.ckv, u * 128 + 128, (2 * ca + rank) * 128, pr.fb);
                w_tma_load(pr.dst + 16384, &P.ckv, u * 128 + 192, (2 * ca + rank) * 128, pr.fb);
            }
        }
    }
    PROF(1);
    mbar_wait(bars + BAR_DEP, 0);
#pragma unroll 1
    for (int rd = 0; rd < 4; rd++) {
        const int h = 8 * rd + cb, p = item_p(ca, rd);
#pragma unroll 1
        for (int ks = 0; ks < 10; ks++) {
            pr.next(SLOT);
            w_tma_load_mc(pr.dst + 16384 + rank * 8192, &P.wq, h * 128 + rank * 64, ks * 64, pr.fb);
            w_tma_load(pr.dst, &P.xn, ks * 64, 256 * p + 128 * rank, pr.fb);
        }
        PROF(8 + rd * 4);
        mbar_wait(bars + BAR_DEP + (1 + rd) * 8, 0);
        const int last = 4 * p + 3, top = h * 32 + last;
#pragma unroll 1
        for (int i = 0; i <= last; i++) {
            const int t = (i == 0) ? top - 1 : (i == last) ? h * 32 + 1 : (i & 1) ? top - 2 - i : top + 2 - i;
            pr.next(SLOT);
            w_tma_load_mc(pr.dst + rank * 16384, &P.kv, rank * 64, t * 128, pr.fb);
            if (i == 2) {
                if (rd < 3) {
                    w_tma_prefetch(&P.wq, (h + 8) * 128 + rank * 64, ca * 64);
                    if (ca < 2) w_tma_prefetch(&P.wq, (h + 8) * 128 + rank * 64, (ca + 8) * 64);
                } else {
#pragma unroll 1
                    for (int j = 0; j < 10; j++) {
                        const int tt = ca + (j >= 5 ? 8 : 0);
                        w_tma_prefetch(&P.wo, 320 * (cb & 1) + 64 * (j >= 5 ? j - 5 : j), (8 * (tt >> 2) + (cb & 6) + ((tt >> 1) & 1)) * 128 + (tt & 1) * 64 + rank * 32);
                    }
                }
            }
        }
        PROF(9 + rd * 4);
    }
    {
        const int n0 = 320 * (cb & 1), kg = cb >> 1;
#pragma unroll 1
        for (int t = 0; t < 16; t++) {
            const int h = 8 * (t >> 2) + 2 * kg + ((t >> 1) & 1), ks = t & 1;
            const int krow = h * 128 + ks * 64 + rank * 32;
            pr.next(SLOT);
            w_tma_load_mc(pr.dst + 16384 + rank * 8192, &P.wo, n0, krow, pr.fb);
            w_tma_load_mc(pr.dst + 16384 + rank * 8192 + 4096, &P.wo, n0 + 64, krow, pr.fb);
            mbar_wait(bars + BAR_DEP + (5 + (t >> 1)) * 8, 0);
            w_tma_load(pr.dst, &P.ctx, ks * 64, h * SEQ + 256 * ca + 128 * rank, pr.fb);
            pr.next(24576);
#pragma unroll
            for (int c = 0; c < 3; c++) w_tma_load_mc(pr.dst + rank * 12288 + c * 4096, &P.wo, n0 + 128 + 64 * c, krow, pr.fb);
        }
    }
}

struct Slot {
    uint32_t bo, dl, par;
};
struct Cons {
    uint32_t bars, rel;
    uint32_t dl0;
    uint32_t lane;
    Slot cur;
    __device__ __forceinline__ Slot slot(int s, uint32_t par) const { return Slot{(uint32_t)s * 8, dl0 + (uint32_t)s * (SLOT >> 4), par}; }
    __device__ __forceinline__ void wait(const Slot& s) const { mbar_wait(bars + BAR_FULL + s.bo, s.par); }
    __device__ __forceinline__ void release(uint32_t bo) const {
        asm volatile("{\n.reg .pred p;\nsetp.lt.u32 p, %1, 2;\n@p mbarrier.arrive.shared::cluster.b64 _, [%0];\n}\n" ::"r"(rel + bo), "r"(lane) : "memory");
    }
    __device__ __forceinline__ Slot next() {
        const Slot s = cur;
        const bool wrap = s.bo == (NSLOT - 1) * 8;
        cur.bo = wrap ? 0u : s.bo + 8;
        cur.dl = wrap ? dl0 : s.dl + (SLOT >> 4);
        cur.par = s.par ^ (wrap ? 1u : 0u);
        return s;
    }
};
__host__ __device__ constexpr uint32_t lbo(uint32_t bytes) { return (bytes >> 4) << 16; }

__device__ __forceinline__ float div640(float x) {
    const float q = x * (1.0f / DM);
    return fmaf(fmaf(-q, (float)DM, x), 1.0f / DM, q);
}
__device__ __forceinline__ float sqrt_approx(float x) {
    float y;
    asm("sqrt.approx.ftz.f32 %0, %1;" : "=f"(y) : "f"(x));
    return y;
}
struct LayerNorm {
    uint4 xv[5], wv[5];
    uint32_t nmb;
    float inv, r;
    __device__ __forceinline__ void stats() {
        float v[40];
#pragma unroll
        for (int i = 0; i < 20; i++) { const uint32_t u = (&xv[i >> 2].x)[i & 3]; v[2 * i] = bf_lo(u); v[2 * i + 1] = bf_hi(u); }
        float sum = 0.f, sq = 0.f;
#pragma unroll
        for (int i = 0; i < 40; i += 4) sum += (v[i] + v[i + 1]) + (v[i + 2] + v[i + 3]);
#pragma unroll
        for (int o = 8; o > 0; o >>= 1) sum += __shfl_xor_sync(0xffffffffu, sum, o);
        const float mean = div640(sum);
#pragma unroll
        for (int i = 0; i < 40; i += 2) { const float d0 = v[i] - mean, d1 = v[i + 1] - mean; sq += fmaf(d0, d0, d1 * d1); }
#pragma unroll
        for (int o = 8; o > 0; o >>= 1) sq += __shfl_xor_sync(0xffffffffu, sq, o);
        nmb = pack_bf16(-mean, -mean);
        inv = rcp(round_bf16(sqrt_approx(round_bf16(round_bf16(div640(sq)) + 1e-5f))));
        r = 0.f;
    }
    template <int I>
    __device__ __forceinline__ void piece(int t, int l) {
        uint32_t o[4], z[4];
#pragma unroll
        for (int j = 0; j < 4; j++) {
            const uint32_t u = (&xv[I].x)[j], w = (&wv[I].x)[j];
            const uint32_t d = add_bf16x2(u, nmb);
            o[j] = pack_bf16(bf_lo(d) * inv, bf_hi(d) * inv);
            const float n0 = bf_lo(o[j]), n1 = bf_hi(o[j]);
            z[j] = add_bf16x2(u, o[j]);
            r = fmaf(n1, bf_hi(w), fmaf(n0, bf_lo(w), r));
        }
        stg128(g_xn + (size_t)perm_row(t) * DM + 8 * (l + 16 * I), o[0], o[1], o[2], o[3]);
        stg128(g_res + (size_t)t * DM + 8 * (l + 16 * I), z[0], z[1], z[2], z[3]);
        if (I == 4) {
#pragma unroll
            for (int k = 8; k > 0; k >>= 1) r += __shfl_xor_sync(0xffffffffu, r, k);
            if (l == 0) g_r[t] = round_bf16(r);
        }
    }
};

constexpr float SM_SCALE = 0.08838834764831845f * 1.4426950408889634f;

template <int J0, int J1, int SEG = 0>
__device__ __forceinline__ void exp_part(float (&s)[64], float n0, float n1, float& r0, float& r1) {
    float a1 = 0.f, b1 = 0.f;
#pragma unroll
    for (int j = J0; j < J1; j++) {
        if (SEG > 0 && j >= SEG && j % (SEG > 0 ? SEG : 1) == 0) {
            n0 = fmaf(s[4 * (j - PACE_LAG)], 0.f, n0);
            n1 = fmaf(s[4 * (j - PACE_LAG)], 0.f, n1);
        }
        s[4 * j + 0] = ex2(fmaf(s[4 * j + 0], SM_SCALE, n0));
        s[4 * j + 1] = ex2(fmaf(s[4 * j + 1], SM_SCALE, n0));
        s[4 * j + 2] = ex2(fmaf(s[4 * j + 2], SM_SCALE, n1));
        s[4 * j + 3] = ex2(fmaf(s[4 * j + 3], SM_SCALE, n1));
        r0 += s[4 * j + 0]; r1 += s[4 * j + 2];
        if (j == J0) { a1 = s[4 * j + 1]; b1 = s[4 * j + 3]; } else { a1 += s[4 * j + 1]; b1 += s[4 * j + 3]; }
    }
    r0 += a1;
    r1 += b1;
}
__device__ __forceinline__ void sched_barrier(float x, float y, uint32_t scratch) {
    asm volatile("{\n.reg .pred p;\nsetp.lt.f32 p, %0, 0f00000000;\n@p st.shared.f32 [%2], %1;\n}\n" ::"f"(x), "f"(y), "r"(scratch) : "memory");
}
__device__ __forceinline__ void pack_tile(const float (&s)[64], uint32_t (&p)[32]) {
#pragma unroll
    for (int i = 0; i < 32; i++) p[i] = pack_bf16(s[2 * i], s[2 * i + 1]);
}
template <bool ZERO>
__device__ __forceinline__ void gemm_rs(float (&d)[64], const uint32_t (&a)[32], uint32_t dl, int acc = 1) {
    const uint32_t b = dl + lbo(16384);
    if (ZERO) wgmma_rs_n128_z<1>(d, a[0], a[1], a[2], a[3], b);
#pragma unroll
    for (int k = ZERO ? 1 : 0; k < 8; k++) wgmma_rs_n128<1>(d, a[4 * k], a[4 * k + 1], a[4 * k + 2], a[4 * k + 3], b + k * 128, k ? 1 : acc);
}
template <int ZERO>
__device__ __forceinline__ void gemm_q(float (&d)[64], uint32_t dl, int role) {
    const uint32_t a = dl + role * 512 + lbo(16), b = dl + 1024 + lbo(8192);
    if (ZERO) wgmma_ss_n128_z<0, 1>(d, a, b);
#pragma unroll
    for (int k = ZERO ? 1 : 0; k < 4; k++) wgmma_ss_n128<0, 1>(d, a + k * 2, b + k * 128, 1);
}
template <bool KT, bool ZERO, int K0, int K1>
__device__ __forceinline__ void gemm_kv(float (&d)[64], uint32_t ckv, uint32_t wt, int wg) {
    if (KT) {
        const uint32_t a = wt + wg * 1024 + lbo(16), b = ckv + lbo(16);
        if (ZERO) wgmma_ss_n128_z<1, 0>(d, a, b);
#pragma unroll
        for (int k = ZERO ? 1 : K0; k < K1; k++) wgmma_ss_n128<1, 0>(d, a + k * 128, b + (k >> 2) * 1024 + (k & 3) * 2, 1);
    } else {
        const uint32_t a = ckv + wg * 512 + lbo(16), b = wt + lbo(16384);
        if (ZERO) wgmma_ss_n128_z<0, 1>(d, a, b);
#pragma unroll
        for (int k = ZERO ? 1 : K0; k < K1; k++) wgmma_ss_n128<0, 1>(d, a + (k >> 2) * 1024 + (k & 3) * 2, b + k * 128, 1);
    }
}
__device__ __forceinline__ void mma16816(float& d0, float& d1, float& d2, float& d3, uint32_t a0, uint32_t a1, uint32_t a2, uint32_t a3, uint32_t b0, uint32_t b1) {
    asm volatile("mma.sync.aligned.m16n8k16.row.col.f32.bf16.bf16.f32 {%0,%1,%2,%3}, {%4,%5,%6,%7}, {%8,%9}, {%0,%1,%2,%3};"
                 : "+f"(d0), "+f"(d1), "+f"(d2), "+f"(d3) : "r"(a0), "r"(a1), "r"(a2), "r"(a3), "r"(b0), "r"(b1));
}
__device__ __forceinline__ uint32_t ld_pair(const __nv_bfloat16* p) {
    const unsigned short* u = reinterpret_cast<const unsigned short*>(p);
    return (uint32_t)__ldcg(u) | ((uint32_t)__ldcg(u + 128) << 16);
}
__device__ __forceinline__ void attention_exact(float (&o)[64], const uint32_t (&qf)[32], float& l0, float& l1, int h, int nblk, int rr, int lane) {
    const int q = lane & 3, lr = lane >> 2;
    float m0 = -INFINITY, m1 = -INFINITY;
    l0 = 0.f; l1 = 0.f;
#pragma unroll
    for (int i = 0; i < 64; i++) o[i] = 0.f;
#pragma unroll 1
    for (int cidx = 0; cidx < nblk * 8; cidx++) {
        const int kc = cidx & 7;
        const __nv_bfloat16* kt = g_kv + (size_t)((h * 16 + (cidx >> 3)) * 2) * 16384;
        float sc[8];
#pragma unroll
        for (int i = 0; i < 8; i++) sc[i] = 0.f;
#pragma unroll
        for (int kk = 0; kk < 8; kk++)
#pragma unroll
            for (int nt = 0; nt < 2; nt++) {
                const __nv_bfloat16* b = kt + (16 * kk + 2 * q) * 128 + 16 * kc + 8 * nt + lr;
                mma16816(sc[4 * nt], sc[4 * nt + 1], sc[4 * nt + 2], sc[4 * nt + 3], qf[4 * kk], qf[4 * kk + 1], qf[4 * kk + 2], qf[4 * kk + 3],
                         ld_pair(b), ld_pair(b + 8 * 128));
            }
        const int lim = rr + ((nblk - 1) - (cidx >> 3)) * 128 - 32 * (kc >> 1) - 4 * (kc & 1);
#pragma unroll
        for (int i = 0; i < 8; i++)
            if (2 * (i >> 2) + (i & 1) > lim + 4 * (i & 2)) sc[i] = -INFINITY;
        float x0 = fmaxf(fmaxf(sc[0], sc[1]), fmaxf(sc[4], sc[5])), x1 = fmaxf(fmaxf(sc[2], sc[3]), fmaxf(sc[6], sc[7]));
        x0 = fmaxf(x0, __shfl_xor_sync(0xffffffffu, x0, 1)); x1 = fmaxf(x1, __shfl_xor_sync(0xffffffffu, x1, 1));
        x0 = fmaxf(x0, __shfl_xor_sync(0xffffffffu, x0, 2)); x1 = fmaxf(x1, __shfl_xor_sync(0xffffffffu, x1, 2));
        x0 = fmaxf(x0, m0); x1 = fmaxf(x1, m1);
        const float a0 = ex2((m0 - x0) * SM_SCALE), a1 = ex2((m1 - x1) * SM_SCALE);
        m0 = x0; m1 = x1;
#pragma unroll
        for (int i = 0; i < 8; i++) sc[i] = ex2((sc[i] - ((i & 2) ? m1 : m0)) * SM_SCALE);
        l0 = l0 * a0 + (sc[0] + sc[1]) + (sc[4] + sc[5]);
        l1 = l1 * a1 + (sc[2] + sc[3]) + (sc[6] + sc[7]);
        const uint32_t p0 = pack_bf16(sc[0], sc[1]), p1 = pack_bf16(sc[2], sc[3]), p2 = pack_bf16(sc[4], sc[5]), p3 = pack_bf16(sc[6], sc[7]);
        const __nv_bfloat16* vb = kt + 16384 + (16 * kc + 2 * q) * 128 + lr;
#pragma unroll
        for (int nt = 0; nt < 16; nt++) {
            o[4 * nt] *= a0; o[4 * nt + 1] *= a0; o[4 * nt + 2] *= a1; o[4 * nt + 3] *= a1;
            mma16816(o[4 * nt], o[4 * nt + 1], o[4 * nt + 2], o[4 * nt + 3], p0, p1, p2, p3, ld_pair(vb + 8 * nt), ld_pair(vb + 8 * nt + 8 * 128));
        }
    }
}

__device__ __forceinline__ void signal(uint32_t bars, int wg, int e, int lane) {
    __syncwarp();
    asm volatile("{\n.reg .pred p;\nsetp.eq.u32 p, %1, 0;\n@p mbarrier.arrive.shared::cta.b64 _, [%0];\n}\n" ::"r"(bars + BAR_SIG + (wg * 9 + e) * 8), "r"(lane) : "memory");
}

__device__ __forceinline__ void consumer(const Params& P, uint32_t smem, uint32_t bars, int ca, int cb, int rank, int wg, LayerNorm& ln) {
    const int lane = threadIdx.x & 31, w = (threadIdx.x >> 5) & 3, q = lane & 3, lr = lane >> 2;
    PROF(7);
    const int ln_t = blockIdx.x * 16 + wg * 8 + w * 2 + (lane >> 4);
    ln.stats();
    ln.piece<0>(ln_t, lane & 15);
    cluster_wait();
    Cons c{bars, mapa(bars + BAR_EMPTY, lane & 1), (smem & 0x3FFFF) >> 4, (uint32_t)lane, Slot{0u, (smem & 0x3FFFF) >> 4, 1u}};
    PROFG(180);
    PROF(1);
    float o[64], s[64];
    uint32_t pend;
    __nv_bfloat16* ep_ptr;
    int ep_step;
    {
        const int krow = 64 * wg + 16 * w + lr;
        const int vrow = 64 * wg + 32 * (w >> 1) + 8 * (lr >> 1) + 4 * (w & 1) + (lr & 1);
        ep_step = 2 * 128;
        int m = 0;
        uint32_t lap = 0;
        auto step = [&](auto kt, auto kc, float (&d)[64], int hh) {
            const Slot sa = c.slot(slot_a(kc.value), 0), sw = c.slot(slot_w(m), lap ^ (m >> 1));
            lap ^= m >> 1;
            m = (m == 2) ? 0 : m + 1;
            TR(1 + (hh * 8 + (kt.value ? 0 : 4) + kc.value) * 2);
            if (kt.value && hh == 0) c.wait(sa);
            c.wait(sw);
            TR(2 + (hh * 8 + (kt.value ? 0 : 4) + kc.value) * 2);
            wgmma_fence();
            gemm_kv<kt.value, kc.value == 0, 0, KVSPLIT>(d, sa.dl, sw.dl, wg);
            wgmma_commit();
            wgmma_wait<1>();
            if (!(kt.value && kc.value == 0 && hh == 0)) c.release(pend);
            if (!kt.value && kc.value > 0 && hh == 3) c.release(slot_a(kc.value - 1) * 8);
            pend = sw.bo;
            wgmma_fence();
            gemm_kv<kt.value, false, KVSPLIT, 8>(d, sa.dl, sw.dl, wg);
            wgmma_commit();
        };
#pragma unroll 1
        for (int hh = 0; hh < 4; hh++) {
            __nv_bfloat16* base = g_kv + (size_t)(((cb + 8 * kv_round(hh)) * 16 + 2 * ca + rank) * 2) * 16384 + 8 * q;
            for4([&](auto kc) {
                step(TrueT{}, kc, s, hh);
                if (hh > 0) {
                    if (kc.value == 0) fence_regs(o);
                    store_chunk<kc.value>(o, ep_ptr, ep_ptr + ep_step, 1.f, 1.f);
                } else {
                    ln.template piece<kc.value + 1>(ln_t, lane & 15);
                }
            });
            signal(bars, wg, hh, lane);
            for4([&](auto kc) {
                step(FalseT{}, kc, o, hh);
                if (kc.value == 0) fence_regs(s);
                store_chunk<kc.value>(s, base + krow * 128, base + (krow + 8) * 128, 1.f, 1.f);
            });
            PROF(24 + hh);
            if (hh == 1) PROFG(181);
            ep_ptr = base + 16384 + vrow * 128;
        }
    }
    PROFG(182);
    PROF(2);
    {
        uint32_t pf[32], qf[32];
        float l0 = 0.25f, l1 = 0.25f;
        const int bar_me = 2 + wg, bar_other = 3 - wg;
#pragma unroll 1
        for (int rd = 0; rd < 4; rd++) {
            const int h = 8 * rd + cb, p = item_p(ca, rd);
            const int role = wg ^ (rd & 1);
            const int nrest = 2 * p + role;
            Slot kfirst;
            {
                auto qstep = [&](auto zero, int ks) {
                    const Slot sl = c.next();
                    BP(2, 4 + 3 * ks);
                    c.wait(sl);
                    BP(2, 5 + 3 * ks);
                    wgmma_fence();
                    gemm_q<zero.value>(s, sl.dl, role);
                    wgmma_commit();
                    wgmma_wait<1>();
                    BP(2, 6 + 3 * ks);
                    c.release(pend);
                    pend = sl.bo;
                };
                qstep(TrueT{}, 0);
                if (rd == 0) c.release(slot_a(3) * 8);
                fence_regs(o);
#pragma unroll 1
                for (int ks = 1; ks < QST; ks++) qstep(FalseT{}, ks);
                for4([&](auto i) {
                    qstep(FalseT{}, QST + i.value);
                    if (i.value == 0) {
                        l0 += __shfl_xor_sync(0xffffffffu, l0, 1); l1 += __shfl_xor_sync(0xffffffffu, l1, 1);
                        l0 += __shfl_xor_sync(0xffffffffu, l0, 2); l1 += __shfl_xor_sync(0xffffffffu, l1, 2);
                        l0 = rcp(l0); l1 = rcp(l1);
                    }
                    store_chunk<i.value>(o, ep_ptr, ep_ptr + ep_step, l0, l1);
                });
                signal(bars, wg, 4 + rd, lane);
                PROF(11 + rd * 4);
#pragma unroll 1
                for (int ks = QST + 4; ks < 10; ks++) qstep(FalseT{}, ks);
                if (!role) { const Slot sl = c.next(); c.wait(sl); c.release(sl.bo); }
                kfirst = c.next();
                c.wait(kfirst);
                wgmma_wait<0>();
                BP(2, 34);
                c.release(pend);
                fence_regs(s);
                pack_tile(s, qf);
            }
            PROF(8 + rd * 4);
            fence_regs(qf);
            BP(2, 35);
            if (PINGPONG && !role) named_sync(bar_me, 256);
            BP(2, 36);
            wgmma_fence();
            gemm_rs<true>(s, qf, kfirst.dl);
            wgmma_commit();
            if (PINGPONG) named_arrive(bar_other, 256);
            BP(2, 37);
            if (!role) { const Slot sl = c.next(); c.wait(sl); c.release(sl.bo); }
            const int dg = __reduce_or_sync(0xffffffffu, 2 * (role ^ rank) + (w >> 1));
            wgmma_wait<0>();
            BP(2, 38);
            fence_regs(s);
            c.release(kfirst.bo);
            float n0, n1;
            l0 = 0.f; l1 = 0.f;
            for4([&](auto a) {
                constexpr int B = 16 * a.value;
                if (a.value == dg) {
                    const int lim = 16 * (w & 1) + lr - 8 * q;
#pragma unroll
                    for (int i = 0; i < 16; i++)
                        if (2 * (i >> 2) + (i & 1) > lim + 4 * (i & 2)) s[B + i] = -INFINITY;
                }
                if (a.value == 0) {
                    n0 = fmaxf(fmaxf(fmaxf(s[0], s[1]), fmaxf(s[4], s[5])), fmaxf(fmaxf(s[8], s[9]), fmaxf(s[12], s[13])));
                    n1 = fmaxf(fmaxf(fmaxf(s[2], s[3]), fmaxf(s[6], s[7])), fmaxf(fmaxf(s[10], s[11]), fmaxf(s[14], s[15])));
                    n0 = fmaxf(n0, __shfl_xor_sync(0xffffffffu, n0, 1)); n1 = fmaxf(n1, __shfl_xor_sync(0xffffffffu, n1, 1));
                    n0 = fmaxf(n0, __shfl_xor_sync(0xffffffffu, n0, 2)); n1 = fmaxf(n1, __shfl_xor_sync(0xffffffffu, n1, 2));
                    n0 *= -SM_SCALE; n1 *= -SM_SCALE;
                }
                if (a.value <= dg) {
                    exp_part<4 * a.value, 4 * a.value + 4>(s, n0, n1, l0, l1);
#pragma unroll
                    for (int i = 0; i < 8; i++) pf[8 * a.value + i] = pack_bf16(s[B + 2 * i], s[B + 2 * i + 1]);
                } else {
#pragma unroll
                    for (int i = 0; i < 8; i++) pf[8 * a.value + i] = 0u;
                }
            });
            PROF(9 + rd * 4);
#pragma unroll 1
            for (int it = 0; it < nrest; it++) {
                const Slot sk = c.next(), sv = c.next();
                LP(0);
                if (it < 3) BP(2, 40 + 4 * it);
                if (it >= nrest - 2) BP(1, 60 + 4 * (it - nrest + 2));
                c.wait(sk);
                c.wait(sv);
                fence_regs(o); fence_regs(pf);
                LP(1);
                if (it < 3) BP(2, 41 + 4 * it);
                if (it >= nrest - 2) BP(1, 61 + 4 * (it - nrest + 2));
                if (PINGPONG) named_sync(bar_me, 256);
                LP(2);
                if (it < 3) BP(2, 42 + 4 * it);
                if (it >= nrest - 2) BP(1, 62 + 4 * (it - nrest + 2));
                wgmma_fence();
                gemm_rs<true>(s, qf, sk.dl);
                wgmma_commit();
                gemm_rs<false>(o, pf, sv.dl, it);
                wgmma_commit();
                if (PINGPONG) named_arrive(bar_other, 256);
                LP(3);
                if (it < 3) BP(2, 43 + 4 * it);
                if (it >= nrest - 2) BP(1, 63 + 4 * (it - nrest + 2));
                wgmma_wait<1>();
                LP(4);
                c.release(sk.bo);
                fence_regs(s);
                exp_part<0, SPLITJ, PACE>(s, n0, n1, l0, l1);
                sched_barrier(l0, l1, bars + MISC_OFF + 16);
                LP(5);
                wgmma_wait<0>();
                LP(6);
                c.release(sv.bo);
                fence_regs(o); fence_regs(pf);
                exp_part<SPLITJ, 16, PACE>(s, n0, n1, l0, l1);
                pack_tile(s, pf);
            }
            PROF(10 + rd * 4);
            PROFG(183 + rd);
            const Slot sv = c.next();
            BP(1, 0);
            c.wait(sv);
            if (nrest == 0) {
#pragma unroll
                for (int i = 0; i < 64; i++) o[i] = 0.f;
            }
            if (__builtin_expect(__any_sync(0xffffffffu, !(l0 < 0x1p60f && l1 < 0x1p60f)), 0)) {
                attention_exact(o, qf, l0, l1, h, nrest + 1, 64 * (role ^ rank) + 16 * w + lr - 8 * q, lane);
#pragma unroll
                for (int i = 0; i < 32; i++) pf[i] = 0u;
            }
            fence_regs(o); fence_regs(pf);
            BP(1, 1);
            if (PINGPONG && !role) named_sync(bar_me, 256);
            BP(1, 2);
            wgmma_fence();
            gemm_rs<false>(o, pf, sv.dl);
            wgmma_commit();
            BP(1, 3);
            pend = sv.bo;
            ep_ptr = g_ctx + (size_t)(h * SEQ + 256 * p + 128 * rank + 64 * role + 16 * w + lr) * HD + 8 * q;
            ep_step = 8 * HD;
        }
        l0 += __shfl_xor_sync(0xffffffffu, l0, 1); l1 += __shfl_xor_sync(0xffffffffu, l1, 1);
        l0 += __shfl_xor_sync(0xffffffffu, l0, 2); l1 += __shfl_xor_sync(0xffffffffu, l1, 2);
        l0 = rcp(l0); l1 = rcp(l1);
        wgmma_wait<0>();
        c.release(pend);
        fence_regs(o); fence_regs(pf);
        for4([&](auto i) { store_chunk<i.value>(o, ep_ptr, ep_ptr + ep_step, l0, l1); });
        signal(bars, wg, 8, lane);
    }
    PROFG(187);
    PROF(3);
    {
        float a1[64], a2[96];
        uint32_t px = 0, py = 0;
#pragma unroll 1
        for (int t = 0; t < 16; t++) {
            const Slot sx = c.next(), sy = c.next();
            c.wait(sx);
            const uint32_t da = sx.dl + wg * 512 + lbo(16), b1 = sx.dl + 1024 + lbo(4096), b2 = sy.dl + lbo(4096);
            wgmma_fence();
#pragma unroll
            for (int k = 0; k < 4; k++) wgmma_ss_n128<0, 1>(a1, da + k * 2, b1 + (k >> 1) * 512 + (k & 1) * 128, k ? 1 : t);
            wgmma_commit();
            wgmma_wait<1>();
            if (t > 0) { c.release(px); c.release(py); }
            px = sx.bo; py = sy.bo;
            c.wait(sy);
            wgmma_fence();
#pragma unroll
            for (int k = 0; k < 4; k++) wgmma_ss_n192<0, 1>(a2, da + k * 2, b2 + (k >> 1) * 768 + (k & 1) * 128, k ? 1 : t);
            wgmma_commit();
        }
        const int nh = cb & 1, kg = cb >> 1, tile = (ca * 2 + rank) * 2 + nh, tid = threadIdx.x - 128;
        const int goff = (unperm_row(256 * ca + 128 * rank + 64 * wg) + 16 * w + 8 * (kg >> 1)) * (DM / 8) + 40 * nh + 20 * (kg & 1) + lane;
        const uint32_t epoch = read_epoch();
        mbar_wait(bars + BAR_DEP + 13 * 8, 0);
        uint4 rv[5];
#pragma unroll
        for (int i = 0; i < 5; i++) {
            const int r = ((lane + 32 * i) * 205) >> 12;
            rv[i] = __ldcg(reinterpret_cast<const uint4*>(g_res) + (goff + 32 * i + 60 * r));
        }
        wgmma_wait<0>();
        fence_regs(a1); fence_regs(a2);
    PROFG(188);
        PROF(4);
        uint32_t own[20];
#pragma unroll
        for (int g = 0; g < 4; g++) {
            uint32_t pk[20];
#pragma unroll
            for (int i = 0; i < 20; i++) {
                const int j = 20 * (g & 1) + i, e = 2 * (g >> 1);
                pk[i] = (j < 16) ? pack_bf16(a1[4 * (j & 15) + e], a1[4 * (j & 15) + e + 1]) : pack_bf16(a2[4 * (j < 16 ? 0 : j - 16) + e], a2[4 * (j < 16 ? 0 : j - 16) + e + 1]);
                if (g == 0 || g == kg) own[i] = pk[i];
            }
            if (g != kg) {
                uint4* dst = g_part + ((tile * 4 + g) * 4 + kg) * 5 * 256 + tid;
#pragma unroll
                for (int i = 0; i < 5; i++) stg128(dst + i * 256, pk[4 * i], pk[4 * i + 1], pk[4 * i + 2], pk[4 * i + 3]);
            }
        }
        __syncwarp();
        if (lane == 0) {
            flag_add(F_PART + tile * 8 + wg * 4 + w);
            flag_wait<20>(F_PART + tile * 8 + wg * 4 + w, 4u * (epoch + 1));
        }
        __syncwarp();
        PROF(5);
        uint4 in[3][5];
#pragma unroll
        for (int k = 0; k < 3; k++)
#pragma unroll
            for (int i = 0; i < 5; i++) in[k][i] = __ldcg(g_part + ((tile * 4 + kg) * 4 + ((kg + 1 + k) & 3)) * 5 * 256 + i * 256 + tid);
        const uint32_t stage = smem + c.cur.bo * (SLOT / 8) + (wg * 4 + w) * 2688;
#pragma unroll
        for (int i = 0; i < 5; i++) {
            uint32_t r[4];
#pragma unroll
            for (int e = 0; e < 4; e++) {
                const uint32_t u0 = (&in[0][i].x)[e], u1 = (&in[1][i].x)[e], u2 = (&in[2][i].x)[e], u3 = own[4 * i + e];
                r[e] = pack_bf16((bf_lo(u0) + bf_lo(u1)) + (bf_lo(u2) + bf_lo(u3)), (bf_hi(u0) + bf_hi(u1)) + (bf_hi(u2) + bf_hi(u3)));
            }
            asm volatile("stmatrix.sync.aligned.m8n8.x4.shared.b16 [%0], {%1, %2, %3, %4};"
                         ::"r"(stage + (lane & 7) * 336 + (4 * i + (lane >> 3)) * 16), "r"(r[0]), "r"(r[1]), "r"(r[2]), "r"(r[3]) : "memory");
        }
        __syncwarp();
#pragma unroll
        for (int i = 0; i < 5; i++) {
            const int r = ((lane + 32 * i) * 205) >> 12;
            uint4 v;
            asm volatile("ld.shared.v4.b32 {%0, %1, %2, %3}, [%4];" : "=r"(v.x), "=r"(v.y), "=r"(v.z), "=r"(v.w) : "r"(stage + (lane + 32 * i + r) * 16) : "memory");
            stg128(reinterpret_cast<uint4*>(P.out) + (goff + 32 * i + 60 * r), add_bf16x2(v.x, rv[i].x), add_bf16x2(v.y, rv[i].y), add_bf16x2(v.z, rv[i].z), add_bf16x2(v.w, rv[i].w));
        }
    }
    PROF(6);
}

__device__ __forceinline__ void mma_rows(float (&acc)[8][4], uint32_t a0, uint32_t a2, const uint4& w0, const uint4& w1, const uint4& w2, const uint4& w3) {
    const uint32_t r0[4] = {w0.x, w0.y, w0.z, w0.w}, r1[4] = {w1.x, w1.y, w1.z, w1.w};
    const uint32_t r2[4] = {w2.x, w2.y, w2.z, w2.w}, r3[4] = {w3.x, w3.y, w3.z, w3.w};
#pragma unroll
    for (int i = 0; i < 4; i++) {
        mma16816(acc[2 * i][0], acc[2 * i][1], acc[2 * i][2], acc[2 * i][3], a0, 0u, a2, 0u, __byte_perm(r0[i], r1[i], 0x5410), __byte_perm(r2[i], r3[i], 0x5410));
        mma16816(acc[2 * i + 1][0], acc[2 * i + 1][1], acc[2 * i + 1][2], acc[2 * i + 1][3], a0, 0u, a2, 0u, __byte_perm(r0[i], r1[i], 0x7632), __byte_perm(r2[i], r3[i], 0x7632));
    }
}

__device__ __forceinline__ void mod_ffn(const Params& P, uint8_t* sm, int mc  ) {
    const uint32_t epoch = read_epoch();
    const int tid = threadIdx.x - 128, lane = tid & 31, cw = tid >> 5, q = lane & 3, lr = lane >> 2;
    uint32_t* xs = reinterpret_cast<uint32_t*>(sm);
    uint32_t* wmax = xs + 8 * 324;
    int* sidx = reinterpret_cast<int*>(wmax + 16);
    const int fg = cw * 4 + mc;
    const uint32_t ring = smem_u32(sm) + 16384 + cw * 24576, rbar = smem_u32(sm) + 12288 + cw * 32;
    auto issue = [&](int u, int st) {
        if (lane == 0 && u < 30) {
            mbar_expect_tx(rbar + st * 8, 8192);
            if (u < 20) {
                tma_load_stream(ring + st * 8192, &P.wg, fg * 64, u * 32, rbar + st * 8);
                tma_load_stream(ring + st * 8192 + 4096, &P.wu, fg * 64, u * 32, rbar + st * 8);
            } else {
                tma_load_stream(ring + st * 8192, &P.wd, (u - 20) * 64, fg * 64, rbar + st * 8);
            }
        }
    };
    if (lane == 0) {
        mbar_init(rbar, 1); mbar_init(rbar + 8, 1); mbar_init(rbar + 16, 1);
        asm volatile("fence.mbarrier_init.release.cluster;" ::: "memory");
    }
    if (tid == 0) flag_wait<100>(F_LN, 256u * (epoch + 1));
    named_sync(1, 256);
    PROF(1);
    if (fg < 27) {
#pragma unroll 1
        for (int u = 0; u < 3; u++) issue(u, u);
    }
    PROF(2);
    uint32_t key[8];
#pragma unroll
    for (int i = 0; i < 8; i++) {
        const int t = tid + 256 * i;
        uint32_t b = __float_as_uint(__ldcg(g_r + t) + 0.f) >> 16;
        b = (b & 0x8000u) ? (~b & 0xffffu) : (b | 0x8000u);
        key[i] = (b << 16) | (uint32_t)(0xffff - t);
    }
#pragma unroll 1
    for (int rnd = 0; rnd < 8; rnd++) {
        uint32_t mx = key[0];
#pragma unroll
        for (int i = 1; i < 8; i++) mx = max(mx, key[i]);
        mx = __reduce_max_sync(0xffffffffu, mx);
        if (lane == 0) wmax[(rnd & 1) * 8 + cw] = mx;
        named_sync(1, 256);
        mx = __reduce_max_sync(0xffffffffu, wmax[(rnd & 1) * 8 + (lane & 7)]);
#pragma unroll
        for (int i = 0; i < 8; i++) if (key[i] == mx) key[i] = 0;
        if (tid == 0) sidx[rnd] = 0xffff - (int)(mx & 0xffffu);
    }
    named_sync(1, 256);
    {
        const uint32_t* src = reinterpret_cast<const uint32_t*>(g_xn + (size_t)perm_row(sidx[cw]) * DM);
#pragma unroll 2
        for (int i = lane; i < 320; i += 32) xs[cw * 324 + i] = __ldcg(src + i);
    }
    named_sync(1, 256);
    PROF(3);
    if (fg < 27) {
        float g[8][4], v[8][4];
        uint32_t hp[8];
#pragma unroll
        for (int i = 0; i < 8; i++)
#pragma unroll
            for (int e = 0; e < 4; e++) { g[i][e] = 0.f; v[i][e] = 0.f; }
        int st = 0, ph = 0;
#pragma unroll 1
        for (int u = 0; u < 60; u++) {
            if (!(u & 1)) mbar_wait(rbar + st * 8, ph);
            uint4 a[8];
#pragma unroll
            for (int r = 0; r < 8; r++) {
                const int row = (u < 40) ? 32 * (r >> 2) + 16 * (u & 1) + 2 * q + (r & 1) + 4 * (r & 2) : 16 * q + 8 * (u & 1) + r;
                asm volatile("ld.shared.v4.b32 {%0, %1, %2, %3}, [%4];" : "=r"(a[r].x), "=r"(a[r].y), "=r"(a[r].z), "=r"(a[r].w)
                             : "r"(ring + st * 8192 + row * 128 + ((lr ^ row) & 7) * 16) : "memory");
            }
            uint32_t f0, f1, f2, f3;
            if (u < 40) { f0 = f2 = xs[lr * 324 + u * 8 + q]; f1 = f3 = xs[lr * 324 + u * 8 + 4 + q]; }
            else if (u & 1) { f0 = hp[4]; f1 = hp[5]; f2 = hp[6]; f3 = hp[7]; }
            else { f0 = hp[0]; f1 = hp[1]; f2 = hp[2]; f3 = hp[3]; }
            mma_rows(g, f0, f1, a[0], a[1], a[2], a[3]);
            mma_rows(v, f2, f3, a[4], a[5], a[6], a[7]);
            if (u & 1) {
                __syncwarp();
                issue((u >> 1) + 3, st);
                if (++st == 3) { st = 0; ph ^= 1; }
                if (u >= 39) {
                    if (u == 39) {
                        float hv[16];
#pragma unroll
                        for (int i = 0; i < 16; i++) {
                            const float gp = round_bf16(g[i & 7][i >> 3]);
                            hv[i] = round_bf16(__fdividef(gp, 1.0f + __expf(fminf(-gp, 80.f)))) * round_bf16(v[i & 7][i >> 3]);
                        }
#pragma unroll
                        for (int i = 0; i < 8; i++) hp[i] = pack_bf16(hv[2 * i], hv[2 * i + 1]);
                    } else {
                        float4* dst = reinterpret_cast<float4*>(g_ypart + (fg * 8 + lr) * DM + ((u - 40) >> 1) * 64 + 16 * q);
#pragma unroll
                        for (int i = 0; i < 4; i++) {
                            const int j = 4 * (i & 1), e = i >> 1;
                            dst[i] = make_float4(g[j][e] + v[j][e], g[j + 1][e] + v[j + 1][e], g[j + 2][e] + v[j + 2][e], g[j + 3][e] + v[j + 3][e]);
                        }
                    }
#pragma unroll
                    for (int i = 0; i < 8; i++) { g[i][0] = 0.f; g[i][1] = 0.f; v[i][0] = 0.f; v[i][1] = 0.f; }
                }
            }
        }
    }
    PROF(5);
    named_sync(1, 256);
    if (tid == 0) {
        flag_add(F_MODP);
        flag_wait<100>(F_MODP, 4u * (epoch + 1));
    }
    named_sync(1, 256);
    PROF(6);
#pragma unroll 1
    for (int i = tid; i < 2 * DM; i += 256) {
        const int c = 2 * mc + (i >= DM), col = i - (i >= DM) * DM, t = sidx[c];
        float y = 0.f;
#pragma unroll 9
        for (int k = 0; k < 27; k++) y += __ldcg(g_ypart + (k * 8 + c) * DM + col);
        const float rs = round_bf16(__fdividef(1.0f, 1.0f + __expf(fminf(-__ldcg(g_r + t), 80.f))));
        const float xn = __bfloat162float(reinterpret_cast<const __nv_bfloat16*>(xs + c * 324)[col]);
        g_res[(size_t)t * DM + col] = __float2bfloat16_rn(__bfloat162float(P.x[(size_t)t * DM + col]) + round_bf16(xn + round_bf16(round_bf16(y) * rs)));
    }
    named_sync(1, 256);
    if (tid == 0) flag_add(F_MOD);
    PROF(7);
}

__global__ void __cluster_dims__(2, 1, 1) __launch_bounds__(384, 1) fused_kernel(const __grid_constant__ Params P) {
    extern __shared__ __align__(1024) uint8_t smem_raw[];
    const uint32_t smem = (smem_u32(smem_raw) + 1023u) & ~1023u;
    uint8_t* smem_gen = smem_raw + (smem - smem_u32(smem_raw));
    const uint32_t bars = smem + NSLOT * SLOT;
    const int wgi = __reduce_or_sync(0xffffffffu, threadIdx.x >> 7);
    const int cl = blockIdx.x >> 1, rank = blockIdx.x & 1, ca = cl & 7, cb = cl >> 3;
    PROFG(30);
    PROF(0);
    LayerNorm ln;
    if (wgi != 0) {
        const uint4* xr = reinterpret_cast<const uint4*>(P.x + (size_t)((blockIdx.x & 127) * 16 + ((threadIdx.x - 128) >> 4)) * DM) + (threadIdx.x & 15);
        const uint4* wr = reinterpret_cast<const uint4*>(P.wr) + (threadIdx.x & 15);
#pragma unroll
        for (int i = 0; i < 5; i++) { ln.xv[i] = ldg_stream(xr + 16 * i); ln.wv[i] = __ldg(wr + 16 * i); }
        PROF(28);
    } else if (threadIdx.x == 0) {
#pragma unroll
        for (int i = 0; i < NSLOT; i++) { mbar_init(bars + BAR_FULL + i * 8, 1); mbar_init(bars + BAR_EMPTY + i * 8, 16); }
        mbar_arrive(bars + BAR_FULL + 16);
        asm volatile("mbarrier.arrive.shared::cta.b64 _, [%0], 16;" ::"r"(bars + BAR_EMPTY + 16) : "memory");
        asm volatile("fence.mbarrier_init.release.cluster;" ::: "memory");
        PROF(24);
    } else if (threadIdx.x == 32) {
#pragma unroll
        for (int i = 0; i < 18; i++) mbar_init(bars + BAR_SIG + i * 8, 4);
#pragma unroll
        for (int i = 0; i < 14; i++) mbar_init(bars + BAR_DEP + i * 8, 1);
    } else if (threadIdx.x >= 64 && cl < 64) {
        const int i = threadIdx.x - 64;
        if (i == 0) { prefetch_map(&P.ckv); prefetch_map(&P.wuk); }
        const char* a = reinterpret_cast<const char*>(P.ckv_ptr) + ((2 * ca + rank) * 128 + cb * 16) * (DC * 2) + i * 256;
        asm volatile("prefetch.global.L2 [%0];" ::"l"(a));
        asm volatile("prefetch.global.L2 [%0];" ::"l"(a + 128));
        asm volatile("prefetch.global.L2 [%0];" ::"l"(P.wuk_ptr + (size_t)(i * 8 + ca) * (NH * HD) + (cb + 8 * kv_round(0)) * 128 + rank * 64));
    }
    __syncthreads();
    PROF(29);
    cluster_arrive();
    if (wgi > 0) {
        asm volatile("setmaxnreg.inc.sync.aligned.u32 232;");
        if (cl >= 64) {
            cluster_wait();
            mod_ffn(P, smem_gen, blockIdx.x - 128);
        } else {
            consumer(P, smem, bars, ca, cb, rank, wgi - 1, ln);
        }
        cluster_arrive();
        PROFG(31);
        PROFDUMP();
    } else {
        asm volatile("setmaxnreg.dec.sync.aligned.u32 40;");
        const int w = __reduce_or_sync(0xffffffffu, threadIdx.x >> 5), lane = threadIdx.x & 31;
        if (threadIdx.x == 32 && cl < 64) {
            mbar_expect_tx(bars + BAR_FULL, SLOT);
            tma_load(smem, &P.ckv, 0, (2 * ca + rank) * 128, bars + BAR_FULL);
            tma_load(smem + 16384, &P.ckv, 64, (2 * ca + rank) * 128, bars + BAR_FULL);
        }
        if (threadIdx.x == 64) {
            prefetch_map(&P.wuv); prefetch_map(&P.xn); prefetch_map(&P.wq); prefetch_map(&P.kv); prefetch_map(&P.ctx); prefetch_map(&P.wo);
        }
        __syncwarp();
        cluster_wait();
        PROF(27);
        if (cl < 64) {
            if (w == 0) {
                producer(P, smem, bars, ca, cb, rank);
            } else if (w < 3 && lane == 0) {
                const int wg = w - 1;
#pragma unroll 1
                for (int e = 0; e < 9; e++) {
                    mbar_wait(bars + BAR_SIG + (wg * 9 + e) * 8, 0);
                    int f;
                    if (e == 0) f = F_LN;
                    else if (e < 5) f = F_KV + cb + 8 * kv_round(e - 1);
                    else { const int rd = e - 5; f = F_CTX + (8 * rd + cb) * 16 + item_p(ca, rd) * 2 + rank; }
                    flag_add(f);
                }
            } else if (lane == 0) {
                const uint32_t epoch = read_epoch();
#pragma unroll 1
                for (int i = 0; i < 14; i++) {
                    const int e = (i < 11) ? i : (i == 11) ? 13 : i - 1;
                    int f;
                    uint32_t n;
                    if (e == 0) { f = F_LN; n = 256; }
                    else if (e < 5) { f = F_KV + cb + 8 * (e - 1); n = 32; }
                    else if (e < 13) { f = F_CTX + (8 * ((e - 5) >> 1) + (cb & 6) + ((e - 5) & 1)) * 16 + ca * 2 + rank; n = 2; }
                    else { f = F_MOD; n = 4; }
                    flag_wait<100>(f, n * (epoch + 1));
                    fence_proxy_async();
                    mbar_arrive(bars + BAR_DEP + e * 8);
                }
            }
        }
        __syncwarp();
        cluster_arrive();
        cluster_wait();
        if (threadIdx.x == 0) atomicAdd(g_flags + F_EXIT * 8, 1u);
        PROFG(31);
        PROFDUMP();
    }
}

typedef CUresult (*EncodeFn)(CUtensorMap*, CUtensorMapDataType, cuuint32_t, void*, const cuuint64_t*, const cuuint64_t*, const cuuint32_t*,
                             const cuuint32_t*, CUtensorMapInterleave, CUtensorMapSwizzle, CUtensorMapL2promotion, CUtensorMapFloatOOBfill);

void make_map(EncodeFn fn, CUtensorMap* m, const void* ptr, uint64_t rows, uint64_t cols, uint32_t box_rows) {
    cuuint64_t dims[2] = {cols, rows};
    cuuint64_t strides[1] = {cols * 2};
    cuuint32_t box[2] = {64, box_rows};
    cuuint32_t es[2] = {1, 1};
    fn(m, CU_TENSOR_MAP_DATA_TYPE_BFLOAT16, 2, const_cast<void*>(ptr), dims, strides, box, es, CU_TENSOR_MAP_INTERLEAVE_NONE,
       CU_TENSOR_MAP_SWIZZLE_128B, CU_TENSOR_MAP_L2_PROMOTION_L2_128B, CU_TENSOR_MAP_FLOAT_OOB_FILL_NONE);
}

}

extern "C" void kernel_launch(void* const* d_in, const int* in_sizes, int n_in, void* d_out, int out_size) {
    (void)in_sizes; (void)n_in; (void)out_size;
    void* fnp = nullptr;
    cudaDriverEntryPointQueryResult qr;
    cudaGetDriverEntryPoint("cuTensorMapEncodeTiled", &fnp, cudaEnableDefault, &qr);
    EncodeFn fn = (EncodeFn)fnp;
    void *xn, *kv, *ctx;
    cudaGetSymbolAddress(&xn, g_xn);
    cudaGetSymbolAddress(&kv, g_kv);
    cudaGetSymbolAddress(&ctx, g_ctx);
    Params P;
    make_map(fn, &P.ckv, d_in[1], SEQ, DC, 128);
    make_map(fn, &P.wq, d_in[2], DM, NH * HD, 64);
    make_map(fn, &P.wuk, d_in[3], DC, NH * HD, 128);
    make_map(fn, &P.wuv, d_in[4], DC, NH * HD, 128);
    make_map(fn, &P.wo, d_in[5], NH * HD, DM, 32);
    make_map(fn, &P.xn, xn, SEQ, DM, 128);
    make_map(fn, &P.kv, kv, NH * 16 * 2 * 128, 128, 128);
    make_map(fn, &P.ctx, ctx, NH * SEQ, HD, 128);
    P.x = (const __nv_bfloat16*)d_in[0];
    P.wr = (const __nv_bfloat16*)d_in[7];
    make_map(fn, &P.wg, d_in[8], DM, FF, 32);
    make_map(fn, &P.wu, d_in[9], DM, FF, 32);
    make_map(fn, &P.wd, d_in[10], FF, DM, 64);
    P.ckv_ptr = (const __nv_bfloat16*)d_in[1];
    P.wuk_ptr = (const __nv_bfloat16*)d_in[3];
    P.out = (__nv_bfloat16*)d_out;
    cudaFuncSetAttribute(fused_kernel, cudaFuncAttributeMaxDynamicSharedMemorySize, SMEM_BYTES);
    fused_kernel<<<NCTA, 384, SMEM_BYTES>>>(P);
}
```

```cpp
#include <cuda_runtime.h>
#include <cuda_bf16.h>
#include <cuda.h>
#include <stdint.h>

namespace {

constexpr int SEQ = 2048, DM = 640, DC = 512, NH = 32, HD = 128, FF = 1728;
constexpr int NSLOT = 7, SLOT = 32768;
constexpr int NCTA = 132;
#define PINGPONG 1
#define SIGMA 1
#define KVORDER 0x1023
#define KVSPLIT 2
#define EF 1
#define QST 4
#define SPLITJ 8
constexpr uint32_t DESC_HI = (1024u >> 4) | (1u << 30);
constexpr int SMEM_BYTES = NSLOT * SLOT + 3072;

constexpr int BAR_FULL = 0, BAR_EMPTY = 64, BAR_SIG = 128  , BAR_DEP = 320  , MISC_OFF = 512;

constexpr int F_EXIT = 0, F_LN = 1, F_MOD = 2, F_MODP = 3, F_KV = 4  , F_PART = 36  , F_CTX = 292  , F_NUM = 804;

__device__ __align__(1024) __nv_bfloat16 g_xn[SEQ * DM];
__device__ __align__(1024) __nv_bfloat16 g_kv[NH * 16 * 2 * 128 * 128];
__device__ __align__(1024) __nv_bfloat16 g_ctx[NH * SEQ * HD];
__device__ __align__(1024) __nv_bfloat16 g_res[SEQ * DM];
__device__ __align__(1024) uint4 g_part[32 * 4 * 4 * 5 * 256];
__device__ __align__(16) float g_r[SEQ];
__device__ __align__(16) float g_ypart[27 * 8 * DM];
__device__ uint32_t g_flags[F_NUM * 8];

struct TrueT { static constexpr bool value = true; };
struct FalseT { static constexpr bool value = false; };

struct Params {
    CUtensorMap ckv, wuk, wuv, xn, wq, kv, ctx, wo, wg, wu, wd;
    const __nv_bfloat16 *x, *wr, *ckv_ptr, *wuk_ptr;
    __nv_bfloat16* out;
};

__device__ __forceinline__ uint32_t smem_u32(const void* p) { return (uint32_t)__cvta_generic_to_shared(p); }
__device__ __forceinline__ void mbar_init(uint32_t bar, uint32_t cnt) {
    asm volatile("mbarrier.init.shared::cta.b64 [%0], %1;" ::"r"(bar), "r"(cnt) : "memory");
}
__device__ __forceinline__ void mbar_expect_tx(uint32_t bar, uint32_t bytes) {
    asm volatile("mbarrier.arrive.expect_tx.shared::cta.b64 _, [%0], %1;" ::"r"(bar), "r"(bytes) : "memory");
}
__device__ __forceinline__ void mbar_arrive(uint32_t bar) {
    asm volatile("mbarrier.arrive.shared::cta.b64 _, [%0];" ::"r"(bar) : "memory");
}
__device__ __forceinline__ uint32_t mapa(uint32_t addr, uint32_t cta) {
    uint32_t r;
    asm("mapa.shared::cluster.u32 %0, %1, %2;" : "=r"(r) : "r"(addr), "r"(cta));
    return r;
}
__device__ __forceinline__ void mbar_wait(uint32_t bar, uint32_t parity) {
    asm volatile(
        "{\n.reg .pred p;\n.reg .b32 c;\n"
        "mov.b32 c, 0;\n"
        "WLOOP:\n"
        "mbarrier.try_wait.parity.shared::cta.b64 p, [%0], %1;\n"
        "@p bra.uni WDONE;\n"
        "add.u32 c, c, 1;\n"
        "setp.lt.u32 p, c, 0x400000;\n"
        "@p bra.uni WLOOP;\n"
        "trap;\n"
        "WDONE:\n}\n" ::"r"(bar), "r"(parity) : "memory");
}
__device__ __forceinline__ void mbar_wait_sleep(uint32_t bar, uint32_t parity) {
    asm volatile(
        "{\n.reg .pred p;\n.reg .b32 c;\n"
        "mov.b32 c, 0;\n"
        "WLOOP:\n"
        "mbarrier.try_wait.parity.shared::cta.b64 p, [%0], %1, 20000;\n"
        "@p bra.uni WDONE;\n"
        "add.u32 c, c, 1;\n"
        "setp.lt.u32 p, c, 0x40000;\n"
        "@p bra.uni WLOOP;\n"
        "trap;\n"
        "WDONE:\n}\n" ::"r"(bar), "r"(parity) : "memory");
}
__device__ __forceinline__ void tma_load(uint32_t dst, const CUtensorMap* m, int c0, int c1, uint32_t bar) {
    asm volatile("cp.async.bulk.tensor.2d.shared::cluster.global.mbarrier::complete_tx::bytes [%0], [%1, {%3, %4}], [%2];"
                 ::"r"(dst), "l"(m), "r"(bar), "r"(c0), "r"(c1) : "memory");
}
#define ELECT "{\n.reg .pred e;\nelect.sync _|e, 0xffffffff;\n@e "
__device__ __forceinline__ void w_expect_tx(uint32_t bar, uint32_t bytes) {
    asm volatile(ELECT "mbarrier.arrive.expect_tx.shared::cta.b64 _, [%0], %1;\n}\n" ::"r"(bar), "r"(bytes) : "memory");
}
__device__ __forceinline__ void w_tma_load(uint32_t dst, const CUtensorMap* m, int c0, int c1, uint32_t bar) {
    asm volatile(ELECT "cp.async.bulk.tensor.2d.shared::cluster.global.mbarrier::complete_tx::bytes [%0], [%1, {%3, %4}], [%2];\n}\n"
                 ::"r"(dst), "l"(m), "r"(bar), "r"(c0), "r"(c1) : "memory");
}
__device__ __forceinline__ void w_tma_load_mc(uint32_t dst, const CUtensorMap* m, int c0, int c1, uint32_t bar) {
    asm volatile(ELECT "cp.async.bulk.tensor.2d.shared::cluster.global.mbarrier::complete_tx::bytes.multicast::cluster [%0], [%1, {%3, %4}], [%2], %5;\n}\n"
                 ::"r"(dst), "l"(m), "r"(bar), "r"(c0), "r"(c1), "h"((uint16_t)3) : "memory");
}
__device__ __forceinline__ void w_tma_prefetch(const CUtensorMap* m, int c0, int c1) {
    asm volatile(ELECT "cp.async.bulk.prefetch.tensor.2d.L2.global [%0, {%1, %2}];\n}\n" ::"l"(m), "r"(c0), "r"(c1) : "memory");
}
__device__ __forceinline__ uint64_t policy_evict_first() {
    uint64_t p;
    asm("createpolicy.fractional.L2::evict_first.b64 %0, 1.0;" : "=l"(p));
    return p;
}
__device__ __forceinline__ void tma_load_stream(uint32_t dst, const CUtensorMap* m, int c0, int c1, uint32_t bar) {
    asm volatile("cp.async.bulk.tensor.2d.shared::cluster.global.mbarrier::complete_tx::bytes.L2::cache_hint [%0], [%1, {%3, %4}], [%2], %5;"
                 ::"r"(dst), "l"(m), "r"(bar), "r"(c0), "r"(c1), "l"(policy_evict_first()) : "memory");
}
__device__ __forceinline__ uint4 ldg_stream(const void* p) {
    uint4 v;
    asm volatile("ld.global.nc.L2::cache_hint.v4.b32 {%0, %1, %2, %3}, [%4], %5;" : "=r"(v.x), "=r"(v.y), "=r"(v.z), "=r"(v.w) : "l"(p), "l"(policy_evict_first()));
    return v;
}
__device__ __forceinline__ void prefetch_map(const CUtensorMap* m) {
    asm volatile("prefetch.tensormap [%0];" ::"l"(m) : "memory");
}
__device__ __forceinline__ void cluster_arrive() { asm volatile("barrier.cluster.arrive.relaxed.aligned;" ::: "memory"); }
__device__ __forceinline__ void cluster_wait() { asm volatile("barrier.cluster.wait.aligned;" ::: "memory"); }
__device__ __forceinline__ void named_sync(int id, int n) { asm volatile("bar.sync %0, %1;" ::"r"(id), "r"(n) : "memory"); }
__device__ __forceinline__ void named_arrive(int id, int n) { asm volatile("bar.arrive %0, %1;" ::"r"(id), "r"(n) : "memory"); }

__device__ __forceinline__ void flag_add(int f) {
    asm volatile("fence.acq_rel.gpu;\nred.relaxed.gpu.global.add.u32 [%0], 1;" ::"l"(g_flags + f * 8) : "memory");
}
template <int SLEEP>
__device__ __forceinline__ void flag_wait(int f, uint32_t target) {
    asm volatile(
        "{\n.reg .pred p;\n.reg .b32 c, v;\n"
        "mov.b32 c, 0;\n"
        "FLOOP:\n"
        "ld.acquire.gpu.global.u32 v, [%0];\n"
        "sub.u32 v, v, %1;\n"
        "setp.ge.s32 p, v, 0;\n"
        "@p bra FDONE;\n"
        "nanosleep.u32 %2;\n"
        "add.u32 c, c, 1;\n"
        "setp.lt.u32 p, c, 0x400000;\n"
        "@p bra FLOOP;\n"
        "trap;\n"
        "FDONE:\n}\n" ::"l"(g_flags + f * 8), "r"(target), "n"(SLEEP) : "memory");
}
__device__ __forceinline__ uint32_t read_epoch() {
    uint32_t e;
    asm volatile("ld.relaxed.gpu.global.u32 %0, [%1];" : "=r"(e) : "l"(g_flags + F_EXIT * 8) : "memory");
    return e / NCTA;
}
__device__ __forceinline__ void fence_proxy_async() { asm volatile("fence.proxy.async;" ::: "memory"); }

__device__ __forceinline__ void wgmma_fence() { asm volatile("wgmma.fence.sync.aligned;" ::: "memory"); }
__device__ __forceinline__ void wgmma_commit() { asm volatile("wgmma.commit_group.sync.aligned;" ::: "memory"); }
template <int N>
__device__ __forceinline__ void wgmma_wait() { asm volatile("wgmma.wait_group.sync.aligned %0;" ::"n"(N) : "memory"); }
template <int N>
__device__ __forceinline__ void fence_regs(float (&d)[N]) {
#pragma unroll
    for (int i = 0; i < N; i++) asm volatile("" : "+f"(d[i])::"memory");
}
template <int N>
__device__ __forceinline__ void fence_regs(uint32_t (&d)[N]) {
#pragma unroll
    for (int i = 0; i < N; i++) asm volatile("" : "+r"(d[i])::"memory");
}

template <int TA, int TB>
__device__ __forceinline__ void wgmma_ss_n128(float (&d)[64], uint32_t alo, uint32_t blo, int scale_d) {
    asm volatile("{\n.reg .pred p;\n.reg .b64 da, db;\nsetp.ne.b32 p, %66, 0;\n"
        "mov.b64 da, {%64, %69};\nmov.b64 db, {%65, %69};\n"
        "wgmma.mma_async.sync.aligned.m64n128k16.f32.bf16.bf16 "
        "{%0, %1, %2, %3, %4, %5, %6, %7, %8, %9, %10, %11, %12, %13, %14, %15, %16, %17, %18, %19, %20, %21, %22, %23, %24, %25, %26, %27, %28, %29, %30, %31, %32, %33, %34, %35, %36, %37, %38, %39, %40, %41, %42, %43, %44, %45, %46, %47, %48, %49, %50, %51, %52, %53, %54, %55, %56, %57, %58, %59, %60, %61, %62, %63}, da, db, p, 1, 1, %67, %68;\n}\n"
        :
          "+f"(d[0]), "+f"(d[1]), "+f"(d[2]), "+f"(d[3]), "+f"(d[4]), "+f"(d[5]), "+f"(d[6]), "+f"(d[7]),
          "+f"(d[8]), "+f"(d[9]), "+f"(d[10]), "+f"(d[11]), "+f"(d[12]), "+f"(d[13]), "+f"(d[14]), "+f"(d[15]),
          "+f"(d[16]), "+f"(d[17]), "+f"(d[18]), "+f"(d[19]), "+f"(d[20]), "+f"(d[21]), "+f"(d[22]), "+f"(d[23]),
          "+f"(d[24]), "+f"(d[25]), "+f"(d[26]), "+f"(d[27]), "+f"(d[28]), "+f"(d[29]), "+f"(d[30]), "+f"(d[31]),
          "+f"(d[32]), "+f"(d[33]), "+f"(d[34]), "+f"(d[35]), "+f"(d[36]), "+f"(d[37]), "+f"(d[38]), "+f"(d[39]),
          "+f"(d[40]), "+f"(d[41]), "+f"(d[42]), "+f"(d[43]), "+f"(d[44]), "+f"(d[45]), "+f"(d[46]), "+f"(d[47]),
          "+f"(d[48]), "+f"(d[49]), "+f"(d[50]), "+f"(d[51]), "+f"(d[52]), "+f"(d[53]), "+f"(d[54]), "+f"(d[55]),
          "+f"(d[56]), "+f"(d[57]), "+f"(d[58]), "+f"(d[59]), "+f"(d[60]), "+f"(d[61]), "+f"(d[62]), "+f"(d[63])
        : "r"(alo), "r"(blo), "r"(scale_d), "n"(TA), "n"(TB), "r"(DESC_HI));
}
template <int TA, int TB>
__device__ __forceinline__ void wgmma_ss_n192(float (&d)[96], uint32_t alo, uint32_t blo, int scale_d) {
    asm volatile("{\n.reg .pred p;\n.reg .b64 da, db;\nsetp.ne.b32 p, %98, 0;\n"
        "mov.b64 da, {%96, %101};\nmov.b64 db, {%97, %101};\n"
        "wgmma.mma_async.sync.aligned.m64n192k16.f32.bf16.bf16 "
        "{%0, %1, %2, %3, %4, %5, %6, %7, %8, %9, %10, %11, %12, %13, %14, %15, %16, %17, %18, %19, %20, %21, %22, %23, %24, %25, %26, %27, %28, %29, %30, %31, %32, %33, %34, %35, %36, %37, %38, %39, %40, %41, %42, %43, %44, %45, %46, %47, %48, %49, %50, %51, %52, %53, %54, %55, %56, %57, %58, %59, %60, %61, %62, %63, %64, %65, %66, %67, %68, %69, %70, %71, %72, %73, %74, %75, %76, %77, %78, %79, %80, %81, %82, %83, %84, %85, %86, %87, %88, %89, %90, %91, %92, %93, %94, %95}, da, db, p, 1, 1, %99, %100;\n}\n"
        :
          "+f"(d[0]), "+f"(d[1]), "+f"(d[2]), "+f"(d[3]), "+f"(d[4]), "+f"(d[5]), "+f"(d[6]), "+f"(d[7]),
          "+f"(d[8]), "+f"(d[9]), "+f"(d[10]), "+f"(d[11]), "+f"(d[12]), "+f"(d[13]), "+f"(d[14]), "+f"(d[15]),
          "+f"(d[16]), "+f"(d[17]), "+f"(d[18]), "+f"(d[19]), "+f"(d[20]), "+f"(d[21]), "+f"(d[22]), "+f"(d[23]),
          "+f"(d[24]), "+f"(d[25]), "+f"(d[26]), "+f"(d[27]), "+f"(d[28]), "+f"(d[29]), "+f"(d[30]), "+f"(d[31]),
          "+f"(d[32]), "+f"(d[33]), "+f"(d[34]), "+f"(d[35]), "+f"(d[36]), "+f"(d[37]), "+f"(d[38]), "+f"(d[39]),
          "+f"(d[40]), "+f"(d[41]), "+f"(d[42]), "+f"(d[43]), "+f"(d[44]), "+f"(d[45]), "+f"(d[46]), "+f"(d[47]),
          "+f"(d[48]), "+f"(d[49]), "+f"(d[50]), "+f"(d[51]), "+f"(d[52]), "+f"(d[53]), "+f"(d[54]), "+f"(d[55]),
          "+f"(d[56]), "+f"(d[57]), "+f"(d[58]), "+f"(d[59]), "+f"(d[60]), "+f"(d[61]), "+f"(d[62]), "+f"(d[63]),
          "+f"(d[64]), "+f"(d[65]), "+f"(d[66]), "+f"(d[67]), "+f"(d[68]), "+f"(d[69]), "+f"(d[70]), "+f"(d[71]),
          "+f"(d[72]), "+f"(d[73]), "+f"(d[74]), "+f"(d[75]), "+f"(d[76]), "+f"(d[77]), "+f"(d[78]), "+f"(d[79]),
          "+f"(d[80]), "+f"(d[81]), "+f"(d[82]), "+f"(d[83]), "+f"(d[84]), "+f"(d[85]), "+f"(d[86]), "+f"(d[87]),
          "+f"(d[88]), "+f"(d[89]), "+f"(d[90]), "+f"(d[91]), "+f"(d[92]), "+f"(d[93]), "+f"(d[94]), "+f"(d[95])
        : "r"(alo), "r"(blo), "r"(scale_d), "n"(TA), "n"(TB), "r"(DESC_HI));
}
template <int TB>
__device__ __forceinline__ void wgmma_rs_n128(float (&d)[64], uint32_t a0, uint32_t a1, uint32_t a2, uint32_t a3, uint32_t blo, int scale_d) {
    asm volatile("{\n.reg .pred p;\n.reg .b64 db;\nsetp.ne.b32 p, %69, 0;\n"
        "mov.b64 db, {%68, %71};\n"
        "wgmma.mma_async.sync.aligned.m64n128k16.f32.bf16.bf16 "
        "{%0, %1, %2, %3, %4, %5, %6, %7, %8, %9, %10, %11, %12, %13, %14, %15, %16, %17, %18, %19, %20, %21, %22, %23, %24, %25, %26, %27, %28, %29, %30, %31, %32, %33, %34, %35, %36, %37, %38, %39, %40, %41, %42, %43, %44, %45, %46, %47, %48, %49, %50, %51, %52, %53, %54, %55, %56, %57, %58, %59, %60, %61, %62, %63}, {%64, %65, %66, %67}, db, p, 1, 1, %70;\n}\n"
        :
          "+f"(d[0]), "+f"(d[1]), "+f"(d[2]), "+f"(d[3]), "+f"(d[4]), "+f"(d[5]), "+f"(d[6]), "+f"(d[7]),
          "+f"(d[8]), "+f"(d[9]), "+f"(d[10]), "+f"(d[11]), "+f"(d[12]), "+f"(d[13]), "+f"(d[14]), "+f"(d[15]),
          "+f"(d[16]), "+f"(d[17]), "+f"(d[18]), "+f"(d[19]), "+f"(d[20]), "+f"(d[21]), "+f"(d[22]), "+f"(d[23]),
          "+f"(d[24]), "+f"(d[25]), "+f"(d[26]), "+f"(d[27]), "+f"(d[28]), "+f"(d[29]), "+f"(d[30]), "+f"(d[31]),
          "+f"(d[32]), "+f"(d[33]), "+f"(d[34]), "+f"(d[35]), "+f"(d[36]), "+f"(d[37]), "+f"(d[38]), "+f"(d[39]),
          "+f"(d[40]), "+f"(d[41]), "+f"(d[42]), "+f"(d[43]), "+f"(d[44]), "+f"(d[45]), "+f"(d[46]), "+f"(d[47]),
          "+f"(d[48]), "+f"(d[49]), "+f"(d[50]), "+f"(d[51]), "+f"(d[52]), "+f"(d[53]), "+f"(d[54]), "+f"(d[55]),
          "+f"(d[56]), "+f"(d[57]), "+f"(d[58]), "+f"(d[59]), "+f"(d[60]), "+f"(d[61]), "+f"(d[62]), "+f"(d[63])
        : "r"(a0), "r"(a1), "r"(a2), "r"(a3), "r"(blo), "r"(scale_d), "n"(TB), "r"(DESC_HI));
}
template <int TB>
__device__ __forceinline__ void wgmma_rs_n128_z(float (&d)[64], uint32_t a0, uint32_t a1, uint32_t a2, uint32_t a3, uint32_t blo) {
    asm volatile("{\n.reg .pred p;\n.reg .b64 db;\nsetp.ne.b32 p, %69, 0;\n"
        "mov.b64 db, {%68, %71};\n"
        "wgmma.mma_async.sync.aligned.m64n128k16.f32.bf16.bf16 "
        "{%0, %1, %2, %3, %4, %5, %6, %7, %8, %9, %10, %11, %12, %13, %14, %15, %16, %17, %18, %19, %20, %21, %22, %23, %24, %25, %26, %27, %28, %29, %30, %31, %32, %33, %34, %35, %36, %37, %38, %39, %40, %41, %42, %43, %44, %45, %46, %47, %48, %49, %50, %51, %52, %53, %54, %55, %56, %57, %58, %59, %60, %61, %62, %63}, {%64, %65, %66, %67}, db, p, 1, 1, %70;\n}\n"
        :
          "=f"(d[0]), "=f"(d[1]), "=f"(d[2]), "=f"(d[3]), "=f"(d[4]), "=f"(d[5]), "=f"(d[6]), "=f"(d[7]),
          "=f"(d[8]), "=f"(d[9]), "=f"(d[10]), "=f"(d[11]), "=f"(d[12]), "=f"(d[13]), "=f"(d[14]), "=f"(d[15]),
          "=f"(d[16]), "=f"(d[17]), "=f"(d[18]), "=f"(d[19]), "=f"(d[20]), "=f"(d[21]), "=f"(d[22]), "=f"(d[23]),
          "=f"(d[24]), "=f"(d[25]), "=f"(d[26]), "=f"(d[27]), "=f"(d[28]), "=f"(d[29]), "=f"(d[30]), "=f"(d[31]),
          "=f"(d[32]), "=f"(d[33]), "=f"(d[34]), "=f"(d[35]), "=f"(d[36]), "=f"(d[37]), "=f"(d[38]), "=f"(d[39]),
          "=f"(d[40]), "=f"(d[41]), "=f"(d[42]), "=f"(d[43]), "=f"(d[44]), "=f"(d[45]), "=f"(d[46]), "=f"(d[47]),
          "=f"(d[48]), "=f"(d[49]), "=f"(d[50]), "=f"(d[51]), "=f"(d[52]), "=f"(d[53]), "=f"(d[54]), "=f"(d[55]),
          "=f"(d[56]), "=f"(d[57]), "=f"(d[58]), "=f"(d[59]), "=f"(d[60]), "=f"(d[61]), "=f"(d[62]), "=f"(d[63])
        : "r"(a0), "r"(a1), "r"(a2), "r"(a3), "r"(blo), "n"(0), "n"(TB), "r"(DESC_HI));
}
template <int TA, int TB>
__device__ __forceinline__ void wgmma_ss_n128_z(float (&d)[64], uint32_t alo, uint32_t blo) {
    asm volatile("{\n.reg .pred p;\n.reg .b64 da, db;\nsetp.ne.b32 p, %66, 0;\n"
        "mov.b64 da, {%64, %69};\nmov.b64 db, {%65, %69};\n"
        "wgmma.mma_async.sync.aligned.m64n128k16.f32.bf16.bf16 "
        "{%0, %1, %2, %3, %4, %5, %6, %7, %8, %9, %10, %11, %12, %13, %14, %15, %16, %17, %18, %19, %20, %21, %22, %23, %24, %25, %26, %27, %28, %29, %30, %31, %32, %33, %34, %35, %36, %37, %38, %39, %40, %41, %42, %43, %44, %45, %46, %47, %48, %49, %50, %51, %52, %53, %54, %55, %56, %57, %58, %59, %60, %61, %62, %63}, da, db, p, 1, 1, %67, %68;\n}\n"
        :
          "=f"(d[0]), "=f"(d[1]), "=f"(d[2]), "=f"(d[3]), "=f"(d[4]), "=f"(d[5]), "=f"(d[6]), "=f"(d[7]),
          "=f"(d[8]), "=f"(d[9]), "=f"(d[10]), "=f"(d[11]), "=f"(d[12]), "=f"(d[13]), "=f"(d[14]), "=f"(d[15]),
          "=f"(d[16]), "=f"(d[17]), "=f"(d[18]), "=f"(d[19]), "=f"(d[20]), "=f"(d[21]), "=f"(d[22]), "=f"(d[23]),
          "=f"(d[24]), "=f"(d[25]), "=f"(d[26]), "=f"(d[27]), "=f"(d[28]), "=f"(d[29]), "=f"(d[30]), "=f"(d[31]),
          "=f"(d[32]), "=f"(d[33]), "=f"(d[34]), "=f"(d[35]), "=f"(d[36]), "=f"(d[37]), "=f"(d[38]), "=f"(d[39]),
          "=f"(d[40]), "=f"(d[41]), "=f"(d[42]), "=f"(d[43]), "=f"(d[44]), "=f"(d[45]), "=f"(d[46]), "=f"(d[47]),
          "=f"(d[48]), "=f"(d[49]), "=f"(d[50]), "=f"(d[51]), "=f"(d[52]), "=f"(d[53]), "=f"(d[54]), "=f"(d[55]),
          "=f"(d[56]), "=f"(d[57]), "=f"(d[58]), "=f"(d[59]), "=f"(d[60]), "=f"(d[61]), "=f"(d[62]), "=f"(d[63])
        : "r"(alo), "r"(blo), "n"(0), "n"(TA), "n"(TB), "r"(DESC_HI));
}

__device__ __forceinline__ uint32_t pack_bf16(float lo, float hi) {
    uint32_t r;
    asm("cvt.rn.bf16x2.f32 %0, %1, %2;" : "=r"(r) : "f"(hi), "f"(lo));
    return r;
}
__device__ __forceinline__ uint32_t add_bf16x2(uint32_t a, uint32_t b) {
    uint32_t r;
    asm("add.rn.bf16x2 %0, %1, %2;" : "=r"(r) : "r"(a), "r"(b));
    return r;
}
__device__ __forceinline__ float bf_lo(uint32_t v) { return __uint_as_float(v << 16); }
__device__ __forceinline__ float bf_hi(uint32_t v) { return __uint_as_float(v & 0xffff0000u); }
__device__ __forceinline__ float round_bf16(float v) { return __bfloat162float(__float2bfloat16_rn(v)); }
__device__ __forceinline__ float ex2(float x) {
    float y;
    asm("ex2.approx.ftz.f32 %0, %1;" : "=f"(y) : "f"(x));
    return y;
}
__device__ __forceinline__ float rcp(float x) {
    float y;
    asm("rcp.approx.ftz.f32 %0, %1;" : "=f"(y) : "f"(x));
    return y;
}
__device__ __forceinline__ void stg128(void* p, uint32_t a, uint32_t b, uint32_t c, uint32_t d) {
    asm volatile("st.global.v4.b32 [%0], {%1, %2, %3, %4};" ::"l"(p), "r"(a), "r"(b), "r"(c), "r"(d) : "memory");
}
__device__ __forceinline__ int perm_row(int t) { return (t & ~255) | (((0x78 >> (((t >> 6) & 3) * 2)) & 3) << 6) | (t & 63); }
__device__ __forceinline__ int unperm_row(int t) { return (t & ~255) | (((0x9C >> (((t >> 6) & 3) * 2)) & 3) << 6) | (t & 63); }

#define PROF(i)
#define PROFG(i)
#define PROFDUMP()
#define TR(i)
#define BP(r, i)
#define LP(i)

template <int I>
__device__ __forceinline__ void store_chunk(const float (&a)[64], __nv_bfloat16* row0, __nv_bfloat16* row1, float s0, float s1) {
    stg128(row0 + 32 * I, pack_bf16(a[16 * I + 0] * s0, a[16 * I + 1] * s0), pack_bf16(a[16 * I + 4] * s0, a[16 * I + 5] * s0),
           pack_bf16(a[16 * I + 8] * s0, a[16 * I + 9] * s0), pack_bf16(a[16 * I + 12] * s0, a[16 * I + 13] * s0));
    stg128(row1 + 32 * I, pack_bf16(a[16 * I + 2] * s1, a[16 * I + 3] * s1), pack_bf16(a[16 * I + 6] * s1, a[16 * I + 7] * s1),
           pack_bf16(a[16 * I + 10] * s1, a[16 * I + 11] * s1), pack_bf16(a[16 * I + 14] * s1, a[16 * I + 15] * s1));
}
template <int I>
struct IntT { static constexpr int value = I; };
template <class F>
__device__ __forceinline__ void for4(F f) { f(IntT<0>{}); f(IntT<1>{}); f(IntT<2>{}); f(IntT<3>{}); }

struct Prod {
    uint32_t smem, bars;
    uint32_t bo, par;
    uint32_t dst, fb;
    __device__ __forceinline__ void acquire(uint32_t o, uint32_t parity, uint32_t bytes) {
        mbar_wait(bars + BAR_EMPTY + o, parity);
        fb = bars + BAR_FULL + o;
        dst = smem + o * (SLOT / 8);
        w_expect_tx(fb, bytes);
    }
    __device__ __forceinline__ void next(uint32_t bytes) {
        acquire(bo, par, bytes);
        const bool wrap = bo == (NSLOT - 1) * 8;
        bo = wrap ? 0u : bo + 8;
        par ^= wrap ? 1u : 0u;
    }
};

__device__ __forceinline__ int item_p(int ca, int rd) {
    const int v = (rd & 1) ? (ca + 4) & 7 : ca;
    return (rd & 2) ? 7 - v : v;
}
__device__ __forceinline__ int kv_round(int i) { return (KVORDER >> (4 * i)) & 3; }
__device__ __forceinline__ int slot_a(int i) { return (0x5310 >> (4 * i)) & 15; }
__device__ __forceinline__ int slot_w(int m) { return (0x264 >> (4 * m)) & 15; }

__device__ __forceinline__ void producer(const Params& P, uint32_t smem, uint32_t bars, int ca, int cb, int rank) {
    Prod pr{smem, bars, 0u, 0u, 0u, 0u};
    {
        int m = 0;
        uint32_t lap = 1;
#pragma unroll 1
        for (int u = 0; u < 32; u++) {
            if (u >= 3) {
                const int v = (u == 3) ? 4 + ca : u + 8;
                if (v < 32 && (u == 3 || (v & 7) == ca)) w_tma_prefetch((v & 4) ? &P.wuv : &P.wuk, (cb + 8 * kv_round(v >> 3)) * 128 + rank * 64, (v & 3) * 128);
                if (u == 24) {
                    w_tma_prefetch(&P.wq, cb * 128 + rank * 64, ca * 64);
                    if (ca < 2) w_tma_prefetch(&P.wq, cb * 128 + rank * 64, (ca + 8) * 64);
                }
            }
            pr.acquire(slot_w(m) * 8, lap ^ (m >> 1), SLOT);
            lap ^= m >> 1;
            m = (m == 2) ? 0 : m + 1;
            TR(1 + u);
            w_tma_load_mc(pr.dst + rank * 16384, (u & 4) ? &P.wuv : &P.wuk, (cb + 8 * kv_round(u >> 3)) * 128 + rank * 64, (u & 3) * 128, pr.fb);
            if (u < 3) {
                pr.acquire(slot_a(u + 1) * 8, 1, SLOT);
                w_tma_load(pr.dst, &P.ckv, u * 128 + 128, (2 * ca + rank) * 128, pr.fb);
                w_tma_load(pr.dst + 16384, &P.ckv, u * 128 + 192, (2 * ca + rank) * 128, pr.fb);
            }
        }
    }
    PROF(1);
    mbar_wait(bars + BAR_DEP, 0);
#pragma unroll 1
    for (int rd = 0; rd < 4; rd++) {
        const int h = 8 * rd + cb, p = item_p(ca, rd);
#pragma unroll 1
        for (int ks = 0; ks < 10; ks++) {
            pr.next(SLOT);
            w_tma_load_mc(pr.dst + 16384 + rank * 8192, &P.wq, h * 128 + rank * 64, ks * 64, pr.fb);
            w_tma_load(pr.dst, &P.xn, ks * 64, 256 * p + 128 * rank, pr.fb);
        }
        PROF(8 + rd * 4);
        mbar_wait(bars + BAR_DEP + (1 + rd) * 8, 0);
        const int last = 4 * p + 3, top = h * 32 + last;
#pragma unroll 1
        for (int i = 0; i <= last; i++) {
            const int t = (i == 0) ? top - 1 : (i == last) ? h * 32 + 1 : (i & 1) ? top - 2 - i : top + 2 - i;
            pr.next(SLOT);
            w_tma_load_mc(pr.dst + rank * 16384, &P.kv, rank * 64, t * 128, pr.fb);
            if (i == 2) {
                if (rd < 3) {
                    w_tma_prefetch(&P.wq, (h + 8) * 128 + rank * 64, ca * 64);
                    if (ca < 2) w_tma_prefetch(&P.wq, (h + 8) * 128 + rank * 64, (ca + 8) * 64);
                } else {
#pragma unroll 1
                    for (int j = 0; j < 10; j++) {
                        const int tt = ca + (j >= 5 ? 8 : 0);
                        w_tma_prefetch(&P.wo, 320 * (cb & 1) + 64 * (j >= 5 ? j - 5 : j), (8 * (tt >> 2) + (cb & 6) + ((tt >> 1) & 1)) * 128 + (tt & 1) * 64 + rank * 32);
                    }
                }
            }
        }
        PROF(9 + rd * 4);
    }
    {
        const int n0 = 320 * (cb & 1), kg = cb >> 1;
#pragma unroll 1
        for (int t = 0; t < 16; t++) {
            const int h = 8 * (t >> 2) + 2 * kg + ((t >> 1) & 1), ks = t & 1;
            const int krow = h * 128 + ks * 64 + rank * 32;
            pr.next(SLOT);
            w_tma_load_mc(pr.dst + 16384 + rank * 8192, &P.wo, n0, krow, pr.fb);
            w_tma_load_mc(pr.dst + 16384 + rank * 8192 + 4096, &P.wo, n0 + 64, krow, pr.fb);
            mbar_wait(bars + BAR_DEP + (5 + (t >> 1)) * 8, 0);
            w_tma_load(pr.dst, &P.ctx, ks * 64, h * SEQ + 256 * ca + 128 * rank, pr.fb);
            pr.next(24576);
#pragma unroll
            for (int c = 0; c < 3; c++) w_tma_load_mc(pr.dst + rank * 12288 + c * 4096, &P.wo, n0 + 128 + 64 * c, krow, pr.fb);
        }
    }
}

struct Slot {
    uint32_t bo, dl, par;
};
struct Cons {
    uint32_t bars, rel;
    uint32_t dl0;
    uint32_t lane;
    Slot cur;
    __device__ __forceinline__ Slot slot(int s, uint32_t par) const { return Slot{(uint32_t)s * 8, dl0 + (uint32_t)s * (SLOT >> 4), par}; }
    __device__ __forceinline__ void wait(const Slot& s) const { mbar_wait(bars + BAR_FULL + s.bo, s.par); }
    __device__ __forceinline__ void release(uint32_t bo) const {
        asm volatile("{\n.reg .pred p;\nsetp.lt.u32 p, %1, 2;\n@p mbarrier.arrive.shared::cluster.b64 _, [%0];\n}\n" ::"r"(rel + bo), "r"(lane) : "memory");
    }
    __device__ __forceinline__ Slot next() {
        const Slot s = cur;
        const bool wrap = s.bo == (NSLOT - 1) * 8;
        cur.bo = wrap ? 0u : s.bo + 8;
        cur.dl = wrap ? dl0 : s.dl + (SLOT >> 4);
        cur.par = s.par ^ (wrap ? 1u : 0u);
        return s;
    }
};
__host__ __device__ constexpr uint32_t lbo(uint32_t bytes) { return (bytes >> 4) << 16; }

__device__ __forceinline__ float div640(float x) {
    const float q = x * (1.0f / DM);
    return fmaf(fmaf(-q, (float)DM, x), 1.0f / DM, q);
}
__device__ __forceinline__ float sqrt_approx(float x) {
    float y;
    asm("sqrt.approx.ftz.f32 %0, %1;" : "=f"(y) : "f"(x));
    return y;
}
struct LayerNorm {
    uint4 xv[5], wv[5];
    uint32_t nmb;
    float inv, r;
    __device__ __forceinline__ void stats() {
        float v[40];
#pragma unroll
        for (int i = 0; i < 20; i++) { const uint32_t u = (&xv[i >> 2].x)[i & 3]; v[2 * i] = bf_lo(u); v[2 * i + 1] = bf_hi(u); }
        float sum = 0.f, sq = 0.f;
#pragma unroll
        for (int i = 0; i < 40; i += 4) sum += (v[i] + v[i + 1]) + (v[i + 2] + v[i + 3]);
#pragma unroll
        for (int o = 8; o > 0; o >>= 1) sum += __shfl_xor_sync(0xffffffffu, sum, o);
        const float mean = div640(sum);
#pragma unroll
        for (int i = 0; i < 40; i += 2) { const float d0 = v[i] - mean, d1 = v[i + 1] - mean; sq += fmaf(d0, d0, d1 * d1); }
#pragma unroll
        for (int o = 8; o > 0; o >>= 1) sq += __shfl_xor_sync(0xffffffffu, sq, o);
        nmb = pack_bf16(-mean, -mean);
        inv = rcp(round_bf16(sqrt_approx(round_bf16(round_bf16(div640(sq)) + 1e-5f))));
        r = 0.f;
    }
    template <int I>
    __device__ __forceinline__ void piece(int t, int l) {
        uint32_t o[4], z[4];
#pragma unroll
        for (int j = 0; j < 4; j++) {
            const uint32_t u = (&xv[I].x)[j], w = (&wv[I].x)[j];
            const uint32_t d = add_bf16x2(u, nmb);
            o[j] = pack_bf16(bf_lo(d) * inv, bf_hi(d) * inv);
            const float n0 = bf_lo(o[j]), n1 = bf_hi(o[j]);
            z[j] = add_bf16x2(u, o[j]);
            r = fmaf(n1, bf_hi(w), fmaf(n0, bf_lo(w), r));
        }
        stg128(g_xn + (size_t)perm_row(t) * DM + 8 * (l + 16 * I), o[0], o[1], o[2], o[3]);
        stg128(g_res + (size_t)t * DM + 8 * (l + 16 * I), z[0], z[1], z[2], z[3]);
        if (I == 4) {
#pragma unroll
            for (int k = 8; k > 0; k >>= 1) r += __shfl_xor_sync(0xffffffffu, r, k);
            if (l == 0) g_r[t] = round_bf16(r);
        }
    }
};

constexpr float SM_SCALE = 0.08838834764831845f * 1.4426950408889634f;

template <int J0, int J1>
__device__ __forceinline__ void exp_part(float (&s)[64], float n0, float n1, float& r0, float& r1) {
    float a1 = 0.f, b1 = 0.f;
#pragma unroll
    for (int j = J0; j < J1; j++) {
        s[4 * j + 0] = ex2(fmaf(s[4 * j + 0], SM_SCALE, n0));
        s[4 * j + 1] = ex2(fmaf(s[4 * j + 1], SM_SCALE, n0));
        s[4 * j + 2] = ex2(fmaf(s[4 * j + 2], SM_SCALE, n1));
        s[4 * j + 3] = ex2(fmaf(s[4 * j + 3], SM_SCALE, n1));
        r0 += s[4 * j + 0]; r1 += s[4 * j + 2];
        if (j == J0) { a1 = s[4 * j + 1]; b1 = s[4 * j + 3]; } else { a1 += s[4 * j + 1]; b1 += s[4 * j + 3]; }
    }
    r0 += a1;
    r1 += b1;
}
__device__ __forceinline__ void sched_barrier(float x, float y, uint32_t scratch) {
    asm volatile("{\n.reg .pred p;\nsetp.lt.f32 p, %0, 0f00000000;\n@p st.shared.f32 [%2], %1;\n}\n" ::"f"(x), "f"(y), "r"(scratch) : "memory");
}
__device__ __forceinline__ void pack_tile(const float (&s)[64], uint32_t (&p)[32]) {
#pragma unroll
    for (int i = 0; i < 32; i++) p[i] = pack_bf16(s[2 * i], s[2 * i + 1]);
}
template <bool ZERO>
__device__ __forceinline__ void gemm_rs(float (&d)[64], const uint32_t (&a)[32], uint32_t dl, int acc = 1) {
    const uint32_t b = dl + lbo(16384);
    if (ZERO) wgmma_rs_n128_z<1>(d, a[0], a[1], a[2], a[3], b);
#pragma unroll
    for (int k = ZERO ? 1 : 0; k < 8; k++) wgmma_rs_n128<1>(d, a[4 * k], a[4 * k + 1], a[4 * k + 2], a[4 * k + 3], b + k * 128, k ? 1 : acc);
}
template <int ZERO>
__device__ __forceinline__ void gemm_q(float (&d)[64], uint32_t dl, int role) {
    const uint32_t a = dl + role * 512 + lbo(16), b = dl + 1024 + lbo(8192);
    if (ZERO) wgmma_ss_n128_z<0, 1>(d, a, b);
#pragma unroll
    for (int k = ZERO ? 1 : 0; k < 4; k++) wgmma_ss_n128<0, 1>(d, a + k * 2, b + k * 128, 1);
}
template <bool KT, bool ZERO, int K0, int K1>
__device__ __forceinline__ void gemm_kv(float (&d)[64], uint32_t ckv, uint32_t wt, int wg) {
    if (KT) {
        const uint32_t a = wt + wg * 1024 + lbo(16), b = ckv + lbo(16);
        if (ZERO) wgmma_ss_n128_z<1, 0>(d, a, b);
#pragma unroll
        for (int k = ZERO ? 1 : K0; k < K1; k++) wgmma_ss_n128<1, 0>(d, a + k * 128, b + (k >> 2) * 1024 + (k & 3) * 2, 1);
    } else {
        const uint32_t a = ckv + wg * 512 + lbo(16), b = wt + lbo(16384);
        if (ZERO) wgmma_ss_n128_z<0, 1>(d, a, b);
#pragma unroll
        for (int k = ZERO ? 1 : K0; k < K1; k++) wgmma_ss_n128<0, 1>(d, a + (k >> 2) * 1024 + (k & 3) * 2, b + k * 128, 1);
    }
}
__device__ __forceinline__ void mma16816(float& d0, float& d1, float& d2, float& d3, uint32_t a0, uint32_t a1, uint32_t a2, uint32_t a3, uint32_t b0, uint32_t b1) {
    asm volatile("mma.sync.aligned.m16n8k16.row.col.f32.bf16.bf16.f32 {%0,%1,%2,%3}, {%4,%5,%6,%7}, {%8,%9}, {%0,%1,%2,%3};"
                 : "+f"(d0), "+f"(d1), "+f"(d2), "+f"(d3) : "r"(a0), "r"(a1), "r"(a2), "r"(a3), "r"(b0), "r"(b1));
}
__device__ __forceinline__ uint32_t ld_pair(const __nv_bfloat16* p) {
    const unsigned short* u = reinterpret_cast<const unsigned short*>(p);
    return (uint32_t)__ldcg(u) | ((uint32_t)__ldcg(u + 128) << 16);
}
__device__ __forceinline__ void attention_exact(float (&o)[64], const uint32_t (&qf)[32], float& l0, float& l1, int h, int nblk, int rr, int lane) {
    const int q = lane & 3, lr = lane >> 2;
    float m0 = -INFINITY, m1 = -INFINITY;
    l0 = 0.f; l1 = 0.f;
#pragma unroll
    for (int i = 0; i < 64; i++) o[i] = 0.f;
#pragma unroll 1
    for (int cidx = 0; cidx < nblk * 8; cidx++) {
        const int kc = cidx & 7;
        const __nv_bfloat16* kt = g_kv + (size_t)((h * 16 + (cidx >> 3)) * 2) * 16384;
        float sc[8];
#pragma unroll
        for (int i = 0; i < 8; i++) sc[i] = 0.f;
#pragma unroll
        for (int kk = 0; kk < 8; kk++)
#pragma unroll
            for (int nt = 0; nt < 2; nt++) {
                const __nv_bfloat16* b = kt + (16 * kk + 2 * q) * 128 + 16 * kc + 8 * nt + lr;
                mma16816(sc[4 * nt], sc[4 * nt + 1], sc[4 * nt + 2], sc[4 * nt + 3], qf[4 * kk], qf[4 * kk + 1], qf[4 * kk + 2], qf[4 * kk + 3],
                         ld_pair(b), ld_pair(b + 8 * 128));
            }
        const int lim = rr + ((nblk - 1) - (cidx >> 3)) * 128 - 32 * (kc >> 1) - 4 * (kc & 1);
#pragma unroll
        for (int i = 0; i < 8; i++)
            if (2 * (i >> 2) + (i & 1) > lim + 4 * (i & 2)) sc[i] = -INFINITY;
        float x0 = fmaxf(fmaxf(sc[0], sc[1]), fmaxf(sc[4], sc[5])), x1 = fmaxf(fmaxf(sc[2], sc[3]), fmaxf(sc[6], sc[7]));
        x0 = fmaxf(x0, __shfl_xor_sync(0xffffffffu, x0, 1)); x1 = fmaxf(x1, __shfl_xor_sync(0xffffffffu, x1, 1));
        x0 = fmaxf(x0, __shfl_xor_sync(0xffffffffu, x0, 2)); x1 = fmaxf(x1, __shfl_xor_sync(0xffffffffu, x1, 2));
        x0 = fmaxf(x0, m0); x1 = fmaxf(x1, m1);
        const float a0 = ex2((m0 - x0) * SM_SCALE), a1 = ex2((m1 - x1) * SM_SCALE);
        m0 = x0; m1 = x1;
#pragma unroll
        for (int i = 0; i < 8; i++) sc[i] = ex2((sc[i] - ((i & 2) ? m1 : m0)) * SM_SCALE);
        l0 = l0 * a0 + (sc[0] + sc[1]) + (sc[4] + sc[5]);
        l1 = l1 * a1 + (sc[2] + sc[3]) + (sc[6] + sc[7]);
        const uint32_t p0 = pack_bf16(sc[0], sc[1]), p1 = pack_bf16(sc[2], sc[3]), p2 = pack_bf16(sc[4], sc[5]), p3 = pack_bf16(sc[6], sc[7]);
        const __nv_bfloat16* vb = kt + 16384 + (16 * kc + 2 * q) * 128 + lr;
#pragma unroll
        for (int nt = 0; nt < 16; nt++) {
            o[4 * nt] *= a0; o[4 * nt + 1] *= a0; o[4 * nt + 2] *= a1; o[4 * nt + 3] *= a1;
            mma16816(o[4 * nt], o[4 * nt + 1], o[4 * nt + 2], o[4 * nt + 3], p0, p1, p2, p3, ld_pair(vb + 8 * nt), ld_pair(vb + 8 * nt + 8 * 128));
        }
    }
}

__device__ __forceinline__ void signal(uint32_t bars, int wg, int e, int lane) {
    __syncwarp();
    asm volatile("{\n.reg .pred p;\nsetp.eq.u32 p, %1, 0;\n@p mbarrier.arrive.shared::cta.b64 _, [%0];\n}\n" ::"r"(bars + BAR_SIG + (wg * 9 + e) * 8), "r"(lane) : "memory");
}

__device__ __forceinline__ void consumer(const Params& P, uint32_t smem, uint32_t bars, int ca, int cb, int rank, int wg, LayerNorm& ln) {
    const int lane = threadIdx.x & 31, w = (threadIdx.x >> 5) & 3, q = lane & 3, lr = lane >> 2;
    PROF(7);
    const int ln_t = blockIdx.x * 16 + wg * 8 + w * 2 + (lane >> 4);
    ln.stats();
    ln.piece<0>(ln_t, lane & 15);
    cluster_wait();
    Cons c{bars, mapa(bars + BAR_EMPTY, lane & 1), (smem & 0x3FFFF) >> 4, (uint32_t)lane, Slot{0u, (smem & 0x3FFFF) >> 4, 1u}};
    PROFG(180);
    PROF(1);
    float o[64], s[64];
    uint32_t pend;
    __nv_bfloat16* ep_ptr;
    int ep_step;
    {
        const int krow = 64 * wg + 16 * w + lr;
        const int vrow = 64 * wg + 32 * (w >> 1) + 8 * (lr >> 1) + 4 * (w & 1) + (lr & 1);
        ep_step = 2 * 128;
        int m = 0;
        uint32_t lap = 0;
        auto step = [&](auto kt, auto kc, float (&d)[64], int hh) {
            const Slot sa = c.slot(slot_a(kc.value), 0), sw = c.slot(slot_w(m), lap ^ (m >> 1));
            lap ^= m >> 1;
            m = (m == 2) ? 0 : m + 1;
            TR(1 + (hh * 8 + (kt.value ? 0 : 4) + kc.value) * 2);
            if (kt.value && hh == 0) c.wait(sa);
            c.wait(sw);
            TR(2 + (hh * 8 + (kt.value ? 0 : 4) + kc.value) * 2);
            wgmma_fence();
            gemm_kv<kt.value, kc.value == 0, 0, KVSPLIT>(d, sa.dl, sw.dl, wg);
            wgmma_commit();
            wgmma_wait<1>();
            if (!(kt.value && kc.value == 0 && hh == 0)) c.release(pend);
            if (!kt.value && kc.value > 0 && hh == 3) c.release(slot_a(kc.value - 1) * 8);
            pend = sw.bo;
            wgmma_fence();
            gemm_kv<kt.value, false, KVSPLIT, 8>(d, sa.dl, sw.dl, wg);
            wgmma_commit();
        };
#pragma unroll 1
        for (int hh = 0; hh < 4; hh++) {
            __nv_bfloat16* base = g_kv + (size_t)(((cb + 8 * kv_round(hh)) * 16 + 2 * ca + rank) * 2) * 16384 + 8 * q;
            for4([&](auto kc) {
                step(TrueT{}, kc, s, hh);
                if (hh > 0) {
                    if (kc.value == 0) fence_regs(o);
                    store_chunk<kc.value>(o, ep_ptr, ep_ptr + ep_step, 1.f, 1.f);
                } else {
                    ln.template piece<kc.value + 1>(ln_t, lane & 15);
                }
            });
            signal(bars, wg, hh, lane);
            for4([&](auto kc) {
                step(FalseT{}, kc, o, hh);
                if (kc.value == 0) fence_regs(s);
                store_chunk<kc.value>(s, base + krow * 128, base + (krow + 8) * 128, 1.f, 1.f);
            });
            PROF(24 + hh);
            if (hh == 1) PROFG(181);
            ep_ptr = base + 16384 + vrow * 128;
        }
    }
    PROFG(182);
    PROF(2);
    {
        uint32_t pf[32], qf[32];
        float l0 = 0.25f, l1 = 0.25f;
        const int bar_me = 2 + wg, bar_other = 3 - wg;
#pragma unroll 1
        for (int rd = 0; rd < 4; rd++) {
            const int h = 8 * rd + cb, p = item_p(ca, rd);
            const int role = wg ^ (rd & 1);
            const int nrest = 2 * p + role;
            Slot kfirst;
            {
                auto qstep = [&](auto zero, int ks) {
                    const Slot sl = c.next();
                    BP(2, 4 + 3 * ks);
                    c.wait(sl);
                    BP(2, 5 + 3 * ks);
                    wgmma_fence();
                    gemm_q<zero.value>(s, sl.dl, role);
                    wgmma_commit();
                    wgmma_wait<1>();
                    BP(2, 6 + 3 * ks);
                    c.release(pend);
                    pend = sl.bo;
                };
                qstep(TrueT{}, 0);
                if (rd == 0) c.release(slot_a(3) * 8);
                fence_regs(o);
#pragma unroll 1
                for (int ks = 1; ks < QST; ks++) qstep(FalseT{}, ks);
                for4([&](auto i) {
                    qstep(FalseT{}, QST + i.value);
                    if (i.value == 0) {
                        l0 += __shfl_xor_sync(0xffffffffu, l0, 1); l1 += __shfl_xor_sync(0xffffffffu, l1, 1);
                        l0 += __shfl_xor_sync(0xffffffffu, l0, 2); l1 += __shfl_xor_sync(0xffffffffu, l1, 2);
                        l0 = rcp(l0); l1 = rcp(l1);
                    }
                    store_chunk<i.value>(o, ep_ptr, ep_ptr + ep_step, l0, l1);
                });
                signal(bars, wg, 4 + rd, lane);
                PROF(11 + rd * 4);
#pragma unroll 1
                for (int ks = QST + 4; ks < 10; ks++) qstep(FalseT{}, ks);
                if (!role) { const Slot sl = c.next(); c.wait(sl); c.release(sl.bo); }
                kfirst = c.next();
                c.wait(kfirst);
                wgmma_wait<0>();
                BP(2, 34);
                c.release(pend);
                fence_regs(s);
                pack_tile(s, qf);
            }
            PROF(8 + rd * 4);
            fence_regs(qf);
            BP(2, 35);
            if (PINGPONG && !role) named_sync(bar_me, 256);
            BP(2, 36);
            wgmma_fence();
            gemm_rs<true>(s, qf, kfirst.dl);
            wgmma_commit();
            if (PINGPONG) named_arrive(bar_other, 256);
            BP(2, 37);
            if (!role) { const Slot sl = c.next(); c.wait(sl); c.release(sl.bo); }
            const int dg = __reduce_or_sync(0xffffffffu, 2 * (role ^ rank) + (w >> 1));
            wgmma_wait<0>();
            BP(2, 38);
            fence_regs(s);
            c.release(kfirst.bo);
            float n0, n1;
            l0 = 0.f; l1 = 0.f;
            for4([&](auto a) {
                constexpr int B = 16 * a.value;
                if (a.value == dg) {
                    const int lim = 16 * (w & 1) + lr - 8 * q;
#pragma unroll
                    for (int i = 0; i < 16; i++)
                        if (2 * (i >> 2) + (i & 1) > lim + 4 * (i & 2)) s[B + i] = -INFINITY;
                }
                if (a.value == 0) {
                    n0 = fmaxf(fmaxf(fmaxf(s[0], s[1]), fmaxf(s[4], s[5])), fmaxf(fmaxf(s[8], s[9]), fmaxf(s[12], s[13])));
                    n1 = fmaxf(fmaxf(fmaxf(s[2], s[3]), fmaxf(s[6], s[7])), fmaxf(fmaxf(s[10], s[11]), fmaxf(s[14], s[15])));
                    n0 = fmaxf(n0, __shfl_xor_sync(0xffffffffu, n0, 1)); n1 = fmaxf(n1, __shfl_xor_sync(0xffffffffu, n1, 1));
                    n0 = fmaxf(n0, __shfl_xor_sync(0xffffffffu, n0, 2)); n1 = fmaxf(n1, __shfl_xor_sync(0xffffffffu, n1, 2));
                    n0 *= -SM_SCALE; n1 *= -SM_SCALE;
                }
                if (a.value <= dg) {
                    exp_part<4 * a.value, 4 * a.value + 4>(s, n0, n1, l0, l1);
#pragma unroll
                    for (int i = 0; i < 8; i++) pf[8 * a.value + i] = pack_bf16(s[B + 2 * i], s[B + 2 * i + 1]);
                } else {
#pragma unroll
                    for (int i = 0; i < 8; i++) pf[8 * a.value + i] = 0u;
                }
            });
            PROF(9 + rd * 4);
#pragma unroll 1
            for (int it = 0; it < nrest; it++) {
                const Slot sk = c.next(), sv = c.next();
                LP(0);
                if (it < 3) BP(2, 40 + 4 * it);
                if (it >= nrest - 2) BP(1, 60 + 4 * (it - nrest + 2));
                c.wait(sk);
                c.wait(sv);
                fence_regs(o); fence_regs(pf);
                LP(1);
                if (it < 3) BP(2, 41 + 4 * it);
                if (it >= nrest - 2) BP(1, 61 + 4 * (it - nrest + 2));
                if (PINGPONG) named_sync(bar_me, 256);
                LP(2);
                if (it < 3) BP(2, 42 + 4 * it);
                if (it >= nrest - 2) BP(1, 62 + 4 * (it - nrest + 2));
                wgmma_fence();
                gemm_rs<true>(s, qf, sk.dl);
                wgmma_commit();
                gemm_rs<false>(o, pf, sv.dl, it);
                wgmma_commit();
                if (PINGPONG) named_arrive(bar_other, 256);
                LP(3);
                if (it < 3) BP(2, 43 + 4 * it);
                if (it >= nrest - 2) BP(1, 63 + 4 * (it - nrest + 2));
                wgmma_wait<1>();
                LP(4);
                c.release(sk.bo);
                fence_regs(s);
                exp_part<0, SPLITJ>(s, n0, n1, l0, l1);
                sched_barrier(l0, l1, bars + MISC_OFF + 16);
                LP(5);
                wgmma_wait<0>();
                LP(6);
                c.release(sv.bo);
                fence_regs(o); fence_regs(pf);
                exp_part<SPLITJ, 16>(s, n0, n1, l0, l1);
                pack_tile(s, pf);
            }
            PROF(10 + rd * 4);
            PROFG(183 + rd);
            const Slot sv = c.next();
            BP(1, 0);
            c.wait(sv);
            if (nrest == 0) {
#pragma unroll
                for (int i = 0; i < 64; i++) o[i] = 0.f;
            }
            if (__builtin_expect(__any_sync(0xffffffffu, !(l0 < 0x1p60f && l1 < 0x1p60f)), 0)) {
                attention_exact(o, qf, l0, l1, h, nrest + 1, 64 * (role ^ rank) + 16 * w + lr - 8 * q, lane);
#pragma unroll
                for (int i = 0; i < 32; i++) pf[i] = 0u;
            }
            fence_regs(o); fence_regs(pf);
            BP(1, 1);
            if (PINGPONG && !role) named_sync(bar_me, 256);
            BP(1, 2);
            wgmma_fence();
            gemm_rs<false>(o, pf, sv.dl);
            wgmma_commit();
            BP(1, 3);
            pend = sv.bo;
            ep_ptr = g_ctx + (size_t)(h * SEQ + 256 * p + 128 * rank + 64 * role + 16 * w + lr) * HD + 8 * q;
            ep_step = 8 * HD;
        }
        l0 += __shfl_xor_sync(0xffffffffu, l0, 1); l1 += __shfl_xor_sync(0xffffffffu, l1, 1);
        l0 += __shfl_xor_sync(0xffffffffu, l0, 2); l1 += __shfl_xor_sync(0xffffffffu, l1, 2);
        l0 = rcp(l0); l1 = rcp(l1);
        wgmma_wait<0>();
        c.release(pend);
        fence_regs(o); fence_regs(pf);
        for4([&](auto i) { store_chunk<i.value>(o, ep_ptr, ep_ptr + ep_step, l0, l1); });
        signal(bars, wg, 8, lane);
    }
    PROFG(187);
    PROF(3);
    {
        float a1[64], a2[96];
        uint32_t px = 0, py = 0;
#pragma unroll 1
        for (int t = 0; t < 16; t++) {
            const Slot sx = c.next(), sy = c.next();
            c.wait(sx);
            const uint32_t da = sx.dl + wg * 512 + lbo(16), b1 = sx.dl + 1024 + lbo(4096), b2 = sy.dl + lbo(4096);
            wgmma_fence();
#pragma unroll
            for (int k = 0; k < 4; k++) wgmma_ss_n128<0, 1>(a1, da + k * 2, b1 + (k >> 1) * 512 + (k & 1) * 128, k ? 1 : t);
            wgmma_commit();
            wgmma_wait<1>();
            if (t > 0) { c.release(px); c.release(py); }
            px = sx.bo; py = sy.bo;
            c.wait(sy);
            wgmma_fence();
#pragma unroll
            for (int k = 0; k < 4; k++) wgmma_ss_n192<0, 1>(a2, da + k * 2, b2 + (k >> 1) * 768 + (k & 1) * 128, k ? 1 : t);
            wgmma_commit();
        }
        const int nh = cb & 1, kg = cb >> 1, tile = (ca * 2 + rank) * 2 + nh, tid = threadIdx.x - 128;
        const int goff = (unperm_row(256 * ca + 128 * rank + 64 * wg) + 16 * w + 8 * (kg >> 1)) * (DM / 8) + 40 * nh + 20 * (kg & 1) + lane;
        const uint32_t epoch = read_epoch();
        mbar_wait(bars + BAR_DEP + 13 * 8, 0);
        uint4 rv[5];
#pragma unroll
        for (int i = 0; i < 5; i++) {
            const int r = ((lane + 32 * i) * 205) >> 12;
            rv[i] = __ldcg(reinterpret_cast<const uint4*>(g_res) + (goff + 32 * i + 60 * r));
        }
        wgmma_wait<0>();
        fence_regs(a1); fence_regs(a2);
    PROFG(188);
        PROF(4);
        uint32_t own[20];
#pragma unroll
        for (int g = 0; g < 4; g++) {
            uint32_t pk[20];
#pragma unroll
            for (int i = 0; i < 20; i++) {
                const int j = 20 * (g & 1) + i, e = 2 * (g >> 1);
                pk[i] = (j < 16) ? pack_bf16(a1[4 * (j & 15) + e], a1[4 * (j & 15) + e + 1]) : pack_bf16(a2[4 * (j < 16 ? 0 : j - 16) + e], a2[4 * (j < 16 ? 0 : j - 16) + e + 1]);
                if (g == 0 || g == kg) own[i] = pk[i];
            }
            if (g != kg) {
                uint4* dst = g_part + ((tile * 4 + g) * 4 + kg) * 5 * 256 + tid;
#pragma unroll
                for (int i = 0; i < 5; i++) stg128(dst + i * 256, pk[4 * i], pk[4 * i + 1], pk[4 * i + 2], pk[4 * i + 3]);
            }
        }
        __syncwarp();
        if (lane == 0) {
            flag_add(F_PART + tile * 8 + wg * 4 + w);
            flag_wait<20>(F_PART + tile * 8 + wg * 4 + w, 4u * (epoch + 1));
        }
        __syncwarp();
        PROF(5);
        uint4 in[3][5];
#pragma unroll
        for (int k = 0; k < 3; k++)
#pragma unroll
            for (int i = 0; i < 5; i++) in[k][i] = __ldcg(g_part + ((tile * 4 + kg) * 4 + ((kg + 1 + k) & 3)) * 5 * 256 + i * 256 + tid);
        const uint32_t stage = smem + c.cur.bo * (SLOT / 8) + (wg * 4 + w) * 2688;
#pragma unroll
        for (int i = 0; i < 5; i++) {
            uint32_t r[4];
#pragma unroll
            for (int e = 0; e < 4; e++) {
                const uint32_t u0 = (&in[0][i].x)[e], u1 = (&in[1][i].x)[e], u2 = (&in[2][i].x)[e], u3 = own[4 * i + e];
                r[e] = pack_bf16((bf_lo(u0) + bf_lo(u1)) + (bf_lo(u2) + bf_lo(u3)), (bf_hi(u0) + bf_hi(u1)) + (bf_hi(u2) + bf_hi(u3)));
            }
            asm volatile("stmatrix.sync.aligned.m8n8.x4.shared.b16 [%0], {%1, %2, %3, %4};"
                         ::"r"(stage + (lane & 7) * 336 + (4 * i + (lane >> 3)) * 16), "r"(r[0]), "r"(r[1]), "r"(r[2]), "r"(r[3]) : "memory");
        }
        __syncwarp();
#pragma unroll
        for (int i = 0; i < 5; i++) {
            const int r = ((lane + 32 * i) * 205) >> 12;
            uint4 v;
            asm volatile("ld.shared.v4.b32 {%0, %1, %2, %3}, [%4];" : "=r"(v.x), "=r"(v.y), "=r"(v.z), "=r"(v.w) : "r"(stage + (lane + 32 * i + r) * 16) : "memory");
            stg128(reinterpret_cast<uint4*>(P.out) + (goff + 32 * i + 60 * r), add_bf16x2(v.x, rv[i].x), add_bf16x2(v.y, rv[i].y), add_bf16x2(v.z, rv[i].z), add_bf16x2(v.w, rv[i].w));
        }
    }
    PROF(6);
}

__device__ __forceinline__ void mma_rows(float (&acc)[8][4], uint32_t a0, uint32_t a2, const uint4& w0, const uint4& w1, const uint4& w2, const uint4& w3) {
    const uint32_t r0[4] = {w0.x, w0.y, w0.z, w0.w}, r1[4] = {w1.x, w1.y, w1.z, w1.w};
    const uint32_t r2[4] = {w2.x, w2.y, w2.z, w2.w}, r3[4] = {w3.x, w3.y, w3.z, w3.w};
#pragma unroll
    for (int i = 0; i < 4; i++) {
        mma16816(acc[2 * i][0], acc[2 * i][1], acc[2 * i][2], acc[2 * i][3], a0, 0u, a2, 0u, __byte_perm(r0[i], r1[i], 0x5410), __byte_perm(r2[i], r3[i], 0x5410));
        mma16816(acc[2 * i + 1][0], acc[2 * i + 1][1], acc[2 * i + 1][2], acc[2 * i + 1][3], a0, 0u, a2, 0u, __byte_perm(r0[i], r1[i], 0x7632), __byte_perm(r2[i], r3[i], 0x7632));
    }
}

__device__ __forceinline__ void mod_ffn(const Params& P, uint8_t* sm, int mc  ) {
    const uint32_t epoch = read_epoch();
    const int tid = threadIdx.x - 128, lane = tid & 31, cw = tid >> 5, q = lane & 3, lr = lane >> 2;
    uint32_t* xs = reinterpret_cast<uint32_t*>(sm);
    uint32_t* wmax = xs + 8 * 324;
    int* sidx = reinterpret_cast<int*>(wmax + 16);
    const int fg = cw * 4 + mc;
    const uint32_t ring = smem_u32(sm) + 16384 + cw * 24576, rbar = smem_u32(sm) + 12288 + cw * 32;
    auto issue = [&](int u, int st) {
        if (lane == 0 && u < 30) {
            mbar_expect_tx(rbar + st * 8, 8192);
            if (u < 20) {
                tma_load_stream(ring + st * 8192, &P.wg, fg * 64, u * 32, rbar + st * 8);
                tma_load_stream(ring + st * 8192 + 4096, &P.wu, fg * 64, u * 32, rbar + st * 8);
            } else {
                tma_load_stream(ring + st * 8192, &P.wd, (u - 20) * 64, fg * 64, rbar + st * 8);
            }
        }
    };
    if (lane == 0) {
        mbar_init(rbar, 1); mbar_init(rbar + 8, 1); mbar_init(rbar + 16, 1);
        asm volatile("fence.mbarrier_init.release.cluster;" ::: "memory");
    }
    if (tid == 0) flag_wait<100>(F_LN, 256u * (epoch + 1));
    named_sync(1, 256);
    PROF(1);
    if (fg < 27) {
#pragma unroll 1
        for (int u = 0; u < 3; u++) issue(u, u);
    }
    PROF(2);
    uint32_t key[8];
#pragma unroll
    for (int i = 0; i < 8; i++) {
        const int t = tid + 256 * i;
        uint32_t b = __float_as_uint(__ldcg(g_r + t) + 0.f) >> 16;
        b = (b & 0x8000u) ? (~b & 0xffffu) : (b | 0x8000u);
        key[i] = (b << 16) | (uint32_t)(0xffff - t);
    }
#pragma unroll 1
    for (int rnd = 0; rnd < 8; rnd++) {
        uint32_t mx = key[0];
#pragma unroll
        for (int i = 1; i < 8; i++) mx = max(mx, key[i]);
        mx = __reduce_max_sync(0xffffffffu, mx);
        if (lane == 0) wmax[(rnd & 1) * 8 + cw] = mx;
        named_sync(1, 256);
        mx = __reduce_max_sync(0xffffffffu, wmax[(rnd & 1) * 8 + (lane & 7)]);
#pragma unroll
        for (int i = 0; i < 8; i++) if (key[i] == mx) key[i] = 0;
        if (tid == 0) sidx[rnd] = 0xffff - (int)(mx & 0xffffu);
    }
    named_sync(1, 256);
    {
        const uint32_t* src = reinterpret_cast<const uint32_t*>(g_xn + (size_t)perm_row(sidx[cw]) * DM);
#pragma unroll 2
        for (int i = lane; i < 320; i += 32) xs[cw * 324 + i] = __ldcg(src + i);
    }
    named_sync(1, 256);
    PROF(3);
    if (fg < 27) {
        float g[8][4], v[8][4];
        uint32_t hp[8];
#pragma unroll
        for (int i = 0; i < 8; i++)
#pragma unroll
            for (int e = 0; e < 4; e++) { g[i][e] = 0.f; v[i][e] = 0.f; }
        int st = 0, ph = 0;
#pragma unroll 1
        for (int u = 0; u < 60; u++) {
            if (!(u & 1)) mbar_wait(rbar + st * 8, ph);
            uint4 a[8];
#pragma unroll
            for (int r = 0; r < 8; r++) {
                const int row = (u < 40) ? 32 * (r >> 2) + 16 * (u & 1) + 2 * q + (r & 1) + 4 * (r & 2) : 16 * q + 8 * (u & 1) + r;
                asm volatile("ld.shared.v4.b32 {%0, %1, %2, %3}, [%4];" : "=r"(a[r].x), "=r"(a[r].y), "=r"(a[r].z), "=r"(a[r].w)
                             : "r"(ring + st * 8192 + row * 128 + ((lr ^ row) & 7) * 16) : "memory");
            }
            uint32_t f0, f1, f2, f3;
            if (u < 40) { f0 = f2 = xs[lr * 324 + u * 8 + q]; f1 = f3 = xs[lr * 324 + u * 8 + 4 + q]; }
            else if (u & 1) { f0 = hp[4]; f1 = hp[5]; f2 = hp[6]; f3 = hp[7]; }
            else { f0 = hp[0]; f1 = hp[1]; f2 = hp[2]; f3 = hp[3]; }
            mma_rows(g, f0, f1, a[0], a[1], a[2], a[3]);
            mma_rows(v, f2, f3, a[4], a[5], a[6], a[7]);
            if (u & 1) {
                __syncwarp();
                issue((u >> 1) + 3, st);
                if (++st == 3) { st = 0; ph ^= 1; }
                if (u >= 39) {
                    if (u == 39) {
                        float hv[16];
#pragma unroll
                        for (int i = 0; i < 16; i++) {
                            const float gp = round_bf16(g[i & 7][i >> 3]);
                            hv[i] = round_bf16(__fdividef(gp, 1.0f + __expf(fminf(-gp, 80.f)))) * round_bf16(v[i & 7][i >> 3]);
                        }
#pragma unroll
                        for (int i = 0; i < 8; i++) hp[i] = pack_bf16(hv[2 * i], hv[2 * i + 1]);
                    } else {
                        float4* dst = reinterpret_cast<float4*>(g_ypart + (fg * 8 + lr) * DM + ((u - 40) >> 1) * 64 + 16 * q);
#pragma unroll
                        for (int i = 0; i < 4; i++) {
                            const int j = 4 * (i & 1), e = i >> 1;
                            dst[i] = make_float4(g[j][e] + v[j][e], g[j + 1][e] + v[j + 1][e], g[j + 2][e] + v[j + 2][e], g[j + 3][e] + v[j + 3][e]);
                        }
                    }
#pragma unroll
                    for (int i = 0; i < 8; i++) { g[i][0] = 0.f; g[i][1] = 0.f; v[i][0] = 0.f; v[i][1] = 0.f; }
                }
            }
        }
    }
    PROF(5);
    named_sync(1, 256);
    if (tid == 0) {
        flag_add(F_MODP);
        flag_wait<100>(F_MODP, 4u * (epoch + 1));
    }
    named_sync(1, 256);
    PROF(6);
#pragma unroll 1
    for (int i = tid; i < 2 * DM; i += 256) {
        const int c = 2 * mc + (i >= DM), col = i - (i >= DM) * DM, t = sidx[c];
        float y = 0.f;
#pragma unroll 9
        for (int k = 0; k < 27; k++) y += __ldcg(g_ypart + (k * 8 + c) * DM + col);
        const float rs = round_bf16(__fdividef(1.0f, 1.0f + __expf(fminf(-__ldcg(g_r + t), 80.f))));
        const float xn = __bfloat162float(reinterpret_cast<const __nv_bfloat16*>(xs + c * 324)[col]);
        g_res[(size_t)t * DM + col] = __float2bfloat16_rn(__bfloat162float(P.x[(size_t)t * DM + col]) + round_bf16(xn + round_bf16(round_bf16(y) * rs)));
    }
    named_sync(1, 256);
    if (tid == 0) flag_add(F_MOD);
    PROF(7);
}

__global__ void __cluster_dims__(2, 1, 1) __launch_bounds__(384, 1) fused_kernel(const __grid_constant__ Params P) {
    extern __shared__ __align__(1024) uint8_t smem_raw[];
    const uint32_t smem = (smem_u32(smem_raw) + 1023u) & ~1023u;
    uint8_t* smem_gen = smem_raw + (smem - smem_u32(smem_raw));
    const uint32_t bars = smem + NSLOT * SLOT;
    const int wgi = __reduce_or_sync(0xffffffffu, threadIdx.x >> 7);
    const int cl = blockIdx.x >> 1, rank = blockIdx.x & 1, ca = cl & 7, cb = cl >> 3;
    PROFG(30);
    PROF(0);
    LayerNorm ln;
    if (wgi != 0) {
        const uint4* xr = reinterpret_cast<const uint4*>(P.x + (size_t)((blockIdx.x & 127) * 16 + ((threadIdx.x - 128) >> 4)) * DM) + (threadIdx.x & 15);
        const uint4* wr = reinterpret_cast<const uint4*>(P.wr) + (threadIdx.x & 15);
#pragma unroll
        for (int i = 0; i < 5; i++) { ln.xv[i] = ldg_stream(xr + 16 * i); ln.wv[i] = __ldg(wr + 16 * i); }
        PROF(28);
    } else if (threadIdx.x == 0) {
#pragma unroll
        for (int i = 0; i < NSLOT; i++) { mbar_init(bars + BAR_FULL + i * 8, 1); mbar_init(bars + BAR_EMPTY + i * 8, 16); }
        mbar_arrive(bars + BAR_FULL + 16);
        asm volatile("mbarrier.arrive.shared::cta.b64 _, [%0], 16;" ::"r"(bars + BAR_EMPTY + 16) : "memory");
        asm volatile("fence.mbarrier_init.release.cluster;" ::: "memory");
        PROF(24);
    } else if (threadIdx.x == 32) {
#pragma unroll
        for (int i = 0; i < 18; i++) mbar_init(bars + BAR_SIG + i * 8, 4);
#pragma unroll
        for (int i = 0; i < 14; i++) mbar_init(bars + BAR_DEP + i * 8, 1);
    } else if (threadIdx.x >= 64 && cl < 64) {
        const int i = threadIdx.x - 64;
        if (i == 0) { prefetch_map(&P.ckv); prefetch_map(&P.wuk); }
        const char* a = reinterpret_cast<const char*>(P.ckv_ptr) + ((2 * ca + rank) * 128 + cb * 16) * (DC * 2) + i * 256;
        asm volatile("prefetch.global.L2 [%0];" ::"l"(a));
        asm volatile("prefetch.global.L2 [%0];" ::"l"(a + 128));
        asm volatile("prefetch.global.L2 [%0];" ::"l"(P.wuk_ptr + (size_t)(i * 8 + ca) * (NH * HD) + (cb + 8 * kv_round(0)) * 128 + rank * 64));
    }
    __syncthreads();
    PROF(29);
    cluster_arrive();
    if (wgi > 0) {
        asm volatile("setmaxnreg.inc.sync.aligned.u32 232;");
        if (cl >= 64) {
            cluster_wait();
            mod_ffn(P, smem_gen, blockIdx.x - 128);
        } else {
            consumer(P, smem, bars, ca, cb, rank, wgi - 1, ln);
        }
        cluster_arrive();
        PROFG(31);
        PROFDUMP();
    } else {
        asm volatile("setmaxnreg.dec.sync.aligned.u32 40;");
        const int w = __reduce_or_sync(0xffffffffu, threadIdx.x >> 5), lane = threadIdx.x & 31;
        if (threadIdx.x == 32 && cl < 64) {
            mbar_expect_tx(bars + BAR_FULL, SLOT);
            tma_load(smem, &P.ckv, 0, (2 * ca + rank) * 128, bars + BAR_FULL);
            tma_load(smem + 16384, &P.ckv, 64, (2 * ca + rank) * 128, bars + BAR_FULL);
        }
        if (threadIdx.x == 64) {
            prefetch_map(&P.wuv); prefetch_map(&P.xn); prefetch_map(&P.wq); prefetch_map(&P.kv); prefetch_map(&P.ctx); prefetch_map(&P.wo);
        }
        __syncwarp();
        cluster_wait();
        PROF(27);
        if (cl < 64) {
            if (w == 0) {
                producer(P, smem, bars, ca, cb, rank);
            } else if (w < 3 && lane == 0) {
                const int wg = w - 1;
#pragma unroll 1
                for (int e = 0; e < 9; e++) {
                    mbar_wait_sleep(bars + BAR_SIG + (wg * 9 + e) * 8, 0);
                    int f;
                    if (e == 0) f = F_LN;
                    else if (e < 5) f = F_KV + cb + 8 * kv_round(e - 1);
                    else { const int rd = e - 5; f = F_CTX + (8 * rd + cb) * 16 + item_p(ca, rd) * 2 + rank; }
                    flag_add(f);
                }
            } else if (lane == 0) {
                const uint32_t epoch = read_epoch();
#pragma unroll 1
                for (int i = 0; i < 14; i++) {
                    const int e = (i < 11) ? i : (i == 11) ? 13 : i - 1;
                    int f;
                    uint32_t n;
                    if (e == 0) { f = F_LN; n = 256; }
                    else if (e < 5) { f = F_KV + cb + 8 * (e - 1); n = 32; }
                    else if (e < 13) { f = F_CTX + (8 * ((e - 5) >> 1) + (cb & 6) + ((e - 5) & 1)) * 16 + ca * 2 + rank; n = 2; }
                    else { f = F_MOD; n = 4; }
                    flag_wait<200>(f, n * (epoch + 1));
                    fence_proxy_async();
                    mbar_arrive(bars + BAR_DEP + e * 8);
                }
            }
        }
        __syncwarp();
        cluster_arrive();
        cluster_wait();
        if (threadIdx.x == 0) atomicAdd(g_flags + F_EXIT * 8, 1u);
        PROFG(31);
        PROFDUMP();
    }
}

typedef CUresult (*EncodeFn)(CUtensorMap*, CUtensorMapDataType, cuuint32_t, void*, const cuuint64_t*, const cuuint64_t*, const cuuint32_t*,
                             const cuuint32_t*, CUtensorMapInterleave, CUtensorMapSwizzle, CUtensorMapL2promotion, CUtensorMapFloatOOBfill);

void make_map(EncodeFn fn, CUtensorMap* m, const void* ptr, uint64_t rows, uint64_t cols, uint32_t box_rows) {
    cuuint64_t dims[2] = {cols, rows};
    cuuint64_t strides[1] = {cols * 2};
    cuuint32_t box[2] = {64, box_rows};
    cuuint32_t es[2] = {1, 1};
    fn(m, CU_TENSOR_MAP_DATA_TYPE_BFLOAT16, 2, const_cast<void*>(ptr), dims, strides, box, es, CU_TENSOR_MAP_INTERLEAVE_NONE,
       CU_TENSOR_MAP_SWIZZLE_128B, CU_TENSOR_MAP_L2_PROMOTION_L2_128B, CU_TENSOR_MAP_FLOAT_OOB_FILL_NONE);
}

}

extern "C" void kernel_launch(void* const* d_in, const int* in_sizes, int n_in, void* d_out, int out_size) {
    (void)in_sizes; (void)n_in; (void)out_size;
    void* fnp = nullptr;
    cudaDriverEntryPointQueryResult qr;
    cudaGetDriverEntryPoint("cuTensorMapEncodeTiled", &fnp, cudaEnableDefault, &qr);
    EncodeFn fn = (EncodeFn)fnp;
    void *xn, *kv, *ctx;
    cudaGetSymbolAddress(&xn, g_xn);
    cudaGetSymbolAddress(&kv, g_kv);
    cudaGetSymbolAddress(&ctx, g_ctx);
    Params P;
    make_map(fn, &P.ckv, d_in[1], SEQ, DC, 128);
    make_map(fn, &P.wq, d_in[2], DM, NH * HD, 64);
    make_map(fn, &P.wuk, d_in[3], DC, NH * HD, 128);
    make_map(fn, &P.wuv, d_in[4], DC, NH * HD, 128);
    make_map(fn, &P.wo, d_in[5], NH * HD, DM, 32);
    make_map(fn, &P.xn, xn, SEQ, DM, 128);
    make_map(fn, &P.kv, kv, NH * 16 * 2 * 128, 128, 128);
    make_map(fn, &P.ctx, ctx, NH * SEQ, HD, 128);
    P.x = (const __nv_bfloat16*)d_in[0];
    P.wr = (const __nv_bfloat16*)d_in[7];
    make_map(fn, &P.wg, d_in[8], DM, FF, 32);
    make_map(fn, &P.wu, d_in[9], DM, FF, 32);
    make_map(fn, &P.wd, d_in[10], FF, DM, 64);
    P.ckv_ptr = (const __nv_bfloat16*)d_in[1];
    P.wuk_ptr = (const __nv_bfloat16*)d_in[3];
    P.out = (__nv_bfloat16*)d_out;
    cudaFuncSetAttribute(fused_kernel, cudaFuncAttributeMaxDynamicSharedMemorySize, SMEM_BYTES);
    fused_kernel<<<NCTA, 384, SMEM_BYTES>>>(P);
}
```

```cpp
#include <cuda_runtime.h>
#include <cuda_bf16.h>
#include <cuda.h>
#include <stdint.h>

namespace {

constexpr int SEQ = 2048, DM = 640, DC = 512, NH = 32, HD = 128, FF = 1728;
constexpr int NSLOT = 7, SLOT = 32768;
constexpr int NCTA = 132;
#define PINGPONG 1
#define SIGMA 1
#define KVORDER 0x1023
#define KVSPLIT 2
#define QST 4
#define LNSTAG 1
#define EARLYPF 1
#define SPLITJ 8
constexpr uint32_t DESC_HI = (1024u >> 4) | (1u << 30);
constexpr int SMEM_BYTES = NSLOT * SLOT + 3072;

constexpr int BAR_FULL = 0, BAR_EMPTY = 64, BAR_SIG = 128  , BAR_DEP = 320  , MISC_OFF = 512;

constexpr int F_EXIT = 0, F_LN = 1, F_MOD = 2, F_MODP = 3, F_KV = 4  , F_PART = 36  , F_CTX = 292  , F_NUM = 804;

__device__ __align__(1024) __nv_bfloat16 g_xn[SEQ * DM];
__device__ __align__(1024) __nv_bfloat16 g_kv[NH * 16 * 2 * 128 * 128];
__device__ __align__(1024) __nv_bfloat16 g_ctx[NH * SEQ * HD];
__device__ __align__(1024) __nv_bfloat16 g_res[SEQ * DM];
__device__ __align__(1024) uint4 g_part[32 * 4 * 4 * 5 * 256];
__device__ __align__(16) float g_r[SEQ];
__device__ __align__(16) float g_ypart[27 * 8 * DM];
__device__ uint32_t g_flags[F_NUM * 8];

struct TrueT { static constexpr bool value = true; };
struct FalseT { static constexpr bool value = false; };

struct Params {
    CUtensorMap ckv, wuk, wuv, xn, wq, kv, ctx, wo, wg, wu, wd;
    const __nv_bfloat16 *x, *wr, *ckv_ptr, *wuk_ptr;
    __nv_bfloat16* out;
};

__device__ __forceinline__ uint32_t smem_u32(const void* p) { return (uint32_t)__cvta_generic_to_shared(p); }
__device__ __forceinline__ void mbar_init(uint32_t bar, uint32_t cnt) {
    asm volatile("mbarrier.init.shared::cta.b64 [%0], %1;" ::"r"(bar), "r"(cnt) : "memory");
}
__device__ __forceinline__ void mbar_expect_tx(uint32_t bar, uint32_t bytes) {
    asm volatile("mbarrier.arrive.expect_tx.shared::cta.b64 _, [%0], %1;" ::"r"(bar), "r"(bytes) : "memory");
}
__device__ __forceinline__ void mbar_arrive(uint32_t bar) {
    asm volatile("mbarrier.arrive.shared::cta.b64 _, [%0];" ::"r"(bar) : "memory");
}
__device__ __forceinline__ uint32_t mapa(uint32_t addr, uint32_t cta) {
    uint32_t r;
    asm("mapa.shared::cluster.u32 %0, %1, %2;" : "=r"(r) : "r"(addr), "r"(cta));
    return r;
}
__device__ __forceinline__ void mbar_wait(uint32_t bar, uint32_t parity) {
    asm volatile(
        "{\n.reg .pred p;\n.reg .b32 c;\n"
        "mov.b32 c, 0;\n"
        "WLOOP:\n"
        "mbarrier.try_wait.parity.shared::cta.b64 p, [%0], %1;\n"
        "@p bra.uni WDONE;\n"
        "add.u32 c, c, 1;\n"
        "setp.lt.u32 p, c, 0x400000;\n"
        "@p bra.uni WLOOP;\n"
        "trap;\n"
        "WDONE:\n}\n" ::"r"(bar), "r"(parity) : "memory");
}
__device__ __forceinline__ void mbar_wait_sleep(uint32_t bar, uint32_t parity) {
    asm volatile(
        "{\n.reg .pred p;\n.reg .b32 c;\n"
        "mov.b32 c, 0;\n"
        "WLOOP:\n"
        "mbarrier.try_wait.parity.shared::cta.b64 p, [%0], %1, 20000;\n"
        "@p bra.uni WDONE;\n"
        "add.u32 c, c, 1;\n"
        "setp.lt.u32 p, c, 0x40000;\n"
        "@p bra.uni WLOOP;\n"
        "trap;\n"
        "WDONE:\n}\n" ::"r"(bar), "r"(parity) : "memory");
}
__device__ __forceinline__ void tma_load(uint32_t dst, const CUtensorMap* m, int c0, int c1, uint32_t bar) {
    asm volatile("cp.async.bulk.tensor.2d.shared::cluster.global.mbarrier::complete_tx::bytes [%0], [%1, {%3, %4}], [%2];"
                 ::"r"(dst), "l"(m), "r"(bar), "r"(c0), "r"(c1) : "memory");
}
#define ELECT "{\n.reg .pred e;\nelect.sync _|e, 0xffffffff;\n@e "
__device__ __forceinline__ void w_expect_tx(uint32_t bar, uint32_t bytes) {
    asm volatile(ELECT "mbarrier.arrive.expect_tx.shared::cta.b64 _, [%0], %1;\n}\n" ::"r"(bar), "r"(bytes) : "memory");
}
__device__ __forceinline__ void w_tma_load(uint32_t dst, const CUtensorMap* m, int c0, int c1, uint32_t bar) {
    asm volatile(ELECT "cp.async.bulk.tensor.2d.shared::cluster.global.mbarrier::complete_tx::bytes [%0], [%1, {%3, %4}], [%2];\n}\n"
                 ::"r"(dst), "l"(m), "r"(bar), "r"(c0), "r"(c1) : "memory");
}
__device__ __forceinline__ void w_tma_load_mc(uint32_t dst, const CUtensorMap* m, int c0, int c1, uint32_t bar) {
    asm volatile(ELECT "cp.async.bulk.tensor.2d.shared::cluster.global.mbarrier::complete_tx::bytes.multicast::cluster [%0], [%1, {%3, %4}], [%2], %5;\n}\n"
                 ::"r"(dst), "l"(m), "r"(bar), "r"(c0), "r"(c1), "h"((uint16_t)3) : "memory");
}
__device__ __forceinline__ void w_tma_prefetch(const CUtensorMap* m, int c0, int c1) {
    asm volatile(ELECT "cp.async.bulk.prefetch.tensor.2d.L2.global [%0, {%1, %2}];\n}\n" ::"l"(m), "r"(c0), "r"(c1) : "memory");
}
__device__ __forceinline__ uint64_t policy_evict_first() {
    uint64_t p;
    asm("createpolicy.fractional.L2::evict_first.b64 %0, 1.0;" : "=l"(p));
    return p;
}
__device__ __forceinline__ void tma_load_stream(uint32_t dst, const CUtensorMap* m, int c0, int c1, uint32_t bar) {
    asm volatile("cp.async.bulk.tensor.2d.shared::cluster.global.mbarrier::complete_tx::bytes.L2::cache_hint [%0], [%1, {%3, %4}], [%2], %5;"
                 ::"r"(dst), "l"(m), "r"(bar), "r"(c0), "r"(c1), "l"(policy_evict_first()) : "memory");
}
__device__ __forceinline__ uint4 ldg_stream(const void* p) {
    uint4 v;
    asm volatile("ld.global.nc.L2::cache_hint.v4.b32 {%0, %1, %2, %3}, [%4], %5;" : "=r"(v.x), "=r"(v.y), "=r"(v.z), "=r"(v.w) : "l"(p), "l"(policy_evict_first()));
    return v;
}
__device__ __forceinline__ void prefetch_map(const CUtensorMap* m) {
    asm volatile("prefetch.tensormap [%0];" ::"l"(m) : "memory");
}
__device__ __forceinline__ void cluster_arrive() { asm volatile("barrier.cluster.arrive.relaxed.aligned;" ::: "memory"); }
__device__ __forceinline__ void cluster_wait() { asm volatile("barrier.cluster.wait.aligned;" ::: "memory"); }
__device__ __forceinline__ void named_sync(int id, int n) { asm volatile("bar.sync %0, %1;" ::"r"(id), "r"(n) : "memory"); }
__device__ __forceinline__ void named_arrive(int id, int n) { asm volatile("bar.arrive %0, %1;" ::"r"(id), "r"(n) : "memory"); }

__device__ __forceinline__ void flag_add(int f) {
    asm volatile("fence.acq_rel.gpu;\nred.relaxed.gpu.global.add.u32 [%0], 1;" ::"l"(g_flags + f * 8) : "memory");
}
template <int SLEEP>
__device__ __forceinline__ void flag_wait(int f, uint32_t target) {
    asm volatile(
        "{\n.reg .pred p;\n.reg .b32 c, v;\n"
        "mov.b32 c, 0;\n"
        "FLOOP:\n"
        "ld.acquire.gpu.global.u32 v, [%0];\n"
        "sub.u32 v, v, %1;\n"
        "setp.ge.s32 p, v, 0;\n"
        "@p bra FDONE;\n"
        "nanosleep.u32 %2;\n"
        "add.u32 c, c, 1;\n"
        "setp.lt.u32 p, c, 0x400000;\n"
        "@p bra FLOOP;\n"
        "trap;\n"
        "FDONE:\n}\n" ::"l"(g_flags + f * 8), "r"(target), "n"(SLEEP) : "memory");
}
__device__ __forceinline__ uint32_t read_epoch() {
    uint32_t e;
    asm volatile("ld.relaxed.gpu.global.u32 %0, [%1];" : "=r"(e) : "l"(g_flags + F_EXIT * 8) : "memory");
    return e / NCTA;
}
__device__ __forceinline__ void fence_proxy_async() { asm volatile("fence.proxy.async;" ::: "memory"); }

__device__ __forceinline__ void wgmma_fence() { asm volatile("wgmma.fence.sync.aligned;" ::: "memory"); }
__device__ __forceinline__ void wgmma_commit() { asm volatile("wgmma.commit_group.sync.aligned;" ::: "memory"); }
template <int N>
__device__ __forceinline__ void wgmma_wait() { asm volatile("wgmma.wait_group.sync.aligned %0;" ::"n"(N) : "memory"); }
template <int N>
__device__ __forceinline__ void fence_regs(float (&d)[N]) {
#pragma unroll
    for (int i = 0; i < N; i++) asm volatile("" : "+f"(d[i])::"memory");
}
template <int N>
__device__ __forceinline__ void fence_regs(uint32_t (&d)[N]) {
#pragma unroll
    for (int i = 0; i < N; i++) asm volatile("" : "+r"(d[i])::"memory");
}

template <int TA, int TB>
__device__ __forceinline__ void wgmma_ss_n128(float (&d)[64], uint32_t alo, uint32_t blo, int scale_d) {
    asm volatile("{\n.reg .pred p;\n.reg .b64 da, db;\nsetp.ne.b32 p, %66, 0;\n"
        "mov.b64 da, {%64, %69};\nmov.b64 db, {%65, %69};\n"
        "wgmma.mma_async.sync.aligned.m64n128k16.f32.bf16.bf16 "
        "{%0, %1, %2, %3, %4, %5, %6, %7, %8, %9, %10, %11, %12, %13, %14, %15, %16, %17, %18, %19, %20, %21, %22, %23, %24, %25, %26, %27, %28, %29, %30, %31, %32, %33, %34, %35, %36, %37, %38, %39, %40, %41, %42, %43, %44, %45, %46, %47, %48, %49, %50, %51, %52, %53, %54, %55, %56, %57, %58, %59, %60, %61, %62, %63}, da, db, p, 1, 1, %67, %68;\n}\n"
        :
          "+f"(d[0]), "+f"(d[1]), "+f"(d[2]), "+f"(d[3]), "+f"(d[4]), "+f"(d[5]), "+f"(d[6]), "+f"(d[7]),
          "+f"(d[8]), "+f"(d[9]), "+f"(d[10]), "+f"(d[11]), "+f"(d[12]), "+f"(d[13]), "+f"(d[14]), "+f"(d[15]),
          "+f"(d[16]), "+f"(d[17]), "+f"(d[18]), "+f"(d[19]), "+f"(d[20]), "+f"(d[21]), "+f"(d[22]), "+f"(d[23]),
          "+f"(d[24]), "+f"(d[25]), "+f"(d[26]), "+f"(d[27]), "+f"(d[28]), "+f"(d[29]), "+f"(d[30]), "+f"(d[31]),
          "+f"(d[32]), "+f"(d[33]), "+f"(d[34]), "+f"(d[35]), "+f"(d[36]), "+f"(d[37]), "+f"(d[38]), "+f"(d[39]),
          "+f"(d[40]), "+f"(d[41]), "+f"(d[42]), "+f"(d[43]), "+f"(d[44]), "+f"(d[45]), "+f"(d[46]), "+f"(d[47]),
          "+f"(d[48]), "+f"(d[49]), "+f"(d[50]), "+f"(d[51]), "+f"(d[52]), "+f"(d[53]), "+f"(d[54]), "+f"(d[55]),
          "+f"(d[56]), "+f"(d[57]), "+f"(d[58]), "+f"(d[59]), "+f"(d[60]), "+f"(d[61]), "+f"(d[62]), "+f"(d[63])
        : "r"(alo), "r"(blo), "r"(scale_d), "n"(TA), "n"(TB), "r"(DESC_HI));
}
template <int TA, int TB>
__device__ __forceinline__ void wgmma_ss_n192(float (&d)[96], uint32_t alo, uint32_t blo, int scale_d) {
    asm volatile("{\n.reg .pred p;\n.reg .b64 da, db;\nsetp.ne.b32 p, %98, 0;\n"
        "mov.b64 da, {%96, %101};\nmov.b64 db, {%97, %101};\n"
        "wgmma.mma_async.sync.aligned.m64n192k16.f32.bf16.bf16 "
        "{%0, %1, %2, %3, %4, %5, %6, %7, %8, %9, %10, %11, %12, %13, %14, %15, %16, %17, %18, %19, %20, %21, %22, %23, %24, %25, %26, %27, %28, %29, %30, %31, %32, %33, %34, %35, %36, %37, %38, %39, %40, %41, %42, %43, %44, %45, %46, %47, %48, %49, %50, %51, %52, %53, %54, %55, %56, %57, %58, %59, %60, %61, %62, %63, %64, %65, %66, %67, %68, %69, %70, %71, %72, %73, %74, %75, %76, %77, %78, %79, %80, %81, %82, %83, %84, %85, %86, %87, %88, %89, %90, %91, %92, %93, %94, %95}, da, db, p, 1, 1, %99, %100;\n}\n"
        :
          "+f"(d[0]), "+f"(d[1]), "+f"(d[2]), "+f"(d[3]), "+f"(d[4]), "+f"(d[5]), "+f"(d[6]), "+f"(d[7]),
          "+f"(d[8]), "+f"(d[9]), "+f"(d[10]), "+f"(d[11]), "+f"(d[12]), "+f"(d[13]), "+f"(d[14]), "+f"(d[15]),
          "+f"(d[16]), "+f"(d[17]), "+f"(d[18]), "+f"(d[19]), "+f"(d[20]), "+f"(d[21]), "+f"(d[22]), "+f"(d[23]),
          "+f"(d[24]), "+f"(d[25]), "+f"(d[26]), "+f"(d[27]), "+f"(d[28]), "+f"(d[29]), "+f"(d[30]), "+f"(d[31]),
          "+f"(d[32]), "+f"(d[33]), "+f"(d[34]), "+f"(d[35]), "+f"(d[36]), "+f"(d[37]), "+f"(d[38]), "+f"(d[39]),
          "+f"(d[40]), "+f"(d[41]), "+f"(d[42]), "+f"(d[43]), "+f"(d[44]), "+f"(d[45]), "+f"(d[46]), "+f"(d[47]),
          "+f"(d[48]), "+f"(d[49]), "+f"(d[50]), "+f"(d[51]), "+f"(d[52]), "+f"(d[53]), "+f"(d[54]), "+f"(d[55]),
          "+f"(d[56]), "+f"(d[57]), "+f"(d[58]), "+f"(d[59]), "+f"(d[60]), "+f"(d[61]), "+f"(d[62]), "+f"(d[63]),
          "+f"(d[64]), "+f"(d[65]), "+f"(d[66]), "+f"(d[67]), "+f"(d[68]), "+f"(d[69]), "+f"(d[70]), "+f"(d[71]),
          "+f"(d[72]), "+f"(d[73]), "+f"(d[74]), "+f"(d[75]), "+f"(d[76]), "+f"(d[77]), "+f"(d[78]), "+f"(d[79]),
          "+f"(d[80]), "+f"(d[81]), "+f"(d[82]), "+f"(d[83]), "+f"(d[84]), "+f"(d[85]), "+f"(d[86]), "+f"(d[87]),
          "+f"(d[88]), "+f"(d[89]), "+f"(d[90]), "+f"(d[91]), "+f"(d[92]), "+f"(d[93]), "+f"(d[94]), "+f"(d[95])
        : "r"(alo), "r"(blo), "r"(scale_d), "n"(TA), "n"(TB), "r"(DESC_HI));
}
template <int TB>
__device__ __forceinline__ void wgmma_rs_n128(float (&d)[64], uint32_t a0, uint32_t a1, uint32_t a2, uint32_t a3, uint32_t blo, int scale_d) {
    asm volatile("{\n.reg .pred p;\n.reg .b64 db;\nsetp.ne.b32 p, %69, 0;\n"
        "mov.b64 db, {%68, %71};\n"
        "wgmma.mma_async.sync.aligned.m64n128k16.f32.bf16.bf16 "
        "{%0, %1, %2, %3, %4, %5, %6, %7, %8, %9, %10, %11, %12, %13, %14, %15, %16, %17, %18, %19, %20, %21, %22, %23, %24, %25, %26, %27, %28, %29, %30, %31, %32, %33, %34, %35, %36, %37, %38, %39, %40, %41, %42, %43, %44, %45, %46, %47, %48, %49, %50, %51, %52, %53, %54, %55, %56, %57, %58, %59, %60, %61, %62, %63}, {%64, %65, %66, %67}, db, p, 1, 1, %70;\n}\n"
        :
          "+f"(d[0]), "+f"(d[1]), "+f"(d[2]), "+f"(d[3]), "+f"(d[4]), "+f"(d[5]), "+f"(d[6]), "+f"(d[7]),
          "+f"(d[8]), "+f"(d[9]), "+f"(d[10]), "+f"(d[11]), "+f"(d[12]), "+f"(d[13]), "+f"(d[14]), "+f"(d[15]),
          "+f"(d[16]), "+f"(d[17]), "+f"(d[18]), "+f"(d[19]), "+f"(d[20]), "+f"(d[21]), "+f"(d[22]), "+f"(d[23]),
          "+f"(d[24]), "+f"(d[25]), "+f"(d[26]), "+f"(d[27]), "+f"(d[28]), "+f"(d[29]), "+f"(d[30]), "+f"(d[31]),
          "+f"(d[32]), "+f"(d[33]), "+f"(d[34]), "+f"(d[35]), "+f"(d[36]), "+f"(d[37]), "+f"(d[38]), "+f"(d[39]),
          "+f"(d[40]), "+f"(d[41]), "+f"(d[42]), "+f"(d[43]), "+f"(d[44]), "+f"(d[45]), "+f"(d[46]), "+f"(d[47]),
          "+f"(d[48]), "+f"(d[49]), "+f"(d[50]), "+f"(d[51]), "+f"(d[52]), "+f"(d[53]), "+f"(d[54]), "+f"(d[55]),
          "+f"(d[56]), "+f"(d[57]), "+f"(d[58]), "+f"(d[59]), "+f"(d[60]), "+f"(d[61]), "+f"(d[62]), "+f"(d[63])
        : "r"(a0), "r"(a1), "r"(a2), "r"(a3), "r"(blo), "r"(scale_d), "n"(TB), "r"(DESC_HI));
}
template <int TB>
__device__ __forceinline__ void wgmma_rs_n128_z(float (&d)[64], uint32_t a0, uint32_t a1, uint32_t a2, uint32_t a3, uint32_t blo) {
    asm volatile("{\n.reg .pred p;\n.reg .b64 db;\nsetp.ne.b32 p, %69, 0;\n"
        "mov.b64 db, {%68, %71};\n"
        "wgmma.mma_async.sync.aligned.m64n128k16.f32.bf16.bf16 "
        "{%0, %1, %2, %3, %4, %5, %6, %7, %8, %9, %10, %11, %12, %13, %14, %15, %16, %17, %18, %19, %20, %21, %22, %23, %24, %25, %26, %27, %28, %29, %30, %31, %32, %33, %34, %35, %36, %37, %38, %39, %40, %41, %42, %43, %44, %45, %46, %47, %48, %49, %50, %51, %52, %53, %54, %55, %56, %57, %58, %59, %60, %61, %62, %63}, {%64, %65, %66, %67}, db, p, 1, 1, %70;\n}\n"
        :
          "=f"(d[0]), "=f"(d[1]), "=f"(d[2]), "=f"(d[3]), "=f"(d[4]), "=f"(d[5]), "=f"(d[6]), "=f"(d[7]),
          "=f"(d[8]), "=f"(d[9]), "=f"(d[10]), "=f"(d[11]), "=f"(d[12]), "=f"(d[13]), "=f"(d[14]), "=f"(d[15]),
          "=f"(d[16]), "=f"(d[17]), "=f"(d[18]), "=f"(d[19]), "=f"(d[20]), "=f"(d[21]), "=f"(d[22]), "=f"(d[23]),
          "=f"(d[24]), "=f"(d[25]), "=f"(d[26]), "=f"(d[27]), "=f"(d[28]), "=f"(d[29]), "=f"(d[30]), "=f"(d[31]),
          "=f"(d[32]), "=f"(d[33]), "=f"(d[34]), "=f"(d[35]), "=f"(d[36]), "=f"(d[37]), "=f"(d[38]), "=f"(d[39]),
          "=f"(d[40]), "=f"(d[41]), "=f"(d[42]), "=f"(d[43]), "=f"(d[44]), "=f"(d[45]), "=f"(d[46]), "=f"(d[47]),
          "=f"(d[48]), "=f"(d[49]), "=f"(d[50]), "=f"(d[51]), "=f"(d[52]), "=f"(d[53]), "=f"(d[54]), "=f"(d[55]),
          "=f"(d[56]), "=f"(d[57]), "=f"(d[58]), "=f"(d[59]), "=f"(d[60]), "=f"(d[61]), "=f"(d[62]), "=f"(d[63])
        : "r"(a0), "r"(a1), "r"(a2), "r"(a3), "r"(blo), "n"(0), "n"(TB), "r"(DESC_HI));
}
template <int TA, int TB>
__device__ __forceinline__ void wgmma_ss_n128_z(float (&d)[64], uint32_t alo, uint32_t blo) {
    asm volatile("{\n.reg .pred p;\n.reg .b64 da, db;\nsetp.ne.b32 p, %66, 0;\n"
        "mov.b64 da, {%64, %69};\nmov.b64 db, {%65, %69};\n"
        "wgmma.mma_async.sync.aligned.m64n128k16.f32.bf16.bf16 "
        "{%0, %1, %2, %3, %4, %5, %6, %7, %8, %9, %10, %11, %12, %13, %14, %15, %16, %17, %18, %19, %20, %21, %22, %23, %24, %25, %26, %27, %28, %29, %30, %31, %32, %33, %34, %35, %36, %37, %38, %39, %40, %41, %42, %43, %44, %45, %46, %47, %48, %49, %50, %51, %52, %53, %54, %55, %56, %57, %58, %59, %60, %61, %62, %63}, da, db, p, 1, 1, %67, %68;\n}\n"
        :
          "=f"(d[0]), "=f"(d[1]), "=f"(d[2]), "=f"(d[3]), "=f"(d[4]), "=f"(d[5]), "=f"(d[6]), "=f"(d[7]),
          "=f"(d[8]), "=f"(d[9]), "=f"(d[10]), "=f"(d[11]), "=f"(d[12]), "=f"(d[13]), "=f"(d[14]), "=f"(d[15]),
          "=f"(d[16]), "=f"(d[17]), "=f"(d[18]), "=f"(d[19]), "=f"(d[20]), "=f"(d[21]), "=f"(d[22]), "=f"(d[23]),
          "=f"(d[24]), "=f"(d[25]), "=f"(d[26]), "=f"(d[27]), "=f"(d[28]), "=f"(d[29]), "=f"(d[30]), "=f"(d[31]),
          "=f"(d[32]), "=f"(d[33]), "=f"(d[34]), "=f"(d[35]), "=f"(d[36]), "=f"(d[37]), "=f"(d[38]), "=f"(d[39]),
          "=f"(d[40]), "=f"(d[41]), "=f"(d[42]), "=f"(d[43]), "=f"(d[44]), "=f"(d[45]), "=f"(d[46]), "=f"(d[47]),
          "=f"(d[48]), "=f"(d[49]), "=f"(d[50]), "=f"(d[51]), "=f"(d[52]), "=f"(d[53]), "=f"(d[54]), "=f"(d[55]),
          "=f"(d[56]), "=f"(d[57]), "=f"(d[58]), "=f"(d[59]), "=f"(d[60]), "=f"(d[61]), "=f"(d[62]), "=f"(d[63])
        : "r"(alo), "r"(blo), "n"(0), "n"(TA), "n"(TB), "r"(DESC_HI));
}

__device__ __forceinline__ uint32_t pack_bf16(float lo, float hi) {
    uint32_t r;
    asm("cvt.rn.bf16x2.f32 %0, %1, %2;" : "=r"(r) : "f"(hi), "f"(lo));
    return r;
}
__device__ __forceinline__ uint32_t add_bf16x2(uint32_t a, uint32_t b) {
    uint32_t r;
    asm("add.rn.bf16x2 %0, %1, %2;" : "=r"(r) : "r"(a), "r"(b));
    return r;
}
__device__ __forceinline__ float bf_lo(uint32_t v) { return __uint_as_float(v << 16); }
__device__ __forceinline__ float bf_hi(uint32_t v) { return __uint_as_float(v & 0xffff0000u); }
__device__ __forceinline__ float round_bf16(float v) { return __bfloat162float(__float2bfloat16_rn(v)); }
__device__ __forceinline__ float ex2(float x) {
    float y;
    asm("ex2.approx.ftz.f32 %0, %1;" : "=f"(y) : "f"(x));
    return y;
}
__device__ __forceinline__ float rcp(float x) {
    float y;
    asm("rcp.approx.ftz.f32 %0, %1;" : "=f"(y) : "f"(x));
    return y;
}
__device__ __forceinline__ void stg128(void* p, uint32_t a, uint32_t b, uint32_t c, uint32_t d) {
    asm volatile("st.global.v4.b32 [%0], {%1, %2, %3, %4};" ::"l"(p), "r"(a), "r"(b), "r"(c), "r"(d) : "memory");
}
__device__ __forceinline__ int perm_row(int t) { return (t & ~255) | (((0x78 >> (((t >> 6) & 3) * 2)) & 3) << 6) | (t & 63); }
__device__ __forceinline__ int unperm_row(int t) { return (t & ~255) | (((0x9C >> (((t >> 6) & 3) * 2)) & 3) << 6) | (t & 63); }

#define PROF(i)
#define PROFG(i)
#define PROFDUMP()
#define TR(i)
#define BP(r, i)
#define LP(i)

template <int I>
__device__ __forceinline__ void store_chunk(const float (&a)[64], __nv_bfloat16* row0, __nv_bfloat16* row1, float s0, float s1) {
    stg128(row0 + 32 * I, pack_bf16(a[16 * I + 0] * s0, a[16 * I + 1] * s0), pack_bf16(a[16 * I + 4] * s0, a[16 * I + 5] * s0),
           pack_bf16(a[16 * I + 8] * s0, a[16 * I + 9] * s0), pack_bf16(a[16 * I + 12] * s0, a[16 * I + 13] * s0));
    stg128(row1 + 32 * I, pack_bf16(a[16 * I + 2] * s1, a[16 * I + 3] * s1), pack_bf16(a[16 * I + 6] * s1, a[16 * I + 7] * s1),
           pack_bf16(a[16 * I + 10] * s1, a[16 * I + 11] * s1), pack_bf16(a[16 * I + 14] * s1, a[16 * I + 15] * s1));
}
template <int I>
struct IntT { static constexpr int value = I; };
template <class F>
__device__ __forceinline__ void for4(F f) { f(IntT<0>{}); f(IntT<1>{}); f(IntT<2>{}); f(IntT<3>{}); }

struct Prod {
    uint32_t smem, bars;
    uint32_t bo, par;
    uint32_t dst, fb;
    __device__ __forceinline__ void acquire(uint32_t o, uint32_t parity, uint32_t bytes) {
        mbar_wait(bars + BAR_EMPTY + o, parity);
        fb = bars + BAR_FULL + o;
        dst = smem + o * (SLOT / 8);
        w_expect_tx(fb, bytes);
    }
    __device__ __forceinline__ void next(uint32_t bytes) {
        acquire(bo, par, bytes);
        const bool wrap = bo == (NSLOT - 1) * 8;
        bo = wrap ? 0u : bo + 8;
        par ^= wrap ? 1u : 0u;
    }
};

__device__ __forceinline__ int item_p(int ca, int rd) {
    const int v = (rd & 1) ? (ca + 4) & 7 : ca;
    return (rd & 2) ? 7 - v : v;
}
__device__ __forceinline__ int kv_round(int i) { return (KVORDER >> (4 * i)) & 3; }
__device__ __forceinline__ int slot_a(int i) { return (0x5310 >> (4 * i)) & 15; }
__device__ __forceinline__ int slot_w(int m) { return (0x264 >> (4 * m)) & 15; }

__device__ __forceinline__ void producer(const Params& P, uint32_t smem, uint32_t bars, int ca, int cb, int rank) {
    Prod pr{smem, bars, 0u, 0u, 0u, 0u};
    {
        int m = 0;
        uint32_t lap = 1;
#pragma unroll 1
        for (int u = 0; u < 32; u++) {
            if (u >= 3) {
                const int v = (u == 3) ? 3 + ca : u + 7;
                if (v < 32 && (u == 3 || (v & 7) == ca)) w_tma_prefetch((v & 4) ? &P.wuv : &P.wuk, (cb + 8 * kv_round(v >> 3)) * 128 + rank * 64, (v & 3) * 128);
                if (u == 24) {
                    w_tma_prefetch(&P.wq, cb * 128 + rank * 64, ca * 64);
                    if (ca < 2) w_tma_prefetch(&P.wq, cb * 128 + rank * 64, (ca + 8) * 64);
                }
            }
            pr.acquire(slot_w(m) * 8, lap ^ (m >> 1), SLOT);
            lap ^= m >> 1;
            m = (m == 2) ? 0 : m + 1;
            TR(1 + u);
            w_tma_load_mc(pr.dst + rank * 16384, (u & 4) ? &P.wuv : &P.wuk, (cb + 8 * kv_round(u >> 3)) * 128 + rank * 64, (u & 3) * 128, pr.fb);
            if (u < 3) {
                pr.acquire(slot_a(u + 1) * 8, 1, SLOT);
                w_tma_load(pr.dst, &P.ckv, u * 128 + 128, (2 * ca + rank) * 128, pr.fb);
                w_tma_load(pr.dst + 16384, &P.ckv, u * 128 + 192, (2 * ca + rank) * 128, pr.fb);
            }
        }
    }
    PROF(1);
    mbar_wait(bars + BAR_DEP, 0);
#pragma unroll 1
    for (int rd = 0; rd < 4; rd++) {
        const int h = 8 * rd + cb, p = item_p(ca, rd);
#pragma unroll 1
        for (int ks = 0; ks < 10; ks++) {
            pr.next(SLOT);
            w_tma_load_mc(pr.dst + 16384 + rank * 8192, &P.wq, h * 128 + rank * 64, ks * 64, pr.fb);
            w_tma_load(pr.dst, &P.xn, ks * 64, 256 * p + 128 * rank, pr.fb);
        }
        PROF(8 + rd * 4);
        mbar_wait(bars + BAR_DEP + (1 + rd) * 8, 0);
        const int last = 4 * p + 3, top = h * 32 + last;
#pragma unroll 1
        for (int i = 0; i <= last; i++) {
            const int t = (i == 0) ? top - 1 : (i == last) ? h * 32 + 1 : (i & 1) ? top - 2 - i : top + 2 - i;
            pr.next(SLOT);
            w_tma_load_mc(pr.dst + rank * 16384, &P.kv, rank * 64, t * 128, pr.fb);
            if (i == 2) {
                if (rd < 3) {
                    w_tma_prefetch(&P.wq, (h + 8) * 128 + rank * 64, ca * 64);
                    if (ca < 2) w_tma_prefetch(&P.wq, (h + 8) * 128 + rank * 64, (ca + 8) * 64);
                } else {
#pragma unroll 1
                    for (int j = 0; j < 10; j++) {
                        const int tt = ca + (j >= 5 ? 8 : 0);
                        w_tma_prefetch(&P.wo, 320 * (cb & 1) + 64 * (j >= 5 ? j - 5 : j), (8 * (tt >> 2) + (cb & 6) + ((tt >> 1) & 1)) * 128 + (tt & 1) * 64 + rank * 32);
                    }
                }
            }
        }
        PROF(9 + rd * 4);
    }
    {
        const int n0 = 320 * (cb & 1), kg = cb >> 1;
#pragma unroll 1
        for (int t = 0; t < 16; t++) {
            const int h = 8 * (t >> 2) + 2 * kg + ((t >> 1) & 1), ks = t & 1;
            const int krow = h * 128 + ks * 64 + rank * 32;
            pr.next(SLOT);
            w_tma_load_mc(pr.dst + 16384 + rank * 8192, &P.wo, n0, krow, pr.fb);
            w_tma_load_mc(pr.dst + 16384 + rank * 8192 + 4096, &P.wo, n0 + 64, krow, pr.fb);
            mbar_wait(bars + BAR_DEP + (5 + (t >> 1)) * 8, 0);
            w_tma_load(pr.dst, &P.ctx, ks * 64, h * SEQ + 256 * ca + 128 * rank, pr.fb);
            pr.next(24576);
#pragma unroll
            for (int c = 0; c < 3; c++) w_tma_load_mc(pr.dst + rank * 12288 + c * 4096, &P.wo, n0 + 128 + 64 * c, krow, pr.fb);
        }
    }
}

struct Slot {
    uint32_t bo, dl, par;
};
struct Cons {
    uint32_t bars, rel;
    uint32_t dl0;
    uint32_t lane;
    Slot cur;
    __device__ __forceinline__ Slot slot(int s, uint32_t par) const { return Slot{(uint32_t)s * 8, dl0 + (uint32_t)s * (SLOT >> 4), par}; }
    __device__ __forceinline__ void wait(const Slot& s) const { mbar_wait(bars + BAR_FULL + s.bo, s.par); }
    __device__ __forceinline__ void release(uint32_t bo) const {
        asm volatile("{\n.reg .pred p;\nsetp.lt.u32 p, %1, 2;\n@p mbarrier.arrive.shared::cluster.b64 _, [%0];\n}\n" ::"r"(rel + bo), "r"(lane) : "memory");
    }
    __device__ __forceinline__ Slot next() {
        const Slot s = cur;
        const bool wrap = s.bo == (NSLOT - 1) * 8;
        cur.bo = wrap ? 0u : s.bo + 8;
        cur.dl = wrap ? dl0 : s.dl + (SLOT >> 4);
        cur.par = s.par ^ (wrap ? 1u : 0u);
        return s;
    }
};
__host__ __device__ constexpr uint32_t lbo(uint32_t bytes) { return (bytes >> 4) << 16; }

__device__ __forceinline__ float div640(float x) {
    const float q = x * (1.0f / DM);
    return fmaf(fmaf(-q, (float)DM, x), 1.0f / DM, q);
}
__device__ __forceinline__ float sqrt_approx(float x) {
    float y;
    asm("sqrt.approx.ftz.f32 %0, %1;" : "=f"(y) : "f"(x));
    return y;
}
struct LayerNorm {
    uint4 xv[5], wv[5];
    float mean, inv, r;
    static __device__ __forceinline__ float half_sum(float v) {
#pragma unroll
        for (int o = 8; o > 0; o >>= 1) v += __shfl_xor_sync(0xffffffffu, v, o);
        return v;
    }
    __device__ __forceinline__ void load(const __nv_bfloat16* x, const __nv_bfloat16* wr, int t, int l) {
#pragma unroll
        for (int i = 0; i < 5; i++) {
            xv[i] = ldg_stream(reinterpret_cast<const uint4*>(x + t * DM) + l + 16 * i);
            wv[i] = __ldg(reinterpret_cast<const uint4*>(wr) + l + 16 * i);
        }
    }
    __device__ __forceinline__ void stat1() {
        float a[4] = {0.f, 0.f, 0.f, 0.f};
#pragma unroll
        for (int i = 0; i < 20; i++) { const uint32_t u = (&xv[i >> 2].x)[i & 3]; a[i & 3] += bf_lo(u) + bf_hi(u); }
        mean = div640(half_sum((a[0] + a[1]) + (a[2] + a[3])));
        r = 0.f;
    }
    template <int H>
    __device__ __forceinline__ void stat2() {
        float a[4] = {r, 0.f, 0.f, 0.f};
#pragma unroll
        for (int i = H ? 12 : 0; i < (H ? 20 : 12); i++) {
            uint32_t u = (&xv[i >> 2].x)[i & 3];
            asm volatile("" : "+r"(u));
            const float d0 = bf_lo(u) - mean, d1 = bf_hi(u) - mean;
            a[i & 3] = fmaf(d0, d0, fmaf(d1, d1, a[i & 3]));
        }
        r = (a[0] + a[1]) + (a[2] + a[3]);
        if (H) {
            inv = rcp(round_bf16(sqrt_approx(round_bf16(round_bf16(div640(half_sum(r))) + 1e-5f))));
            r = 0.f;
        }
    }
    template <int I>
    __device__ __forceinline__ void piece(int t, int l) {
        const uint32_t nmb = pack_bf16(-mean, -mean);
        uint32_t o[4], z[4];
        float a[4];
#pragma unroll
        for (int j = 0; j < 4; j++) {
            const uint32_t u = (&xv[I].x)[j], w = (&wv[I].x)[j];
            const uint32_t d = add_bf16x2(u, nmb);
            o[j] = pack_bf16(bf_lo(d) * inv, bf_hi(d) * inv);
            z[j] = add_bf16x2(u, o[j]);
            a[j] = fmaf(bf_hi(o[j]), bf_hi(w), bf_lo(o[j]) * bf_lo(w));
        }
        r += (a[0] + a[1]) + (a[2] + a[3]);
        stg128(g_xn + perm_row(t) * DM + 8 * (l + 16 * I), o[0], o[1], o[2], o[3]);
        stg128(g_res + t * DM + 8 * (l + 16 * I), z[0], z[1], z[2], z[3]);
        if (I == 4) {
            r = half_sum(r);
            if (l == 0) g_r[t] = round_bf16(r);
        }
    }
};

constexpr float SM_SCALE = 0.08838834764831845f * 1.4426950408889634f;

template <int J0, int J1>
__device__ __forceinline__ void exp_part(float (&s)[64], float n0, float n1, float& r0, float& r1) {
    float a1 = 0.f, b1 = 0.f;
#pragma unroll
    for (int j = J0; j < J1; j++) {
        s[4 * j + 0] = ex2(fmaf(s[4 * j + 0], SM_SCALE, n0));
        s[4 * j + 1] = ex2(fmaf(s[4 * j + 1], SM_SCALE, n0));
        s[4 * j + 2] = ex2(fmaf(s[4 * j + 2], SM_SCALE, n1));
        s[4 * j + 3] = ex2(fmaf(s[4 * j + 3], SM_SCALE, n1));
        r0 += s[4 * j + 0]; r1 += s[4 * j + 2];
        if (j == J0) { a1 = s[4 * j + 1]; b1 = s[4 * j + 3]; } else { a1 += s[4 * j + 1]; b1 += s[4 * j + 3]; }
    }
    r0 += a1;
    r1 += b1;
}
__device__ __forceinline__ void sched_barrier(float x, float y, uint32_t scratch) {
    asm volatile("{\n.reg .pred p;\nsetp.lt.f32 p, %0, 0f00000000;\n@p st.shared.f32 [%2], %1;\n}\n" ::"f"(x), "f"(y), "r"(scratch) : "memory");
}
__device__ __forceinline__ void pack_tile(const float (&s)[64], uint32_t (&p)[32]) {
#pragma unroll
    for (int i = 0; i < 32; i++) p[i] = pack_bf16(s[2 * i], s[2 * i + 1]);
}
template <bool ZERO>
__device__ __forceinline__ void gemm_rs(float (&d)[64], const uint32_t (&a)[32], uint32_t dl, int acc = 1) {
    const uint32_t b = dl + lbo(16384);
    if (ZERO) wgmma_rs_n128_z<1>(d, a[0], a[1], a[2], a[3], b);
#pragma unroll
    for (int k = ZERO ? 1 : 0; k < 8; k++) wgmma_rs_n128<1>(d, a[4 * k], a[4 * k + 1], a[4 * k + 2], a[4 * k + 3], b + k * 128, k ? 1 : acc);
}
template <int ZERO>
__device__ __forceinline__ void gemm_q(float (&d)[64], uint32_t dl, int role) {
    const uint32_t a = dl + role * 512 + lbo(16), b = dl + 1024 + lbo(8192);
    if (ZERO) wgmma_ss_n128_z<0, 1>(d, a, b);
#pragma unroll
    for (int k = ZERO ? 1 : 0; k < 4; k++) wgmma_ss_n128<0, 1>(d, a + k * 2, b + k * 128, 1);
}
template <bool KT, bool ZERO, int K0, int K1>
__device__ __forceinline__ void gemm_kv(float (&d)[64], uint32_t ckv, uint32_t wt, int wg) {
    if (KT) {
        const uint32_t a = wt + wg * 1024 + lbo(16), b = ckv + lbo(16);
        if (ZERO) wgmma_ss_n128_z<1, 0>(d, a, b);
#pragma unroll
        for (int k = ZERO ? 1 : K0; k < K1; k++) wgmma_ss_n128<1, 0>(d, a + k * 128, b + (k >> 2) * 1024 + (k & 3) * 2, 1);
    } else {
        const uint32_t a = ckv + wg * 512 + lbo(16), b = wt + lbo(16384);
        if (ZERO) wgmma_ss_n128_z<0, 1>(d, a, b);
#pragma unroll
        for (int k = ZERO ? 1 : K0; k < K1; k++) wgmma_ss_n128<0, 1>(d, a + (k >> 2) * 1024 + (k & 3) * 2, b + k * 128, 1);
    }
}
__device__ __forceinline__ void mma16816(float& d0, float& d1, float& d2, float& d3, uint32_t a0, uint32_t a1, uint32_t a2, uint32_t a3, uint32_t b0, uint32_t b1) {
    asm volatile("mma.sync.aligned.m16n8k16.row.col.f32.bf16.bf16.f32 {%0,%1,%2,%3}, {%4,%5,%6,%7}, {%8,%9}, {%0,%1,%2,%3};"
                 : "+f"(d0), "+f"(d1), "+f"(d2), "+f"(d3) : "r"(a0), "r"(a1), "r"(a2), "r"(a3), "r"(b0), "r"(b1));
}
__device__ __forceinline__ uint32_t ld_pair(const __nv_bfloat16* p) {
    const unsigned short* u = reinterpret_cast<const unsigned short*>(p);
    return (uint32_t)__ldcg(u) | ((uint32_t)__ldcg(u + 128) << 16);
}
__device__ __forceinline__ void attention_exact(float (&o)[64], const uint32_t (&qf)[32], float& l0, float& l1, int h, int nblk, int rr, int lane) {
    const int q = lane & 3, lr = lane >> 2;
    float m0 = -INFINITY, m1 = -INFINITY;
    l0 = 0.f; l1 = 0.f;
#pragma unroll
    for (int i = 0; i < 64; i++) o[i] = 0.f;
#pragma unroll 1
    for (int cidx = 0; cidx < nblk * 8; cidx++) {
        const int kc = cidx & 7;
        const __nv_bfloat16* kt = g_kv + (size_t)((h * 16 + (cidx >> 3)) * 2) * 16384;
        float sc[8];
#pragma unroll
        for (int i = 0; i < 8; i++) sc[i] = 0.f;
#pragma unroll
        for (int kk = 0; kk < 8; kk++)
#pragma unroll
            for (int nt = 0; nt < 2; nt++) {
                const __nv_bfloat16* b = kt + (16 * kk + 2 * q) * 128 + 16 * kc + 8 * nt + lr;
                mma16816(sc[4 * nt], sc[4 * nt + 1], sc[4 * nt + 2], sc[4 * nt + 3], qf[4 * kk], qf[4 * kk + 1], qf[4 * kk + 2], qf[4 * kk + 3],
                         ld_pair(b), ld_pair(b + 8 * 128));
            }
        const int lim = rr + ((nblk - 1) - (cidx >> 3)) * 128 - 32 * (kc >> 1) - 4 * (kc & 1);
#pragma unroll
        for (int i = 0; i < 8; i++)
            if (2 * (i >> 2) + (i & 1) > lim + 4 * (i & 2)) sc[i] = -INFINITY;
        float x0 = fmaxf(fmaxf(sc[0], sc[1]), fmaxf(sc[4], sc[5])), x1 = fmaxf(fmaxf(sc[2], sc[3]), fmaxf(sc[6], sc[7]));
        x0 = fmaxf(x0, __shfl_xor_sync(0xffffffffu, x0, 1)); x1 = fmaxf(x1, __shfl_xor_sync(0xffffffffu, x1, 1));
        x0 = fmaxf(x0, __shfl_xor_sync(0xffffffffu, x0, 2)); x1 = fmaxf(x1, __shfl_xor_sync(0xffffffffu, x1, 2));
        x0 = fmaxf(x0, m0); x1 = fmaxf(x1, m1);
        const float a0 = ex2((m0 - x0) * SM_SCALE), a1 = ex2((m1 - x1) * SM_SCALE);
        m0 = x0; m1 = x1;
#pragma unroll
        for (int i = 0; i < 8; i++) sc[i] = ex2((sc[i] - ((i & 2) ? m1 : m0)) * SM_SCALE);
        l0 = l0 * a0 + (sc[0] + sc[1]) + (sc[4] + sc[5]);
        l1 = l1 * a1 + (sc[2] + sc[3]) + (sc[6] + sc[7]);
        const uint32_t p0 = pack_bf16(sc[0], sc[1]), p1 = pack_bf16(sc[2], sc[3]), p2 = pack_bf16(sc[4], sc[5]), p3 = pack_bf16(sc[6], sc[7]);
        const __nv_bfloat16* vb = kt + 16384 + (16 * kc + 2 * q) * 128 + lr;
#pragma unroll
        for (int nt = 0; nt < 16; nt++) {
            o[4 * nt] *= a0; o[4 * nt + 1] *= a0; o[4 * nt + 2] *= a1; o[4 * nt + 3] *= a1;
            mma16816(o[4 * nt], o[4 * nt + 1], o[4 * nt + 2], o[4 * nt + 3], p0, p1, p2, p3, ld_pair(vb + 8 * nt), ld_pair(vb + 8 * nt + 8 * 128));
        }
    }
}

__device__ __forceinline__ void signal(uint32_t bars, int wg, int e, int lane) {
    __syncwarp();
    asm volatile("{\n.reg .pred p;\nsetp.eq.u32 p, %1, 0;\n@p mbarrier.arrive.shared::cta.b64 _, [%0];\n}\n" ::"r"(bars + BAR_SIG + (wg * 9 + e) * 8), "r"(lane) : "memory");
}

__device__ __forceinline__ void consumer(const Params& P, uint32_t smem, uint32_t bars, int ca, int cb, int rank, int wg) {
    const int lane = threadIdx.x & 31, w = (threadIdx.x >> 5) & 3, q = lane & 3, lr = lane >> 2;
    PROF(7);
    cluster_wait();
    Cons c{bars, mapa(bars + BAR_EMPTY, lane & 1), (smem & 0x3FFFF) >> 4, (uint32_t)lane, Slot{0u, (smem & 0x3FFFF) >> 4, 1u}};
    PROFG(180);
    PROF(1);
    float o[64], s[64];
    uint32_t pend;
    __nv_bfloat16* ep_ptr;
    int ep_step;
    {
        const int ln_t = blockIdx.x * 16 + wg * 8 + w * 2 + (lane >> 4);
        const int krow = 64 * wg + 16 * w + lr;
        const int vrow = 64 * wg + 32 * (w >> 1) + 8 * (lr >> 1) + 4 * (w & 1) + (lr & 1);
        ep_step = 2 * 128;
        int m = 0;
        uint32_t lap = 0;
        LayerNorm ln;
        auto step = [&](auto kt, auto kc, float (&d)[64], int hh) {
            const Slot sa = c.slot(slot_a(kc.value), 0), sw = c.slot(slot_w(m), lap ^ (m >> 1));
            lap ^= m >> 1;
            m = (m == 2) ? 0 : m + 1;
            TR(1 + (hh * 8 + (kt.value ? 0 : 4) + kc.value) * 2);
            if (kt.value && hh == 0) c.wait(sa);
            c.wait(sw);
            TR(2 + (hh * 8 + (kt.value ? 0 : 4) + kc.value) * 2);
            wgmma_fence();
            gemm_kv<kt.value, kc.value == 0, 0, KVSPLIT>(d, sa.dl, sw.dl, wg);
            wgmma_commit();
            wgmma_wait<1>();
            if (!(kt.value && kc.value == 0 && hh == 0)) c.release(pend);
            if (!kt.value && kc.value > 0 && hh == 3) c.release(slot_a(kc.value - 1) * 8);
            pend = sw.bo;
            wgmma_fence();
            gemm_kv<kt.value, false, KVSPLIT, 8>(d, sa.dl, sw.dl, wg);
            wgmma_commit();
        };
#pragma unroll 1
        for (int hh = 0; hh < 4; hh++) {
            __nv_bfloat16* base = g_kv + (size_t)(((cb + 8 * kv_round(hh)) * 16 + 2 * ca + rank) * 2) * 16384 + 8 * q;
            const bool do_ln = hh == wg * LNSTAG + 1;
            for4([&](auto kc) {
                step(TrueT{}, kc, s, hh);
                if (hh > 0) {
                    if (kc.value == 0) fence_regs(o);
                    store_chunk<kc.value>(o, ep_ptr, ep_ptr + ep_step, 1.f, 1.f);
                }
                if (do_ln) {
                    if (kc.value == 0) ln.stat1();
                    if (kc.value == 1) ln.template stat2<0>();
                    if (kc.value == 2) ln.template stat2<1>();
                    if (kc.value == 3) ln.template piece<0>(ln_t, lane & 15);
                }
            });
            if (hh > 0) signal(bars, wg, hh, lane);
            for4([&](auto kc) {
                step(FalseT{}, kc, o, hh);
                if (kc.value == 0) fence_regs(s);
                store_chunk<kc.value>(s, base + krow * 128, base + (krow + 8) * 128, 1.f, 1.f);
                if (do_ln) ln.template piece<kc.value + 1>(ln_t, lane & 15);
                if (kc.value == 1 && hh == wg * LNSTAG) ln.load(P.x, P.wr, ln_t, lane & 15);
            });
            if (do_ln) signal(bars, wg, 0, lane);
            PROF(24 + hh);
            if (hh == 1) PROFG(181);
            ep_ptr = base + 16384 + vrow * 128;
        }
    }
    PROFG(182);
    PROF(2);
    {
        uint32_t pf[32], qf[32];
        float l0 = 0.25f, l1 = 0.25f;
        const int bar_me = 2 + wg, bar_other = 3 - wg;
#pragma unroll 1
        for (int rd = 0; rd < 4; rd++) {
            const int h = 8 * rd + cb, p = item_p(ca, rd);
            const int role = wg ^ (rd & 1);
            const int nrest = 2 * p + role;
            Slot kfirst;
            {
                auto qstep = [&](auto zero, int ks) {
                    const Slot sl = c.next();
                    BP(2, 4 + 3 * ks);
                    c.wait(sl);
                    BP(2, 5 + 3 * ks);
                    wgmma_fence();
                    gemm_q<zero.value>(s, sl.dl, role);
                    wgmma_commit();
                    wgmma_wait<1>();
                    BP(2, 6 + 3 * ks);
                    c.release(pend);
                    pend = sl.bo;
                };
                qstep(TrueT{}, 0);
                if (rd == 0) c.release(slot_a(3) * 8);
                fence_regs(o);
#pragma unroll 1
                for (int ks = 1; ks < QST; ks++) qstep(FalseT{}, ks);
                for4([&](auto i) {
                    qstep(FalseT{}, QST + i.value);
                    if (i.value == 0) {
                        l0 += __shfl_xor_sync(0xffffffffu, l0, 1); l1 += __shfl_xor_sync(0xffffffffu, l1, 1);
                        l0 += __shfl_xor_sync(0xffffffffu, l0, 2); l1 += __shfl_xor_sync(0xffffffffu, l1, 2);
                        l0 = rcp(l0); l1 = rcp(l1);
                    }
                    store_chunk<i.value>(o, ep_ptr, ep_ptr + ep_step, l0, l1);
                });
                signal(bars, wg, 4 + rd, lane);
                PROF(11 + rd * 4);
#pragma unroll 1
                for (int ks = QST + 4; ks < 10; ks++) qstep(FalseT{}, ks);
                if (!role) { const Slot sl = c.next(); c.wait(sl); c.release(sl.bo); }
                kfirst = c.next();
                c.wait(kfirst);
                wgmma_wait<0>();
                BP(2, 34);
                c.release(pend);
                fence_regs(s);
                pack_tile(s, qf);
            }
            PROF(8 + rd * 4);
            fence_regs(qf);
            BP(2, 35);
            if (PINGPONG && !role) named_sync(bar_me, 256);
            BP(2, 36);
            wgmma_fence();
            gemm_rs<true>(s, qf, kfirst.dl);
            wgmma_commit();
            if (PINGPONG) named_arrive(bar_other, 256);
            BP(2, 37);
            if (!role) { const Slot sl = c.next(); c.wait(sl); c.release(sl.bo); }
            const int dg = __reduce_or_sync(0xffffffffu, 2 * (role ^ rank) + (w >> 1));
            wgmma_wait<0>();
            BP(2, 38);
            fence_regs(s);
            c.release(kfirst.bo);
            float n0, n1;
            l0 = 0.f; l1 = 0.f;
            for4([&](auto a) {
                constexpr int B = 16 * a.value;
                if (a.value == dg) {
                    const int lim = 16 * (w & 1) + lr - 8 * q;
#pragma unroll
                    for (int i = 0; i < 16; i++)
                        if (2 * (i >> 2) + (i & 1) > lim + 4 * (i & 2)) s[B + i] = -INFINITY;
                }
                if (a.value == 0) {
                    n0 = fmaxf(fmaxf(fmaxf(s[0], s[1]), fmaxf(s[4], s[5])), fmaxf(fmaxf(s[8], s[9]), fmaxf(s[12], s[13])));
                    n1 = fmaxf(fmaxf(fmaxf(s[2], s[3]), fmaxf(s[6], s[7])), fmaxf(fmaxf(s[10], s[11]), fmaxf(s[14], s[15])));
                    n0 = fmaxf(n0, __shfl_xor_sync(0xffffffffu, n0, 1)); n1 = fmaxf(n1, __shfl_xor_sync(0xffffffffu, n1, 1));
                    n0 = fmaxf(n0, __shfl_xor_sync(0xffffffffu, n0, 2)); n1 = fmaxf(n1, __shfl_xor_sync(0xffffffffu, n1, 2));
                    n0 *= -SM_SCALE; n1 *= -SM_SCALE;
                }
                if (a.value <= dg) {
                    exp_part<4 * a.value, 4 * a.value + 4>(s, n0, n1, l0, l1);
#pragma unroll
                    for (int i = 0; i < 8; i++) pf[8 * a.value + i] = pack_bf16(s[B + 2 * i], s[B + 2 * i + 1]);
                } else {
#pragma unroll
                    for (int i = 0; i < 8; i++) pf[8 * a.value + i] = 0u;
                }
            });
            PROF(9 + rd * 4);
#pragma unroll 1
            for (int it = 0; it < nrest; it++) {
                const Slot sk = c.next(), sv = c.next();
                LP(0);
                if (it < 3) BP(2, 40 + 4 * it);
                if (it >= nrest - 2) BP(1, 60 + 4 * (it - nrest + 2));
                c.wait(sk);
                c.wait(sv);
                fence_regs(o); fence_regs(pf);
                LP(1);
                if (it < 3) BP(2, 41 + 4 * it);
                if (it >= nrest - 2) BP(1, 61 + 4 * (it - nrest + 2));
                if (PINGPONG) named_sync(bar_me, 256);
                LP(2);
                if (it < 3) BP(2, 42 + 4 * it);
                if (it >= nrest - 2) BP(1, 62 + 4 * (it - nrest + 2));
                wgmma_fence();
                gemm_rs<true>(s, qf, sk.dl);
                wgmma_commit();
                gemm_rs<false>(o, pf, sv.dl, it);
                wgmma_commit();
                if (PINGPONG) named_arrive(bar_other, 256);
                LP(3);
                if (it < 3) BP(2, 43 + 4 * it);
                if (it >= nrest - 2) BP(1, 63 + 4 * (it - nrest + 2));
                wgmma_wait<1>();
                LP(4);
                c.release(sk.bo);
                fence_regs(s);
                exp_part<0, SPLITJ>(s, n0, n1, l0, l1);
                sched_barrier(l0, l1, bars + MISC_OFF + 16);
                LP(5);
                wgmma_wait<0>();
                LP(6);
                c.release(sv.bo);
                fence_regs(o); fence_regs(pf);
                exp_part<SPLITJ, 16>(s, n0, n1, l0, l1);
                pack_tile(s, pf);
            }
            PROF(10 + rd * 4);
            PROFG(183 + rd);
            const Slot sv = c.next();
            BP(1, 0);
            c.wait(sv);
            if (nrest == 0) {
#pragma unroll
                for (int i = 0; i < 64; i++) o[i] = 0.f;
            }
            if (__builtin_expect(__any_sync(0xffffffffu, !(l0 < 0x1p60f && l1 < 0x1p60f)), 0)) {
                attention_exact(o, qf, l0, l1, h, nrest + 1, 64 * (role ^ rank) + 16 * w + lr - 8 * q, lane);
#pragma unroll
                for (int i = 0; i < 32; i++) pf[i] = 0u;
            }
            fence_regs(o); fence_regs(pf);
            BP(1, 1);
            if (PINGPONG && !role) named_sync(bar_me, 256);
            BP(1, 2);
            wgmma_fence();
            gemm_rs<false>(o, pf, sv.dl);
            wgmma_commit();
            BP(1, 3);
            pend = sv.bo;
            ep_ptr = g_ctx + (size_t)(h * SEQ + 256 * p + 128 * rank + 64 * role + 16 * w + lr) * HD + 8 * q;
            ep_step = 8 * HD;
        }
        l0 += __shfl_xor_sync(0xffffffffu, l0, 1); l1 += __shfl_xor_sync(0xffffffffu, l1, 1);
        l0 += __shfl_xor_sync(0xffffffffu, l0, 2); l1 += __shfl_xor_sync(0xffffffffu, l1, 2);
        l0 = rcp(l0); l1 = rcp(l1);
        wgmma_wait<0>();
        c.release(pend);
        fence_regs(o); fence_regs(pf);
        for4([&](auto i) { store_chunk<i.value>(o, ep_ptr, ep_ptr + ep_step, l0, l1); });
        signal(bars, wg, 8, lane);
    }
    PROFG(187);
    PROF(3);
    {
        float a1[64], a2[96];
        uint32_t px = 0, py = 0;
#pragma unroll 1
        for (int t = 0; t < 16; t++) {
            const Slot sx = c.next(), sy = c.next();
            c.wait(sx);
            const uint32_t da = sx.dl + wg * 512 + lbo(16), b1 = sx.dl + 1024 + lbo(4096), b2 = sy.dl + lbo(4096);
            wgmma_fence();
#pragma unroll
            for (int k = 0; k < 4; k++) wgmma_ss_n128<0, 1>(a1, da + k * 2, b1 + (k >> 1) * 512 + (k & 1) * 128, k ? 1 : t);
            wgmma_commit();
            wgmma_wait<1>();
            if (t > 0) { c.release(px); c.release(py); }
            px = sx.bo; py = sy.bo;
            c.wait(sy);
            wgmma_fence();
#pragma unroll
            for (int k = 0; k < 4; k++) wgmma_ss_n192<0, 1>(a2, da + k * 2, b2 + (k >> 1) * 768 + (k & 1) * 128, k ? 1 : t);
            wgmma_commit();
        }
        const int nh = cb & 1, kg = cb >> 1, tile = (ca * 2 + rank) * 2 + nh, tid = threadIdx.x - 128;
        const int goff = (unperm_row(256 * ca + 128 * rank + 64 * wg) + 16 * w + 8 * (kg >> 1)) * (DM / 8) + 40 * nh + 20 * (kg & 1) + lane;
        const uint32_t epoch = read_epoch();
        mbar_wait(bars + BAR_DEP + 13 * 8, 0);
        uint4 rv[5];
#pragma unroll
        for (int i = 0; i < 5; i++) {
            const int r = ((lane + 32 * i) * 205) >> 12;
            rv[i] = __ldcg(reinterpret_cast<const uint4*>(g_res) + (goff + 32 * i + 60 * r));
        }
        wgmma_wait<0>();
        fence_regs(a1); fence_regs(a2);
    PROFG(188);
        PROF(4);
        uint32_t own[20];
#pragma unroll
        for (int g = 0; g < 4; g++) {
            uint32_t pk[20];
#pragma unroll
            for (int i = 0; i < 20; i++) {
                const int j = 20 * (g & 1) + i, e = 2 * (g >> 1);
                pk[i] = (j < 16) ? pack_bf16(a1[4 * (j & 15) + e], a1[4 * (j & 15) + e + 1]) : pack_bf16(a2[4 * (j < 16 ? 0 : j - 16) + e], a2[4 * (j < 16 ? 0 : j - 16) + e + 1]);
                if (g == 0 || g == kg) own[i] = pk[i];
            }
            if (g != kg) {
                uint4* dst = g_part + ((tile * 4 + g) * 4 + kg) * 5 * 256 + tid;
#pragma unroll
                for (int i = 0; i < 5; i++) stg128(dst + i * 256, pk[4 * i], pk[4 * i + 1], pk[4 * i + 2], pk[4 * i + 3]);
            }
        }
        __syncwarp();
        if (lane == 0) {
            flag_add(F_PART + tile * 8 + wg * 4 + w);
            flag_wait<20>(F_PART + tile * 8 + wg * 4 + w, 4u * (epoch + 1));
        }
        __syncwarp();
        PROF(5);
        uint4 in[3][5];
#pragma unroll
        for (int k = 0; k < 3; k++)
#pragma unroll
            for (int i = 0; i < 5; i++) in[k][i] = __ldcg(g_part + ((tile * 4 + kg) * 4 + ((kg + 1 + k) & 3)) * 5 * 256 + i * 256 + tid);
        const uint32_t stage = smem + c.cur.bo * (SLOT / 8) + (wg * 4 + w) * 2688;
#pragma unroll
        for (int i = 0; i < 5; i++) {
            uint32_t r[4];
#pragma unroll
            for (int e = 0; e < 4; e++) {
                const uint32_t u0 = (&in[0][i].x)[e], u1 = (&in[1][i].x)[e], u2 = (&in[2][i].x)[e], u3 = own[4 * i + e];
                r[e] = pack_bf16((bf_lo(u0) + bf_lo(u1)) + (bf_lo(u2) + bf_lo(u3)), (bf_hi(u0) + bf_hi(u1)) + (bf_hi(u2) + bf_hi(u3)));
            }
            asm volatile("stmatrix.sync.aligned.m8n8.x4.shared.b16 [%0], {%1, %2, %3, %4};"
                         ::"r"(stage + (lane & 7) * 336 + (4 * i + (lane >> 3)) * 16), "r"(r[0]), "r"(r[1]), "r"(r[2]), "r"(r[3]) : "memory");
        }
        __syncwarp();
#pragma unroll
        for (int i = 0; i < 5; i++) {
            const int r = ((lane + 32 * i) * 205) >> 12;
            uint4 v;
            asm volatile("ld.shared.v4.b32 {%0, %1, %2, %3}, [%4];" : "=r"(v.x), "=r"(v.y), "=r"(v.z), "=r"(v.w) : "r"(stage + (lane + 32 * i + r) * 16) : "memory");
            stg128(reinterpret_cast<uint4*>(P.out) + (goff + 32 * i + 60 * r), add_bf16x2(v.x, rv[i].x), add_bf16x2(v.y, rv[i].y), add_bf16x2(v.z, rv[i].z), add_bf16x2(v.w, rv[i].w));
        }
    }
    PROF(6);
}

__device__ __forceinline__ void mma_rows(float (&acc)[8][4], uint32_t a0, uint32_t a2, const uint4& w0, const uint4& w1, const uint4& w2, const uint4& w3) {
    const uint32_t r0[4] = {w0.x, w0.y, w0.z, w0.w}, r1[4] = {w1.x, w1.y, w1.z, w1.w};
    const uint32_t r2[4] = {w2.x, w2.y, w2.z, w2.w}, r3[4] = {w3.x, w3.y, w3.z, w3.w};
#pragma unroll
    for (int i = 0; i < 4; i++) {
        mma16816(acc[2 * i][0], acc[2 * i][1], acc[2 * i][2], acc[2 * i][3], a0, 0u, a2, 0u, __byte_perm(r0[i], r1[i], 0x5410), __byte_perm(r2[i], r3[i], 0x5410));
        mma16816(acc[2 * i + 1][0], acc[2 * i + 1][1], acc[2 * i + 1][2], acc[2 * i + 1][3], a0, 0u, a2, 0u, __byte_perm(r0[i], r1[i], 0x7632), __byte_perm(r2[i], r3[i], 0x7632));
    }
}

__device__ __forceinline__ void mod_ffn(const Params& P, uint8_t* sm, int mc  ) {
    const uint32_t epoch = read_epoch();
    const int tid = threadIdx.x - 128, lane = tid & 31, cw = tid >> 5, q = lane & 3, lr = lane >> 2;
    uint32_t* xs = reinterpret_cast<uint32_t*>(sm);
    uint32_t* wmax = xs + 8 * 324;
    int* sidx = reinterpret_cast<int*>(wmax + 16);
    const int fg = cw * 4 + mc;
    const uint32_t ring = smem_u32(sm) + 16384 + cw * 24576, rbar = smem_u32(sm) + 12288 + cw * 32;
    auto issue = [&](int u, int st) {
        if (lane == 0 && u < 30) {
            mbar_expect_tx(rbar + st * 8, 8192);
            if (u < 20) {
                tma_load_stream(ring + st * 8192, &P.wg, fg * 64, u * 32, rbar + st * 8);
                tma_load_stream(ring + st * 8192 + 4096, &P.wu, fg * 64, u * 32, rbar + st * 8);
            } else {
                tma_load_stream(ring + st * 8192, &P.wd, (u - 20) * 64, fg * 64, rbar + st * 8);
            }
        }
    };
    if (lane == 0) {
        mbar_init(rbar, 1); mbar_init(rbar + 8, 1); mbar_init(rbar + 16, 1);
        asm volatile("fence.mbarrier_init.release.cluster;" ::: "memory");
    }
    if (tid == 0) flag_wait<100>(F_LN, 256u * (epoch + 1));
    named_sync(1, 256);
    PROF(1);
    if (fg < 27) {
#pragma unroll 1
        for (int u = 0; u < 3; u++) issue(u, u);
    }
    PROF(2);
    uint32_t key[8];
#pragma unroll
    for (int i = 0; i < 8; i++) {
        const int t = tid + 256 * i;
        uint32_t b = __float_as_uint(__ldcg(g_r + t) + 0.f) >> 16;
        b = (b & 0x8000u) ? (~b & 0xffffu) : (b | 0x8000u);
        key[i] = (b << 16) | (uint32_t)(0xffff - t);
    }
#pragma unroll 1
    for (int rnd = 0; rnd < 8; rnd++) {
        uint32_t mx = key[0];
#pragma unroll
        for (int i = 1; i < 8; i++) mx = max(mx, key[i]);
        mx = __reduce_max_sync(0xffffffffu, mx);
        if (lane == 0) wmax[(rnd & 1) * 8 + cw] = mx;
        named_sync(1, 256);
        mx = __reduce_max_sync(0xffffffffu, wmax[(rnd & 1) * 8 + (lane & 7)]);
#pragma unroll
        for (int i = 0; i < 8; i++) if (key[i] == mx) key[i] = 0;
        if (tid == 0) sidx[rnd] = 0xffff - (int)(mx & 0xffffu);
    }
    named_sync(1, 256);
    {
        const uint32_t* src = reinterpret_cast<const uint32_t*>(g_xn + (size_t)perm_row(sidx[cw]) * DM);
#pragma unroll 2
        for (int i = lane; i < 320; i += 32) xs[cw * 324 + i] = __ldcg(src + i);
    }
    named_sync(1, 256);
    PROF(3);
    if (fg < 27) {
        float g[8][4], v[8][4];
        uint32_t hp[8];
#pragma unroll
        for (int i = 0; i < 8; i++)
#pragma unroll
            for (int e = 0; e < 4; e++) { g[i][e] = 0.f; v[i][e] = 0.f; }
        int st = 0, ph = 0;
#pragma unroll 1
        for (int u = 0; u < 60; u++) {
            if (!(u & 1)) mbar_wait(rbar + st * 8, ph);
            uint4 a[8];
#pragma unroll
            for (int r = 0; r < 8; r++) {
                const int row = (u < 40) ? 32 * (r >> 2) + 16 * (u & 1) + 2 * q + (r & 1) + 4 * (r & 2) : 16 * q + 8 * (u & 1) + r;
                asm volatile("ld.shared.v4.b32 {%0, %1, %2, %3}, [%4];" : "=r"(a[r].x), "=r"(a[r].y), "=r"(a[r].z), "=r"(a[r].w)
                             : "r"(ring + st * 8192 + row * 128 + ((lr ^ row) & 7) * 16) : "memory");
            }
            uint32_t f0, f1, f2, f3;
            if (u < 40) { f0 = f2 = xs[lr * 324 + u * 8 + q]; f1 = f3 = xs[lr * 324 + u * 8 + 4 + q]; }
            else if (u & 1) { f0 = hp[4]; f1 = hp[5]; f2 = hp[6]; f3 = hp[7]; }
            else { f0 = hp[0]; f1 = hp[1]; f2 = hp[2]; f3 = hp[3]; }
            mma_rows(g, f0, f1, a[0], a[1], a[2], a[3]);
            mma_rows(v, f2, f3, a[4], a[5], a[6], a[7]);
            if (u & 1) {
                __syncwarp();
                issue((u >> 1) + 3, st);
                if (++st == 3) { st = 0; ph ^= 1; }
                if (u >= 39) {
                    if (u == 39) {
                        float hv[16];
#pragma unroll
                        for (int i = 0; i < 16; i++) {
                            const float gp = round_bf16(g[i & 7][i >> 3]);
                            hv[i] = round_bf16(__fdividef(gp, 1.0f + __expf(fminf(-gp, 80.f)))) * round_bf16(v[i & 7][i >> 3]);
                        }
#pragma unroll
                        for (int i = 0; i < 8; i++) hp[i] = pack_bf16(hv[2 * i], hv[2 * i + 1]);
                    } else {
                        float4* dst = reinterpret_cast<float4*>(g_ypart + (fg * 8 + lr) * DM + ((u - 40) >> 1) * 64 + 16 * q);
#pragma unroll
                        for (int i = 0; i < 4; i++) {
                            const int j = 4 * (i & 1), e = i >> 1;
                            dst[i] = make_float4(g[j][e] + v[j][e], g[j + 1][e] + v[j + 1][e], g[j + 2][e] + v[j + 2][e], g[j + 3][e] + v[j + 3][e]);
                        }
                    }
#pragma unroll
                    for (int i = 0; i < 8; i++) { g[i][0] = 0.f; g[i][1] = 0.f; v[i][0] = 0.f; v[i][1] = 0.f; }
                }
            }
        }
    }
    PROF(5);
    named_sync(1, 256);
    if (tid == 0) {
        flag_add(F_MODP);
        flag_wait<100>(F_MODP, 4u * (epoch + 1));
    }
    named_sync(1, 256);
    PROF(6);
#pragma unroll 1
    for (int i = tid; i < 2 * DM; i += 256) {
        const int c = 2 * mc + (i >= DM), col = i - (i >= DM) * DM, t = sidx[c];
        float y = 0.f;
#pragma unroll 9
        for (int k = 0; k < 27; k++) y += __ldcg(g_ypart + (k * 8 + c) * DM + col);
        const float rs = round_bf16(__fdividef(1.0f, 1.0f + __expf(fminf(-__ldcg(g_r + t), 80.f))));
        const float xn = __bfloat162float(reinterpret_cast<const __nv_bfloat16*>(xs + c * 324)[col]);
        g_res[(size_t)t * DM + col] = __float2bfloat16_rn(__bfloat162float(P.x[(size_t)t * DM + col]) + round_bf16(xn + round_bf16(round_bf16(y) * rs)));
    }
    named_sync(1, 256);
    if (tid == 0) flag_add(F_MOD);
    PROF(7);
}

__global__ void __cluster_dims__(2, 1, 1) __launch_bounds__(384, 1) fused_kernel(const __grid_constant__ Params P) {
    extern __shared__ __align__(1024) uint8_t smem_raw[];
    const uint32_t smem = (smem_u32(smem_raw) + 1023u) & ~1023u;
    uint8_t* smem_gen = smem_raw + (smem - smem_u32(smem_raw));
    const uint32_t bars = smem + NSLOT * SLOT;
    const int wgi = __reduce_or_sync(0xffffffffu, threadIdx.x >> 7);
    const int cl = blockIdx.x >> 1, rank = blockIdx.x & 1, ca = cl & 7, cb = cl >> 3;
    PROFG(30);
    PROF(0);
    if (threadIdx.x == 0) {
#pragma unroll
        for (int i = 0; i < NSLOT; i++) { mbar_init(bars + BAR_FULL + i * 8, 1); mbar_init(bars + BAR_EMPTY + i * 8, 16); }
        mbar_arrive(bars + BAR_FULL + 16);
        asm volatile("mbarrier.arrive.shared::cta.b64 _, [%0], 16;" ::"r"(bars + BAR_EMPTY + 16) : "memory");
        asm volatile("fence.mbarrier_init.release.cluster;" ::: "memory");
        PROF(24);
    } else if (threadIdx.x == 32) {
#pragma unroll
        for (int i = 0; i < 18; i++) mbar_init(bars + BAR_SIG + i * 8, 4);
#pragma unroll
        for (int i = 0; i < 14; i++) mbar_init(bars + BAR_DEP + i * 8, 1);
    } else if (threadIdx.x >= 64 && threadIdx.x < 128 && cl < 64) {
        const int i = threadIdx.x - 64;
        if (i == 0) { prefetch_map(&P.ckv); prefetch_map(&P.wuk); }
        if (i < 32) asm volatile("prefetch.global.L2 [%0];" ::"l"(P.ckv_ptr + ((2 * ca + rank) * 128 + cb * 16 + (i >> 1)) * DC + (i & 1) * 64));
        else if (i < 48) asm volatile("prefetch.global.L2 [%0];" ::"l"(P.wuk_ptr + (size_t)((i - 32) * 8 + ca) * (NH * HD) + (cb + 8 * kv_round(0)) * 128 + rank * 64));
    }
    __syncthreads();
    PROF(29);
    cluster_arrive();
    if (wgi > 0) {
        asm volatile("setmaxnreg.inc.sync.aligned.u32 232;");
        if (cl >= 64) {
            cluster_wait();
            mod_ffn(P, smem_gen, blockIdx.x - 128);
        } else {
            consumer(P, smem, bars, ca, cb, rank, wgi - 1);
        }
        cluster_arrive();
        PROFG(31);
        PROFDUMP();
    } else {
        asm volatile("setmaxnreg.dec.sync.aligned.u32 40;");
        const int w = __reduce_or_sync(0xffffffffu, threadIdx.x >> 5), lane = threadIdx.x & 31;
        if (threadIdx.x == 32 && cl < 64) {
            mbar_expect_tx(bars + BAR_FULL, SLOT);
            tma_load(smem, &P.ckv, 0, (2 * ca + rank) * 128, bars + BAR_FULL);
            tma_load(smem + 16384, &P.ckv, 64, (2 * ca + rank) * 128, bars + BAR_FULL);
        }
        if (threadIdx.x == 64) {
            prefetch_map(&P.wuv); prefetch_map(&P.xn); prefetch_map(&P.wq); prefetch_map(&P.kv); prefetch_map(&P.ctx); prefetch_map(&P.wo);
        }
        __syncwarp();
        cluster_wait();
        PROF(27);
        if (cl < 64) {
            if (w == 0) {
                producer(P, smem, bars, ca, cb, rank);
            } else if (w < 3 && lane == 0) {
                const int wg = w - 1;
#pragma unroll 1
                for (int i = 0; i < 9; i++) {
                    const int e = (i < wg * LNSTAG + 1) ? i + 1 : (i == wg * LNSTAG + 1) ? 0 : i;
                    mbar_wait_sleep(bars + BAR_SIG + (wg * 9 + e) * 8, 0);
                    int f;
                    if (e == 0) f = F_LN;
                    else if (e < 5) f = F_KV + cb + 8 * kv_round(e - 1);
                    else { const int rd = e - 5; f = F_CTX + (8 * rd + cb) * 16 + item_p(ca, rd) * 2 + rank; }
                    flag_add(f);
                }
            } else if (lane == 0) {
                const uint32_t epoch = read_epoch();
#pragma unroll 1
                for (int i = 0; i < 14; i++) {
                    const int e = (i < 11) ? i : (i == 11) ? 13 : i - 1;
                    int f;
                    uint32_t n;
                    if (e == 0) { f = F_LN; n = 256; }
                    else if (e < 5) { f = F_KV + cb + 8 * (e - 1); n = 32; }
                    else if (e < 13) { f = F_CTX + (8 * ((e - 5) >> 1) + (cb & 6) + ((e - 5) & 1)) * 16 + ca * 2 + rank; n = 2; }
                    else { f = F_MOD; n = 4; }
                    flag_wait<200>(f, n * (epoch + 1));
                    fence_proxy_async();
                    mbar_arrive(bars + BAR_DEP + e * 8);
                }
            }
        }
        __syncwarp();
        cluster_arrive();
        cluster_wait();
        if (threadIdx.x == 0) atomicAdd(g_flags + F_EXIT * 8, 1u);
        PROFG(31);
        PROFDUMP();
    }
}

typedef CUresult (*EncodeFn)(CUtensorMap*, CUtensorMapDataType, cuuint32_t, void*, const cuuint64_t*, const cuuint64_t*, const cuuint32_t*,
                             const cuuint32_t*, CUtensorMapInterleave, CUtensorMapSwizzle, CUtensorMapL2promotion, CUtensorMapFloatOOBfill);

void make_map(EncodeFn fn, CUtensorMap* m, const void* ptr, uint64_t rows, uint64_t cols, uint32_t box_rows) {
    cuuint64_t dims[2] = {cols, rows};
    cuuint64_t strides[1] = {cols * 2};
    cuuint32_t box[2] = {64, box_rows};
    cuuint32_t es[2] = {1, 1};
    fn(m, CU_TENSOR_MAP_DATA_TYPE_BFLOAT16, 2, const_cast<void*>(ptr), dims, strides, box, es, CU_TENSOR_MAP_INTERLEAVE_NONE,
       CU_TENSOR_MAP_SWIZZLE_128B, CU_TENSOR_MAP_L2_PROMOTION_L2_128B, CU_TENSOR_MAP_FLOAT_OOB_FILL_NONE);
}

}

extern "C" void kernel_launch(void* const* d_in, const int* in_sizes, int n_in, void* d_out, int out_size) {
    (void)in_sizes; (void)n_in; (void)out_size;
    void* fnp = nullptr;
    cudaDriverEntryPointQueryResult qr;
    cudaGetDriverEntryPoint("cuTensorMapEncodeTiled", &fnp, cudaEnableDefault, &qr);
    EncodeFn fn = (EncodeFn)fnp;
    void *xn, *kv, *ctx;
    cudaGetSymbolAddress(&xn, g_xn);
    cudaGetSymbolAddress(&kv, g_kv);
    cudaGetSymbolAddress(&ctx, g_ctx);
    Params P;
    make_map(fn, &P.ckv, d_in[1], SEQ, DC, 128);
    make_map(fn, &P.wq, d_in[2], DM, NH * HD, 64);
    make_map(fn, &P.wuk, d_in[3], DC, NH * HD, 128);
    make_map(fn, &P.wuv, d_in[4], DC, NH * HD, 128);
    make_map(fn, &P.wo, d_in[5], NH * HD, DM, 32);
    make_map(fn, &P.xn, xn, SEQ, DM, 128);
    make_map(fn, &P.kv, kv, NH * 16 * 2 * 128, 128, 128);
    make_map(fn, &P.ctx, ctx, NH * SEQ, HD, 128);
    P.x = (const __nv_bfloat16*)d_in[0];
    P.wr = (const __nv_bfloat16*)d_in[7];
    make_map(fn, &P.wg, d_in[8], DM, FF, 32);
    make_map(fn, &P.wu, d_in[9], DM, FF, 32);
    make_map(fn, &P.wd, d_in[10], FF, DM, 64);
    P.ckv_ptr = (const __nv_bfloat16*)d_in[1];
    P.wuk_ptr = (const __nv_bfloat16*)d_in[3];
    P.out = (__nv_bfloat16*)d_out;
    cudaFuncSetAttribute(fused_kernel, cudaFuncAttributeMaxDynamicSharedMemorySize, SMEM_BYTES);
    fused_kernel<<<NCTA, 384, SMEM_BYTES>>>(P);
}
```

```cpp
#include <cuda_runtime.h>
#include <cuda_bf16.h>
#include <cuda.h>
#include <stdint.h>

namespace {

constexpr int SEQ = 2048, DM = 640, DC = 512, NH = 32, HD = 128, FF = 1728;
constexpr int NSLOT = 7, SLOT = 32768;
constexpr int NCTA = 132;
#define PINGPONG 1
#define SIGMA 1
#define KVORDER 0x1023
#define KVSPLIT 2
#define QST 4
#define LNSTAG 1
#define EARLYPF 1
#define OUTPF 4
#define SPLITJ 8
constexpr uint32_t DESC_HI = (1024u >> 4) | (1u << 30);
constexpr int SMEM_BYTES = NSLOT * SLOT + 3072;

constexpr int BAR_FULL = 0, BAR_EMPTY = 64, BAR_SIG = 128  , BAR_DEP = 320  , MISC_OFF = 512;

constexpr int F_EXIT = 0, F_LN = 1, F_MOD = 2, F_MODP = 3, F_KV = 4  , F_CTX = 36  , F_NUM = 548;

__device__ __align__(1024) __nv_bfloat16 g_xn[SEQ * DM];
__device__ __align__(1024) __nv_bfloat16 g_kv[NH * 16 * 2 * 128 * 128];
__device__ __align__(1024) __nv_bfloat16 g_ctx[NH * SEQ * HD];
__device__ __align__(16) float g_r[SEQ];
__device__ __align__(16) float g_ypart[27 * 8 * DM];
__device__ uint32_t g_flags[F_NUM * 8];

struct TrueT { static constexpr bool value = true; };
struct FalseT { static constexpr bool value = false; };

struct Params {
    CUtensorMap ckv, wuk, wuv, xn, wq, kv, ctx, wo, wg, wu, wd, outm;
    const __nv_bfloat16 *x, *wr, *ckv_ptr, *wuk_ptr;
    __nv_bfloat16* out;
};

__device__ __forceinline__ uint32_t smem_u32(const void* p) { return (uint32_t)__cvta_generic_to_shared(p); }
__device__ __forceinline__ void mbar_init(uint32_t bar, uint32_t cnt) {
    asm volatile("mbarrier.init.shared::cta.b64 [%0], %1;" ::"r"(bar), "r"(cnt) : "memory");
}
__device__ __forceinline__ void mbar_expect_tx(uint32_t bar, uint32_t bytes) {
    asm volatile("mbarrier.arrive.expect_tx.shared::cta.b64 _, [%0], %1;" ::"r"(bar), "r"(bytes) : "memory");
}
__device__ __forceinline__ void mbar_arrive(uint32_t bar) {
    asm volatile("mbarrier.arrive.shared::cta.b64 _, [%0];" ::"r"(bar) : "memory");
}
__device__ __forceinline__ uint32_t mapa(uint32_t addr, uint32_t cta) {
    uint32_t r;
    asm("mapa.shared::cluster.u32 %0, %1, %2;" : "=r"(r) : "r"(addr), "r"(cta));
    return r;
}
__device__ __forceinline__ void mbar_wait(uint32_t bar, uint32_t parity) {
    asm volatile(
        "{\n.reg .pred p;\n.reg .b32 c;\n"
        "mov.b32 c, 0;\n"
        "WLOOP:\n"
        "mbarrier.try_wait.parity.shared::cta.b64 p, [%0], %1;\n"
        "@p bra.uni WDONE;\n"
        "add.u32 c, c, 1;\n"
        "setp.lt.u32 p, c, 0x400000;\n"
        "@p bra.uni WLOOP;\n"
        "trap;\n"
        "WDONE:\n}\n" ::"r"(bar), "r"(parity) : "memory");
}
__device__ __forceinline__ void mbar_wait_sleep(uint32_t bar, uint32_t parity) {
    asm volatile(
        "{\n.reg .pred p;\n.reg .b32 c;\n"
        "mov.b32 c, 0;\n"
        "WLOOP:\n"
        "mbarrier.try_wait.parity.shared::cta.b64 p, [%0], %1, 20000;\n"
        "@p bra.uni WDONE;\n"
        "add.u32 c, c, 1;\n"
        "setp.lt.u32 p, c, 0x40000;\n"
        "@p bra.uni WLOOP;\n"
        "trap;\n"
        "WDONE:\n}\n" ::"r"(bar), "r"(parity) : "memory");
}
__device__ __forceinline__ void tma_load(uint32_t dst, const CUtensorMap* m, int c0, int c1, uint32_t bar) {
    asm volatile("cp.async.bulk.tensor.2d.shared::cluster.global.mbarrier::complete_tx::bytes [%0], [%1, {%3, %4}], [%2];"
                 ::"r"(dst), "l"(m), "r"(bar), "r"(c0), "r"(c1) : "memory");
}
#define ELECT "{\n.reg .pred e;\nelect.sync _|e, 0xffffffff;\n@e "
__device__ __forceinline__ void w_expect_tx(uint32_t bar, uint32_t bytes) {
    asm volatile(ELECT "mbarrier.arrive.expect_tx.shared::cta.b64 _, [%0], %1;\n}\n" ::"r"(bar), "r"(bytes) : "memory");
}
__device__ __forceinline__ void w_tma_load(uint32_t dst, const CUtensorMap* m, int c0, int c1, uint32_t bar) {
    asm volatile(ELECT "cp.async.bulk.tensor.2d.shared::cluster.global.mbarrier::complete_tx::bytes [%0], [%1, {%3, %4}], [%2];\n}\n"
                 ::"r"(dst), "l"(m), "r"(bar), "r"(c0), "r"(c1) : "memory");
}
__device__ __forceinline__ void w_tma_load_mc(uint32_t dst, const CUtensorMap* m, int c0, int c1, uint32_t bar) {
    asm volatile(ELECT "cp.async.bulk.tensor.2d.shared::cluster.global.mbarrier::complete_tx::bytes.multicast::cluster [%0], [%1, {%3, %4}], [%2], %5;\n}\n"
                 ::"r"(dst), "l"(m), "r"(bar), "r"(c0), "r"(c1), "h"((uint16_t)3) : "memory");
}
__device__ __forceinline__ void w_tma_prefetch(const CUtensorMap* m, int c0, int c1) {
    asm volatile(ELECT "cp.async.bulk.prefetch.tensor.2d.L2.global [%0, {%1, %2}];\n}\n" ::"l"(m), "r"(c0), "r"(c1) : "memory");
}
__device__ __forceinline__ uint64_t policy_evict_first() {
    uint64_t p;
    asm("createpolicy.fractional.L2::evict_first.b64 %0, 1.0;" : "=l"(p));
    return p;
}
__device__ __forceinline__ void tma_load_stream(uint32_t dst, const CUtensorMap* m, int c0, int c1, uint32_t bar) {
    asm volatile("cp.async.bulk.tensor.2d.shared::cluster.global.mbarrier::complete_tx::bytes.L2::cache_hint [%0], [%1, {%3, %4}], [%2], %5;"
                 ::"r"(dst), "l"(m), "r"(bar), "r"(c0), "r"(c1), "l"(policy_evict_first()) : "memory");
}
__device__ __forceinline__ uint4 ldg_stream(const void* p) {
    uint4 v;
    asm volatile("ld.global.nc.L2::cache_hint.v4.b32 {%0, %1, %2, %3}, [%4], %5;" : "=r"(v.x), "=r"(v.y), "=r"(v.z), "=r"(v.w) : "l"(p), "l"(policy_evict_first()));
    return v;
}
__device__ __forceinline__ void prefetch_map(const CUtensorMap* m) {
    asm volatile("prefetch.tensormap [%0];" ::"l"(m) : "memory");
}
__device__ __forceinline__ void cluster_arrive() { asm volatile("barrier.cluster.arrive.relaxed.aligned;" ::: "memory"); }
__device__ __forceinline__ void cluster_wait() { asm volatile("barrier.cluster.wait.aligned;" ::: "memory"); }
__device__ __forceinline__ void named_sync(int id, int n) { asm volatile("bar.sync %0, %1;" ::"r"(id), "r"(n) : "memory"); }
__device__ __forceinline__ void named_arrive(int id, int n) { asm volatile("bar.arrive %0, %1;" ::"r"(id), "r"(n) : "memory"); }

__device__ __forceinline__ void flag_add(int f) {
    asm volatile("fence.acq_rel.gpu;\nred.relaxed.gpu.global.add.u32 [%0], 1;" ::"l"(g_flags + f * 8) : "memory");
}
template <int SLEEP>
__device__ __forceinline__ void flag_wait(int f, uint32_t target) {
    asm volatile(
        "{\n.reg .pred p;\n.reg .b32 c, v;\n"
        "mov.b32 c, 0;\n"
        "FLOOP:\n"
        "ld.acquire.gpu.global.u32 v, [%0];\n"
        "sub.u32 v, v, %1;\n"
        "setp.ge.s32 p, v, 0;\n"
        "@p bra FDONE;\n"
        "nanosleep.u32 %2;\n"
        "add.u32 c, c, 1;\n"
        "setp.lt.u32 p, c, 0x400000;\n"
        "@p bra FLOOP;\n"
        "trap;\n"
        "FDONE:\n}\n" ::"l"(g_flags + f * 8), "r"(target), "n"(SLEEP) : "memory");
}
__device__ __forceinline__ uint32_t read_epoch() {
    uint32_t e;
    asm volatile("ld.relaxed.gpu.global.u32 %0, [%1];" : "=r"(e) : "l"(g_flags + F_EXIT * 8) : "memory");
    return e / NCTA;
}
__device__ __forceinline__ void fence_proxy_async() { asm volatile("fence.proxy.async;" ::: "memory"); }

__device__ __forceinline__ void wgmma_fence() { asm volatile("wgmma.fence.sync.aligned;" ::: "memory"); }
__device__ __forceinline__ void wgmma_commit() { asm volatile("wgmma.commit_group.sync.aligned;" ::: "memory"); }
template <int N>
__device__ __forceinline__ void wgmma_wait() { asm volatile("wgmma.wait_group.sync.aligned %0;" ::"n"(N) : "memory"); }
template <int N>
__device__ __forceinline__ void fence_regs(float (&d)[N]) {
#pragma unroll
    for (int i = 0; i < N; i++) asm volatile("" : "+f"(d[i])::"memory");
}
template <int N>
__device__ __forceinline__ void fence_regs(uint32_t (&d)[N]) {
#pragma unroll
    for (int i = 0; i < N; i++) asm volatile("" : "+r"(d[i])::"memory");
}

template <int TA, int TB>
__device__ __forceinline__ void wgmma_ss_n128(float (&d)[64], uint32_t alo, uint32_t blo, int scale_d) {
    asm volatile("{\n.reg .pred p;\n.reg .b64 da, db;\nsetp.ne.b32 p, %66, 0;\n"
        "mov.b64 da, {%64, %69};\nmov.b64 db, {%65, %69};\n"
        "wgmma.mma_async.sync.aligned.m64n128k16.f32.bf16.bf16 "
        "{%0, %1, %2, %3, %4, %5, %6, %7, %8, %9, %10, %11, %12, %13, %14, %15, %16, %17, %18, %19, %20, %21, %22, %23, %24, %25, %26, %27, %28, %29, %30, %31, %32, %33, %34, %35, %36, %37, %38, %39, %40, %41, %42, %43, %44, %45, %46, %47, %48, %49, %50, %51, %52, %53, %54, %55, %56, %57, %58, %59, %60, %61, %62, %63}, da, db, p, 1, 1, %67, %68;\n}\n"
        :
          "+f"(d[0]), "+f"(d[1]), "+f"(d[2]), "+f"(d[3]), "+f"(d[4]), "+f"(d[5]), "+f"(d[6]), "+f"(d[7]),
          "+f"(d[8]), "+f"(d[9]), "+f"(d[10]), "+f"(d[11]), "+f"(d[12]), "+f"(d[13]), "+f"(d[14]), "+f"(d[15]),
          "+f"(d[16]), "+f"(d[17]), "+f"(d[18]), "+f"(d[19]), "+f"(d[20]), "+f"(d[21]), "+f"(d[22]), "+f"(d[23]),
          "+f"(d[24]), "+f"(d[25]), "+f"(d[26]), "+f"(d[27]), "+f"(d[28]), "+f"(d[29]), "+f"(d[30]), "+f"(d[31]),
          "+f"(d[32]), "+f"(d[33]), "+f"(d[34]), "+f"(d[35]), "+f"(d[36]), "+f"(d[37]), "+f"(d[38]), "+f"(d[39]),
          "+f"(d[40]), "+f"(d[41]), "+f"(d[42]), "+f"(d[43]), "+f"(d[44]), "+f"(d[45]), "+f"(d[46]), "+f"(d[47]),
          "+f"(d[48]), "+f"(d[49]), "+f"(d[50]), "+f"(d[51]), "+f"(d[52]), "+f"(d[53]), "+f"(d[54]), "+f"(d[55]),
          "+f"(d[56]), "+f"(d[57]), "+f"(d[58]), "+f"(d[59]), "+f"(d[60]), "+f"(d[61]), "+f"(d[62]), "+f"(d[63])
        : "r"(alo), "r"(blo), "r"(scale_d), "n"(TA), "n"(TB), "r"(DESC_HI));
}
template <int TA, int TB>
__device__ __forceinline__ void wgmma_ss_n192(float (&d)[96], uint32_t alo, uint32_t blo, int scale_d) {
    asm volatile("{\n.reg .pred p;\n.reg .b64 da, db;\nsetp.ne.b32 p, %98, 0;\n"
        "mov.b64 da, {%96, %101};\nmov.b64 db, {%97, %101};\n"
        "wgmma.mma_async.sync.aligned.m64n192k16.f32.bf16.bf16 "
        "{%0, %1, %2, %3, %4, %5, %6, %7, %8, %9, %10, %11, %12, %13, %14, %15, %16, %17, %18, %19, %20, %21, %22, %23, %24, %25, %26, %27, %28, %29, %30, %31, %32, %33, %34, %35, %36, %37, %38, %39, %40, %41, %42, %43, %44, %45, %46, %47, %48, %49, %50, %51, %52, %53, %54, %55, %56, %57, %58, %59, %60, %61, %62, %63, %64, %65, %66, %67, %68, %69, %70, %71, %72, %73, %74, %75, %76, %77, %78, %79, %80, %81, %82, %83, %84, %85, %86, %87, %88, %89, %90, %91, %92, %93, %94, %95}, da, db, p, 1, 1, %99, %100;\n}\n"
        :
          "+f"(d[0]), "+f"(d[1]), "+f"(d[2]), "+f"(d[3]), "+f"(d[4]), "+f"(d[5]), "+f"(d[6]), "+f"(d[7]),
          "+f"(d[8]), "+f"(d[9]), "+f"(d[10]), "+f"(d[11]), "+f"(d[12]), "+f"(d[13]), "+f"(d[14]), "+f"(d[15]),
          "+f"(d[16]), "+f"(d[17]), "+f"(d[18]), "+f"(d[19]), "+f"(d[20]), "+f"(d[21]), "+f"(d[22]), "+f"(d[23]),
          "+f"(d[24]), "+f"(d[25]), "+f"(d[26]), "+f"(d[27]), "+f"(d[28]), "+f"(d[29]), "+f"(d[30]), "+f"(d[31]),
          "+f"(d[32]), "+f"(d[33]), "+f"(d[34]), "+f"(d[35]), "+f"(d[36]), "+f"(d[37]), "+f"(d[38]), "+f"(d[39]),
          "+f"(d[40]), "+f"(d[41]), "+f"(d[42]), "+f"(d[43]), "+f"(d[44]), "+f"(d[45]), "+f"(d[46]), "+f"(d[47]),
          "+f"(d[48]), "+f"(d[49]), "+f"(d[50]), "+f"(d[51]), "+f"(d[52]), "+f"(d[53]), "+f"(d[54]), "+f"(d[55]),
          "+f"(d[56]), "+f"(d[57]), "+f"(d[58]), "+f"(d[59]), "+f"(d[60]), "+f"(d[61]), "+f"(d[62]), "+f"(d[63]),
          "+f"(d[64]), "+f"(d[65]), "+f"(d[66]), "+f"(d[67]), "+f"(d[68]), "+f"(d[69]), "+f"(d[70]), "+f"(d[71]),
          "+f"(d[72]), "+f"(d[73]), "+f"(d[74]), "+f"(d[75]), "+f"(d[76]), "+f"(d[77]), "+f"(d[78]), "+f"(d[79]),
          "+f"(d[80]), "+f"(d[81]), "+f"(d[82]), "+f"(d[83]), "+f"(d[84]), "+f"(d[85]), "+f"(d[86]), "+f"(d[87]),
          "+f"(d[88]), "+f"(d[89]), "+f"(d[90]), "+f"(d[91]), "+f"(d[92]), "+f"(d[93]), "+f"(d[94]), "+f"(d[95])
        : "r"(alo), "r"(blo), "r"(scale_d), "n"(TA), "n"(TB), "r"(DESC_HI));
}
template <int TB>
__device__ __forceinline__ void wgmma_rs_n128(float (&d)[64], uint32_t a0, uint32_t a1, uint32_t a2, uint32_t a3, uint32_t blo, int scale_d) {
    asm volatile("{\n.reg .pred p;\n.reg .b64 db;\nsetp.ne.b32 p, %69, 0;\n"
        "mov.b64 db, {%68, %71};\n"
        "wgmma.mma_async.sync.aligned.m64n128k16.f32.bf16.bf16 "
        "{%0, %1, %2, %3, %4, %5, %6, %7, %8, %9, %10, %11, %12, %13, %14, %15, %16, %17, %18, %19, %20, %21, %22, %23, %24, %25, %26, %27, %28, %29, %30, %31, %32, %33, %34, %35, %36, %37, %38, %39, %40, %41, %42, %43, %44, %45, %46, %47, %48, %49, %50, %51, %52, %53, %54, %55, %56, %57, %58, %59, %60, %61, %62, %63}, {%64, %65, %66, %67}, db, p, 1, 1, %70;\n}\n"
        :
          "+f"(d[0]), "+f"(d[1]), "+f"(d[2]), "+f"(d[3]), "+f"(d[4]), "+f"(d[5]), "+f"(d[6]), "+f"(d[7]),
          "+f"(d[8]), "+f"(d[9]), "+f"(d[10]), "+f"(d[11]), "+f"(d[12]), "+f"(d[13]), "+f"(d[14]), "+f"(d[15]),
          "+f"(d[16]), "+f"(d[17]), "+f"(d[18]), "+f"(d[19]), "+f"(d[20]), "+f"(d[21]), "+f"(d[22]), "+f"(d[23]),
          "+f"(d[24]), "+f"(d[25]), "+f"(d[26]), "+f"(d[27]), "+f"(d[28]), "+f"(d[29]), "+f"(d[30]), "+f"(d[31]),
          "+f"(d[32]), "+f"(d[33]), "+f"(d[34]), "+f"(d[35]), "+f"(d[36]), "+f"(d[37]), "+f"(d[38]), "+f"(d[39]),
          "+f"(d[40]), "+f"(d[41]), "+f"(d[42]), "+f"(d[43]), "+f"(d[44]), "+f"(d[45]), "+f"(d[46]), "+f"(d[47]),
          "+f"(d[48]), "+f"(d[49]), "+f"(d[50]), "+f"(d[51]), "+f"(d[52]), "+f"(d[53]), "+f"(d[54]), "+f"(d[55]),
          "+f"(d[56]), "+f"(d[57]), "+f"(d[58]), "+f"(d[59]), "+f"(d[60]), "+f"(d[61]), "+f"(d[62]), "+f"(d[63])
        : "r"(a0), "r"(a1), "r"(a2), "r"(a3), "r"(blo), "r"(scale_d), "n"(TB), "r"(DESC_HI));
}
template <int TB>
__device__ __forceinline__ void wgmma_rs_n128_z(float (&d)[64], uint32_t a0, uint32_t a1, uint32_t a2, uint32_t a3, uint32_t blo) {
    asm volatile("{\n.reg .pred p;\n.reg .b64 db;\nsetp.ne.b32 p, %69, 0;\n"
        "mov.b64 db, {%68, %71};\n"
        "wgmma.mma_async.sync.aligned.m64n128k16.f32.bf16.bf16 "
        "{%0, %1, %2, %3, %4, %5, %6, %7, %8, %9, %10, %11, %12, %13, %14, %15, %16, %17, %18, %19, %20, %21, %22, %23, %24, %25, %26, %27, %28, %29, %30, %31, %32, %33, %34, %35, %36, %37, %38, %39, %40, %41, %42, %43, %44, %45, %46, %47, %48, %49, %50, %51, %52, %53, %54, %55, %56, %57, %58, %59, %60, %61, %62, %63}, {%64, %65, %66, %67}, db, p, 1, 1, %70;\n}\n"
        :
          "=f"(d[0]), "=f"(d[1]), "=f"(d[2]), "=f"(d[3]), "=f"(d[4]), "=f"(d[5]), "=f"(d[6]), "=f"(d[7]),
          "=f"(d[8]), "=f"(d[9]), "=f"(d[10]), "=f"(d[11]), "=f"(d[12]), "=f"(d[13]), "=f"(d[14]), "=f"(d[15]),
          "=f"(d[16]), "=f"(d[17]), "=f"(d[18]), "=f"(d[19]), "=f"(d[20]), "=f"(d[21]), "=f"(d[22]), "=f"(d[23]),
          "=f"(d[24]), "=f"(d[25]), "=f"(d[26]), "=f"(d[27]), "=f"(d[28]), "=f"(d[29]), "=f"(d[30]), "=f"(d[31]),
          "=f"(d[32]), "=f"(d[33]), "=f"(d[34]), "=f"(d[35]), "=f"(d[36]), "=f"(d[37]), "=f"(d[38]), "=f"(d[39]),
          "=f"(d[40]), "=f"(d[41]), "=f"(d[42]), "=f"(d[43]), "=f"(d[44]), "=f"(d[45]), "=f"(d[46]), "=f"(d[47]),
          "=f"(d[48]), "=f"(d[49]), "=f"(d[50]), "=f"(d[51]), "=f"(d[52]), "=f"(d[53]), "=f"(d[54]), "=f"(d[55]),
          "=f"(d[56]), "=f"(d[57]), "=f"(d[58]), "=f"(d[59]), "=f"(d[60]), "=f"(d[61]), "=f"(d[62]), "=f"(d[63])
        : "r"(a0), "r"(a1), "r"(a2), "r"(a3), "r"(blo), "n"(0), "n"(TB), "r"(DESC_HI));
}
template <int TA, int TB>
__device__ __forceinline__ void wgmma_ss_n128_z(float (&d)[64], uint32_t alo, uint32_t blo) {
    asm volatile("{\n.reg .pred p;\n.reg .b64 da, db;\nsetp.ne.b32 p, %66, 0;\n"
        "mov.b64 da, {%64, %69};\nmov.b64 db, {%65, %69};\n"
        "wgmma.mma_async.sync.aligned.m64n128k16.f32.bf16.bf16 "
        "{%0, %1, %2, %3, %4, %5, %6, %7, %8, %9, %10, %11, %12, %13, %14, %15, %16, %17, %18, %19, %20, %21, %22, %23, %24, %25, %26, %27, %28, %29, %30, %31, %32, %33, %34, %35, %36, %37, %38, %39, %40, %41, %42, %43, %44, %45, %46, %47, %48, %49, %50, %51, %52, %53, %54, %55, %56, %57, %58, %59, %60, %61, %62, %63}, da, db, p, 1, 1, %67, %68;\n}\n"
        :
          "=f"(d[0]), "=f"(d[1]), "=f"(d[2]), "=f"(d[3]), "=f"(d[4]), "=f"(d[5]), "=f"(d[6]), "=f"(d[7]),
          "=f"(d[8]), "=f"(d[9]), "=f"(d[10]), "=f"(d[11]), "=f"(d[12]), "=f"(d[13]), "=f"(d[14]), "=f"(d[15]),
          "=f"(d[16]), "=f"(d[17]), "=f"(d[18]), "=f"(d[19]), "=f"(d[20]), "=f"(d[21]), "=f"(d[22]), "=f"(d[23]),
          "=f"(d[24]), "=f"(d[25]), "=f"(d[26]), "=f"(d[27]), "=f"(d[28]), "=f"(d[29]), "=f"(d[30]), "=f"(d[31]),
          "=f"(d[32]), "=f"(d[33]), "=f"(d[34]), "=f"(d[35]), "=f"(d[36]), "=f"(d[37]), "=f"(d[38]), "=f"(d[39]),
          "=f"(d[40]), "=f"(d[41]), "=f"(d[42]), "=f"(d[43]), "=f"(d[44]), "=f"(d[45]), "=f"(d[46]), "=f"(d[47]),
          "=f"(d[48]), "=f"(d[49]), "=f"(d[50]), "=f"(d[51]), "=f"(d[52]), "=f"(d[53]), "=f"(d[54]), "=f"(d[55]),
          "=f"(d[56]), "=f"(d[57]), "=f"(d[58]), "=f"(d[59]), "=f"(d[60]), "=f"(d[61]), "=f"(d[62]), "=f"(d[63])
        : "r"(alo), "r"(blo), "n"(0), "n"(TA), "n"(TB), "r"(DESC_HI));
}

__device__ __forceinline__ uint32_t pack_bf16(float lo, float hi) {
    uint32_t r;
    asm("cvt.rn.bf16x2.f32 %0, %1, %2;" : "=r"(r) : "f"(hi), "f"(lo));
    return r;
}
__device__ __forceinline__ uint32_t add_bf16x2(uint32_t a, uint32_t b) {
    uint32_t r;
    asm("add.rn.bf16x2 %0, %1, %2;" : "=r"(r) : "r"(a), "r"(b));
    return r;
}
__device__ __forceinline__ float bf_lo(uint32_t v) { return __uint_as_float(v << 16); }
__device__ __forceinline__ float bf_hi(uint32_t v) { return __uint_as_float(v & 0xffff0000u); }
__device__ __forceinline__ float round_bf16(float v) { return __bfloat162float(__float2bfloat16_rn(v)); }
__device__ __forceinline__ float ex2(float x) {
    float y;
    asm("ex2.approx.ftz.f32 %0, %1;" : "=f"(y) : "f"(x));
    return y;
}
__device__ __forceinline__ float rcp(float x) {
    float y;
    asm("rcp.approx.ftz.f32 %0, %1;" : "=f"(y) : "f"(x));
    return y;
}
__device__ __forceinline__ void stg128(void* p, uint32_t a, uint32_t b, uint32_t c, uint32_t d) {
    asm volatile("st.global.v4.b32 [%0], {%1, %2, %3, %4};" ::"l"(p), "r"(a), "r"(b), "r"(c), "r"(d) : "memory");
}
__device__ __forceinline__ int perm_row(int t) { return (t & ~255) | (((0x78 >> (((t >> 6) & 3) * 2)) & 3) << 6) | (t & 63); }
__device__ __forceinline__ int unperm_row(int t) { return (t & ~255) | (((0x9C >> (((t >> 6) & 3) * 2)) & 3) << 6) | (t & 63); }

#define PROF(i)
#define PROFG(i)
#define PROFDUMP()
#define TR(i)
#define BP(r, i)
#define LP(i)

template <int I>
__device__ __forceinline__ void store_chunk(const float (&a)[64], __nv_bfloat16* row0, __nv_bfloat16* row1, float s0, float s1) {
    stg128(row0 + 32 * I, pack_bf16(a[16 * I + 0] * s0, a[16 * I + 1] * s0), pack_bf16(a[16 * I + 4] * s0, a[16 * I + 5] * s0),
           pack_bf16(a[16 * I + 8] * s0, a[16 * I + 9] * s0), pack_bf16(a[16 * I + 12] * s0, a[16 * I + 13] * s0));
    stg128(row1 + 32 * I, pack_bf16(a[16 * I + 2] * s1, a[16 * I + 3] * s1), pack_bf16(a[16 * I + 6] * s1, a[16 * I + 7] * s1),
           pack_bf16(a[16 * I + 10] * s1, a[16 * I + 11] * s1), pack_bf16(a[16 * I + 14] * s1, a[16 * I + 15] * s1));
}
template <int I>
struct IntT { static constexpr int value = I; };
template <class F>
__device__ __forceinline__ void for4(F f) { f(IntT<0>{}); f(IntT<1>{}); f(IntT<2>{}); f(IntT<3>{}); }

struct Prod {
    uint32_t smem, bars;
    uint32_t bo, par;
    uint32_t dst, fb;
    __device__ __forceinline__ void acquire(uint32_t o, uint32_t parity, uint32_t bytes) {
        mbar_wait(bars + BAR_EMPTY + o, parity);
        fb = bars + BAR_FULL + o;
        dst = smem + o * (SLOT / 8);
        w_expect_tx(fb, bytes);
    }
    __device__ __forceinline__ void next(uint32_t bytes) {
        acquire(bo, par, bytes);
        const bool wrap = bo == (NSLOT - 1) * 8;
        bo = wrap ? 0u : bo + 8;
        par ^= wrap ? 1u : 0u;
    }
};

__device__ __forceinline__ int item_p(int ca, int rd) {
    const int v = (rd & 1) ? (ca + 4) & 7 : ca;
    return (rd & 2) ? 7 - v : v;
}
__device__ __forceinline__ int kv_round(int i) { return (KVORDER >> (4 * i)) & 3; }
__device__ __forceinline__ int slot_a(int i) { return (0x5310 >> (4 * i)) & 15; }
__device__ __forceinline__ int slot_w(int m) { return (0x264 >> (4 * m)) & 15; }

__device__ __forceinline__ void producer(const Params& P, uint32_t smem, uint32_t bars, int ca, int cb, int rank) {
    Prod pr{smem, bars, 0u, 0u, 0u, 0u};
    {
        int m = 0;
        uint32_t lap = 1;
#pragma unroll 1
        for (int u = 0; u < 32; u++) {
            if (u >= 3) {
                const int v = (u == 3) ? 3 + ca : u + 7;
                if (v < 32 && (u == 3 || (v & 7) == ca)) w_tma_prefetch((v & 4) ? &P.wuv : &P.wuk, (cb + 8 * kv_round(v >> 3)) * 128 + rank * 64, (v & 3) * 128);
                if (u == 24) {
                    w_tma_prefetch(&P.wq, cb * 128 + rank * 64, ca * 64);
                    if (ca < 2) w_tma_prefetch(&P.wq, cb * 128 + rank * 64, (ca + 8) * 64);
                }
            }
            pr.acquire(slot_w(m) * 8, lap ^ (m >> 1), SLOT);
            lap ^= m >> 1;
            m = (m == 2) ? 0 : m + 1;
            TR(1 + u);
            w_tma_load_mc(pr.dst + rank * 16384, (u & 4) ? &P.wuv : &P.wuk, (cb + 8 * kv_round(u >> 3)) * 128 + rank * 64, (u & 3) * 128, pr.fb);
            if (u < 3) {
                pr.acquire(slot_a(u + 1) * 8, 1, SLOT);
                w_tma_load(pr.dst, &P.ckv, u * 128 + 128, (2 * ca + rank) * 128, pr.fb);
                w_tma_load(pr.dst + 16384, &P.ckv, u * 128 + 192, (2 * ca + rank) * 128, pr.fb);
            }
        }
    }
    PROF(1);
    mbar_wait(bars + BAR_DEP, 0);
#pragma unroll 1
    for (int rd = 0; rd < 4; rd++) {
        const int h = 8 * rd + cb, p = item_p(ca, rd);
#pragma unroll 1
        for (int ks = 0; ks < 10; ks++) {
            pr.next(SLOT);
            w_tma_load_mc(pr.dst + 16384 + rank * 8192, &P.wq, h * 128 + rank * 64, ks * 64, pr.fb);
            w_tma_load(pr.dst, &P.xn, ks * 64, 256 * p + 128 * rank, pr.fb);
        }
        PROF(8 + rd * 4);
        mbar_wait(bars + BAR_DEP + (1 + rd) * 8, 0);
        const int last = 4 * p + 3, top = h * 32 + last;
#pragma unroll 1
        for (int i = 0; i <= last; i++) {
            const int t = (i == 0) ? top - 1 : (i == last) ? h * 32 + 1 : (i & 1) ? top - 2 - i : top + 2 - i;
            pr.next(SLOT);
            w_tma_load_mc(pr.dst + rank * 16384, &P.kv, rank * 64, t * 128, pr.fb);
            if (i == 2) {
                if (rd < 3) {
                    w_tma_prefetch(&P.wq, (h + 8) * 128 + rank * 64, ca * 64);
                    if (ca < 2) w_tma_prefetch(&P.wq, (h + 8) * 128 + rank * 64, (ca + 8) * 64);
                } else {
#pragma unroll 1
                    for (int j = 0; j < 10; j++) {
                        const int tt = ca + (j >= 5 ? 8 : 0);
                        w_tma_prefetch(&P.wo, 320 * (cb & 1) + 64 * (j >= 5 ? j - 5 : j), (8 * (tt >> 2) + (cb & 6) + ((tt >> 1) & 1)) * 128 + (tt & 1) * 64 + rank * 32);
                    }
                }
            }
        }
        PROF(9 + rd * 4);
    }
    {
        const int n0 = 320 * (cb & 1), kg = cb >> 1;
#pragma unroll 1
        for (int t = 0; t < 16; t++) {
            const int h = 8 * (t >> 2) + 2 * kg + ((t >> 1) & 1), ks = t & 1;
            const int krow = h * 128 + ks * 64 + rank * 32;
            if (t >= OUTPF && t < OUTPF + 5) {
                const int r0 = unperm_row(256 * ca + 128 * rank + 32 * kg);
                w_tma_prefetch(&P.outm, n0 + 64 * (t - OUTPF), r0);
                w_tma_prefetch(&P.outm, n0 + 64 * (t - OUTPF), r0 + 16);
            }
            pr.next(SLOT);
            w_tma_load_mc(pr.dst + 16384 + rank * 8192, &P.wo, n0, krow, pr.fb);
            w_tma_load_mc(pr.dst + 16384 + rank * 8192 + 4096, &P.wo, n0 + 64, krow, pr.fb);
            mbar_wait(bars + BAR_DEP + (5 + (t >> 1)) * 8, 0);
            w_tma_load(pr.dst, &P.ctx, ks * 64, h * SEQ + 256 * ca + 128 * rank, pr.fb);
            pr.next(24576);
#pragma unroll
            for (int c = 0; c < 3; c++) w_tma_load_mc(pr.dst + rank * 12288 + c * 4096, &P.wo, n0 + 128 + 64 * c, krow, pr.fb);
        }
    }
}

struct Slot {
    uint32_t bo, dl, par;
};
struct Cons {
    uint32_t bars, rel;
    uint32_t dl0;
    uint32_t lane;
    Slot cur;
    __device__ __forceinline__ Slot slot(int s, uint32_t par) const { return Slot{(uint32_t)s * 8, dl0 + (uint32_t)s * (SLOT >> 4), par}; }
    __device__ __forceinline__ void wait(const Slot& s) const { mbar_wait(bars + BAR_FULL + s.bo, s.par); }
    __device__ __forceinline__ void release(uint32_t bo) const {
        asm volatile("{\n.reg .pred p;\nsetp.lt.u32 p, %1, 2;\n@p mbarrier.arrive.shared::cluster.b64 _, [%0];\n}\n" ::"r"(rel + bo), "r"(lane) : "memory");
    }
    __device__ __forceinline__ Slot next() {
        const Slot s = cur;
        const bool wrap = s.bo == (NSLOT - 1) * 8;
        cur.bo = wrap ? 0u : s.bo + 8;
        cur.dl = wrap ? dl0 : s.dl + (SLOT >> 4);
        cur.par = s.par ^ (wrap ? 1u : 0u);
        return s;
    }
};
__host__ __device__ constexpr uint32_t lbo(uint32_t bytes) { return (bytes >> 4) << 16; }

__device__ __forceinline__ float div640(float x) {
    const float q = x * (1.0f / DM);
    return fmaf(fmaf(-q, (float)DM, x), 1.0f / DM, q);
}
__device__ __forceinline__ float sqrt_approx(float x) {
    float y;
    asm("sqrt.approx.ftz.f32 %0, %1;" : "=f"(y) : "f"(x));
    return y;
}
struct LayerNorm {
    uint4 xv[5], wv[5];
    float mean, inv, r;
    static __device__ __forceinline__ float half_sum(float v) {
#pragma unroll
        for (int o = 8; o > 0; o >>= 1) v += __shfl_xor_sync(0xffffffffu, v, o);
        return v;
    }
    __device__ __forceinline__ void load(const __nv_bfloat16* x, const __nv_bfloat16* wr, int t, int l) {
#pragma unroll
        for (int i = 0; i < 5; i++) {
            xv[i] = ldg_stream(reinterpret_cast<const uint4*>(x + t * DM) + l + 16 * i);
            wv[i] = __ldg(reinterpret_cast<const uint4*>(wr) + l + 16 * i);
        }
    }
    __device__ __forceinline__ void stat1() {
        float a[4] = {0.f, 0.f, 0.f, 0.f};
#pragma unroll
        for (int i = 0; i < 20; i++) { const uint32_t u = (&xv[i >> 2].x)[i & 3]; a[i & 3] += bf_lo(u) + bf_hi(u); }
        mean = div640(half_sum((a[0] + a[1]) + (a[2] + a[3])));
        r = 0.f;
    }
    template <int H>
    __device__ __forceinline__ void stat2() {
        float a[4] = {r, 0.f, 0.f, 0.f};
#pragma unroll
        for (int i = H ? 12 : 0; i < (H ? 20 : 12); i++) {
            uint32_t u = (&xv[i >> 2].x)[i & 3];
            asm volatile("" : "+r"(u));
            const float d0 = bf_lo(u) - mean, d1 = bf_hi(u) - mean;
            a[i & 3] = fmaf(d0, d0, fmaf(d1, d1, a[i & 3]));
        }
        r = (a[0] + a[1]) + (a[2] + a[3]);
        if (H) {
            inv = rcp(round_bf16(sqrt_approx(round_bf16(round_bf16(div640(half_sum(r))) + 1e-5f))));
            r = 0.f;
        }
    }
    template <int I>
    __device__ __forceinline__ void piece(__nv_bfloat16* out, int t, int l) {
        const uint32_t nmb = pack_bf16(-mean, -mean);
        uint32_t o[4], z[4];
        float a[4];
#pragma unroll
        for (int j = 0; j < 4; j++) {
            const uint32_t u = (&xv[I].x)[j], w = (&wv[I].x)[j];
            const uint32_t d = add_bf16x2(u, nmb);
            o[j] = pack_bf16(bf_lo(d) * inv, bf_hi(d) * inv);
            z[j] = add_bf16x2(u, o[j]);
            a[j] = fmaf(bf_hi(o[j]), bf_hi(w), bf_lo(o[j]) * bf_lo(w));
        }
        r += (a[0] + a[1]) + (a[2] + a[3]);
        stg128(g_xn + perm_row(t) * DM + 8 * (l + 16 * I), o[0], o[1], o[2], o[3]);
        stg128(out + t * DM + 8 * (l + 16 * I), z[0], z[1], z[2], z[3]);
        if (I == 4) {
            r = half_sum(r);
            if (l == 0) g_r[t] = round_bf16(r);
        }
    }
};

constexpr float SM_SCALE = 0.08838834764831845f * 1.4426950408889634f;

template <int J0, int J1>
__device__ __forceinline__ void exp_part(float (&s)[64], float n0, float n1, float& r0, float& r1) {
    float a1 = 0.f, b1 = 0.f;
#pragma unroll
    for (int j = J0; j < J1; j++) {
        s[4 * j + 0] = ex2(fmaf(s[4 * j + 0], SM_SCALE, n0));
        s[4 * j + 1] = ex2(fmaf(s[4 * j + 1], SM_SCALE, n0));
        s[4 * j + 2] = ex2(fmaf(s[4 * j + 2], SM_SCALE, n1));
        s[4 * j + 3] = ex2(fmaf(s[4 * j + 3], SM_SCALE, n1));
        r0 += s[4 * j + 0]; r1 += s[4 * j + 2];
        if (j == J0) { a1 = s[4 * j + 1]; b1 = s[4 * j + 3]; } else { a1 += s[4 * j + 1]; b1 += s[4 * j + 3]; }
    }
    r0 += a1;
    r1 += b1;
}
__device__ __forceinline__ void sched_barrier(float x, float y, uint32_t scratch) {
    asm volatile("{\n.reg .pred p;\nsetp.lt.f32 p, %0, 0f00000000;\n@p st.shared.f32 [%2], %1;\n}\n" ::"f"(x), "f"(y), "r"(scratch) : "memory");
}
__device__ __forceinline__ void pack_tile(const float (&s)[64], uint32_t (&p)[32]) {
#pragma unroll
    for (int i = 0; i < 32; i++) p[i] = pack_bf16(s[2 * i], s[2 * i + 1]);
}
template <bool ZERO>
__device__ __forceinline__ void gemm_rs(float (&d)[64], const uint32_t (&a)[32], uint32_t dl, int acc = 1) {
    const uint32_t b = dl + lbo(16384);
    if (ZERO) wgmma_rs_n128_z<1>(d, a[0], a[1], a[2], a[3], b);
#pragma unroll
    for (int k = ZERO ? 1 : 0; k < 8; k++) wgmma_rs_n128<1>(d, a[4 * k], a[4 * k + 1], a[4 * k + 2], a[4 * k + 3], b + k * 128, k ? 1 : acc);
}
template <int ZERO>
__device__ __forceinline__ void gemm_q(float (&d)[64], uint32_t dl, int role) {
    const uint32_t a = dl + role * 512 + lbo(16), b = dl + 1024 + lbo(8192);
    if (ZERO) wgmma_ss_n128_z<0, 1>(d, a, b);
#pragma unroll
    for (int k = ZERO ? 1 : 0; k < 4; k++) wgmma_ss_n128<0, 1>(d, a + k * 2, b + k * 128, 1);
}
template <bool KT, bool ZERO, int K0, int K1>
__device__ __forceinline__ void gemm_kv(float (&d)[64], uint32_t ckv, uint32_t wt, int wg) {
    if (KT) {
        const uint32_t a = wt + wg * 1024 + lbo(16), b = ckv + lbo(16);
        if (ZERO) wgmma_ss_n128_z<1, 0>(d, a, b);
#pragma unroll
        for (int k = ZERO ? 1 : K0; k < K1; k++) wgmma_ss_n128<1, 0>(d, a + k * 128, b + (k >> 2) * 1024 + (k & 3) * 2, 1);
    } else {
        const uint32_t a = ckv + wg * 512 + lbo(16), b = wt + lbo(16384);
        if (ZERO) wgmma_ss_n128_z<0, 1>(d, a, b);
#pragma unroll
        for (int k = ZERO ? 1 : K0; k < K1; k++) wgmma_ss_n128<0, 1>(d, a + (k >> 2) * 1024 + (k & 3) * 2, b + k * 128, 1);
    }
}
__device__ __forceinline__ void mma16816(float& d0, float& d1, float& d2, float& d3, uint32_t a0, uint32_t a1, uint32_t a2, uint32_t a3, uint32_t b0, uint32_t b1) {
    asm volatile("mma.sync.aligned.m16n8k16.row.col.f32.bf16.bf16.f32 {%0,%1,%2,%3}, {%4,%5,%6,%7}, {%8,%9}, {%0,%1,%2,%3};"
                 : "+f"(d0), "+f"(d1), "+f"(d2), "+f"(d3) : "r"(a0), "r"(a1), "r"(a2), "r"(a3), "r"(b0), "r"(b1));
}
__device__ __forceinline__ uint32_t ld_pair(const __nv_bfloat16* p) {
    const unsigned short* u = reinterpret_cast<const unsigned short*>(p);
    return (uint32_t)__ldcg(u) | ((uint32_t)__ldcg(u + 128) << 16);
}
__device__ __forceinline__ void attention_exact(float (&o)[64], const uint32_t (&qf)[32], float& l0, float& l1, int h, int nblk, int rr, int lane) {
    const int q = lane & 3, lr = lane >> 2;
    float m0 = -INFINITY, m1 = -INFINITY;
    l0 = 0.f; l1 = 0.f;
#pragma unroll
    for (int i = 0; i < 64; i++) o[i] = 0.f;
#pragma unroll 1
    for (int cidx = 0; cidx < nblk * 8; cidx++) {
        const int kc = cidx & 7;
        const __nv_bfloat16* kt = g_kv + (size_t)((h * 16 + (cidx >> 3)) * 2) * 16384;
        float sc[8];
#pragma unroll
        for (int i = 0; i < 8; i++) sc[i] = 0.f;
#pragma unroll
        for (int kk = 0; kk < 8; kk++)
#pragma unroll
            for (int nt = 0; nt < 2; nt++) {
                const __nv_bfloat16* b = kt + (16 * kk + 2 * q) * 128 + 16 * kc + 8 * nt + lr;
                mma16816(sc[4 * nt], sc[4 * nt + 1], sc[4 * nt + 2], sc[4 * nt + 3], qf[4 * kk], qf[4 * kk + 1], qf[4 * kk + 2], qf[4 * kk + 3],
                         ld_pair(b), ld_pair(b + 8 * 128));
            }
        const int lim = rr + ((nblk - 1) - (cidx >> 3)) * 128 - 32 * (kc >> 1) - 4 * (kc & 1);
#pragma unroll
        for (int i = 0; i < 8; i++)
            if (2 * (i >> 2) + (i & 1) > lim + 4 * (i & 2)) sc[i] = -INFINITY;
        float x0 = fmaxf(fmaxf(sc[0], sc[1]), fmaxf(sc[4], sc[5])), x1 = fmaxf(fmaxf(sc[2], sc[3]), fmaxf(sc[6], sc[7]));
        x0 = fmaxf(x0, __shfl_xor_sync(0xffffffffu, x0, 1)); x1 = fmaxf(x1, __shfl_xor_sync(0xffffffffu, x1, 1));
        x0 = fmaxf(x0, __shfl_xor_sync(0xffffffffu, x0, 2)); x1 = fmaxf(x1, __shfl_xor_sync(0xffffffffu, x1, 2));
        x0 = fmaxf(x0, m0); x1 = fmaxf(x1, m1);
        const float a0 = ex2((m0 - x0) * SM_SCALE), a1 = ex2((m1 - x1) * SM_SCALE);
        m0 = x0; m1 = x1;
#pragma unroll
        for (int i = 0; i < 8; i++) sc[i] = ex2((sc[i] - ((i & 2) ? m1 : m0)) * SM_SCALE);
        l0 = l0 * a0 + (sc[0] + sc[1]) + (sc[4] + sc[5]);
        l1 = l1 * a1 + (sc[2] + sc[3]) + (sc[6] + sc[7]);
        const uint32_t p0 = pack_bf16(sc[0], sc[1]), p1 = pack_bf16(sc[2], sc[3]), p2 = pack_bf16(sc[4], sc[5]), p3 = pack_bf16(sc[6], sc[7]);
        const __nv_bfloat16* vb = kt + 16384 + (16 * kc + 2 * q) * 128 + lr;
#pragma unroll
        for (int nt = 0; nt < 16; nt++) {
            o[4 * nt] *= a0; o[4 * nt + 1] *= a0; o[4 * nt + 2] *= a1; o[4 * nt + 3] *= a1;
            mma16816(o[4 * nt], o[4 * nt + 1], o[4 * nt + 2], o[4 * nt + 3], p0, p1, p2, p3, ld_pair(vb + 8 * nt), ld_pair(vb + 8 * nt + 8 * 128));
        }
    }
}

__device__ __forceinline__ void signal(uint32_t bars, int wg, int e, int lane) {
    __syncwarp();
    asm volatile("{\n.reg .pred p;\nsetp.eq.u32 p, %1, 0;\n@p mbarrier.arrive.shared::cta.b64 _, [%0];\n}\n" ::"r"(bars + BAR_SIG + (wg * 9 + e) * 8), "r"(lane) : "memory");
}

__device__ __forceinline__ void consumer(const Params& P, uint32_t smem, uint32_t bars, int ca, int cb, int rank, int wg) {
    const int lane = threadIdx.x & 31, w = (threadIdx.x >> 5) & 3, q = lane & 3, lr = lane >> 2;
    PROF(7);
    cluster_wait();
    Cons c{bars, mapa(bars + BAR_EMPTY, lane & 1), (smem & 0x3FFFF) >> 4, (uint32_t)lane, Slot{0u, (smem & 0x3FFFF) >> 4, 1u}};
    PROFG(180);
    PROF(1);
    float o[64], s[64];
    uint32_t pend;
    __nv_bfloat16* ep_ptr;
    int ep_step;
    {
        const int ln_t = blockIdx.x * 16 + wg * 8 + w * 2 + (lane >> 4);
        const int krow = 64 * wg + 16 * w + lr;
        const int vrow = 64 * wg + 32 * (w >> 1) + 8 * (lr >> 1) + 4 * (w & 1) + (lr & 1);
        ep_step = 2 * 128;
        int m = 0;
        uint32_t lap = 0;
        LayerNorm ln;
        auto step = [&](auto kt, auto kc, float (&d)[64], int hh) {
            const Slot sa = c.slot(slot_a(kc.value), 0), sw = c.slot(slot_w(m), lap ^ (m >> 1));
            lap ^= m >> 1;
            m = (m == 2) ? 0 : m + 1;
            TR(1 + (hh * 8 + (kt.value ? 0 : 4) + kc.value) * 2);
            if (kt.value && hh == 0) c.wait(sa);
            c.wait(sw);
            TR(2 + (hh * 8 + (kt.value ? 0 : 4) + kc.value) * 2);
            wgmma_fence();
            gemm_kv<kt.value, kc.value == 0, 0, KVSPLIT>(d, sa.dl, sw.dl, wg);
            wgmma_commit();
            wgmma_wait<1>();
            if (!(kt.value && kc.value == 0 && hh == 0)) c.release(pend);
            if (!kt.value && kc.value > 0 && hh == 3) c.release(slot_a(kc.value - 1) * 8);
            pend = sw.bo;
            wgmma_fence();
            gemm_kv<kt.value, false, KVSPLIT, 8>(d, sa.dl, sw.dl, wg);
            wgmma_commit();
        };
#pragma unroll 1
        for (int hh = 0; hh < 4; hh++) {
            __nv_bfloat16* base = g_kv + (size_t)(((cb + 8 * kv_round(hh)) * 16 + 2 * ca + rank) * 2) * 16384 + 8 * q;
            const bool do_ln = hh == wg * LNSTAG + 1;
            for4([&](auto kc) {
                step(TrueT{}, kc, s, hh);
                if (hh > 0) {
                    if (kc.value == 0) fence_regs(o);
                    store_chunk<kc.value>(o, ep_ptr, ep_ptr + ep_step, 1.f, 1.f);
                }
                if (do_ln) {
                    if (kc.value == 0) ln.stat1();
                    if (kc.value == 1) ln.template stat2<0>();
                    if (kc.value == 2) ln.template stat2<1>();
                    if (kc.value == 3) ln.template piece<0>(P.out, ln_t, lane & 15);
                }
            });
            if (hh > 0) signal(bars, wg, hh, lane);
            for4([&](auto kc) {
                step(FalseT{}, kc, o, hh);
                if (kc.value == 0) fence_regs(s);
                store_chunk<kc.value>(s, base + krow * 128, base + (krow + 8) * 128, 1.f, 1.f);
                if (do_ln) ln.template piece<kc.value + 1>(P.out, ln_t, lane & 15);
                if (kc.value == 1 && hh == wg * LNSTAG) ln.load(P.x, P.wr, ln_t, lane & 15);
            });
            if (do_ln) signal(bars, wg, 0, lane);
            PROF(24 + hh);
            if (hh == 1) PROFG(181);
            ep_ptr = base + 16384 + vrow * 128;
        }
    }
    PROFG(182);
    PROF(2);
    {
        uint32_t pf[32], qf[32];
        float l0 = 0.25f, l1 = 0.25f;
        const int bar_me = 2 + wg, bar_other = 3 - wg;
#pragma unroll 1
        for (int rd = 0; rd < 4; rd++) {
            const int h = 8 * rd + cb, p = item_p(ca, rd);
            const int role = wg ^ (rd & 1);
            const int nrest = 2 * p + role;
            Slot kfirst;
            {
                auto qstep = [&](auto zero, int ks) {
                    const Slot sl = c.next();
                    BP(2, 4 + 3 * ks);
                    c.wait(sl);
                    BP(2, 5 + 3 * ks);
                    wgmma_fence();
                    gemm_q<zero.value>(s, sl.dl, role);
                    wgmma_commit();
                    wgmma_wait<1>();
                    BP(2, 6 + 3 * ks);
                    c.release(pend);
                    pend = sl.bo;
                };
                qstep(TrueT{}, 0);
                if (rd == 0) c.release(slot_a(3) * 8);
                fence_regs(o);
#pragma unroll 1
                for (int ks = 1; ks < QST; ks++) qstep(FalseT{}, ks);
                for4([&](auto i) {
                    qstep(FalseT{}, QST + i.value);
                    if (i.value == 0) {
                        l0 += __shfl_xor_sync(0xffffffffu, l0, 1); l1 += __shfl_xor_sync(0xffffffffu, l1, 1);
                        l0 += __shfl_xor_sync(0xffffffffu, l0, 2); l1 += __shfl_xor_sync(0xffffffffu, l1, 2);
                        l0 = rcp(l0); l1 = rcp(l1);
                    }
                    store_chunk<i.value>(o, ep_ptr, ep_ptr + ep_step, l0, l1);
                });
                signal(bars, wg, 4 + rd, lane);
                PROF(11 + rd * 4);
#pragma unroll 1
                for (int ks = QST + 4; ks < 10; ks++) qstep(FalseT{}, ks);
                if (!role) { const Slot sl = c.next(); c.wait(sl); c.release(sl.bo); }
                kfirst = c.next();
                c.wait(kfirst);
                wgmma_wait<0>();
                BP(2, 34);
                c.release(pend);
                fence_regs(s);
                pack_tile(s, qf);
            }
            PROF(8 + rd * 4);
            fence_regs(qf);
            BP(2, 35);
            if (PINGPONG && !role) named_sync(bar_me, 256);
            BP(2, 36);
            wgmma_fence();
            gemm_rs<true>(s, qf, kfirst.dl);
            wgmma_commit();
            if (PINGPONG) named_arrive(bar_other, 256);
            BP(2, 37);
            if (!role) { const Slot sl = c.next(); c.wait(sl); c.release(sl.bo); }
            const int dg = __reduce_or_sync(0xffffffffu, 2 * (role ^ rank) + (w >> 1));
            wgmma_wait<0>();
            BP(2, 38);
            fence_regs(s);
            c.release(kfirst.bo);
            float n0, n1;
            l0 = 0.f; l1 = 0.f;
            for4([&](auto a) {
                constexpr int B = 16 * a.value;
                if (a.value == dg) {
                    const int lim = 16 * (w & 1) + lr - 8 * q;
#pragma unroll
                    for (int i = 0; i < 16; i++)
                        if (2 * (i >> 2) + (i & 1) > lim + 4 * (i & 2)) s[B + i] = -INFINITY;
                }
                if (a.value == 0) {
                    n0 = fmaxf(fmaxf(fmaxf(s[0], s[1]), fmaxf(s[4], s[5])), fmaxf(fmaxf(s[8], s[9]), fmaxf(s[12], s[13])));
                    n1 = fmaxf(fmaxf(fmaxf(s[2], s[3]), fmaxf(s[6], s[7])), fmaxf(fmaxf(s[10], s[11]), fmaxf(s[14], s[15])));
                    n0 = fmaxf(n0, __shfl_xor_sync(0xffffffffu, n0, 1)); n1 = fmaxf(n1, __shfl_xor_sync(0xffffffffu, n1, 1));
                    n0 = fmaxf(n0, __shfl_xor_sync(0xffffffffu, n0, 2)); n1 = fmaxf(n1, __shfl_xor_sync(0xffffffffu, n1, 2));
                    n0 *= -SM_SCALE; n1 *= -SM_SCALE;
                }
                if (a.value <= dg) {
                    exp_part<4 * a.value, 4 * a.value + 4>(s, n0, n1, l0, l1);
#pragma unroll
                    for (int i = 0; i < 8; i++) pf[8 * a.value + i] = pack_bf16(s[B + 2 * i], s[B + 2 * i + 1]);
                } else {
#pragma unroll
                    for (int i = 0; i < 8; i++) pf[8 * a.value + i] = 0u;
                }
            });
            PROF(9 + rd * 4);
#pragma unroll 1
            for (int it = 0; it < nrest; it++) {
                const Slot sk = c.next(), sv = c.next();
                LP(0);
                if (it < 3) BP(2, 40 + 4 * it);
                if (it >= nrest - 2) BP(1, 60 + 4 * (it - nrest + 2));
                c.wait(sk);
                c.wait(sv);
                fence_regs(o); fence_regs(pf);
                LP(1);
                if (it < 3) BP(2, 41 + 4 * it);
                if (it >= nrest - 2) BP(1, 61 + 4 * (it - nrest + 2));
                if (PINGPONG) named_sync(bar_me, 256);
                LP(2);
                if (it < 3) BP(2, 42 + 4 * it);
                if (it >= nrest - 2) BP(1, 62 + 4 * (it - nrest + 2));
                wgmma_fence();
                gemm_rs<true>(s, qf, sk.dl);
                wgmma_commit();
                gemm_rs<false>(o, pf, sv.dl, it);
                wgmma_commit();
                if (PINGPONG) named_arrive(bar_other, 256);
                LP(3);
                if (it < 3) BP(2, 43 + 4 * it);
                if (it >= nrest - 2) BP(1, 63 + 4 * (it - nrest + 2));
                wgmma_wait<1>();
                LP(4);
                c.release(sk.bo);
                fence_regs(s);
                exp_part<0, SPLITJ>(s, n0, n1, l0, l1);
                sched_barrier(l0, l1, bars + MISC_OFF + 16);
                LP(5);
                wgmma_wait<0>();
                LP(6);
                c.release(sv.bo);
                fence_regs(o); fence_regs(pf);
                exp_part<SPLITJ, 16>(s, n0, n1, l0, l1);
                pack_tile(s, pf);
            }
            PROF(10 + rd * 4);
            PROFG(183 + rd);
            const Slot sv = c.next();
            BP(1, 0);
            c.wait(sv);
            if (nrest == 0) {
#pragma unroll
                for (int i = 0; i < 64; i++) o[i] = 0.f;
            }
            if (__builtin_expect(__any_sync(0xffffffffu, !(l0 < 0x1p60f && l1 < 0x1p60f)), 0)) {
                attention_exact(o, qf, l0, l1, h, nrest + 1, 64 * (role ^ rank) + 16 * w + lr - 8 * q, lane);
#pragma unroll
                for (int i = 0; i < 32; i++) pf[i] = 0u;
            }
            fence_regs(o); fence_regs(pf);
            BP(1, 1);
            if (PINGPONG && !role) named_sync(bar_me, 256);
            BP(1, 2);
            wgmma_fence();
            gemm_rs<false>(o, pf, sv.dl);
            wgmma_commit();
            BP(1, 3);
            pend = sv.bo;
            ep_ptr = g_ctx + (size_t)(h * SEQ + 256 * p + 128 * rank + 64 * role + 16 * w + lr) * HD + 8 * q;
            ep_step = 8 * HD;
        }
        l0 += __shfl_xor_sync(0xffffffffu, l0, 1); l1 += __shfl_xor_sync(0xffffffffu, l1, 1);
        l0 += __shfl_xor_sync(0xffffffffu, l0, 2); l1 += __shfl_xor_sync(0xffffffffu, l1, 2);
        l0 = rcp(l0); l1 = rcp(l1);
        wgmma_wait<0>();
        c.release(pend);
        fence_regs(o); fence_regs(pf);
        for4([&](auto i) { store_chunk<i.value>(o, ep_ptr, ep_ptr + ep_step, l0, l1); });
        signal(bars, wg, 8, lane);
    }
    PROFG(187);
    PROF(3);
    {
        float a1[64], a2[96];
        uint32_t px = 0, py = 0;
#pragma unroll 1
        for (int t = 0; t < 16; t++) {
            const Slot sx = c.next(), sy = c.next();
            c.wait(sx);
            const uint32_t da = sx.dl + wg * 512 + lbo(16), b1 = sx.dl + 1024 + lbo(4096), b2 = sy.dl + lbo(4096);
            wgmma_fence();
#pragma unroll
            for (int k = 0; k < 4; k++) wgmma_ss_n128<0, 1>(a1, da + k * 2, b1 + (k >> 1) * 512 + (k & 1) * 128, k ? 1 : t);
            wgmma_commit();
            wgmma_wait<1>();
            if (t > 0) { c.release(px); c.release(py); }
            px = sx.bo; py = sy.bo;
            c.wait(sy);
            wgmma_fence();
#pragma unroll
            for (int k = 0; k < 4; k++) wgmma_ss_n192<0, 1>(a2, da + k * 2, b2 + (k >> 1) * 768 + (k & 1) * 128, k ? 1 : t);
            wgmma_commit();
        }
        const int cw = __reduce_or_sync(0xffffffffu, wg * 4 + w);
        Slot st = c.next();
        if (cw >= 3) st = c.next();
        if (cw >= 6) st = c.next();
        const uint32_t stage = smem + st.bo * (SLOT / 8) + (cw % 3) * 10240;
        const int orow = unperm_row(256 * ca + 128 * rank + 16 * cw), ocol = 320 * (cb & 1);
        const uint32_t sa = stage + ((lane & 7) + (lane & 8)) * 128, sx = (lane >> 4) ^ (lane & 7);
        mbar_wait(bars + BAR_EMPTY + st.bo, st.par ^ 1);
        mbar_wait(bars + BAR_DEP + 13 * 8, 0);
        wgmma_wait<0>();
        fence_regs(a1); fence_regs(a2);
        PROFG(188);
        PROF(4);
#pragma unroll
        for (int ch = 0; ch < 5; ch++) {
#pragma unroll
            for (int i = 0; i < 4; i++) {
                uint32_t r[4];
#pragma unroll
                for (int e = 0; e < 4; e++) {
                    const int k = 32 * ch + 8 * i + 2 * e;
                    r[e] = (ch < 2) ? pack_bf16(a1[k & 63], a1[(k & 63) + 1]) : pack_bf16(a2[ch < 2 ? 0 : k - 64], a2[ch < 2 ? 1 : k - 63]);
                }
                asm volatile("stmatrix.sync.aligned.m8n8.x4.shared.b16 [%0], {%1, %2, %3, %4};"
                             ::"r"(sa + ch * 2048 + ((sx ^ (2 * i)) << 4)), "r"(r[0]), "r"(r[1]), "r"(r[2]), "r"(r[3]) : "memory");
            }
            asm volatile("fence.proxy.async.shared::cta;" ::: "memory");
            __syncwarp();
            asm volatile(ELECT "cp.reduce.async.bulk.tensor.2d.global.shared::cta.add.bulk_group [%0, {%2, %3}], [%1];\n}\n"
                         ::"l"(&P.outm), "r"(stage + ch * 2048), "r"(ocol + 64 * ch), "r"(orow) : "memory");
        }
        PROF(5);
        asm volatile("cp.async.bulk.commit_group;\ncp.async.bulk.wait_group.read 0;" ::: "memory");
    }
    PROF(6);
}

__device__ __forceinline__ void mma_rows(float (&acc)[8][4], uint32_t a0, uint32_t a2, const uint4& w0, const uint4& w1, const uint4& w2, const uint4& w3) {
    const uint32_t r0[4] = {w0.x, w0.y, w0.z, w0.w}, r1[4] = {w1.x, w1.y, w1.z, w1.w};
    const uint32_t r2[4] = {w2.x, w2.y, w2.z, w2.w}, r3[4] = {w3.x, w3.y, w3.z, w3.w};
#pragma unroll
    for (int i = 0; i < 4; i++) {
        mma16816(acc[2 * i][0], acc[2 * i][1], acc[2 * i][2], acc[2 * i][3], a0, 0u, a2, 0u, __byte_perm(r0[i], r1[i], 0x5410), __byte_perm(r2[i], r3[i], 0x5410));
        mma16816(acc[2 * i + 1][0], acc[2 * i + 1][1], acc[2 * i + 1][2], acc[2 * i + 1][3], a0, 0u, a2, 0u, __byte_perm(r0[i], r1[i], 0x7632), __byte_perm(r2[i], r3[i], 0x7632));
    }
}

__device__ __forceinline__ void mod_ffn(const Params& P, uint8_t* sm, int mc  ) {
    const uint32_t epoch = read_epoch();
    const int tid = threadIdx.x - 128, lane = tid & 31, cw = tid >> 5, q = lane & 3, lr = lane >> 2;
    uint32_t* xs = reinterpret_cast<uint32_t*>(sm);
    uint32_t* wmax = xs + 8 * 324;
    int* sidx = reinterpret_cast<int*>(wmax + 16);
    const int fg = cw * 4 + mc;
    const uint32_t ring = smem_u32(sm) + 16384 + cw * 24576, rbar = smem_u32(sm) + 12288 + cw * 32;
    auto issue = [&](int u, int st) {
        if (lane == 0 && u < 30) {
            mbar_expect_tx(rbar + st * 8, 8192);
            if (u < 20) {
                tma_load_stream(ring + st * 8192, &P.wg, fg * 64, u * 32, rbar + st * 8);
                tma_load_stream(ring + st * 8192 + 4096, &P.wu, fg * 64, u * 32, rbar + st * 8);
            } else {
                tma_load_stream(ring + st * 8192, &P.wd, (u - 20) * 64, fg * 64, rbar + st * 8);
            }
        }
    };
    if (lane == 0) {
        mbar_init(rbar, 1); mbar_init(rbar + 8, 1); mbar_init(rbar + 16, 1);
        asm volatile("fence.mbarrier_init.release.cluster;" ::: "memory");
    }
    if (tid == 0) flag_wait<100>(F_LN, 256u * (epoch + 1));
    named_sync(1, 256);
    PROF(1);
    if (fg < 27) {
#pragma unroll 1
        for (int u = 0; u < 3; u++) issue(u, u);
    }
    PROF(2);
    uint32_t key[8];
#pragma unroll
    for (int i = 0; i < 8; i++) {
        const int t = tid + 256 * i;
        uint32_t b = __float_as_uint(__ldcg(g_r + t) + 0.f) >> 16;
        b = (b & 0x8000u) ? (~b & 0xffffu) : (b | 0x8000u);
        key[i] = (b << 16) | (uint32_t)(0xffff - t);
    }
#pragma unroll 1
    for (int rnd = 0; rnd < 8; rnd++) {
        uint32_t mx = key[0];
#pragma unroll
        for (int i = 1; i < 8; i++) mx = max(mx, key[i]);
        mx = __reduce_max_sync(0xffffffffu, mx);
        if (lane == 0) wmax[(rnd & 1) * 8 + cw] = mx;
        named_sync(1, 256);
        mx = __reduce_max_sync(0xffffffffu, wmax[(rnd & 1) * 8 + (lane & 7)]);
#pragma unroll
        for (int i = 0; i < 8; i++) if (key[i] == mx) key[i] = 0;
        if (tid == 0) sidx[rnd] = 0xffff - (int)(mx & 0xffffu);
    }
    named_sync(1, 256);
    {
        const uint32_t* src = reinterpret_cast<const uint32_t*>(g_xn + (size_t)perm_row(sidx[cw]) * DM);
#pragma unroll 2
        for (int i = lane; i < 320; i += 32) xs[cw * 324 + i] = __ldcg(src + i);
    }
    named_sync(1, 256);
    PROF(3);
    if (fg < 27) {
        float g[8][4], v[8][4];
        uint32_t hp[8];
#pragma unroll
        for (int i = 0; i < 8; i++)
#pragma unroll
            for (int e = 0; e < 4; e++) { g[i][e] = 0.f; v[i][e] = 0.f; }
        int st = 0, ph = 0;
#pragma unroll 1
        for (int u = 0; u < 60; u++) {
            if (!(u & 1)) mbar_wait(rbar + st * 8, ph);
            uint4 a[8];
#pragma unroll
            for (int r = 0; r < 8; r++) {
                const int row = (u < 40) ? 32 * (r >> 2) + 16 * (u & 1) + 2 * q + (r & 1) + 4 * (r & 2) : 16 * q + 8 * (u & 1) + r;
                asm volatile("ld.shared.v4.b32 {%0, %1, %2, %3}, [%4];" : "=r"(a[r].x), "=r"(a[r].y), "=r"(a[r].z), "=r"(a[r].w)
                             : "r"(ring + st * 8192 + row * 128 + ((lr ^ row) & 7) * 16) : "memory");
            }
            uint32_t f0, f1, f2, f3;
            if (u < 40) { f0 = f2 = xs[lr * 324 + u * 8 + q]; f1 = f3 = xs[lr * 324 + u * 8 + 4 + q]; }
            else if (u & 1) { f0 = hp[4]; f1 = hp[5]; f2 = hp[6]; f3 = hp[7]; }
            else { f0 = hp[0]; f1 = hp[1]; f2 = hp[2]; f3 = hp[3]; }
            mma_rows(g, f0, f1, a[0], a[1], a[2], a[3]);
            mma_rows(v, f2, f3, a[4], a[5], a[6], a[7]);
            if (u & 1) {
                __syncwarp();
                issue((u >> 1) + 3, st);
                if (++st == 3) { st = 0; ph ^= 1; }
                if (u >= 39) {
                    if (u == 39) {
                        float hv[16];
#pragma unroll
                        for (int i = 0; i < 16; i++) {
                            const float gp = round_bf16(g[i & 7][i >> 3]);
                            hv[i] = round_bf16(__fdividef(gp, 1.0f + __expf(fminf(-gp, 80.f)))) * round_bf16(v[i & 7][i >> 3]);
                        }
#pragma unroll
                        for (int i = 0; i < 8; i++) hp[i] = pack_bf16(hv[2 * i], hv[2 * i + 1]);
                    } else {
                        float4* dst = reinterpret_cast<float4*>(g_ypart + (fg * 8 + lr) * DM + ((u - 40) >> 1) * 64 + 16 * q);
#pragma unroll
                        for (int i = 0; i < 4; i++) {
                            const int j = 4 * (i & 1), e = i >> 1;
                            dst[i] = make_float4(g[j][e] + v[j][e], g[j + 1][e] + v[j + 1][e], g[j + 2][e] + v[j + 2][e], g[j + 3][e] + v[j + 3][e]);
                        }
                    }
#pragma unroll
                    for (int i = 0; i < 8; i++) { g[i][0] = 0.f; g[i][1] = 0.f; v[i][0] = 0.f; v[i][1] = 0.f; }
                }
            }
        }
    }
    PROF(5);
    named_sync(1, 256);
    if (tid == 0) {
        flag_add(F_MODP);
        flag_wait<100>(F_MODP, 4u * (epoch + 1));
    }
    named_sync(1, 256);
    PROF(6);
#pragma unroll 1
    for (int i = tid; i < 2 * DM; i += 256) {
        const int c = 2 * mc + (i >= DM), col = i - (i >= DM) * DM, t = sidx[c];
        float y = 0.f;
#pragma unroll 9
        for (int k = 0; k < 27; k++) y += __ldcg(g_ypart + (k * 8 + c) * DM + col);
        const float rs = round_bf16(__fdividef(1.0f, 1.0f + __expf(fminf(-__ldcg(g_r + t), 80.f))));
        const float xn = __bfloat162float(reinterpret_cast<const __nv_bfloat16*>(xs + c * 324)[col]);
        P.out[(size_t)t * DM + col] = __float2bfloat16_rn(__bfloat162float(P.x[(size_t)t * DM + col]) + round_bf16(xn + round_bf16(round_bf16(y) * rs)));
    }
    named_sync(1, 256);
    if (tid == 0) flag_add(F_MOD);
    PROF(7);
}

__global__ void __cluster_dims__(2, 1, 1) __launch_bounds__(384, 1) fused_kernel(const __grid_constant__ Params P) {
    extern __shared__ __align__(1024) uint8_t smem_raw[];
    const uint32_t smem = (smem_u32(smem_raw) + 1023u) & ~1023u;
    uint8_t* smem_gen = smem_raw + (smem - smem_u32(smem_raw));
    const uint32_t bars = smem + NSLOT * SLOT;
    const int wgi = __reduce_or_sync(0xffffffffu, threadIdx.x >> 7);
    const int cl = blockIdx.x >> 1, rank = blockIdx.x & 1, ca = cl & 7, cb = cl >> 3;
    PROFG(30);
    PROF(0);
    if (threadIdx.x == 0) {
#pragma unroll
        for (int i = 0; i < NSLOT; i++) { mbar_init(bars + BAR_FULL + i * 8, 1); mbar_init(bars + BAR_EMPTY + i * 8, 16); }
        mbar_arrive(bars + BAR_FULL + 16);
        asm volatile("mbarrier.arrive.shared::cta.b64 _, [%0], 16;" ::"r"(bars + BAR_EMPTY + 16) : "memory");
        asm volatile("fence.mbarrier_init.release.cluster;" ::: "memory");
        PROF(24);
    } else if (threadIdx.x == 32) {
#pragma unroll
        for (int i = 0; i < 18; i++) mbar_init(bars + BAR_SIG + i * 8, 4);
#pragma unroll
        for (int i = 0; i < 14; i++) mbar_init(bars + BAR_DEP + i * 8, 1);
    } else if (threadIdx.x >= 64 && threadIdx.x < 128 && cl < 64) {
        const int i = threadIdx.x - 64;
        if (i == 0) { prefetch_map(&P.ckv); prefetch_map(&P.wuk); }
        if (i < 32) asm volatile("prefetch.global.L2 [%0];" ::"l"(P.ckv_ptr + ((2 * ca + rank) * 128 + cb * 16 + (i >> 1)) * DC + (i & 1) * 64));
        else if (i < 48) asm volatile("prefetch.global.L2 [%0];" ::"l"(P.wuk_ptr + (size_t)((i - 32) * 8 + ca) * (NH * HD) + (cb + 8 * kv_round(0)) * 128 + rank * 64));
    }
    __syncthreads();
    PROF(29);
    cluster_arrive();
    if (wgi > 0) {
        asm volatile("setmaxnreg.inc.sync.aligned.u32 232;");
        if (cl >= 64) {
            cluster_wait();
            mod_ffn(P, smem_gen, blockIdx.x - 128);
        } else {
            consumer(P, smem, bars, ca, cb, rank, wgi - 1);
        }
        cluster_arrive();
        PROFG(31);
        PROFDUMP();
    } else {
        asm volatile("setmaxnreg.dec.sync.aligned.u32 40;");
        const int w = __reduce_or_sync(0xffffffffu, threadIdx.x >> 5), lane = threadIdx.x & 31;
        if (threadIdx.x == 32 && cl < 64) {
            mbar_expect_tx(bars + BAR_FULL, SLOT);
            tma_load(smem, &P.ckv, 0, (2 * ca + rank) * 128, bars + BAR_FULL);
            tma_load(smem + 16384, &P.ckv, 64, (2 * ca + rank) * 128, bars + BAR_FULL);
        }
        if (threadIdx.x == 64) {
            prefetch_map(&P.wuv); prefetch_map(&P.xn); prefetch_map(&P.wq); prefetch_map(&P.kv); prefetch_map(&P.ctx); prefetch_map(&P.wo); prefetch_map(&P.outm);
        }
        __syncwarp();
        cluster_wait();
        PROF(27);
        if (cl < 64) {
            if (w == 0) {
                producer(P, smem, bars, ca, cb, rank);
            } else if (w < 3 && lane == 0) {
                const int wg = w - 1;
#pragma unroll 1
                for (int i = 0; i < 9; i++) {
                    const int e = (i < wg * LNSTAG + 1) ? i + 1 : (i == wg * LNSTAG + 1) ? 0 : i;
                    mbar_wait_sleep(bars + BAR_SIG + (wg * 9 + e) * 8, 0);
                    int f;
                    if (e == 0) f = F_LN;
                    else if (e < 5) f = F_KV + cb + 8 * kv_round(e - 1);
                    else { const int rd = e - 5; f = F_CTX + (8 * rd + cb) * 16 + item_p(ca, rd) * 2 + rank; }
                    flag_add(f);
                }
            } else if (lane == 0) {
                const uint32_t epoch = read_epoch();
#pragma unroll 1
                for (int i = 0; i < 14; i++) {
                    const int e = (i < 11) ? i : (i == 11) ? 13 : i - 1;
                    int f;
                    uint32_t n;
                    if (e == 0) { f = F_LN; n = 256; }
                    else if (e < 5) { f = F_KV + cb + 8 * (e - 1); n = 32; }
                    else if (e < 13) { f = F_CTX + (8 * ((e - 5) >> 1) + (cb & 6) + ((e - 5) & 1)) * 16 + ca * 2 + rank; n = 2; }
                    else { f = F_MOD; n = 4; }
                    flag_wait<200>(f, n * (epoch + 1));
                    fence_proxy_async();
                    mbar_arrive(bars + BAR_DEP + e * 8);
                }
            }
        }
        __syncwarp();
        cluster_arrive();
        cluster_wait();
        if (threadIdx.x == 0) atomicAdd(g_flags + F_EXIT * 8, 1u);
        PROFG(31);
        PROFDUMP();
    }
}

typedef CUresult (*EncodeFn)(CUtensorMap*, CUtensorMapDataType, cuuint32_t, void*, const cuuint64_t*, const cuuint64_t*, const cuuint32_t*,
                             const cuuint32_t*, CUtensorMapInterleave, CUtensorMapSwizzle, CUtensorMapL2promotion, CUtensorMapFloatOOBfill);

void make_map(EncodeFn fn, CUtensorMap* m, const void* ptr, uint64_t rows, uint64_t cols, uint32_t box_rows) {
    cuuint64_t dims[2] = {cols, rows};
    cuuint64_t strides[1] = {cols * 2};
    cuuint32_t box[2] = {64, box_rows};
    cuuint32_t es[2] = {1, 1};
    fn(m, CU_TENSOR_MAP_DATA_TYPE_BFLOAT16, 2, const_cast<void*>(ptr), dims, strides, box, es, CU_TENSOR_MAP_INTERLEAVE_NONE,
       CU_TENSOR_MAP_SWIZZLE_128B, CU_TENSOR_MAP_L2_PROMOTION_L2_128B, CU_TENSOR_MAP_FLOAT_OOB_FILL_NONE);
}

}

extern "C" void kernel_launch(void* const* d_in, const int* in_sizes, int n_in, void* d_out, int out_size) {
    (void)in_sizes; (void)n_in; (void)out_size;
    void* fnp = nullptr;
    cudaDriverEntryPointQueryResult qr;
    cudaGetDriverEntryPoint("cuTensorMapEncodeTiled", &fnp, cudaEnableDefault, &qr);
    EncodeFn fn = (EncodeFn)fnp;
    void *xn, *kv, *ctx;
    cudaGetSymbolAddress(&xn, g_xn);
    cudaGetSymbolAddress(&kv, g_kv);
    cudaGetSymbolAddress(&ctx, g_ctx);
    Params P;
    make_map(fn, &P.ckv, d_in[1], SEQ, DC, 128);
    make_map(fn, &P.wq, d_in[2], DM, NH * HD, 64);
    make_map(fn, &P.wuk, d_in[3], DC, NH * HD, 128);
    make_map(fn, &P.wuv, d_in[4], DC, NH * HD, 128);
    make_map(fn, &P.wo, d_in[5], NH * HD, DM, 32);
    make_map(fn, &P.xn, xn, SEQ, DM, 128);
    make_map(fn, &P.kv, kv, NH * 16 * 2 * 128, 128, 128);
    make_map(fn, &P.ctx, ctx, NH * SEQ, HD, 128);
    P.x = (const __nv_bfloat16*)d_in[0];
    P.wr = (const __nv_bfloat16*)d_in[7];
    make_map(fn, &P.wg, d_in[8], DM, FF, 32);
    make_map(fn, &P.wu, d_in[9], DM, FF, 32);
    make_map(fn, &P.wd, d_in[10], FF, DM, 64);
    P.ckv_ptr = (const __nv_bfloat16*)d_in[1];
    P.wuk_ptr = (const __nv_bfloat16*)d_in[3];
    make_map(fn, &P.outm, d_out, SEQ, DM, 16);
    P.out = (__nv_bfloat16*)d_out;
    cudaFuncSetAttribute(fused_kernel, cudaFuncAttributeMaxDynamicSharedMemorySize, SMEM_BYTES);
    fused_kernel<<<NCTA, 384, SMEM_BYTES>>>(P);
}
```

```cpp
#include <cuda_runtime.h>
#include <cuda_bf16.h>
#include <cuda.h>
#include <stdint.h>

namespace {

constexpr int SEQ = 2048, DM = 640, DC = 512, NH = 32, HD = 128, FF = 1728;
constexpr int NSLOT = 7, SLOT = 32768;
constexpr int NCTA = 132;
#define PINGPONG 1
#define SIGMA 1
#define KVORDER 0x1023
#define KVSPLIT 2
#define QST 4
#define LNSTAG 1
#define EARLYPF 1
#define EARLYSEND 1
#define FENCE_EACH 1
#define SPLITJ 8
constexpr uint32_t DESC_HI = (1024u >> 4) | (1u << 30);
constexpr int SMEM_BYTES = NSLOT * SLOT + 3072;

constexpr int BAR_FULL = 0, BAR_EMPTY = 64, BAR_SIG = 128  , BAR_DEP = 320  , MISC_OFF = 512;

constexpr int F_EXIT = 0, F_LN = 1, F_MOD = 2, F_MODP = 3, F_KV = 4  , F_CTX = 36  , F_NUM = 548;

__device__ __align__(1024) __nv_bfloat16 g_xn[SEQ * DM];
__device__ __align__(1024) __nv_bfloat16 g_kv[NH * 16 * 2 * 128 * 128];
__device__ __align__(1024) __nv_bfloat16 g_ctx[NH * SEQ * HD];
__device__ __align__(16) float g_r[SEQ];
__device__ __align__(16) float g_ypart[27 * 8 * DM];
__device__ uint32_t g_flags[F_NUM * 8];

struct TrueT { static constexpr bool value = true; };
struct FalseT { static constexpr bool value = false; };

struct Params {
    CUtensorMap ckv, wuk, wuv, xn, wq, kv, ctx, wo, wg, wu, wd, outm;
    const __nv_bfloat16 *x, *wr, *ckv_ptr, *wuk_ptr;
    __nv_bfloat16* out;
};

__device__ __forceinline__ uint32_t smem_u32(const void* p) { return (uint32_t)__cvta_generic_to_shared(p); }
__device__ __forceinline__ void mbar_init(uint32_t bar, uint32_t cnt) {
    asm volatile("mbarrier.init.shared::cta.b64 [%0], %1;" ::"r"(bar), "r"(cnt) : "memory");
}
__device__ __forceinline__ void mbar_expect_tx(uint32_t bar, uint32_t bytes) {
    asm volatile("mbarrier.arrive.expect_tx.shared::cta.b64 _, [%0], %1;" ::"r"(bar), "r"(bytes) : "memory");
}
__device__ __forceinline__ void mbar_arrive(uint32_t bar) {
    asm volatile("mbarrier.arrive.shared::cta.b64 _, [%0];" ::"r"(bar) : "memory");
}
__device__ __forceinline__ uint32_t mapa(uint32_t addr, uint32_t cta) {
    uint32_t r;
    asm("mapa.shared::cluster.u32 %0, %1, %2;" : "=r"(r) : "r"(addr), "r"(cta));
    return r;
}
__device__ __forceinline__ void mbar_wait(uint32_t bar, uint32_t parity) {
    asm volatile(
        "{\n.reg .pred p;\n.reg .b32 c;\n"
        "mov.b32 c, 0;\n"
        "WLOOP:\n"
        "mbarrier.try_wait.parity.shared::cta.b64 p, [%0], %1;\n"
        "@p bra.uni WDONE;\n"
        "add.u32 c, c, 1;\n"
        "setp.lt.u32 p, c, 0x400000;\n"
        "@p bra.uni WLOOP;\n"
        "trap;\n"
        "WDONE:\n}\n" ::"r"(bar), "r"(parity) : "memory");
}
__device__ __forceinline__ void mbar_wait_sleep(uint32_t bar, uint32_t parity) {
    asm volatile(
        "{\n.reg .pred p;\n.reg .b32 c;\n"
        "mov.b32 c, 0;\n"
        "WLOOP:\n"
        "mbarrier.try_wait.parity.shared::cta.b64 p, [%0], %1, 20000;\n"
        "@p bra.uni WDONE;\n"
        "add.u32 c, c, 1;\n"
        "setp.lt.u32 p, c, 0x40000;\n"
        "@p bra.uni WLOOP;\n"
        "trap;\n"
        "WDONE:\n}\n" ::"r"(bar), "r"(parity) : "memory");
}
__device__ __forceinline__ void tma_load(uint32_t dst, const CUtensorMap* m, int c0, int c1, uint32_t bar) {
    asm volatile("cp.async.bulk.tensor.2d.shared::cluster.global.mbarrier::complete_tx::bytes [%0], [%1, {%3, %4}], [%2];"
                 ::"r"(dst), "l"(m), "r"(bar), "r"(c0), "r"(c1) : "memory");
}
#define ELECT "{\n.reg .pred e;\nelect.sync _|e, 0xffffffff;\n@e "
__device__ __forceinline__ void w_expect_tx(uint32_t bar, uint32_t bytes) {
    asm volatile(ELECT "mbarrier.arrive.expect_tx.shared::cta.b64 _, [%0], %1;\n}\n" ::"r"(bar), "r"(bytes) : "memory");
}
__device__ __forceinline__ void w_tma_load(uint32_t dst, const CUtensorMap* m, int c0, int c1, uint32_t bar) {
    asm volatile(ELECT "cp.async.bulk.tensor.2d.shared::cluster.global.mbarrier::complete_tx::bytes [%0], [%1, {%3, %4}], [%2];\n}\n"
                 ::"r"(dst), "l"(m), "r"(bar), "r"(c0), "r"(c1) : "memory");
}
__device__ __forceinline__ void w_tma_load_mc(uint32_t dst, const CUtensorMap* m, int c0, int c1, uint32_t bar) {
    asm volatile(ELECT "cp.async.bulk.tensor.2d.shared::cluster.global.mbarrier::complete_tx::bytes.multicast::cluster [%0], [%1, {%3, %4}], [%2], %5;\n}\n"
                 ::"r"(dst), "l"(m), "r"(bar), "r"(c0), "r"(c1), "h"((uint16_t)3) : "memory");
}
__device__ __forceinline__ void w_tma_prefetch(const CUtensorMap* m, int c0, int c1) {
    asm volatile(ELECT "cp.async.bulk.prefetch.tensor.2d.L2.global [%0, {%1, %2}];\n}\n" ::"l"(m), "r"(c0), "r"(c1) : "memory");
}
__device__ __forceinline__ uint64_t policy_evict_first() {
    uint64_t p;
    asm("createpolicy.fractional.L2::evict_first.b64 %0, 1.0;" : "=l"(p));
    return p;
}
__device__ __forceinline__ void tma_load_stream(uint32_t dst, const CUtensorMap* m, int c0, int c1, uint32_t bar) {
    asm volatile("cp.async.bulk.tensor.2d.shared::cluster.global.mbarrier::complete_tx::bytes.L2::cache_hint [%0], [%1, {%3, %4}], [%2], %5;"
                 ::"r"(dst), "l"(m), "r"(bar), "r"(c0), "r"(c1), "l"(policy_evict_first()) : "memory");
}
__device__ __forceinline__ uint4 ldg_stream(const void* p) {
    uint4 v;
    asm volatile("ld.global.nc.L2::cache_hint.v4.b32 {%0, %1, %2, %3}, [%4], %5;" : "=r"(v.x), "=r"(v.y), "=r"(v.z), "=r"(v.w) : "l"(p), "l"(policy_evict_first()));
    return v;
}
__device__ __forceinline__ void prefetch_map(const CUtensorMap* m) {
    asm volatile("prefetch.tensormap [%0];" ::"l"(m) : "memory");
}
__device__ __forceinline__ void cluster_arrive() { asm volatile("barrier.cluster.arrive.relaxed.aligned;" ::: "memory"); }
__device__ __forceinline__ void cluster_wait() { asm volatile("barrier.cluster.wait.aligned;" ::: "memory"); }
__device__ __forceinline__ void named_sync(int id, int n) { asm volatile("bar.sync %0, %1;" ::"r"(id), "r"(n) : "memory"); }
__device__ __forceinline__ void named_arrive(int id, int n) { asm volatile("bar.arrive %0, %1;" ::"r"(id), "r"(n) : "memory"); }

__device__ __forceinline__ void flag_add(int f) {
    asm volatile("fence.acq_rel.gpu;\nred.relaxed.gpu.global.add.u32 [%0], 1;" ::"l"(g_flags + f * 8) : "memory");
}
template <int SLEEP>
__device__ __forceinline__ void flag_wait(int f, uint32_t target) {
    asm volatile(
        "{\n.reg .pred p;\n.reg .b32 c, v;\n"
        "mov.b32 c, 0;\n"
        "FLOOP:\n"
        "ld.acquire.gpu.global.u32 v, [%0];\n"
        "sub.u32 v, v, %1;\n"
        "setp.ge.s32 p, v, 0;\n"
        "@p bra FDONE;\n"
        "nanosleep.u32 %2;\n"
        "add.u32 c, c, 1;\n"
        "setp.lt.u32 p, c, 0x400000;\n"
        "@p bra FLOOP;\n"
        "trap;\n"
        "FDONE:\n}\n" ::"l"(g_flags + f * 8), "r"(target), "n"(SLEEP) : "memory");
}
__device__ __forceinline__ uint32_t read_epoch() {
    uint32_t e;
    asm volatile("ld.relaxed.gpu.global.u32 %0, [%1];" : "=r"(e) : "l"(g_flags + F_EXIT * 8) : "memory");
    return e / NCTA;
}
__device__ __forceinline__ void fence_proxy_async() { asm volatile("fence.proxy.async;" ::: "memory"); }

__device__ __forceinline__ void wgmma_fence() { asm volatile("wgmma.fence.sync.aligned;" ::: "memory"); }
__device__ __forceinline__ void wgmma_commit() { asm volatile("wgmma.commit_group.sync.aligned;" ::: "memory"); }
template <int N>
__device__ __forceinline__ void wgmma_wait() { asm volatile("wgmma.wait_group.sync.aligned %0;" ::"n"(N) : "memory"); }
template <int N>
__device__ __forceinline__ void fence_regs(float (&d)[N]) {
#pragma unroll
    for (int i = 0; i < N; i++) asm volatile("" : "+f"(d[i])::"memory");
}
template <int N>
__device__ __forceinline__ void fence_regs(uint32_t (&d)[N]) {
#pragma unroll
    for (int i = 0; i < N; i++) asm volatile("" : "+r"(d[i])::"memory");
}

template <int TA, int TB>
__device__ __forceinline__ void wgmma_ss_n128(float (&d)[64], uint32_t alo, uint32_t blo, int scale_d) {
    asm volatile("{\n.reg .pred p;\n.reg .b64 da, db;\nsetp.ne.b32 p, %66, 0;\n"
        "mov.b64 da, {%64, %69};\nmov.b64 db, {%65, %69};\n"
        "wgmma.mma_async.sync.aligned.m64n128k16.f32.bf16.bf16 "
        "{%0, %1, %2, %3, %4, %5, %6, %7, %8, %9, %10, %11, %12, %13, %14, %15, %16, %17, %18, %19, %20, %21, %22, %23, %24, %25, %26, %27, %28, %29, %30, %31, %32, %33, %34, %35, %36, %37, %38, %39, %40, %41, %42, %43, %44, %45, %46, %47, %48, %49, %50, %51, %52, %53, %54, %55, %56, %57, %58, %59, %60, %61, %62, %63}, da, db, p, 1, 1, %67, %68;\n}\n"
        :
          "+f"(d[0]), "+f"(d[1]), "+f"(d[2]), "+f"(d[3]), "+f"(d[4]), "+f"(d[5]), "+f"(d[6]), "+f"(d[7]),
          "+f"(d[8]), "+f"(d[9]), "+f"(d[10]), "+f"(d[11]), "+f"(d[12]), "+f"(d[13]), "+f"(d[14]), "+f"(d[15]),
          "+f"(d[16]), "+f"(d[17]), "+f"(d[18]), "+f"(d[19]), "+f"(d[20]), "+f"(d[21]), "+f"(d[22]), "+f"(d[23]),
          "+f"(d[24]), "+f"(d[25]), "+f"(d[26]), "+f"(d[27]), "+f"(d[28]), "+f"(d[29]), "+f"(d[30]), "+f"(d[31]),
          "+f"(d[32]), "+f"(d[33]), "+f"(d[34]), "+f"(d[35]), "+f"(d[36]), "+f"(d[37]), "+f"(d[38]), "+f"(d[39]),
          "+f"(d[40]), "+f"(d[41]), "+f"(d[42]), "+f"(d[43]), "+f"(d[44]), "+f"(d[45]), "+f"(d[46]), "+f"(d[47]),
          "+f"(d[48]), "+f"(d[49]), "+f"(d[50]), "+f"(d[51]), "+f"(d[52]), "+f"(d[53]), "+f"(d[54]), "+f"(d[55]),
          "+f"(d[56]), "+f"(d[57]), "+f"(d[58]), "+f"(d[59]), "+f"(d[60]), "+f"(d[61]), "+f"(d[62]), "+f"(d[63])
        : "r"(alo), "r"(blo), "r"(scale_d), "n"(TA), "n"(TB), "r"(DESC_HI));
}
template <int TA, int TB>
__device__ __forceinline__ void wgmma_ss_n192(float (&d)[96], uint32_t alo, uint32_t blo, int scale_d) {
    asm volatile("{\n.reg .pred p;\n.reg .b64 da, db;\nsetp.ne.b32 p, %98, 0;\n"
        "mov.b64 da, {%96, %101};\nmov.b64 db, {%97, %101};\n"
        "wgmma.mma_async.sync.aligned.m64n192k16.f32.bf16.bf16 "
        "{%0, %1, %2, %3, %4, %5, %6, %7, %8, %9, %10, %11, %12, %13, %14, %15, %16, %17, %18, %19, %20, %21, %22, %23, %24, %25, %26, %27, %28, %29, %30, %31, %32, %33, %34, %35, %36, %37, %38, %39, %40, %41, %42, %43, %44, %45, %46, %47, %48, %49, %50, %51, %52, %53, %54, %55, %56, %57, %58, %59, %60, %61, %62, %63, %64, %65, %66, %67, %68, %69, %70, %71, %72, %73, %74, %75, %76, %77, %78, %79, %80, %81, %82, %83, %84, %85, %86, %87, %88, %89, %90, %91, %92, %93, %94, %95}, da, db, p, 1, 1, %99, %100;\n}\n"
        :
          "+f"(d[0]), "+f"(d[1]), "+f"(d[2]), "+f"(d[3]), "+f"(d[4]), "+f"(d[5]), "+f"(d[6]), "+f"(d[7]),
          "+f"(d[8]), "+f"(d[9]), "+f"(d[10]), "+f"(d[11]), "+f"(d[12]), "+f"(d[13]), "+f"(d[14]), "+f"(d[15]),
          "+f"(d[16]), "+f"(d[17]), "+f"(d[18]), "+f"(d[19]), "+f"(d[20]), "+f"(d[21]), "+f"(d[22]), "+f"(d[23]),
          "+f"(d[24]), "+f"(d[25]), "+f"(d[26]), "+f"(d[27]), "+f"(d[28]), "+f"(d[29]), "+f"(d[30]), "+f"(d[31]),
          "+f"(d[32]), "+f"(d[33]), "+f"(d[34]), "+f"(d[35]), "+f"(d[36]), "+f"(d[37]), "+f"(d[38]), "+f"(d[39]),
          "+f"(d[40]), "+f"(d[41]), "+f"(d[42]), "+f"(d[43]), "+f"(d[44]), "+f"(d[45]), "+f"(d[46]), "+f"(d[47]),
          "+f"(d[48]), "+f"(d[49]), "+f"(d[50]), "+f"(d[51]), "+f"(d[52]), "+f"(d[53]), "+f"(d[54]), "+f"(d[55]),
          "+f"(d[56]), "+f"(d[57]), "+f"(d[58]), "+f"(d[59]), "+f"(d[60]), "+f"(d[61]), "+f"(d[62]), "+f"(d[63]),
          "+f"(d[64]), "+f"(d[65]), "+f"(d[66]), "+f"(d[67]), "+f"(d[68]), "+f"(d[69]), "+f"(d[70]), "+f"(d[71]),
          "+f"(d[72]), "+f"(d[73]), "+f"(d[74]), "+f"(d[75]), "+f"(d[76]), "+f"(d[77]), "+f"(d[78]), "+f"(d[79]),
          "+f"(d[80]), "+f"(d[81]), "+f"(d[82]), "+f"(d[83]), "+f"(d[84]), "+f"(d[85]), "+f"(d[86]), "+f"(d[87]),
          "+f"(d[88]), "+f"(d[89]), "+f"(d[90]), "+f"(d[91]), "+f"(d[92]), "+f"(d[93]), "+f"(d[94]), "+f"(d[95])
        : "r"(alo), "r"(blo), "r"(scale_d), "n"(TA), "n"(TB), "r"(DESC_HI));
}
template <int TB>
__device__ __forceinline__ void wgmma_rs_n128(float (&d)[64], uint32_t a0, uint32_t a1, uint32_t a2, uint32_t a3, uint32_t blo, int scale_d) {
    asm volatile("{\n.reg .pred p;\n.reg .b64 db;\nsetp.ne.b32 p, %69, 0;\n"
        "mov.b64 db, {%68, %71};\n"
        "wgmma.mma_async.sync.aligned.m64n128k16.f32.bf16.bf16 "
        "{%0, %1, %2, %3, %4, %5, %6, %7, %8, %9, %10, %11, %12, %13, %14, %15, %16, %17, %18, %19, %20, %21, %22, %23, %24, %25, %26, %27, %28, %29, %30, %31, %32, %33, %34, %35, %36, %37, %38, %39, %40, %41, %42, %43, %44, %45, %46, %47, %48, %49, %50, %51, %52, %53, %54, %55, %56, %57, %58, %59, %60, %61, %62, %63}, {%64, %65, %66, %67}, db, p, 1, 1, %70;\n}\n"
        :
          "+f"(d[0]), "+f"(d[1]), "+f"(d[2]), "+f"(d[3]), "+f"(d[4]), "+f"(d[5]), "+f"(d[6]), "+f"(d[7]),
          "+f"(d[8]), "+f"(d[9]), "+f"(d[10]), "+f"(d[11]), "+f"(d[12]), "+f"(d[13]), "+f"(d[14]), "+f"(d[15]),
          "+f"(d[16]), "+f"(d[17]), "+f"(d[18]), "+f"(d[19]), "+f"(d[20]), "+f"(d[21]), "+f"(d[22]), "+f"(d[23]),
          "+f"(d[24]), "+f"(d[25]), "+f"(d[26]), "+f"(d[27]), "+f"(d[28]), "+f"(d[29]), "+f"(d[30]), "+f"(d[31]),
          "+f"(d[32]), "+f"(d[33]), "+f"(d[34]), "+f"(d[35]), "+f"(d[36]), "+f"(d[37]), "+f"(d[38]), "+f"(d[39]),
          "+f"(d[40]), "+f"(d[41]), "+f"(d[42]), "+f"(d[43]), "+f"(d[44]), "+f"(d[45]), "+f"(d[46]), "+f"(d[47]),
          "+f"(d[48]), "+f"(d[49]), "+f"(d[50]), "+f"(d[51]), "+f"(d[52]), "+f"(d[53]), "+f"(d[54]), "+f"(d[55]),
          "+f"(d[56]), "+f"(d[57]), "+f"(d[58]), "+f"(d[59]), "+f"(d[60]), "+f"(d[61]), "+f"(d[62]), "+f"(d[63])
        : "r"(a0), "r"(a1), "r"(a2), "r"(a3), "r"(blo), "r"(scale_d), "n"(TB), "r"(DESC_HI));
}
template <int TB>
__device__ __forceinline__ void wgmma_rs_n128_z(float (&d)[64], uint32_t a0, uint32_t a1, uint32_t a2, uint32_t a3, uint32_t blo) {
    asm volatile("{\n.reg .pred p;\n.reg .b64 db;\nsetp.ne.b32 p, %69, 0;\n"
        "mov.b64 db, {%68, %71};\n"
        "wgmma.mma_async.sync.aligned.m64n128k16.f32.bf16.bf16 "
        "{%0, %1, %2, %3, %4, %5, %6, %7, %8, %9, %10, %11, %12, %13, %14, %15, %16, %17, %18, %19, %20, %21, %22, %23, %24, %25, %26, %27, %28, %29, %30, %31, %32, %33, %34, %35, %36, %37, %38, %39, %40, %41, %42, %43, %44, %45, %46, %47, %48, %49, %50, %51, %52, %53, %54, %55, %56, %57, %58, %59, %60, %61, %62, %63}, {%64, %65, %66, %67}, db, p, 1, 1, %70;\n}\n"
        :
          "=f"(d[0]), "=f"(d[1]), "=f"(d[2]), "=f"(d[3]), "=f"(d[4]), "=f"(d[5]), "=f"(d[6]), "=f"(d[7]),
          "=f"(d[8]), "=f"(d[9]), "=f"(d[10]), "=f"(d[11]), "=f"(d[12]), "=f"(d[13]), "=f"(d[14]), "=f"(d[15]),
          "=f"(d[16]), "=f"(d[17]), "=f"(d[18]), "=f"(d[19]), "=f"(d[20]), "=f"(d[21]), "=f"(d[22]), "=f"(d[23]),
          "=f"(d[24]), "=f"(d[25]), "=f"(d[26]), "=f"(d[27]), "=f"(d[28]), "=f"(d[29]), "=f"(d[30]), "=f"(d[31]),
          "=f"(d[32]), "=f"(d[33]), "=f"(d[34]), "=f"(d[35]), "=f"(d[36]), "=f"(d[37]), "=f"(d[38]), "=f"(d[39]),
          "=f"(d[40]), "=f"(d[41]), "=f"(d[42]), "=f"(d[43]), "=f"(d[44]), "=f"(d[45]), "=f"(d[46]), "=f"(d[47]),
          "=f"(d[48]), "=f"(d[49]), "=f"(d[50]), "=f"(d[51]), "=f"(d[52]), "=f"(d[53]), "=f"(d[54]), "=f"(d[55]),
          "=f"(d[56]), "=f"(d[57]), "=f"(d[58]), "=f"(d[59]), "=f"(d[60]), "=f"(d[61]), "=f"(d[62]), "=f"(d[63])
        : "r"(a0), "r"(a1), "r"(a2), "r"(a3), "r"(blo), "n"(0), "n"(TB), "r"(DESC_HI));
}
template <int TA, int TB>
__device__ __forceinline__ void wgmma_ss_n128_z(float (&d)[64], uint32_t alo, uint32_t blo) {
    asm volatile("{\n.reg .pred p;\n.reg .b64 da, db;\nsetp.ne.b32 p, %66, 0;\n"
        "mov.b64 da, {%64, %69};\nmov.b64 db, {%65, %69};\n"
        "wgmma.mma_async.sync.aligned.m64n128k16.f32.bf16.bf16 "
        "{%0, %1, %2, %3, %4, %5, %6, %7, %8, %9, %10, %11, %12, %13, %14, %15, %16, %17, %18, %19, %20, %21, %22, %23, %24, %25, %26, %27, %28, %29, %30, %31, %32, %33, %34, %35, %36, %37, %38, %39, %40, %41, %42, %43, %44, %45, %46, %47, %48, %49, %50, %51, %52, %53, %54, %55, %56, %57, %58, %59, %60, %61, %62, %63}, da, db, p, 1, 1, %67, %68;\n}\n"
        :
          "=f"(d[0]), "=f"(d[1]), "=f"(d[2]), "=f"(d[3]), "=f"(d[4]), "=f"(d[5]), "=f"(d[6]), "=f"(d[7]),
          "=f"(d[8]), "=f"(d[9]), "=f"(d[10]), "=f"(d[11]), "=f"(d[12]), "=f"(d[13]), "=f"(d[14]), "=f"(d[15]),
          "=f"(d[16]), "=f"(d[17]), "=f"(d[18]), "=f"(d[19]), "=f"(d[20]), "=f"(d[21]), "=f"(d[22]), "=f"(d[23]),
          "=f"(d[24]), "=f"(d[25]), "=f"(d[26]), "=f"(d[27]), "=f"(d[28]), "=f"(d[29]), "=f"(d[30]), "=f"(d[31]),
          "=f"(d[32]), "=f"(d[33]), "=f"(d[34]), "=f"(d[35]), "=f"(d[36]), "=f"(d[37]), "=f"(d[38]), "=f"(d[39]),
          "=f"(d[40]), "=f"(d[41]), "=f"(d[42]), "=f"(d[43]), "=f"(d[44]), "=f"(d[45]), "=f"(d[46]), "=f"(d[47]),
          "=f"(d[48]), "=f"(d[49]), "=f"(d[50]), "=f"(d[51]), "=f"(d[52]), "=f"(d[53]), "=f"(d[54]), "=f"(d[55]),
          "=f"(d[56]), "=f"(d[57]), "=f"(d[58]), "=f"(d[59]), "=f"(d[60]), "=f"(d[61]), "=f"(d[62]), "=f"(d[63])
        : "r"(alo), "r"(blo), "n"(0), "n"(TA), "n"(TB), "r"(DESC_HI));
}

__device__ __forceinline__ uint32_t pack_bf16(float lo, float hi) {
    uint32_t r;
    asm("cvt.rn.bf16x2.f32 %0, %1, %2;" : "=r"(r) : "f"(hi), "f"(lo));
    return r;
}
__device__ __forceinline__ uint32_t add_bf16x2(uint32_t a, uint32_t b) {
    uint32_t r;
    asm("add.rn.bf16x2 %0, %1, %2;" : "=r"(r) : "r"(a), "r"(b));
    return r;
}
__device__ __forceinline__ float bf_lo(uint32_t v) { return __uint_as_float(v << 16); }
__device__ __forceinline__ float bf_hi(uint32_t v) { return __uint_as_float(v & 0xffff0000u); }
__device__ __forceinline__ float round_bf16(float v) { return __bfloat162float(__float2bfloat16_rn(v)); }
__device__ __forceinline__ float ex2(float x) {
    float y;
    asm("ex2.approx.ftz.f32 %0, %1;" : "=f"(y) : "f"(x));
    return y;
}
__device__ __forceinline__ float rcp(float x) {
    float y;
    asm("rcp.approx.ftz.f32 %0, %1;" : "=f"(y) : "f"(x));
    return y;
}
__device__ __forceinline__ void stg128(void* p, uint32_t a, uint32_t b, uint32_t c, uint32_t d) {
    asm volatile("st.global.v4.b32 [%0], {%1, %2, %3, %4};" ::"l"(p), "r"(a), "r"(b), "r"(c), "r"(d) : "memory");
}
__device__ __forceinline__ int perm_row(int t) { return (t & ~255) | (((0x78 >> (((t >> 6) & 3) * 2)) & 3) << 6) | (t & 63); }
__device__ __forceinline__ int unperm_row(int t) { return (t & ~255) | (((0x9C >> (((t >> 6) & 3) * 2)) & 3) << 6) | (t & 63); }

#define PROF(i)
#define PROFG(i)
#define PROFDUMP()
#define TR(i)
#define BP(r, i)
#define LP(i)

template <int I>
__device__ __forceinline__ void store_chunk(const float (&a)[64], __nv_bfloat16* row0, __nv_bfloat16* row1, float s0, float s1) {
    stg128(row0 + 32 * I, pack_bf16(a[16 * I + 0] * s0, a[16 * I + 1] * s0), pack_bf16(a[16 * I + 4] * s0, a[16 * I + 5] * s0),
           pack_bf16(a[16 * I + 8] * s0, a[16 * I + 9] * s0), pack_bf16(a[16 * I + 12] * s0, a[16 * I + 13] * s0));
    stg128(row1 + 32 * I, pack_bf16(a[16 * I + 2] * s1, a[16 * I + 3] * s1), pack_bf16(a[16 * I + 6] * s1, a[16 * I + 7] * s1),
           pack_bf16(a[16 * I + 10] * s1, a[16 * I + 11] * s1), pack_bf16(a[16 * I + 14] * s1, a[16 * I + 15] * s1));
}
template <int I>
struct IntT { static constexpr int value = I; };
template <class F>
__device__ __forceinline__ void for4(F f) { f(IntT<0>{}); f(IntT<1>{}); f(IntT<2>{}); f(IntT<3>{}); }

struct Prod {
    uint32_t smem, bars;
    uint32_t bo, par;
    uint32_t dst, fb;
    __device__ __forceinline__ void acquire(uint32_t o, uint32_t parity, uint32_t bytes) {
        mbar_wait(bars + BAR_EMPTY + o, parity);
        fb = bars + BAR_FULL + o;
        dst = smem + o * (SLOT / 8);
        w_expect_tx(fb, bytes);
    }
    __device__ __forceinline__ void next(uint32_t bytes) {
        acquire(bo, par, bytes);
        const bool wrap = bo == (NSLOT - 1) * 8;
        bo = wrap ? 0u : bo + 8;
        par ^= wrap ? 1u : 0u;
    }
};

__device__ __forceinline__ int item_p(int ca, int rd) {
    const int v = (rd & 1) ? (ca + 4) & 7 : ca;
    return (rd & 2) ? 7 - v : v;
}
__device__ __forceinline__ int kv_round(int i) { return (KVORDER >> (4 * i)) & 3; }
__device__ __forceinline__ int slot_a(int i) { return (0x5310 >> (4 * i)) & 15; }
__device__ __forceinline__ int slot_w(int m) { return (0x264 >> (4 * m)) & 15; }

__device__ __forceinline__ void producer(const Params& P, uint32_t smem, uint32_t bars, int ca, int cb, int rank) {
    Prod pr{smem, bars, 0u, 0u, 0u, 0u};
    {
        int m = 0;
        uint32_t lap = 1;
#pragma unroll 1
        for (int u = 0; u < 32; u++) {
            if (u >= 3) {
                const int v = (u == 3) ? 3 + ca : u + 7;
                if (v < 32 && (u == 3 || (v & 7) == ca)) w_tma_prefetch((v & 4) ? &P.wuv : &P.wuk, (cb + 8 * kv_round(v >> 3)) * 128 + rank * 64, (v & 3) * 128);
                if (u == 24) {
                    w_tma_prefetch(&P.wq, cb * 128 + rank * 64, ca * 64);
                    if (ca < 2) w_tma_prefetch(&P.wq, cb * 128 + rank * 64, (ca + 8) * 64);
                }
            }
            pr.acquire(slot_w(m) * 8, lap ^ (m >> 1), SLOT);
            lap ^= m >> 1;
            m = (m == 2) ? 0 : m + 1;
            TR(1 + u);
            w_tma_load_mc(pr.dst + rank * 16384, (u & 4) ? &P.wuv : &P.wuk, (cb + 8 * kv_round(u >> 3)) * 128 + rank * 64, (u & 3) * 128, pr.fb);
            if (u < 3) {
                pr.acquire(slot_a(u + 1) * 8, 1, SLOT);
                w_tma_load(pr.dst, &P.ckv, u * 128 + 128, (2 * ca + rank) * 128, pr.fb);
                w_tma_load(pr.dst + 16384, &P.ckv, u * 128 + 192, (2 * ca + rank) * 128, pr.fb);
            }
        }
    }
    PROF(1);
    mbar_wait(bars + BAR_DEP, 0);
#pragma unroll 1
    for (int rd = 0; rd < 4; rd++) {
        const int h = 8 * rd + cb, p = item_p(ca, rd);
#pragma unroll 1
        for (int ks = 0; ks < 10; ks++) {
            pr.next(SLOT);
            w_tma_load_mc(pr.dst + 16384 + rank * 8192, &P.wq, h * 128 + rank * 64, ks * 64, pr.fb);
            w_tma_load(pr.dst, &P.xn, ks * 64, 256 * p + 128 * rank, pr.fb);
        }
        PROF(8 + rd * 4);
        mbar_wait(bars + BAR_DEP + (1 + rd) * 8, 0);
        const int last = 4 * p + 3, top = h * 32 + last;
#pragma unroll 1
        for (int i = 0; i <= last; i++) {
            const int t = (i == 0) ? top - 1 : (i == last) ? h * 32 + 1 : (i & 1) ? top - 2 - i : top + 2 - i;
            pr.next(SLOT);
            w_tma_load_mc(pr.dst + rank * 16384, &P.kv, rank * 64, t * 128, pr.fb);
            if (i == 2) {
                if (rd < 3) {
                    w_tma_prefetch(&P.wq, (h + 8) * 128 + rank * 64, ca * 64);
                    if (ca < 2) w_tma_prefetch(&P.wq, (h + 8) * 128 + rank * 64, (ca + 8) * 64);
                } else {
#pragma unroll 1
                    for (int j = 0; j < 10; j++) {
                        const int tt = ca + (j >= 5 ? 8 : 0);
                        w_tma_prefetch(&P.wo, 320 * (cb & 1) + 64 * (j >= 5 ? j - 5 : j), (8 * (tt >> 2) + (cb & 6) + ((tt >> 1) & 1)) * 128 + (tt & 1) * 64 + rank * 32);
                    }
                }
            }
        }
        PROF(9 + rd * 4);
    }
    {
        const int n0 = 320 * (cb & 1), kg = cb >> 1;
#pragma unroll 1
        for (int t = 0; t < 16; t++) {
            const int h = 8 * (t >> 2) + 2 * kg + ((t >> 1) & 1), ks = t & 1;
            const int krow = h * 128 + ks * 64 + rank * 32;
            pr.next(SLOT);
            w_tma_load_mc(pr.dst + 16384 + rank * 8192, &P.wo, n0, krow, pr.fb);
            w_tma_load_mc(pr.dst + 16384 + rank * 8192 + 4096, &P.wo, n0 + 64, krow, pr.fb);
            mbar_wait(bars + BAR_DEP + (5 + (t >> 1)) * 8, 0);
            w_tma_load(pr.dst, &P.ctx, ks * 64, h * SEQ + 256 * ca + 128 * rank, pr.fb);
            pr.next(24576);
#pragma unroll
            for (int c = 0; c < 3; c++) w_tma_load_mc(pr.dst + rank * 12288 + c * 4096, &P.wo, n0 + 128 + 64 * c, krow, pr.fb);
        }
    }
}

struct Slot {
    uint32_t bo, dl, par;
};
struct Cons {
    uint32_t bars, rel;
    uint32_t dl0;
    uint32_t lane;
    Slot cur;
    __device__ __forceinline__ Slot slot(int s, uint32_t par) const { return Slot{(uint32_t)s * 8, dl0 + (uint32_t)s * (SLOT >> 4), par}; }
    __device__ __forceinline__ void wait(const Slot& s) const { mbar_wait(bars + BAR_FULL + s.bo, s.par); }
    __device__ __forceinline__ void release(uint32_t bo) const {
        asm volatile("{\n.reg .pred p;\nsetp.lt.u32 p, %1, 2;\n@p mbarrier.arrive.shared::cluster.b64 _, [%0];\n}\n" ::"r"(rel + bo), "r"(lane) : "memory");
    }
    __device__ __forceinline__ Slot next() {
        const Slot s = cur;
        const bool wrap = s.bo == (NSLOT - 1) * 8;
        cur.bo = wrap ? 0u : s.bo + 8;
        cur.dl = wrap ? dl0 : s.dl + (SLOT >> 4);
        cur.par = s.par ^ (wrap ? 1u : 0u);
        return s;
    }
};
__host__ __device__ constexpr uint32_t lbo(uint32_t bytes) { return (bytes >> 4) << 16; }

__device__ __forceinline__ float div640(float x) {
    const float q = x * (1.0f / DM);
    return fmaf(fmaf(-q, (float)DM, x), 1.0f / DM, q);
}
__device__ __forceinline__ float sqrt_approx(float x) {
    float y;
    asm("sqrt.approx.ftz.f32 %0, %1;" : "=f"(y) : "f"(x));
    return y;
}
struct LayerNorm {
    uint4 xv[5], wv[5];
    float mean, inv, r;
    static __device__ __forceinline__ float half_sum(float v) {
#pragma unroll
        for (int o = 8; o > 0; o >>= 1) v += __shfl_xor_sync(0xffffffffu, v, o);
        return v;
    }
    __device__ __forceinline__ void load(const __nv_bfloat16* x, const __nv_bfloat16* wr, int t, int l) {
#pragma unroll
        for (int i = 0; i < 5; i++) {
            xv[i] = ldg_stream(reinterpret_cast<const uint4*>(x + t * DM) + l + 16 * i);
            wv[i] = __ldg(reinterpret_cast<const uint4*>(wr) + l + 16 * i);
        }
    }
    __device__ __forceinline__ void stat1() {
        float a[4] = {0.f, 0.f, 0.f, 0.f};
#pragma unroll
        for (int i = 0; i < 20; i++) { const uint32_t u = (&xv[i >> 2].x)[i & 3]; a[i & 3] += bf_lo(u) + bf_hi(u); }
        mean = div640(half_sum((a[0] + a[1]) + (a[2] + a[3])));
        r = 0.f;
    }
    template <int H>
    __device__ __forceinline__ void stat2() {
        float a[4] = {r, 0.f, 0.f, 0.f};
#pragma unroll
        for (int i = H ? 12 : 0; i < (H ? 20 : 12); i++) {
            uint32_t u = (&xv[i >> 2].x)[i & 3];
            asm volatile("" : "+r"(u));
            const float d0 = bf_lo(u) - mean, d1 = bf_hi(u) - mean;
            a[i & 3] = fmaf(d0, d0, fmaf(d1, d1, a[i & 3]));
        }
        r = (a[0] + a[1]) + (a[2] + a[3]);
        if (H) {
            inv = rcp(round_bf16(sqrt_approx(round_bf16(round_bf16(div640(half_sum(r))) + 1e-5f))));
            r = 0.f;
        }
    }
    template <int I>
    __device__ __forceinline__ void piece(__nv_bfloat16* out, int t, int l) {
        const uint32_t nmb = pack_bf16(-mean, -mean);
        uint32_t o[4], z[4];
        float a[4];
#pragma unroll
        for (int j = 0; j < 4; j++) {
            const uint32_t u = (&xv[I].x)[j], w = (&wv[I].x)[j];
            const uint32_t d = add_bf16x2(u, nmb);
            o[j] = pack_bf16(bf_lo(d) * inv, bf_hi(d) * inv);
            z[j] = add_bf16x2(u, o[j]);
            a[j] = fmaf(bf_hi(o[j]), bf_hi(w), bf_lo(o[j]) * bf_lo(w));
        }
        r += (a[0] + a[1]) + (a[2] + a[3]);
        stg128(g_xn + perm_row(t) * DM + 8 * (l + 16 * I), o[0], o[1], o[2], o[3]);
        stg128(out + t * DM + 8 * (l + 16 * I), z[0], z[1], z[2], z[3]);
        if (I == 4) {
            r = half_sum(r);
            if (l == 0) g_r[t] = round_bf16(r);
        }
    }
};

constexpr float SM_SCALE = 0.08838834764831845f * 1.4426950408889634f;

template <int J0, int J1>
__device__ __forceinline__ void exp_part(float (&s)[64], float n0, float n1, float& r0, float& r1) {
    float a1 = 0.f, b1 = 0.f;
#pragma unroll
    for (int j = J0; j < J1; j++) {
        s[4 * j + 0] = ex2(fmaf(s[4 * j + 0], SM_SCALE, n0));
        s[4 * j + 1] = ex2(fmaf(s[4 * j + 1], SM_SCALE, n0));
        s[4 * j + 2] = ex2(fmaf(s[4 * j + 2], SM_SCALE, n1));
        s[4 * j + 3] = ex2(fmaf(s[4 * j + 3], SM_SCALE, n1));
        r0 += s[4 * j + 0]; r1 += s[4 * j + 2];
        if (j == J0) { a1 = s[4 * j + 1]; b1 = s[4 * j + 3]; } else { a1 += s[4 * j + 1]; b1 += s[4 * j + 3]; }
    }
    r0 += a1;
    r1 += b1;
}
__device__ __forceinline__ void sched_barrier(float x, float y, uint32_t scratch) {
    asm volatile("{\n.reg .pred p;\nsetp.lt.f32 p, %0, 0f00000000;\n@p st.shared.f32 [%2], %1;\n}\n" ::"f"(x), "f"(y), "r"(scratch) : "memory");
}
__device__ __forceinline__ void pack_tile(const float (&s)[64], uint32_t (&p)[32]) {
#pragma unroll
    for (int i = 0; i < 32; i++) p[i] = pack_bf16(s[2 * i], s[2 * i + 1]);
}
template <bool ZERO>
__device__ __forceinline__ void gemm_rs(float (&d)[64], const uint32_t (&a)[32], uint32_t dl, int acc = 1) {
    const uint32_t b = dl + lbo(16384);
    if (ZERO) wgmma_rs_n128_z<1>(d, a[0], a[1], a[2], a[3], b);
#pragma unroll
    for (int k = ZERO ? 1 : 0; k < 8; k++) wgmma_rs_n128<1>(d, a[4 * k], a[4 * k + 1], a[4 * k + 2], a[4 * k + 3], b + k * 128, k ? 1 : acc);
}
template <int ZERO>
__device__ __forceinline__ void gemm_q(float (&d)[64], uint32_t dl, int role) {
    const uint32_t a = dl + role * 512 + lbo(16), b = dl + 1024 + lbo(8192);
    if (ZERO) wgmma_ss_n128_z<0, 1>(d, a, b);
#pragma unroll
    for (int k = ZERO ? 1 : 0; k < 4; k++) wgmma_ss_n128<0, 1>(d, a + k * 2, b + k * 128, 1);
}
template <bool KT, bool ZERO, int K0, int K1>
__device__ __forceinline__ void gemm_kv(float (&d)[64], uint32_t ckv, uint32_t wt, int wg) {
    if (KT) {
        const uint32_t a = wt + wg * 1024 + lbo(16), b = ckv + lbo(16);
        if (ZERO) wgmma_ss_n128_z<1, 0>(d, a, b);
#pragma unroll
        for (int k = ZERO ? 1 : K0; k < K1; k++) wgmma_ss_n128<1, 0>(d, a + k * 128, b + (k >> 2) * 1024 + (k & 3) * 2, 1);
    } else {
        const uint32_t a = ckv + wg * 512 + lbo(16), b = wt + lbo(16384);
        if (ZERO) wgmma_ss_n128_z<0, 1>(d, a, b);
#pragma unroll
        for (int k = ZERO ? 1 : K0; k < K1; k++) wgmma_ss_n128<0, 1>(d, a + (k >> 2) * 1024 + (k & 3) * 2, b + k * 128, 1);
    }
}
__device__ __forceinline__ void mma16816(float& d0, float& d1, float& d2, float& d3, uint32_t a0, uint32_t a1, uint32_t a2, uint32_t a3, uint32_t b0, uint32_t b1) {
    asm volatile("mma.sync.aligned.m16n8k16.row.col.f32.bf16.bf16.f32 {%0,%1,%2,%3}, {%4,%5,%6,%7}, {%8,%9}, {%0,%1,%2,%3};"
                 : "+f"(d0), "+f"(d1), "+f"(d2), "+f"(d3) : "r"(a0), "r"(a1), "r"(a2), "r"(a3), "r"(b0), "r"(b1));
}
__device__ __forceinline__ uint32_t ld_pair(const __nv_bfloat16* p) {
    const unsigned short* u = reinterpret_cast<const unsigned short*>(p);
    return (uint32_t)__ldcg(u) | ((uint32_t)__ldcg(u + 128) << 16);
}
__device__ __forceinline__ void attention_exact(float (&o)[64], const uint32_t (&qf)[32], float& l0, float& l1, int h, int nblk, int rr, int lane) {
    const int q = lane & 3, lr = lane >> 2;
    float m0 = -INFINITY, m1 = -INFINITY;
    l0 = 0.f; l1 = 0.f;
#pragma unroll
    for (int i = 0; i < 64; i++) o[i] = 0.f;
#pragma unroll 1
    for (int cidx = 0; cidx < nblk * 8; cidx++) {
        const int kc = cidx & 7;
        const __nv_bfloat16* kt = g_kv + (size_t)((h * 16 + (cidx >> 3)) * 2) * 16384;
        float sc[8];
#pragma unroll
        for (int i = 0; i < 8; i++) sc[i] = 0.f;
#pragma unroll
        for (int kk = 0; kk < 8; kk++)
#pragma unroll
            for (int nt = 0; nt < 2; nt++) {
                const __nv_bfloat16* b = kt + (16 * kk + 2 * q) * 128 + 16 * kc + 8 * nt + lr;
                mma16816(sc[4 * nt], sc[4 * nt + 1], sc[4 * nt + 2], sc[4 * nt + 3], qf[4 * kk], qf[4 * kk + 1], qf[4 * kk + 2], qf[4 * kk + 3],
                         ld_pair(b), ld_pair(b + 8 * 128));
            }
        const int lim = rr + ((nblk - 1) - (cidx >> 3)) * 128 - 32 * (kc >> 1) - 4 * (kc & 1);
#pragma unroll
        for (int i = 0; i < 8; i++)
            if (2 * (i >> 2) + (i & 1) > lim + 4 * (i & 2)) sc[i] = -INFINITY;
        float x0 = fmaxf(fmaxf(sc[0], sc[1]), fmaxf(sc[4], sc[5])), x1 = fmaxf(fmaxf(sc[2], sc[3]), fmaxf(sc[6], sc[7]));
        x0 = fmaxf(x0, __shfl_xor_sync(0xffffffffu, x0, 1)); x1 = fmaxf(x1, __shfl_xor_sync(0xffffffffu, x1, 1));
        x0 = fmaxf(x0, __shfl_xor_sync(0xffffffffu, x0, 2)); x1 = fmaxf(x1, __shfl_xor_sync(0xffffffffu, x1, 2));
        x0 = fmaxf(x0, m0); x1 = fmaxf(x1, m1);
        const float a0 = ex2((m0 - x0) * SM_SCALE), a1 = ex2((m1 - x1) * SM_SCALE);
        m0 = x0; m1 = x1;
#pragma unroll
        for (int i = 0; i < 8; i++) sc[i] = ex2((sc[i] - ((i & 2) ? m1 : m0)) * SM_SCALE);
        l0 = l0 * a0 + (sc[0] + sc[1]) + (sc[4] + sc[5]);
        l1 = l1 * a1 + (sc[2] + sc[3]) + (sc[6] + sc[7]);
        const uint32_t p0 = pack_bf16(sc[0], sc[1]), p1 = pack_bf16(sc[2], sc[3]), p2 = pack_bf16(sc[4], sc[5]), p3 = pack_bf16(sc[6], sc[7]);
        const __nv_bfloat16* vb = kt + 16384 + (16 * kc + 2 * q) * 128 + lr;
#pragma unroll
        for (int nt = 0; nt < 16; nt++) {
            o[4 * nt] *= a0; o[4 * nt + 1] *= a0; o[4 * nt + 2] *= a1; o[4 * nt + 3] *= a1;
            mma16816(o[4 * nt], o[4 * nt + 1], o[4 * nt + 2], o[4 * nt + 3], p0, p1, p2, p3, ld_pair(vb + 8 * nt), ld_pair(vb + 8 * nt + 8 * 128));
        }
    }
}

__device__ __forceinline__ void signal(uint32_t bars, int wg, int e, int lane) {
    __syncwarp();
    asm volatile("{\n.reg .pred p;\nsetp.eq.u32 p, %1, 0;\n@p mbarrier.arrive.shared::cta.b64 _, [%0];\n}\n" ::"r"(bars + BAR_SIG + (wg * 9 + e) * 8), "r"(lane) : "memory");
}

__device__ __forceinline__ void consumer(const Params& P, uint32_t smem, uint32_t bars, int ca, int cb, int rank, int wg) {
    const int lane = threadIdx.x & 31, w = (threadIdx.x >> 5) & 3, q = lane & 3, lr = lane >> 2;
    PROF(7);
    cluster_wait();
    Cons c{bars, mapa(bars + BAR_EMPTY, lane & 1), (smem & 0x3FFFF) >> 4, (uint32_t)lane, Slot{0u, (smem & 0x3FFFF) >> 4, 1u}};
    PROFG(180);
    PROF(1);
    float o[64], s[64];
    uint32_t pend;
    __nv_bfloat16* ep_ptr;
    int ep_step;
    {
        const int ln_t = blockIdx.x * 16 + wg * 8 + w * 2 + (lane >> 4);
        const int krow = 64 * wg + 16 * w + lr;
        const int vrow = 64 * wg + 32 * (w >> 1) + 8 * (lr >> 1) + 4 * (w & 1) + (lr & 1);
        ep_step = 2 * 128;
        int m = 0;
        uint32_t lap = 0;
        LayerNorm ln;
        auto step = [&](auto kt, auto kc, float (&d)[64], int hh) {
            const Slot sa = c.slot(slot_a(kc.value), 0), sw = c.slot(slot_w(m), lap ^ (m >> 1));
            lap ^= m >> 1;
            m = (m == 2) ? 0 : m + 1;
            TR(1 + (hh * 8 + (kt.value ? 0 : 4) + kc.value) * 2);
            if (kt.value && hh == 0) c.wait(sa);
            c.wait(sw);
            TR(2 + (hh * 8 + (kt.value ? 0 : 4) + kc.value) * 2);
            wgmma_fence();
            gemm_kv<kt.value, kc.value == 0, 0, KVSPLIT>(d, sa.dl, sw.dl, wg);
            wgmma_commit();
            wgmma_wait<1>();
            if (!(kt.value && kc.value == 0 && hh == 0)) c.release(pend);
            if (!kt.value && kc.value > 0 && hh == 3) c.release(slot_a(kc.value - 1) * 8);
            pend = sw.bo;
            wgmma_fence();
            gemm_kv<kt.value, false, KVSPLIT, 8>(d, sa.dl, sw.dl, wg);
            wgmma_commit();
        };
#pragma unroll 1
        for (int hh = 0; hh < 4; hh++) {
            __nv_bfloat16* base = g_kv + (size_t)(((cb + 8 * kv_round(hh)) * 16 + 2 * ca + rank) * 2) * 16384 + 8 * q;
            const bool do_ln = hh == wg * LNSTAG + 1;
            for4([&](auto kc) {
                step(TrueT{}, kc, s, hh);
                if (hh > 0) {
                    if (kc.value == 0) fence_regs(o);
                    store_chunk<kc.value>(o, ep_ptr, ep_ptr + ep_step, 1.f, 1.f);
                }
                if (do_ln) {
                    if (kc.value == 0) ln.stat1();
                    if (kc.value == 1) ln.template stat2<0>();
                    if (kc.value == 2) ln.template stat2<1>();
                    if (kc.value == 3) ln.template piece<0>(P.out, ln_t, lane & 15);
                }
            });
            if (hh > 0) signal(bars, wg, hh, lane);
            for4([&](auto kc) {
                step(FalseT{}, kc, o, hh);
                if (kc.value == 0) fence_regs(s);
                store_chunk<kc.value>(s, base + krow * 128, base + (krow + 8) * 128, 1.f, 1.f);
                if (do_ln) ln.template piece<kc.value + 1>(P.out, ln_t, lane & 15);
                if (kc.value == 1 && hh == wg * LNSTAG) ln.load(P.x, P.wr, ln_t, lane & 15);
            });
            if (do_ln) signal(bars, wg, 0, lane);
            PROF(24 + hh);
            if (hh == 1) PROFG(181);
            ep_ptr = base + 16384 + vrow * 128;
        }
    }
    PROFG(182);
    PROF(2);
    {
        uint32_t pf[32], qf[32];
        float l0 = 0.25f, l1 = 0.25f;
        const int bar_me = 2 + wg, bar_other = 3 - wg;
#pragma unroll 1
        for (int rd = 0; rd < 4; rd++) {
            const int h = 8 * rd + cb, p = item_p(ca, rd);
            const int role = wg ^ (rd & 1);
            const int nrest = 2 * p + role;
            Slot kfirst;
            {
                auto qstep = [&](auto zero, int ks) {
                    const Slot sl = c.next();
                    BP(2, 4 + 3 * ks);
                    c.wait(sl);
                    BP(2, 5 + 3 * ks);
                    wgmma_fence();
                    gemm_q<zero.value>(s, sl.dl, role);
                    wgmma_commit();
                    wgmma_wait<1>();
                    BP(2, 6 + 3 * ks);
                    c.release(pend);
                    pend = sl.bo;
                };
                qstep(TrueT{}, 0);
                if (rd == 0) c.release(slot_a(3) * 8);
                fence_regs(o);
#pragma unroll 1
                for (int ks = 1; ks < QST; ks++) qstep(FalseT{}, ks);
                for4([&](auto i) {
                    qstep(FalseT{}, QST + i.value);
                    if (i.value == 0) {
                        l0 += __shfl_xor_sync(0xffffffffu, l0, 1); l1 += __shfl_xor_sync(0xffffffffu, l1, 1);
                        l0 += __shfl_xor_sync(0xffffffffu, l0, 2); l1 += __shfl_xor_sync(0xffffffffu, l1, 2);
                        l0 = rcp(l0); l1 = rcp(l1);
                    }
                    store_chunk<i.value>(o, ep_ptr, ep_ptr + ep_step, l0, l1);
                });
                signal(bars, wg, 4 + rd, lane);
                PROF(11 + rd * 4);
#pragma unroll 1
                for (int ks = QST + 4; ks < 10; ks++) qstep(FalseT{}, ks);
                if (!role) { const Slot sl = c.next(); c.wait(sl); c.release(sl.bo); }
                kfirst = c.next();
                c.wait(kfirst);
                wgmma_wait<0>();
                BP(2, 34);
                c.release(pend);
                fence_regs(s);
                pack_tile(s, qf);
            }
            PROF(8 + rd * 4);
            fence_regs(qf);
            BP(2, 35);
            if (PINGPONG && !role) named_sync(bar_me, 256);
            BP(2, 36);
            wgmma_fence();
            gemm_rs<true>(s, qf, kfirst.dl);
            wgmma_commit();
            if (PINGPONG) named_arrive(bar_other, 256);
            BP(2, 37);
            if (!role) { const Slot sl = c.next(); c.wait(sl); c.release(sl.bo); }
            const int dg = __reduce_or_sync(0xffffffffu, 2 * (role ^ rank) + (w >> 1));
            wgmma_wait<0>();
            BP(2, 38);
            fence_regs(s);
            c.release(kfirst.bo);
            float n0, n1;
            l0 = 0.f; l1 = 0.f;
            for4([&](auto a) {
                constexpr int B = 16 * a.value;
                if (a.value == dg) {
                    const int lim = 16 * (w & 1) + lr - 8 * q;
#pragma unroll
                    for (int i = 0; i < 16; i++)
                        if (2 * (i >> 2) + (i & 1) > lim + 4 * (i & 2)) s[B + i] = -INFINITY;
                }
                if (a.value == 0) {
                    n0 = fmaxf(fmaxf(fmaxf(s[0], s[1]), fmaxf(s[4], s[5])), fmaxf(fmaxf(s[8], s[9]), fmaxf(s[12], s[13])));
                    n1 = fmaxf(fmaxf(fmaxf(s[2], s[3]), fmaxf(s[6], s[7])), fmaxf(fmaxf(s[10], s[11]), fmaxf(s[14], s[15])));
                    n0 = fmaxf(n0, __shfl_xor_sync(0xffffffffu, n0, 1)); n1 = fmaxf(n1, __shfl_xor_sync(0xffffffffu, n1, 1));
                    n0 = fmaxf(n0, __shfl_xor_sync(0xffffffffu, n0, 2)); n1 = fmaxf(n1, __shfl_xor_sync(0xffffffffu, n1, 2));
                    n0 *= -SM_SCALE; n1 *= -SM_SCALE;
                }
                if (a.value <= dg) {
                    exp_part<4 * a.value, 4 * a.value + 4>(s, n0, n1, l0, l1);
#pragma unroll
                    for (int i = 0; i < 8; i++) pf[8 * a.value + i] = pack_bf16(s[B + 2 * i], s[B + 2 * i + 1]);
                } else {
#pragma unroll
                    for (int i = 0; i < 8; i++) pf[8 * a.value + i] = 0u;
                }
            });
            PROF(9 + rd * 4);
#pragma unroll 1
            for (int it = 0; it < nrest; it++) {
                const Slot sk = c.next(), sv = c.next();
                LP(0);
                if (it < 3) BP(2, 40 + 4 * it);
                if (it >= nrest - 2) BP(1, 60 + 4 * (it - nrest + 2));
                c.wait(sk);
                c.wait(sv);
                fence_regs(o); fence_regs(pf);
                LP(1);
                if (it < 3) BP(2, 41 + 4 * it);
                if (it >= nrest - 2) BP(1, 61 + 4 * (it - nrest + 2));
                if (PINGPONG) named_sync(bar_me, 256);
                LP(2);
                if (it < 3) BP(2, 42 + 4 * it);
                if (it >= nrest - 2) BP(1, 62 + 4 * (it - nrest + 2));
                wgmma_fence();
                gemm_rs<true>(s, qf, sk.dl);
                wgmma_commit();
                gemm_rs<false>(o, pf, sv.dl, it);
                wgmma_commit();
                if (PINGPONG) named_arrive(bar_other, 256);
                LP(3);
                if (it < 3) BP(2, 43 + 4 * it);
                if (it >= nrest - 2) BP(1, 63 + 4 * (it - nrest + 2));
                wgmma_wait<1>();
                LP(4);
                c.release(sk.bo);
                fence_regs(s);
                exp_part<0, SPLITJ>(s, n0, n1, l0, l1);
                sched_barrier(l0, l1, bars + MISC_OFF + 16);
                LP(5);
                wgmma_wait<0>();
                LP(6);
                c.release(sv.bo);
                fence_regs(o); fence_regs(pf);
                exp_part<SPLITJ, 16>(s, n0, n1, l0, l1);
                pack_tile(s, pf);
            }
            PROF(10 + rd * 4);
            PROFG(183 + rd);
            const Slot sv = c.next();
            BP(1, 0);
            c.wait(sv);
            if (nrest == 0) {
#pragma unroll
                for (int i = 0; i < 64; i++) o[i] = 0.f;
            }
            if (__builtin_expect(__any_sync(0xffffffffu, !(l0 < 0x1p60f && l1 < 0x1p60f)), 0)) {
                attention_exact(o, qf, l0, l1, h, nrest + 1, 64 * (role ^ rank) + 16 * w + lr - 8 * q, lane);
#pragma unroll
                for (int i = 0; i < 32; i++) pf[i] = 0u;
            }
            fence_regs(o); fence_regs(pf);
            BP(1, 1);
            if (PINGPONG && !role) named_sync(bar_me, 256);
            BP(1, 2);
            wgmma_fence();
            gemm_rs<false>(o, pf, sv.dl);
            wgmma_commit();
            BP(1, 3);
            pend = sv.bo;
            ep_ptr = g_ctx + (size_t)(h * SEQ + 256 * p + 128 * rank + 64 * role + 16 * w + lr) * HD + 8 * q;
            ep_step = 8 * HD;
        }
        l0 += __shfl_xor_sync(0xffffffffu, l0, 1); l1 += __shfl_xor_sync(0xffffffffu, l1, 1);
        l0 += __shfl_xor_sync(0xffffffffu, l0, 2); l1 += __shfl_xor_sync(0xffffffffu, l1, 2);
        l0 = rcp(l0); l1 = rcp(l1);
        wgmma_wait<0>();
        c.release(pend);
        fence_regs(o); fence_regs(pf);
        for4([&](auto i) { store_chunk<i.value>(o, ep_ptr, ep_ptr + ep_step, l0, l1); });
        signal(bars, wg, 8, lane);
    }
    PROFG(187);
    PROF(3);
    {
        float a1[64], a2[96];
        uint32_t px = 0, py = 0;
        auto mma1 = [&](const Slot& x, int acc) {
#pragma unroll
            for (int k = 0; k < 4; k++) wgmma_ss_n128<0, 1>(a1, x.dl + wg * 512 + lbo(16) + k * 2, x.dl + 1024 + lbo(4096) + (k >> 1) * 512 + (k & 1) * 128, k ? 1 : acc);
        };
        auto mma2 = [&](const Slot& x, const Slot& y, int acc) {
#pragma unroll
            for (int k = 0; k < 4; k++) wgmma_ss_n192<0, 1>(a2, x.dl + wg * 512 + lbo(16) + k * 2, y.dl + lbo(4096) + (k >> 1) * 768 + (k & 1) * 128, k ? 1 : acc);
        };
#pragma unroll 1
        for (int t = 0; t < (EARLYSEND ? 14 : 16); t++) {
            const Slot sx = c.next(), sy = c.next();
            c.wait(sx);
            wgmma_fence();
            mma1(sx, t);
            wgmma_commit();
            wgmma_wait<1>();
            if (t > 0) { c.release(px); c.release(py); }
            px = sx.bo; py = sy.bo;
            c.wait(sy);
            wgmma_fence();
            mma2(sx, sy, t);
            wgmma_commit();
        }
        if (EARLYSEND) {
            const Slot x0 = c.next(), y0 = c.next(), x1 = c.next(), y1 = c.next();
            c.wait(x0);
            c.wait(y0);
            wgmma_fence();
            mma2(x0, y0, 1);
            wgmma_commit();
            wgmma_wait<1>();
            c.release(px); c.release(py);
            c.wait(x1);
            c.wait(y1);
            wgmma_fence();
            mma2(x1, y1, 1);
            wgmma_commit();
            mma1(x0, 1);
            mma1(x1, 1);
            wgmma_commit();
        }
        const int cw = __reduce_or_sync(0xffffffffu, wg * 4 + w);
        Slot st = c.next();
        if (cw >= 3) st = c.next();
        if (cw >= 6) st = c.next();
        const uint32_t stage = smem + st.bo * (SLOT / 8) + (cw % 3) * 10240;
        const int orow = unperm_row(256 * ca + 128 * rank + 16 * cw), ocol = 320 * (cb & 1);
        const uint32_t sa = stage + ((lane & 7) + (lane & 8)) * 128, sx = (lane >> 4) ^ (lane & 7);
        auto send = [&](auto c0, auto c1) {
#pragma unroll
            for (int ch = c0.value; ch < c1.value; ch++) {
#pragma unroll
                for (int i = 0; i < 4; i++) {
                    uint32_t r[4];
#pragma unroll
                    for (int e = 0; e < 4; e++) {
                        const int k = 32 * ch + 8 * i + 2 * e;
                        r[e] = (ch < 2) ? pack_bf16(a1[k & 63], a1[(k & 63) + 1]) : pack_bf16(a2[ch < 2 ? 0 : k - 64], a2[ch < 2 ? 1 : k - 63]);
                    }
                    asm volatile("stmatrix.sync.aligned.m8n8.x4.shared.b16 [%0], {%1, %2, %3, %4};"
                                 ::"r"(sa + ch * 2048 + ((sx ^ (2 * i)) << 4)), "r"(r[0]), "r"(r[1]), "r"(r[2]), "r"(r[3]) : "memory");
                }
                if (FENCE_EACH || ch == c1.value - 1) {
                    asm volatile("fence.proxy.async.shared::cta;" ::: "memory");
                    __syncwarp();
#pragma unroll
                    for (int b = FENCE_EACH ? ch : c0.value; b <= ch; b++)
                        asm volatile(ELECT "cp.reduce.async.bulk.tensor.2d.global.shared::cta.add.bulk_group [%0, {%2, %3}], [%1];\n}\n"
                                     ::"l"(&P.outm), "r"(stage + b * 2048), "r"(ocol + 64 * b), "r"(orow) : "memory");
                }
            }
        };
        mbar_wait(bars + BAR_EMPTY + st.bo, st.par ^ 1);
        mbar_wait(bars + BAR_DEP + 13 * 8, 0);
        wgmma_wait<EARLYSEND>();
        fence_regs(a2);
        send(IntT<2>{}, IntT<5>{});
        wgmma_wait<0>();
        fence_regs(a1);
        PROFG(188);
        PROF(4);
        send(IntT<0>{}, IntT<2>{});
        PROF(5);
        asm volatile("cp.async.bulk.commit_group;\ncp.async.bulk.wait_group.read 0;" ::: "memory");
    }
    PROF(6);
}

__device__ __forceinline__ void mma_rows(float (&acc)[8][4], uint32_t a0, uint32_t a2, const uint4& w0, const uint4& w1, const uint4& w2, const uint4& w3) {
    const uint32_t r0[4] = {w0.x, w0.y, w0.z, w0.w}, r1[4] = {w1.x, w1.y, w1.z, w1.w};
    const uint32_t r2[4] = {w2.x, w2.y, w2.z, w2.w}, r3[4] = {w3.x, w3.y, w3.z, w3.w};
#pragma unroll
    for (int i = 0; i < 4; i++) {
        mma16816(acc[2 * i][0], acc[2 * i][1], acc[2 * i][2], acc[2 * i][3], a0, 0u, a2, 0u, __byte_perm(r0[i], r1[i], 0x5410), __byte_perm(r2[i], r3[i], 0x5410));
        mma16816(acc[2 * i + 1][0], acc[2 * i + 1][1], acc[2 * i + 1][2], acc[2 * i + 1][3], a0, 0u, a2, 0u, __byte_perm(r0[i], r1[i], 0x7632), __byte_perm(r2[i], r3[i], 0x7632));
    }
}

__device__ __forceinline__ void mod_ffn(const Params& P, uint8_t* sm, int mc  ) {
    const uint32_t epoch = read_epoch();
    const int tid = threadIdx.x - 128, lane = tid & 31, cw = tid >> 5, q = lane & 3, lr = lane >> 2;
    uint32_t* xs = reinterpret_cast<uint32_t*>(sm);
    uint32_t* wmax = xs + 8 * 324;
    int* sidx = reinterpret_cast<int*>(wmax + 16);
    const int fg = cw * 4 + mc;
    const uint32_t ring = smem_u32(sm) + 16384 + cw * 24576, rbar = smem_u32(sm) + 12288 + cw * 32;
    auto issue = [&](int u, int st) {
        if (lane == 0 && u < 30) {
            mbar_expect_tx(rbar + st * 8, 8192);
            if (u < 20) {
                tma_load_stream(ring + st * 8192, &P.wg, fg * 64, u * 32, rbar + st * 8);
                tma_load_stream(ring + st * 8192 + 4096, &P.wu, fg * 64, u * 32, rbar + st * 8);
            } else {
                tma_load_stream(ring + st * 8192, &P.wd, (u - 20) * 64, fg * 64, rbar + st * 8);
            }
        }
    };
    if (lane == 0) {
        mbar_init(rbar, 1); mbar_init(rbar + 8, 1); mbar_init(rbar + 16, 1);
        asm volatile("fence.mbarrier_init.release.cluster;" ::: "memory");
    }
    if (tid == 0) flag_wait<100>(F_LN, 256u * (epoch + 1));
    named_sync(1, 256);
    PROF(1);
    if (fg < 27) {
#pragma unroll 1
        for (int u = 0; u < 3; u++) issue(u, u);
    }
    PROF(2);
    uint32_t key[8];
#pragma unroll
    for (int i = 0; i < 8; i++) {
        const int t = tid + 256 * i;
        uint32_t b = __float_as_uint(__ldcg(g_r + t) + 0.f) >> 16;
        b = (b & 0x8000u) ? (~b & 0xffffu) : (b | 0x8000u);
        key[i] = (b << 16) | (uint32_t)(0xffff - t);
    }
#pragma unroll 1
    for (int rnd = 0; rnd < 8; rnd++) {
        uint32_t mx = key[0];
#pragma unroll
        for (int i = 1; i < 8; i++) mx = max(mx, key[i]);
        mx = __reduce_max_sync(0xffffffffu, mx);
        if (lane == 0) wmax[(rnd & 1) * 8 + cw] = mx;
        named_sync(1, 256);
        mx = __reduce_max_sync(0xffffffffu, wmax[(rnd & 1) * 8 + (lane & 7)]);
#pragma unroll
        for (int i = 0; i < 8; i++) if (key[i] == mx) key[i] = 0;
        if (tid == 0) sidx[rnd] = 0xffff - (int)(mx & 0xffffu);
    }
    named_sync(1, 256);
    {
        const uint32_t* src = reinterpret_cast<const uint32_t*>(g_xn + (size_t)perm_row(sidx[cw]) * DM);
#pragma unroll 2
        for (int i = lane; i < 320; i += 32) xs[cw * 324 + i] = __ldcg(src + i);
    }
    named_sync(1, 256);
    PROF(3);
    if (fg < 27) {
        float g[8][4], v[8][4];
        uint32_t hp[8];
#pragma unroll
        for (int i = 0; i < 8; i++)
#pragma unroll
            for (int e = 0; e < 4; e++) { g[i][e] = 0.f; v[i][e] = 0.f; }
        int st = 0, ph = 0;
#pragma unroll 1
        for (int u = 0; u < 60; u++) {
            if (!(u & 1)) mbar_wait(rbar + st * 8, ph);
            uint4 a[8];
#pragma unroll
            for (int r = 0; r < 8; r++) {
                const int row = (u < 40) ? 32 * (r >> 2) + 16 * (u & 1) + 2 * q + (r & 1) + 4 * (r & 2) : 16 * q + 8 * (u & 1) + r;
                asm volatile("ld.shared.v4.b32 {%0, %1, %2, %3}, [%4];" : "=r"(a[r].x), "=r"(a[r].y), "=r"(a[r].z), "=r"(a[r].w)
                             : "r"(ring + st * 8192 + row * 128 + ((lr ^ row) & 7) * 16) : "memory");
            }
            uint32_t f0, f1, f2, f3;
            if (u < 40) { f0 = f2 = xs[lr * 324 + u * 8 + q]; f1 = f3 = xs[lr * 324 + u * 8 + 4 + q]; }
            else if (u & 1) { f0 = hp[4]; f1 = hp[5]; f2 = hp[6]; f3 = hp[7]; }
            else { f0 = hp[0]; f1 = hp[1]; f2 = hp[2]; f3 = hp[3]; }
            mma_rows(g, f0, f1, a[0], a[1], a[2], a[3]);
            mma_rows(v, f2, f3, a[4], a[5], a[6], a[7]);
            if (u & 1) {
                __syncwarp();
                issue((u >> 1) + 3, st);
                if (++st == 3) { st = 0; ph ^= 1; }
                if (u >= 39) {
                    if (u == 39) {
                        float hv[16];
#pragma unroll
                        for (int i = 0; i < 16; i++) {
                            const float gp = round_bf16(g[i & 7][i >> 3]);
                            hv[i] = round_bf16(__fdividef(gp, 1.0f + __expf(fminf(-gp, 80.f)))) * round_bf16(v[i & 7][i >> 3]);
                        }
#pragma unroll
                        for (int i = 0; i < 8; i++) hp[i] = pack_bf16(hv[2 * i], hv[2 * i + 1]);
                    } else {
                        float4* dst = reinterpret_cast<float4*>(g_ypart + (fg * 8 + lr) * DM + ((u - 40) >> 1) * 64 + 16 * q);
#pragma unroll
                        for (int i = 0; i < 4; i++) {
                            const int j = 4 * (i & 1), e = i >> 1;
                            dst[i] = make_float4(g[j][e] + v[j][e], g[j + 1][e] + v[j + 1][e], g[j + 2][e] + v[j + 2][e], g[j + 3][e] + v[j + 3][e]);
                        }
                    }
#pragma unroll
                    for (int i = 0; i < 8; i++) { g[i][0] = 0.f; g[i][1] = 0.f; v[i][0] = 0.f; v[i][1] = 0.f; }
                }
            }
        }
    }
    PROF(5);
    named_sync(1, 256);
    if (tid == 0) {
        flag_add(F_MODP);
        flag_wait<100>(F_MODP, 4u * (epoch + 1));
    }
    named_sync(1, 256);
    PROF(6);
#pragma unroll 1
    for (int i = tid; i < 2 * DM; i += 256) {
        const int c = 2 * mc + (i >= DM), col = i - (i >= DM) * DM, t = sidx[c];
        float y = 0.f;
#pragma unroll 9
        for (int k = 0; k < 27; k++) y += __ldcg(g_ypart + (k * 8 + c) * DM + col);
        const float rs = round_bf16(__fdividef(1.0f, 1.0f + __expf(fminf(-__ldcg(g_r + t), 80.f))));
        const float xn = __bfloat162float(reinterpret_cast<const __nv_bfloat16*>(xs + c * 324)[col]);
        P.out[(size_t)t * DM + col] = __float2bfloat16_rn(__bfloat162float(P.x[(size_t)t * DM + col]) + round_bf16(xn + round_bf16(round_bf16(y) * rs)));
    }
    named_sync(1, 256);
    if (tid == 0) flag_add(F_MOD);
    PROF(7);
}

__global__ void __cluster_dims__(2, 1, 1) __launch_bounds__(384, 1) fused_kernel(const __grid_constant__ Params P) {
    extern __shared__ __align__(1024) uint8_t smem_raw[];
    const uint32_t smem = (smem_u32(smem_raw) + 1023u) & ~1023u;
    uint8_t* smem_gen = smem_raw + (smem - smem_u32(smem_raw));
    const uint32_t bars = smem + NSLOT * SLOT;
    const int wgi = __reduce_or_sync(0xffffffffu, threadIdx.x >> 7);
    const int cl = blockIdx.x >> 1, rank = blockIdx.x & 1, ca = cl & 7, cb = cl >> 3;
    PROFG(30);
    PROF(0);
    if (threadIdx.x == 0) {
#pragma unroll
        for (int i = 0; i < NSLOT; i++) { mbar_init(bars + BAR_FULL + i * 8, 1); mbar_init(bars + BAR_EMPTY + i * 8, 16); }
        mbar_arrive(bars + BAR_FULL + 16);
        asm volatile("mbarrier.arrive.shared::cta.b64 _, [%0], 16;" ::"r"(bars + BAR_EMPTY + 16) : "memory");
        asm volatile("fence.mbarrier_init.release.cluster;" ::: "memory");
        PROF(24);
    } else if (threadIdx.x == 32) {
#pragma unroll
        for (int i = 0; i < 18; i++) mbar_init(bars + BAR_SIG + i * 8, 4);
#pragma unroll
        for (int i = 0; i < 14; i++) mbar_init(bars + BAR_DEP + i * 8, 1);
    } else if (threadIdx.x >= 64 && threadIdx.x < 128 && cl < 64) {
        const int i = threadIdx.x - 64;
        if (i == 0) { prefetch_map(&P.ckv); prefetch_map(&P.wuk); }
        if (i < 32) asm volatile("prefetch.global.L2 [%0];" ::"l"(P.ckv_ptr + ((2 * ca + rank) * 128 + cb * 16 + (i >> 1)) * DC + (i & 1) * 64));
        else if (i < 48) asm volatile("prefetch.global.L2 [%0];" ::"l"(P.wuk_ptr + (size_t)((i - 32) * 8 + ca) * (NH * HD) + (cb + 8 * kv_round(0)) * 128 + rank * 64));
    }
    __syncthreads();
    PROF(29);
    cluster_arrive();
    if (wgi > 0) {
        asm volatile("setmaxnreg.inc.sync.aligned.u32 232;");
        if (cl >= 64) {
            cluster_wait();
            mod_ffn(P, smem_gen, blockIdx.x - 128);
        } else {
            consumer(P, smem, bars, ca, cb, rank, wgi - 1);
        }
        cluster_arrive();
        PROFG(31);
        PROFDUMP();
    } else {
        asm volatile("setmaxnreg.dec.sync.aligned.u32 40;");
        const int w = __reduce_or_sync(0xffffffffu, threadIdx.x >> 5), lane = threadIdx.x & 31;
        if (threadIdx.x == 32 && cl < 64) {
            mbar_expect_tx(bars + BAR_FULL, SLOT);
            tma_load(smem, &P.ckv, 0, (2 * ca + rank) * 128, bars + BAR_FULL);
            tma_load(smem + 16384, &P.ckv, 64, (2 * ca + rank) * 128, bars + BAR_FULL);
        }
        if (threadIdx.x == 64) {
            prefetch_map(&P.wuv); prefetch_map(&P.xn); prefetch_map(&P.wq); prefetch_map(&P.kv); prefetch_map(&P.ctx); prefetch_map(&P.wo); prefetch_map(&P.outm);
        }
        __syncwarp();
        cluster_wait();
        PROF(27);
        if (cl < 64) {
            if (w == 0) {
                producer(P, smem, bars, ca, cb, rank);
            } else if (w < 3 && lane == 0) {
                const int wg = w - 1;
#pragma unroll 1
                for (int i = 0; i < 9; i++) {
                    const int e = (i < wg * LNSTAG + 1) ? i + 1 : (i == wg * LNSTAG + 1) ? 0 : i;
                    mbar_wait_sleep(bars + BAR_SIG + (wg * 9 + e) * 8, 0);
                    int f;
                    if (e == 0) f = F_LN;
                    else if (e < 5) f = F_KV + cb + 8 * kv_round(e - 1);
                    else { const int rd = e - 5; f = F_CTX + (8 * rd + cb) * 16 + item_p(ca, rd) * 2 + rank; }
                    flag_add(f);
                }
            } else if (lane == 0) {
                const uint32_t epoch = read_epoch();
#pragma unroll 1
                for (int i = 0; i < 14; i++) {
                    const int e = (i < 11) ? i : (i == 11) ? 13 : i - 1;
                    int f;
                    uint32_t n;
                    if (e == 0) { f = F_LN; n = 256; }
                    else if (e < 5) { f = F_KV + cb + 8 * (e - 1); n = 32; }
                    else if (e < 13) { f = F_CTX + (8 * ((e - 5) >> 1) + (cb & 6) + ((e - 5) & 1)) * 16 + ca * 2 + rank; n = 2; }
                    else { f = F_MOD; n = 4; }
                    flag_wait<200>(f, n * (epoch + 1));
                    fence_proxy_async();
                    mbar_arrive(bars + BAR_DEP + e * 8);
                }
            }
        }
        __syncwarp();
        cluster_arrive();
        cluster_wait();
        if (threadIdx.x == 0) atomicAdd(g_flags + F_EXIT * 8, 1u);
        PROFG(31);
        PROFDUMP();
    }
}

typedef CUresult (*EncodeFn)(CUtensorMap*, CUtensorMapDataType, cuuint32_t, void*, const cuuint64_t*, const cuuint64_t*, const cuuint32_t*,
                             const cuuint32_t*, CUtensorMapInterleave, CUtensorMapSwizzle, CUtensorMapL2promotion, CUtensorMapFloatOOBfill);

void make_map(EncodeFn fn, CUtensorMap* m, const void* ptr, uint64_t rows, uint64_t cols, uint32_t box_rows) {
    cuuint64_t dims[2] = {cols, rows};
    cuuint64_t strides[1] = {cols * 2};
    cuuint32_t box[2] = {64, box_rows};
    cuuint32_t es[2] = {1, 1};
    fn(m, CU_TENSOR_MAP_DATA_TYPE_BFLOAT16, 2, const_cast<void*>(ptr), dims, strides, box, es, CU_TENSOR_MAP_INTERLEAVE_NONE,
       CU_TENSOR_MAP_SWIZZLE_128B, CU_TENSOR_MAP_L2_PROMOTION_L2_128B, CU_TENSOR_MAP_FLOAT_OOB_FILL_NONE);
}

}

extern "C" void kernel_launch(void* const* d_in, const int* in_sizes, int n_in, void* d_out, int out_size) {
    (void)in_sizes; (void)n_in; (void)out_size;
    void* fnp = nullptr;
    cudaDriverEntryPointQueryResult qr;
    cudaGetDriverEntryPoint("cuTensorMapEncodeTiled", &fnp, cudaEnableDefault, &qr);
    EncodeFn fn = (EncodeFn)fnp;
    void *xn, *kv, *ctx;
    cudaGetSymbolAddress(&xn, g_xn);
    cudaGetSymbolAddress(&kv, g_kv);
    cudaGetSymbolAddress(&ctx, g_ctx);
    Params P;
    make_map(fn, &P.ckv, d_in[1], SEQ, DC, 128);
    make_map(fn, &P.wq, d_in[2], DM, NH * HD, 64);
    make_map(fn, &P.wuk, d_in[3], DC, NH * HD, 128);
    make_map(fn, &P.wuv, d_in[4], DC, NH * HD, 128);
    make_map(fn, &P.wo, d_in[5], NH * HD, DM, 32);
    make_map(fn, &P.xn, xn, SEQ, DM, 128);
    make_map(fn, &P.kv, kv, NH * 16 * 2 * 128, 128, 128);
    make_map(fn, &P.ctx, ctx, NH * SEQ, HD, 128);
    P.x = (const __nv_bfloat16*)d_in[0];
    P.wr = (const __nv_bfloat16*)d_in[7];
    make_map(fn, &P.wg, d_in[8], DM, FF, 32);
    make_map(fn, &P.wu, d_in[9], DM, FF, 32);
    make_map(fn, &P.wd, d_in[10], FF, DM, 64);
    P.ckv_ptr = (const __nv_bfloat16*)d_in[1];
    P.wuk_ptr = (const __nv_bfloat16*)d_in[3];
    make_map(fn, &P.outm, d_out, SEQ, DM, 16);
    P.out = (__nv_bfloat16*)d_out;
    cudaFuncSetAttribute(fused_kernel, cudaFuncAttributeMaxDynamicSharedMemorySize, SMEM_BYTES);
    fused_kernel<<<NCTA, 384, SMEM_BYTES>>>(P);
}
```

```cpp
#include <cuda_runtime.h>
#include <cuda_bf16.h>
#include <cuda.h>
#include <stdint.h>

namespace {

constexpr int SEQ = 2048, DM = 640, DC = 512, NH = 32, HD = 128, FF = 1728;
constexpr int NSLOT = 7, SLOT = 32768;
constexpr int NCTA = 132;
#define PINGPONG 1
#define SIGMA 1
#define KVORDER 0x1023
#define KVSPLIT 1
#define QST 4
#define LNSTAG 1
#define EARLYPF 1
#define EARLYSEND 1
#define FENCE_EACH 1
#define LATEST 1
#define LASTRD 7
#define LASTN 2
#define EFMASK 13
#define SPLITJ 8
constexpr uint32_t DESC_HI = (1024u >> 4) | (1u << 30);
constexpr int SMEM_BYTES = NSLOT * SLOT + 3072;

constexpr int BAR_FULL = 0, BAR_EMPTY = 64, BAR_SIG = 128  , BAR_DEP = 320  , MISC_OFF = 512;

constexpr int F_EXIT = 0, F_LN = 1, F_MOD = 2, F_MODP = 3, F_KV = 4  , F_CTX = 36  , F_NUM = 548;

__device__ __align__(1024) __nv_bfloat16 g_xn[SEQ * DM];
__device__ __align__(1024) __nv_bfloat16 g_kv[NH * 16 * 2 * 128 * 128];
__device__ __align__(1024) __nv_bfloat16 g_ctx[NH * SEQ * HD];
__device__ __align__(16) float g_r[SEQ];
__device__ __align__(16) float g_ypart[27 * 8 * DM];
__device__ uint32_t g_flags[F_NUM * 8];

struct TrueT { static constexpr bool value = true; };
struct FalseT { static constexpr bool value = false; };

struct Params {
    CUtensorMap ckv, wuk, wuv, xn, wq, kv, ctx, wo, wg, wu, wd, outm;
    const __nv_bfloat16 *x, *wr, *ckv_ptr, *wuk_ptr;
    __nv_bfloat16* out;
};

__device__ __forceinline__ uint32_t smem_u32(const void* p) { return (uint32_t)__cvta_generic_to_shared(p); }
__device__ __forceinline__ void mbar_init(uint32_t bar, uint32_t cnt) {
    asm volatile("mbarrier.init.shared::cta.b64 [%0], %1;" ::"r"(bar), "r"(cnt) : "memory");
}
__device__ __forceinline__ void mbar_expect_tx(uint32_t bar, uint32_t bytes) {
    asm volatile("mbarrier.arrive.expect_tx.shared::cta.b64 _, [%0], %1;" ::"r"(bar), "r"(bytes) : "memory");
}
__device__ __forceinline__ void mbar_arrive(uint32_t bar) {
    asm volatile("mbarrier.arrive.shared::cta.b64 _, [%0];" ::"r"(bar) : "memory");
}
__device__ __forceinline__ uint32_t mapa(uint32_t addr, uint32_t cta) {
    uint32_t r;
    asm("mapa.shared::cluster.u32 %0, %1, %2;" : "=r"(r) : "r"(addr), "r"(cta));
    return r;
}
__device__ __forceinline__ void mbar_wait(uint32_t bar, uint32_t parity) {
    asm volatile(
        "{\n.reg .pred p;\n.reg .b32 c;\n"
        "mov.b32 c, 0;\n"
        "WLOOP:\n"
        "mbarrier.try_wait.parity.shared::cta.b64 p, [%0], %1;\n"
        "@p bra.uni WDONE;\n"
        "add.u32 c, c, 1;\n"
        "setp.lt.u32 p, c, 0x400000;\n"
        "@p bra.uni WLOOP;\n"
        "trap;\n"
        "WDONE:\n}\n" ::"r"(bar), "r"(parity) : "memory");
}
__device__ __forceinline__ void mbar_wait_sleep(uint32_t bar, uint32_t parity) {
    asm volatile(
        "{\n.reg .pred p;\n.reg .b32 c;\n"
        "mov.b32 c, 0;\n"
        "WLOOP:\n"
        "mbarrier.try_wait.parity.shared::cta.b64 p, [%0], %1, 20000;\n"
        "@p bra.uni WDONE;\n"
        "add.u32 c, c, 1;\n"
        "setp.lt.u32 p, c, 0x40000;\n"
        "@p bra.uni WLOOP;\n"
        "trap;\n"
        "WDONE:\n}\n" ::"r"(bar), "r"(parity) : "memory");
}
__device__ __forceinline__ void tma_load(uint32_t dst, const CUtensorMap* m, int c0, int c1, uint32_t bar) {
    asm volatile("cp.async.bulk.tensor.2d.shared::cluster.global.mbarrier::complete_tx::bytes [%0], [%1, {%3, %4}], [%2];"
                 ::"r"(dst), "l"(m), "r"(bar), "r"(c0), "r"(c1) : "memory");
}
#define ELECT "{\n.reg .pred e;\nelect.sync _|e, 0xffffffff;\n@e "
__device__ __forceinline__ void w_expect_tx(uint32_t bar, uint32_t bytes) {
    asm volatile(ELECT "mbarrier.arrive.expect_tx.shared::cta.b64 _, [%0], %1;\n}\n" ::"r"(bar), "r"(bytes) : "memory");
}
__device__ __forceinline__ void w_tma_load(uint32_t dst, const CUtensorMap* m, int c0, int c1, uint32_t bar) {
    asm volatile(ELECT "cp.async.bulk.tensor.2d.shared::cluster.global.mbarrier::complete_tx::bytes [%0], [%1, {%3, %4}], [%2];\n}\n"
                 ::"r"(dst), "l"(m), "r"(bar), "r"(c0), "r"(c1) : "memory");
}
__device__ __forceinline__ void w_tma_load_mc(uint32_t dst, const CUtensorMap* m, int c0, int c1, uint32_t bar) {
    asm volatile(ELECT "cp.async.bulk.tensor.2d.shared::cluster.global.mbarrier::complete_tx::bytes.multicast::cluster [%0], [%1, {%3, %4}], [%2], %5;\n}\n"
                 ::"r"(dst), "l"(m), "r"(bar), "r"(c0), "r"(c1), "h"((uint16_t)3) : "memory");
}
__device__ __forceinline__ void w_tma_prefetch(const CUtensorMap* m, int c0, int c1) {
    asm volatile(ELECT "cp.async.bulk.prefetch.tensor.2d.L2.global [%0, {%1, %2}];\n}\n" ::"l"(m), "r"(c0), "r"(c1) : "memory");
}
__device__ __forceinline__ uint64_t policy_evict_first() {
    uint64_t p;
    asm("createpolicy.fractional.L2::evict_first.b64 %0, 1.0;" : "=l"(p));
    return p;
}
__device__ __forceinline__ void w_tma_load_mc_last(uint32_t dst, const CUtensorMap* m, int c0, int c1, uint32_t bar) {
    asm volatile(ELECT "cp.async.bulk.tensor.2d.shared::cluster.global.mbarrier::complete_tx::bytes.multicast::cluster.L2::cache_hint [%0], [%1, {%3, %4}], [%2], %5, %6;\n}\n"
                 ::"r"(dst), "l"(m), "r"(bar), "r"(c0), "r"(c1), "h"((uint16_t)3), "l"(policy_evict_first()) : "memory");
}
__device__ __forceinline__ void tma_load_stream(uint32_t dst, const CUtensorMap* m, int c0, int c1, uint32_t bar) {
    asm volatile("cp.async.bulk.tensor.2d.shared::cluster.global.mbarrier::complete_tx::bytes.L2::cache_hint [%0], [%1, {%3, %4}], [%2], %5;"
                 ::"r"(dst), "l"(m), "r"(bar), "r"(c0), "r"(c1), "l"(policy_evict_first()) : "memory");
}
__device__ __forceinline__ uint4 ldg_stream(const void* p) {
    uint4 v;
    asm volatile("ld.global.nc.L2::cache_hint.v4.b32 {%0, %1, %2, %3}, [%4], %5;" : "=r"(v.x), "=r"(v.y), "=r"(v.z), "=r"(v.w) : "l"(p), "l"(policy_evict_first()));
    return v;
}
__device__ __forceinline__ void prefetch_map(const CUtensorMap* m) {
    asm volatile("prefetch.tensormap [%0];" ::"l"(m) : "memory");
}
__device__ __forceinline__ void cluster_arrive() { asm volatile("barrier.cluster.arrive.relaxed.aligned;" ::: "memory"); }
__device__ __forceinline__ void cluster_wait() { asm volatile("barrier.cluster.wait.aligned;" ::: "memory"); }
__device__ __forceinline__ void named_sync(int id, int n) { asm volatile("bar.sync %0, %1;" ::"r"(id), "r"(n) : "memory"); }
__device__ __forceinline__ void named_arrive(int id, int n) { asm volatile("bar.arrive %0, %1;" ::"r"(id), "r"(n) : "memory"); }

__device__ __forceinline__ void flag_add(int f) {
    asm volatile("fence.acq_rel.gpu;\nred.relaxed.gpu.global.add.u32 [%0], 1;" ::"l"(g_flags + f * 8) : "memory");
}
template <int SLEEP>
__device__ __forceinline__ void flag_wait(int f, uint32_t target) {
    asm volatile(
        "{\n.reg .pred p;\n.reg .b32 c, v;\n"
        "mov.b32 c, 0;\n"
        "FLOOP:\n"
        "ld.acquire.gpu.global.u32 v, [%0];\n"
        "sub.u32 v, v, %1;\n"
        "setp.ge.s32 p, v, 0;\n"
        "@p bra FDONE;\n"
        "nanosleep.u32 %2;\n"
        "add.u32 c, c, 1;\n"
        "setp.lt.u32 p, c, 0x400000;\n"
        "@p bra FLOOP;\n"
        "trap;\n"
        "FDONE:\n}\n" ::"l"(g_flags + f * 8), "r"(target), "n"(SLEEP) : "memory");
}
__device__ __forceinline__ uint32_t read_epoch() {
    uint32_t e;
    asm volatile("ld.relaxed.gpu.global.u32 %0, [%1];" : "=r"(e) : "l"(g_flags + F_EXIT * 8) : "memory");
    return e / NCTA;
}
__device__ __forceinline__ void fence_proxy_async() { asm volatile("fence.proxy.async;" ::: "memory"); }

__device__ __forceinline__ void wgmma_fence() { asm volatile("wgmma.fence.sync.aligned;" ::: "memory"); }
__device__ __forceinline__ void wgmma_commit() { asm volatile("wgmma.commit_group.sync.aligned;" ::: "memory"); }
template <int N>
__device__ __forceinline__ void wgmma_wait() { asm volatile("wgmma.wait_group.sync.aligned %0;" ::"n"(N) : "memory"); }
template <int N>
__device__ __forceinline__ void fence_regs(float (&d)[N]) {
#pragma unroll
    for (int i = 0; i < N; i++) asm volatile("" : "+f"(d[i])::"memory");
}
template <int N>
__device__ __forceinline__ void fence_regs(uint32_t (&d)[N]) {
#pragma unroll
    for (int i = 0; i < N; i++) asm volatile("" : "+r"(d[i])::"memory");
}

template <int TA, int TB>
__device__ __forceinline__ void wgmma_ss_n128(float (&d)[64], uint32_t alo, uint32_t blo, int scale_d) {
    asm volatile("{\n.reg .pred p;\n.reg .b64 da, db;\nsetp.ne.b32 p, %66, 0;\n"
        "mov.b64 da, {%64, %69};\nmov.b64 db, {%65, %69};\n"
        "wgmma.mma_async.sync.aligned.m64n128k16.f32.bf16.bf16 "
        "{%0, %1, %2, %3, %4, %5, %6, %7, %8, %9, %10, %11, %12, %13, %14, %15, %16, %17, %18, %19, %20, %21, %22, %23, %24, %25, %26, %27, %28, %29, %30, %31, %32, %33, %34, %35, %36, %37, %38, %39, %40, %41, %42, %43, %44, %45, %46, %47, %48, %49, %50, %51, %52, %53, %54, %55, %56, %57, %58, %59, %60, %61, %62, %63}, da, db, p, 1, 1, %67, %68;\n}\n"
        :
          "+f"(d[0]), "+f"(d[1]), "+f"(d[2]), "+f"(d[3]), "+f"(d[4]), "+f"(d[5]), "+f"(d[6]), "+f"(d[7]),
          "+f"(d[8]), "+f"(d[9]), "+f"(d[10]), "+f"(d[11]), "+f"(d[12]), "+f"(d[13]), "+f"(d[14]), "+f"(d[15]),
          "+f"(d[16]), "+f"(d[17]), "+f"(d[18]), "+f"(d[19]), "+f"(d[20]), "+f"(d[21]), "+f"(d[22]), "+f"(d[23]),
          "+f"(d[24]), "+f"(d[25]), "+f"(d[26]), "+f"(d[27]), "+f"(d[28]), "+f"(d[29]), "+f"(d[30]), "+f"(d[31]),
          "+f"(d[32]), "+f"(d[33]), "+f"(d[34]), "+f"(d[35]), "+f"(d[36]), "+f"(d[37]), "+f"(d[38]), "+f"(d[39]),
          "+f"(d[40]), "+f"(d[41]), "+f"(d[42]), "+f"(d[43]), "+f"(d[44]), "+f"(d[45]), "+f"(d[46]), "+f"(d[47]),
          "+f"(d[48]), "+f"(d[49]), "+f"(d[50]), "+f"(d[51]), "+f"(d[52]), "+f"(d[53]), "+f"(d[54]), "+f"(d[55]),
          "+f"(d[56]), "+f"(d[57]), "+f"(d[58]), "+f"(d[59]), "+f"(d[60]), "+f"(d[61]), "+f"(d[62]), "+f"(d[63])
        : "r"(alo), "r"(blo), "r"(scale_d), "n"(TA), "n"(TB), "r"(DESC_HI));
}
template <int TA, int TB>
__device__ __forceinline__ void wgmma_ss_n192(float (&d)[96], uint32_t alo, uint32_t blo, int scale_d) {
    asm volatile("{\n.reg .pred p;\n.reg .b64 da, db;\nsetp.ne.b32 p, %98, 0;\n"
        "mov.b64 da, {%96, %101};\nmov.b64 db, {%97, %101};\n"
        "wgmma.mma_async.sync.aligned.m64n192k16.f32.bf16.bf16 "
        "{%0, %1, %2, %3, %4, %5, %6, %7, %8, %9, %10, %11, %12, %13, %14, %15, %16, %17, %18, %19, %20, %21, %22, %23, %24, %25, %26, %27, %28, %29, %30, %31, %32, %33, %34, %35, %36, %37, %38, %39, %40, %41, %42, %43, %44, %45, %46, %47, %48, %49, %50, %51, %52, %53, %54, %55, %56, %57, %58, %59, %60, %61, %62, %63, %64, %65, %66, %67, %68, %69, %70, %71, %72, %73, %74, %75, %76, %77, %78, %79, %80, %81, %82, %83, %84, %85, %86, %87, %88, %89, %90, %91, %92, %93, %94, %95}, da, db, p, 1, 1, %99, %100;\n}\n"
        :
          "+f"(d[0]), "+f"(d[1]), "+f"(d[2]), "+f"(d[3]), "+f"(d[4]), "+f"(d[5]), "+f"(d[6]), "+f"(d[7]),
          "+f"(d[8]), "+f"(d[9]), "+f"(d[10]), "+f"(d[11]), "+f"(d[12]), "+f"(d[13]), "+f"(d[14]), "+f"(d[15]),
          "+f"(d[16]), "+f"(d[17]), "+f"(d[18]), "+f"(d[19]), "+f"(d[20]), "+f"(d[21]), "+f"(d[22]), "+f"(d[23]),
          "+f"(d[24]), "+f"(d[25]), "+f"(d[26]), "+f"(d[27]), "+f"(d[28]), "+f"(d[29]), "+f"(d[30]), "+f"(d[31]),
          "+f"(d[32]), "+f"(d[33]), "+f"(d[34]), "+f"(d[35]), "+f"(d[36]), "+f"(d[37]), "+f"(d[38]), "+f"(d[39]),
          "+f"(d[40]), "+f"(d[41]), "+f"(d[42]), "+f"(d[43]), "+f"(d[44]), "+f"(d[45]), "+f"(d[46]), "+f"(d[47]),
          "+f"(d[48]), "+f"(d[49]), "+f"(d[50]), "+f"(d[51]), "+f"(d[52]), "+f"(d[53]), "+f"(d[54]), "+f"(d[55]),
          "+f"(d[56]), "+f"(d[57]), "+f"(d[58]), "+f"(d[59]), "+f"(d[60]), "+f"(d[61]), "+f"(d[62]), "+f"(d[63]),
          "+f"(d[64]), "+f"(d[65]), "+f"(d[66]), "+f"(d[67]), "+f"(d[68]), "+f"(d[69]), "+f"(d[70]), "+f"(d[71]),
          "+f"(d[72]), "+f"(d[73]), "+f"(d[74]), "+f"(d[75]), "+f"(d[76]), "+f"(d[77]), "+f"(d[78]), "+f"(d[79]),
          "+f"(d[80]), "+f"(d[81]), "+f"(d[82]), "+f"(d[83]), "+f"(d[84]), "+f"(d[85]), "+f"(d[86]), "+f"(d[87]),
          "+f"(d[88]), "+f"(d[89]), "+f"(d[90]), "+f"(d[91]), "+f"(d[92]), "+f"(d[93]), "+f"(d[94]), "+f"(d[95])
        : "r"(alo), "r"(blo), "r"(scale_d), "n"(TA), "n"(TB), "r"(DESC_HI));
}
template <int TB>
__device__ __forceinline__ void wgmma_rs_n128(float (&d)[64], uint32_t a0, uint32_t a1, uint32_t a2, uint32_t a3, uint32_t blo, int scale_d) {
    asm volatile("{\n.reg .pred p;\n.reg .b64 db;\nsetp.ne.b32 p, %69, 0;\n"
        "mov.b64 db, {%68, %71};\n"
        "wgmma.mma_async.sync.aligned.m64n128k16.f32.bf16.bf16 "
        "{%0, %1, %2, %3, %4, %5, %6, %7, %8, %9, %10, %11, %12, %13, %14, %15, %16, %17, %18, %19, %20, %21, %22, %23, %24, %25, %26, %27, %28, %29, %30, %31, %32, %33, %34, %35, %36, %37, %38, %39, %40, %41, %42, %43, %44, %45, %46, %47, %48, %49, %50, %51, %52, %53, %54, %55, %56, %57, %58, %59, %60, %61, %62, %63}, {%64, %65, %66, %67}, db, p, 1, 1, %70;\n}\n"
        :
          "+f"(d[0]), "+f"(d[1]), "+f"(d[2]), "+f"(d[3]), "+f"(d[4]), "+f"(d[5]), "+f"(d[6]), "+f"(d[7]),
          "+f"(d[8]), "+f"(d[9]), "+f"(d[10]), "+f"(d[11]), "+f"(d[12]), "+f"(d[13]), "+f"(d[14]), "+f"(d[15]),
          "+f"(d[16]), "+f"(d[17]), "+f"(d[18]), "+f"(d[19]), "+f"(d[20]), "+f"(d[21]), "+f"(d[22]), "+f"(d[23]),
          "+f"(d[24]), "+f"(d[25]), "+f"(d[26]), "+f"(d[27]), "+f"(d[28]), "+f"(d[29]), "+f"(d[30]), "+f"(d[31]),
          "+f"(d[32]), "+f"(d[33]), "+f"(d[34]), "+f"(d[35]), "+f"(d[36]), "+f"(d[37]), "+f"(d[38]), "+f"(d[39]),
          "+f"(d[40]), "+f"(d[41]), "+f"(d[42]), "+f"(d[43]), "+f"(d[44]), "+f"(d[45]), "+f"(d[46]), "+f"(d[47]),
          "+f"(d[48]), "+f"(d[49]), "+f"(d[50]), "+f"(d[51]), "+f"(d[52]), "+f"(d[53]), "+f"(d[54]), "+f"(d[55]),
          "+f"(d[56]), "+f"(d[57]), "+f"(d[58]), "+f"(d[59]), "+f"(d[60]), "+f"(d[61]), "+f"(d[62]), "+f"(d[63])
        : "r"(a0), "r"(a1), "r"(a2), "r"(a3), "r"(blo), "r"(scale_d), "n"(TB), "r"(DESC_HI));
}
template <int TB>
__device__ __forceinline__ void wgmma_rs_n128_z(float (&d)[64], uint32_t a0, uint32_t a1, uint32_t a2, uint32_t a3, uint32_t blo) {
    asm volatile("{\n.reg .pred p;\n.reg .b64 db;\nsetp.ne.b32 p, %69, 0;\n"
        "mov.b64 db, {%68, %71};\n"
        "wgmma.mma_async.sync.aligned.m64n128k16.f32.bf16.bf16 "
        "{%0, %1, %2, %3, %4, %5, %6, %7, %8, %9, %10, %11, %12, %13, %14, %15, %16, %17, %18, %19, %20, %21, %22, %23, %24, %25, %26, %27, %28, %29, %30, %31, %32, %33, %34, %35, %36, %37, %38, %39, %40, %41, %42, %43, %44, %45, %46, %47, %48, %49, %50, %51, %52, %53, %54, %55, %56, %57, %58, %59, %60, %61, %62, %63}, {%64, %65, %66, %67}, db, p, 1, 1, %70;\n}\n"
        :
          "=f"(d[0]), "=f"(d[1]), "=f"(d[2]), "=f"(d[3]), "=f"(d[4]), "=f"(d[5]), "=f"(d[6]), "=f"(d[7]),
          "=f"(d[8]), "=f"(d[9]), "=f"(d[10]), "=f"(d[11]), "=f"(d[12]), "=f"(d[13]), "=f"(d[14]), "=f"(d[15]),
          "=f"(d[16]), "=f"(d[17]), "=f"(d[18]), "=f"(d[19]), "=f"(d[20]), "=f"(d[21]), "=f"(d[22]), "=f"(d[23]),
          "=f"(d[24]), "=f"(d[25]), "=f"(d[26]), "=f"(d[27]), "=f"(d[28]), "=f"(d[29]), "=f"(d[30]), "=f"(d[31]),
          "=f"(d[32]), "=f"(d[33]), "=f"(d[34]), "=f"(d[35]), "=f"(d[36]), "=f"(d[37]), "=f"(d[38]), "=f"(d[39]),
          "=f"(d[40]), "=f"(d[41]), "=f"(d[42]), "=f"(d[43]), "=f"(d[44]), "=f"(d[45]), "=f"(d[46]), "=f"(d[47]),
          "=f"(d[48]), "=f"(d[49]), "=f"(d[50]), "=f"(d[51]), "=f"(d[52]), "=f"(d[53]), "=f"(d[54]), "=f"(d[55]),
          "=f"(d[56]), "=f"(d[57]), "=f"(d[58]), "=f"(d[59]), "=f"(d[60]), "=f"(d[61]), "=f"(d[62]), "=f"(d[63])
        : "r"(a0), "r"(a1), "r"(a2), "r"(a3), "r"(blo), "n"(0), "n"(TB), "r"(DESC_HI));
}
template <int TA, int TB>
__device__ __forceinline__ void wgmma_ss_n128_z(float (&d)[64], uint32_t alo, uint32_t blo) {
    asm volatile("{\n.reg .pred p;\n.reg .b64 da, db;\nsetp.ne.b32 p, %66, 0;\n"
        "mov.b64 da, {%64, %69};\nmov.b64 db, {%65, %69};\n"
        "wgmma.mma_async.sync.aligned.m64n128k16.f32.bf16.bf16 "
        "{%0, %1, %2, %3, %4, %5, %6, %7, %8, %9, %10, %11, %12, %13, %14, %15, %16, %17, %18, %19, %20, %21, %22, %23, %24, %25, %26, %27, %28, %29, %30, %31, %32, %33, %34, %35, %36, %37, %38, %39, %40, %41, %42, %43, %44, %45, %46, %47, %48, %49, %50, %51, %52, %53, %54, %55, %56, %57, %58, %59, %60, %61, %62, %63}, da, db, p, 1, 1, %67, %68;\n}\n"
        :
          "=f"(d[0]), "=f"(d[1]), "=f"(d[2]), "=f"(d[3]), "=f"(d[4]), "=f"(d[5]), "=f"(d[6]), "=f"(d[7]),
          "=f"(d[8]), "=f"(d[9]), "=f"(d[10]), "=f"(d[11]), "=f"(d[12]), "=f"(d[13]), "=f"(d[14]), "=f"(d[15]),
          "=f"(d[16]), "=f"(d[17]), "=f"(d[18]), "=f"(d[19]), "=f"(d[20]), "=f"(d[21]), "=f"(d[22]), "=f"(d[23]),
          "=f"(d[24]), "=f"(d[25]), "=f"(d[26]), "=f"(d[27]), "=f"(d[28]), "=f"(d[29]), "=f"(d[30]), "=f"(d[31]),
          "=f"(d[32]), "=f"(d[33]), "=f"(d[34]), "=f"(d[35]), "=f"(d[36]), "=f"(d[37]), "=f"(d[38]), "=f"(d[39]),
          "=f"(d[40]), "=f"(d[41]), "=f"(d[42]), "=f"(d[43]), "=f"(d[44]), "=f"(d[45]), "=f"(d[46]), "=f"(d[47]),
          "=f"(d[48]), "=f"(d[49]), "=f"(d[50]), "=f"(d[51]), "=f"(d[52]), "=f"(d[53]), "=f"(d[54]), "=f"(d[55]),
          "=f"(d[56]), "=f"(d[57]), "=f"(d[58]), "=f"(d[59]), "=f"(d[60]), "=f"(d[61]), "=f"(d[62]), "=f"(d[63])
        : "r"(alo), "r"(blo), "n"(0), "n"(TA), "n"(TB), "r"(DESC_HI));
}

__device__ __forceinline__ uint32_t pack_bf16(float lo, float hi) {
    uint32_t r;
    asm("cvt.rn.bf16x2.f32 %0, %1, %2;" : "=r"(r) : "f"(hi), "f"(lo));
    return r;
}
__device__ __forceinline__ uint32_t add_bf16x2(uint32_t a, uint32_t b) {
    uint32_t r;
    asm("add.rn.bf16x2 %0, %1, %2;" : "=r"(r) : "r"(a), "r"(b));
    return r;
}
__device__ __forceinline__ float bf_lo(uint32_t v) { return __uint_as_float(v << 16); }
__device__ __forceinline__ float bf_hi(uint32_t v) { return __uint_as_float(v & 0xffff0000u); }
__device__ __forceinline__ float round_bf16(float v) { return __bfloat162float(__float2bfloat16_rn(v)); }
__device__ __forceinline__ float ex2(float x) {
    float y;
    asm("ex2.approx.ftz.f32 %0, %1;" : "=f"(y) : "f"(x));
    return y;
}
__device__ __forceinline__ float rcp(float x) {
    float y;
    asm("rcp.approx.ftz.f32 %0, %1;" : "=f"(y) : "f"(x));
    return y;
}
__device__ __forceinline__ void stg128(void* p, uint32_t a, uint32_t b, uint32_t c, uint32_t d) {
    asm volatile("st.global.v4.b32 [%0], {%1, %2, %3, %4};" ::"l"(p), "r"(a), "r"(b), "r"(c), "r"(d) : "memory");
}
__device__ __forceinline__ void stg128p(void* p, uint32_t a, uint32_t b, uint32_t c, uint32_t d, uint64_t pol) {
    asm volatile("st.global.L2::cache_hint.v4.b32 [%0], {%1, %2, %3, %4}, %5;" ::"l"(p), "r"(a), "r"(b), "r"(c), "r"(d), "l"(pol) : "memory");
}
__device__ __forceinline__ uint64_t policy_sel(bool first) {
    uint64_t p;
    asm("createpolicy.fractional.L2::evict_normal.b64 %0, 1.0;" : "=l"(p));
    return first ? policy_evict_first() : p;
}
__device__ __forceinline__ int perm_row(int t) { return (t & ~255) | (((0x78 >> (((t >> 6) & 3) * 2)) & 3) << 6) | (t & 63); }
__device__ __forceinline__ int unperm_row(int t) { return (t & ~255) | (((0x9C >> (((t >> 6) & 3) * 2)) & 3) << 6) | (t & 63); }

#define PROF(i)
#define PROFG(i)
#define PROFDUMP()
#define TR(i)
#define BP(r, i)
#define LP(i)

template <int I>
__device__ __forceinline__ void store_chunk(const float (&a)[64], __nv_bfloat16* row0, __nv_bfloat16* row1, float s0, float s1, uint64_t pol) {
    stg128p(row0 + 32 * I, pack_bf16(a[16 * I + 0] * s0, a[16 * I + 1] * s0), pack_bf16(a[16 * I + 4] * s0, a[16 * I + 5] * s0),
           pack_bf16(a[16 * I + 8] * s0, a[16 * I + 9] * s0), pack_bf16(a[16 * I + 12] * s0, a[16 * I + 13] * s0), pol);
    stg128p(row1 + 32 * I, pack_bf16(a[16 * I + 2] * s1, a[16 * I + 3] * s1), pack_bf16(a[16 * I + 6] * s1, a[16 * I + 7] * s1),
           pack_bf16(a[16 * I + 10] * s1, a[16 * I + 11] * s1), pack_bf16(a[16 * I + 14] * s1, a[16 * I + 15] * s1), pol);
}
template <int I>
struct IntT { static constexpr int value = I; };
template <class F>
__device__ __forceinline__ void for4(F f) { f(IntT<0>{}); f(IntT<1>{}); f(IntT<2>{}); f(IntT<3>{}); }

struct Prod {
    uint32_t smem, bars;
    uint32_t bo, par;
    uint32_t dst, fb;
    __device__ __forceinline__ void acquire(uint32_t o, uint32_t parity, uint32_t bytes) {
        mbar_wait(bars + BAR_EMPTY + o, parity);
        fb = bars + BAR_FULL + o;
        dst = smem + o * (SLOT / 8);
        w_expect_tx(fb, bytes);
    }
    __device__ __forceinline__ void next(uint32_t bytes) {
        acquire(bo, par, bytes);
        const bool wrap = bo == (NSLOT - 1) * 8;
        bo = wrap ? 0u : bo + 8;
        par ^= wrap ? 1u : 0u;
    }
};

__device__ __forceinline__ int item_p(int ca, int rd) {
    const int v = (rd & 1) ? (ca + 4) & 7 : ca;
    return (rd & 2) ? 7 - v : v;
}
__device__ __forceinline__ int kv_round(int i) { return (KVORDER >> (4 * i)) & 3; }
__device__ __forceinline__ int slot_a(int i) { return (0x5310 >> (4 * i)) & 15; }
__device__ __forceinline__ int slot_w(int m) { return (0x264 >> (4 * m)) & 15; }

__device__ __forceinline__ void producer(const Params& P, uint32_t smem, uint32_t bars, int ca, int cb, int rank) {
    Prod pr{smem, bars, 0u, 0u, 0u, 0u};
    {
        int m = 0;
        uint32_t lap = 1;
#pragma unroll 1
        for (int u = 0; u < 32; u++) {
            if (u >= 3) {
                const int v = (u == 3) ? 3 + ca : u + 7;
                if (v < 32 && (u == 3 || (v & 7) == ca)) w_tma_prefetch((v & 4) ? &P.wuv : &P.wuk, (cb + 8 * kv_round(v >> 3)) * 128 + rank * 64, (v & 3) * 128);
                if (u == 24) {
                    w_tma_prefetch(&P.wq, cb * 128 + rank * 64, ca * 64);
                    if (ca < 2) w_tma_prefetch(&P.wq, cb * 128 + rank * 64, (ca + 8) * 64);
                }
            }
            pr.acquire(slot_w(m) * 8, lap ^ (m >> 1), SLOT);
            lap ^= m >> 1;
            m = (m == 2) ? 0 : m + 1;
            TR(1 + u);
            w_tma_load_mc(pr.dst + rank * 16384, (u & 4) ? &P.wuv : &P.wuk, (cb + 8 * kv_round(u >> 3)) * 128 + rank * 64, (u & 3) * 128, pr.fb);
            if (u < 3) {
                pr.acquire(slot_a(u + 1) * 8, 1, SLOT);
                w_tma_load(pr.dst, &P.ckv, u * 128 + 128, (2 * ca + rank) * 128, pr.fb);
                w_tma_load(pr.dst + 16384, &P.ckv, u * 128 + 192, (2 * ca + rank) * 128, pr.fb);
            }
        }
    }
    PROF(1);
    mbar_wait(bars + BAR_DEP, 0);
#pragma unroll 1
    for (int rd = 0; rd < 4; rd++) {
        const int h = 8 * rd + cb, p = item_p(ca, rd);
#pragma unroll 1
        for (int ks = 0; ks < 10; ks++) {
            pr.next(SLOT);
            w_tma_load_mc(pr.dst + 16384 + rank * 8192, &P.wq, h * 128 + rank * 64, ks * 64, pr.fb);
            w_tma_load(pr.dst, &P.xn, ks * 64, 256 * p + 128 * rank, pr.fb);
        }
        PROF(8 + rd * 4);
        mbar_wait(bars + BAR_DEP + (1 + rd) * 8, 0);
        const int last = 4 * p + 3, top = h * 32 + last;
#pragma unroll 1
        for (int i = 0; i <= last; i++) {
            const int t = (i == 0) ? top - 1 : (i == last) ? h * 32 + 1 : (i & 1) ? top - 2 - i : top + 2 - i;
            pr.next(SLOT);
            const bool lastrd = (rd == 0) ? ((LASTRD & 1) && ca >= 8 - LASTN) : (rd == 1) ? ((LASTRD & 2) && (ca & 3) >= 4 - LASTN) : (rd == 2) ? ((LASTRD & 4) && (ca == 3 || (ca < 3 && (t & 31) >= 4 * p))) : (LASTRD & 8) != 0;
            if (lastrd) w_tma_load_mc_last(pr.dst + rank * 16384, &P.kv, rank * 64, t * 128, pr.fb);
            else w_tma_load_mc(pr.dst + rank * 16384, &P.kv, rank * 64, t * 128, pr.fb);
            if (i == 2) {
                if (rd < 3) {
                    w_tma_prefetch(&P.wq, (h + 8) * 128 + rank * 64, ca * 64);
                    if (ca < 2) w_tma_prefetch(&P.wq, (h + 8) * 128 + rank * 64, (ca + 8) * 64);
                } else {
#pragma unroll 1
                    for (int j = 0; j < 10; j++) {
                        const int tt = ca + (j >= 5 ? 8 : 0);
                        w_tma_prefetch(&P.wo, 320 * (cb & 1) + 64 * (j >= 5 ? j - 5 : j), (8 * (tt >> 2) + (cb & 6) + ((tt >> 1) & 1)) * 128 + (tt & 1) * 64 + rank * 32);
                    }
                }
            }
        }
        PROF(9 + rd * 4);
    }
    {
        const int n0 = 320 * (cb & 1), kg = cb >> 1;
#pragma unroll 1
        for (int t = 0; t < 16; t++) {
            const int h = 8 * (t >> 2) + 2 * kg + ((t >> 1) & 1), ks = t & 1;
            const int krow = h * 128 + ks * 64 + rank * 32;
            pr.next(SLOT);
            w_tma_load_mc(pr.dst + 16384 + rank * 8192, &P.wo, n0, krow, pr.fb);
            w_tma_load_mc(pr.dst + 16384 + rank * 8192 + 4096, &P.wo, n0 + 64, krow, pr.fb);
            mbar_wait(bars + BAR_DEP + (5 + (t >> 1)) * 8, 0);
            w_tma_load(pr.dst, &P.ctx, ks * 64, h * SEQ + 256 * ca + 128 * rank, pr.fb);
            pr.next(24576);
#pragma unroll
            for (int c = 0; c < 3; c++) w_tma_load_mc(pr.dst + rank * 12288 + c * 4096, &P.wo, n0 + 128 + 64 * c, krow, pr.fb);
        }
    }
}

struct Slot {
    uint32_t bo, dl, par;
};
struct Cons {
    uint32_t bars, rel;
    uint32_t dl0;
    uint32_t lane;
    Slot cur;
    __device__ __forceinline__ Slot slot(int s, uint32_t par) const { return Slot{(uint32_t)s * 8, dl0 + (uint32_t)s * (SLOT >> 4), par}; }
    __device__ __forceinline__ void wait(const Slot& s) const { mbar_wait(bars + BAR_FULL + s.bo, s.par); }
    __device__ __forceinline__ void release(uint32_t bo) const {
        asm volatile("{\n.reg .pred p;\nsetp.lt.u32 p, %1, 2;\n@p mbarrier.arrive.shared::cluster.b64 _, [%0];\n}\n" ::"r"(rel + bo), "r"(lane) : "memory");
    }
    __device__ __forceinline__ Slot next() {
        const Slot s = cur;
        const bool wrap = s.bo == (NSLOT - 1) * 8;
        cur.bo = wrap ? 0u : s.bo + 8;
        cur.dl = wrap ? dl0 : s.dl + (SLOT >> 4);
        cur.par = s.par ^ (wrap ? 1u : 0u);
        return s;
    }
};
__host__ __device__ constexpr uint32_t lbo(uint32_t bytes) { return (bytes >> 4) << 16; }

__device__ __forceinline__ float div640(float x) {
    const float q = x * (1.0f / DM);
    return fmaf(fmaf(-q, (float)DM, x), 1.0f / DM, q);
}
__device__ __forceinline__ float sqrt_approx(float x) {
    float y;
    asm("sqrt.approx.ftz.f32 %0, %1;" : "=f"(y) : "f"(x));
    return y;
}
struct LayerNorm {
    uint4 xv[5], wv[5];
    float mean, inv, r;
    static __device__ __forceinline__ float half_sum(float v) {
#pragma unroll
        for (int o = 8; o > 0; o >>= 1) v += __shfl_xor_sync(0xffffffffu, v, o);
        return v;
    }
    __device__ __forceinline__ void load(const __nv_bfloat16* x, const __nv_bfloat16* wr, int t, int l) {
#pragma unroll
        for (int i = 0; i < 5; i++) {
            xv[i] = ldg_stream(reinterpret_cast<const uint4*>(x + t * DM) + l + 16 * i);
            wv[i] = __ldg(reinterpret_cast<const uint4*>(wr) + l + 16 * i);
        }
    }
    __device__ __forceinline__ void stat1() {
        float a[4] = {0.f, 0.f, 0.f, 0.f};
#pragma unroll
        for (int i = 0; i < 20; i++) { const uint32_t u = (&xv[i >> 2].x)[i & 3]; a[i & 3] += bf_lo(u) + bf_hi(u); }
        mean = div640(half_sum((a[0] + a[1]) + (a[2] + a[3])));
        r = 0.f;
    }
    template <int H>
    __device__ __forceinline__ void stat2() {
        float a[4] = {r, 0.f, 0.f, 0.f};
#pragma unroll
        for (int i = H ? 12 : 0; i < (H ? 20 : 12); i++) {
            uint32_t u = (&xv[i >> 2].x)[i & 3];
            asm volatile("" : "+r"(u));
            const float d0 = bf_lo(u) - mean, d1 = bf_hi(u) - mean;
            a[i & 3] = fmaf(d0, d0, fmaf(d1, d1, a[i & 3]));
        }
        r = (a[0] + a[1]) + (a[2] + a[3]);
        if (H) {
            inv = rcp(round_bf16(sqrt_approx(round_bf16(round_bf16(div640(half_sum(r))) + 1e-5f))));
            r = 0.f;
        }
    }
    template <int I>
    __device__ __forceinline__ void piece(__nv_bfloat16* out, int t, int l) {
        const uint32_t nmb = pack_bf16(-mean, -mean);
        uint32_t o[4], z[4];
        float a[4];
#pragma unroll
        for (int j = 0; j < 4; j++) {
            const uint32_t u = (&xv[I].x)[j], w = (&wv[I].x)[j];
            const uint32_t d = add_bf16x2(u, nmb);
            o[j] = pack_bf16(bf_lo(d) * inv, bf_hi(d) * inv);
            z[j] = add_bf16x2(u, o[j]);
            a[j] = fmaf(bf_hi(o[j]), bf_hi(w), bf_lo(o[j]) * bf_lo(w));
        }
        r += (a[0] + a[1]) + (a[2] + a[3]);
        stg128(g_xn + perm_row(t) * DM + 8 * (l + 16 * I), o[0], o[1], o[2], o[3]);
        stg128p(out + t * DM + 8 * (l + 16 * I), z[0], z[1], z[2], z[3], policy_sel(EFMASK & 1));
        if (I == 4) {
            r = half_sum(r);
            if (l == 0) g_r[t] = round_bf16(r);
        }
    }
};

constexpr float SM_SCALE = 0.08838834764831845f * 1.4426950408889634f;

template <int J0, int J1>
__device__ __forceinline__ void exp_part(float (&s)[64], float n0, float n1, float& r0, float& r1) {
    float a1 = 0.f, b1 = 0.f;
#pragma unroll
    for (int j = J0; j < J1; j++) {
        s[4 * j + 0] = ex2(fmaf(s[4 * j + 0], SM_SCALE, n0));
        s[4 * j + 1] = ex2(fmaf(s[4 * j + 1], SM_SCALE, n0));
        s[4 * j + 2] = ex2(fmaf(s[4 * j + 2], SM_SCALE, n1));
        s[4 * j + 3] = ex2(fmaf(s[4 * j + 3], SM_SCALE, n1));
        r0 += s[4 * j + 0]; r1 += s[4 * j + 2];
        if (j == J0) { a1 = s[4 * j + 1]; b1 = s[4 * j + 3]; } else { a1 += s[4 * j + 1]; b1 += s[4 * j + 3]; }
    }
    r0 += a1;
    r1 += b1;
}
__device__ __forceinline__ void sched_barrier(float x, float y, uint32_t scratch) {
    asm volatile("{\n.reg .pred p;\nsetp.lt.f32 p, %0, 0f00000000;\n@p st.shared.f32 [%2], %1;\n}\n" ::"f"(x), "f"(y), "r"(scratch) : "memory");
}
__device__ __forceinline__ void pack_tile(const float (&s)[64], uint32_t (&p)[32]) {
#pragma unroll
    for (int i = 0; i < 32; i++) p[i] = pack_bf16(s[2 * i], s[2 * i + 1]);
}
template <bool ZERO>
__device__ __forceinline__ void gemm_rs(float (&d)[64], const uint32_t (&a)[32], uint32_t dl, int acc = 1) {
    const uint32_t b = dl + lbo(16384);
    if (ZERO) wgmma_rs_n128_z<1>(d, a[0], a[1], a[2], a[3], b);
#pragma unroll
    for (int k = ZERO ? 1 : 0; k < 8; k++) wgmma_rs_n128<1>(d, a[4 * k], a[4 * k + 1], a[4 * k + 2], a[4 * k + 3], b + k * 128, k ? 1 : acc);
}
template <int ZERO>
__device__ __forceinline__ void gemm_q(float (&d)[64], uint32_t dl, int role) {
    const uint32_t a = dl + role * 512 + lbo(16), b = dl + 1024 + lbo(8192);
    if (ZERO) wgmma_ss_n128_z<0, 1>(d, a, b);
#pragma unroll
    for (int k = ZERO ? 1 : 0; k < 4; k++) wgmma_ss_n128<0, 1>(d, a + k * 2, b + k * 128, 1);
}
template <bool KT, bool ZERO, int K0, int K1>
__device__ __forceinline__ void gemm_kv(float (&d)[64], uint32_t ckv, uint32_t wt, int wg) {
    if (KT) {
        const uint32_t a = wt + wg * 1024 + lbo(16), b = ckv + lbo(16);
        if (ZERO) wgmma_ss_n128_z<1, 0>(d, a, b);
#pragma unroll
        for (int k = ZERO ? 1 : K0; k < K1; k++) wgmma_ss_n128<1, 0>(d, a + k * 128, b + (k >> 2) * 1024 + (k & 3) * 2, 1);
    } else {
        const uint32_t a = ckv + wg * 512 + lbo(16), b = wt + lbo(16384);
        if (ZERO) wgmma_ss_n128_z<0, 1>(d, a, b);
#pragma unroll
        for (int k = ZERO ? 1 : K0; k < K1; k++) wgmma_ss_n128<0, 1>(d, a + (k >> 2) * 1024 + (k & 3) * 2, b + k * 128, 1);
    }
}
__device__ __forceinline__ void mma16816(float& d0, float& d1, float& d2, float& d3, uint32_t a0, uint32_t a1, uint32_t a2, uint32_t a3, uint32_t b0, uint32_t b1) {
    asm volatile("mma.sync.aligned.m16n8k16.row.col.f32.bf16.bf16.f32 {%0,%1,%2,%3}, {%4,%5,%6,%7}, {%8,%9}, {%0,%1,%2,%3};"
                 : "+f"(d0), "+f"(d1), "+f"(d2), "+f"(d3) : "r"(a0), "r"(a1), "r"(a2), "r"(a3), "r"(b0), "r"(b1));
}
__device__ __forceinline__ uint32_t ld_pair(const __nv_bfloat16* p) {
    const unsigned short* u = reinterpret_cast<const unsigned short*>(p);
    return (uint32_t)__ldcg(u) | ((uint32_t)__ldcg(u + 128) << 16);
}
__device__ __forceinline__ void attention_exact(float (&o)[64], const uint32_t (&qf)[32], float& l0, float& l1, int h, int nblk, int rr, int lane) {
    const int q = lane & 3, lr = lane >> 2;
    float m0 = -INFINITY, m1 = -INFINITY;
    l0 = 0.f; l1 = 0.f;
#pragma unroll
    for (int i = 0; i < 64; i++) o[i] = 0.f;
#pragma unroll 1
    for (int cidx = 0; cidx < nblk * 8; cidx++) {
        const int kc = cidx & 7;
        const __nv_bfloat16* kt = g_kv + (size_t)((h * 16 + (cidx >> 3)) * 2) * 16384;
        float sc[8];
#pragma unroll
        for (int i = 0; i < 8; i++) sc[i] = 0.f;
#pragma unroll
        for (int kk = 0; kk < 8; kk++)
#pragma unroll
            for (int nt = 0; nt < 2; nt++) {
                const __nv_bfloat16* b = kt + (16 * kk + 2 * q) * 128 + 16 * kc + 8 * nt + lr;
                mma16816(sc[4 * nt], sc[4 * nt + 1], sc[4 * nt + 2], sc[4 * nt + 3], qf[4 * kk], qf[4 * kk + 1], qf[4 * kk + 2], qf[4 * kk + 3],
                         ld_pair(b), ld_pair(b + 8 * 128));
            }
        const int lim = rr + ((nblk - 1) - (cidx >> 3)) * 128 - 32 * (kc >> 1) - 4 * (kc & 1);
#pragma unroll
        for (int i = 0; i < 8; i++)
            if (2 * (i >> 2) + (i & 1) > lim + 4 * (i & 2)) sc[i] = -INFINITY;
        float x0 = fmaxf(fmaxf(sc[0], sc[1]), fmaxf(sc[4], sc[5])), x1 = fmaxf(fmaxf(sc[2], sc[3]), fmaxf(sc[6], sc[7]));
        x0 = fmaxf(x0, __shfl_xor_sync(0xffffffffu, x0, 1)); x1 = fmaxf(x1, __shfl_xor_sync(0xffffffffu, x1, 1));
        x0 = fmaxf(x0, __shfl_xor_sync(0xffffffffu, x0, 2)); x1 = fmaxf(x1, __shfl_xor_sync(0xffffffffu, x1, 2));
        x0 = fmaxf(x0, m0); x1 = fmaxf(x1, m1);
        const float a0 = ex2((m0 - x0) * SM_SCALE), a1 = ex2((m1 - x1) * SM_SCALE);
        m0 = x0; m1 = x1;
#pragma unroll
        for (int i = 0; i < 8; i++) sc[i] = ex2((sc[i] - ((i & 2) ? m1 : m0)) * SM_SCALE);
        l0 = l0 * a0 + (sc[0] + sc[1]) + (sc[4] + sc[5]);
        l1 = l1 * a1 + (sc[2] + sc[3]) + (sc[6] + sc[7]);
        const uint32_t p0 = pack_bf16(sc[0], sc[1]), p1 = pack_bf16(sc[2], sc[3]), p2 = pack_bf16(sc[4], sc[5]), p3 = pack_bf16(sc[6], sc[7]);
        const __nv_bfloat16* vb = kt + 16384 + (16 * kc + 2 * q) * 128 + lr;
#pragma unroll
        for (int nt = 0; nt < 16; nt++) {
            o[4 * nt] *= a0; o[4 * nt + 1] *= a0; o[4 * nt + 2] *= a1; o[4 * nt + 3] *= a1;
            mma16816(o[4 * nt], o[4 * nt + 1], o[4 * nt + 2], o[4 * nt + 3], p0, p1, p2, p3, ld_pair(vb + 8 * nt), ld_pair(vb + 8 * nt + 8 * 128));
        }
    }
}

__device__ __forceinline__ void signal(uint32_t bars, int wg, int e, int lane) {
    __syncwarp();
    asm volatile("{\n.reg .pred p;\nsetp.eq.u32 p, %1, 0;\n@p mbarrier.arrive.shared::cta.b64 _, [%0];\n}\n" ::"r"(bars + BAR_SIG + (wg * 9 + e) * 8), "r"(lane) : "memory");
}

__device__ __forceinline__ void consumer(const Params& P, uint32_t smem, uint32_t bars, int ca, int cb, int rank, int wg) {
    const int lane = threadIdx.x & 31, w = (threadIdx.x >> 5) & 3, q = lane & 3, lr = lane >> 2;
    PROF(7);
    cluster_wait();
    Cons c{bars, mapa(bars + BAR_EMPTY, lane & 1), (smem & 0x3FFFF) >> 4, (uint32_t)lane, Slot{0u, (smem & 0x3FFFF) >> 4, 1u}};
    PROFG(180);
    PROF(1);
    float o[64], s[64];
    uint32_t pend;
    __nv_bfloat16* ep_ptr;
    int ep_step;
    {
        const int ln_t = blockIdx.x * 16 + wg * 8 + w * 2 + (lane >> 4);
        const int krow = 64 * wg + 16 * w + lr;
        const int vrow = 64 * wg + 32 * (w >> 1) + 8 * (lr >> 1) + 4 * (w & 1) + (lr & 1);
        ep_step = 2 * 128;
        int m = 0;
        uint32_t lap = 0;
        LayerNorm ln;
        auto step = [&](auto kt, auto kc, float (&d)[64], int hh) {
            const Slot sa = c.slot(slot_a(kc.value), 0), sw = c.slot(slot_w(m), lap ^ (m >> 1));
            lap ^= m >> 1;
            m = (m == 2) ? 0 : m + 1;
            TR(1 + (hh * 8 + (kt.value ? 0 : 4) + kc.value) * 2);
            if (kt.value && hh == 0) c.wait(sa);
            c.wait(sw);
            TR(2 + (hh * 8 + (kt.value ? 0 : 4) + kc.value) * 2);
            wgmma_fence();
            gemm_kv<kt.value, kc.value == 0, 0, KVSPLIT>(d, sa.dl, sw.dl, wg);
            wgmma_commit();
            wgmma_wait<1>();
            if (!(kt.value && kc.value == 0 && hh == 0)) c.release(pend);
            if (!kt.value && kc.value > 0 && hh == 3) c.release(slot_a(kc.value - 1) * 8);
            pend = sw.bo;
            wgmma_fence();
            gemm_kv<kt.value, false, KVSPLIT, 8>(d, sa.dl, sw.dl, wg);
            wgmma_commit();
        };
#pragma unroll 1
        for (int hh = 0; hh < 4; hh++) {
            __nv_bfloat16* base = g_kv + (size_t)(((cb + 8 * kv_round(hh)) * 16 + 2 * ca + rank) * 2) * 16384 + 8 * q;
            const bool do_ln = hh == wg * LNSTAG + 1;
            for4([&](auto kc) {
                step(TrueT{}, kc, s, hh);
                if (hh > 0) {
                    if (kc.value == 0) fence_regs(o);
                    store_chunk<kc.value>(o, ep_ptr, ep_ptr + ep_step, 1.f, 1.f, policy_sel((EFMASK & 2) && hh == 1));
                }
                if (do_ln) {
                    if (kc.value == 0) ln.stat1();
                    if (kc.value == 1) ln.template stat2<0>();
                    if (kc.value == 2) ln.template stat2<1>();
                    if (kc.value == 3) ln.template piece<0>(P.out, ln_t, lane & 15);
                }
            });
            if (hh > 0) signal(bars, wg, hh, lane);
            for4([&](auto kc) {
                step(FalseT{}, kc, o, hh);
                if (kc.value == 0) fence_regs(s);
                store_chunk<kc.value>(s, base + krow * 128, base + (krow + 8) * 128, 1.f, 1.f, policy_sel((EFMASK & 2) && hh == 0));
                if (do_ln) ln.template piece<kc.value + 1>(P.out, ln_t, lane & 15);
                if (kc.value == 1 && hh == wg * LNSTAG) ln.load(P.x, P.wr, ln_t, lane & 15);
            });
            if (do_ln) signal(bars, wg, 0, lane);
            PROF(24 + hh);
            if (hh == 1) PROFG(181);
            ep_ptr = base + 16384 + vrow * 128;
        }
    }
    PROFG(182);
    PROF(2);
    uint32_t pf[32];
    {
        uint32_t qf[32];
        float l0 = 0.25f, l1 = 0.25f;
        const int bar_me = 2 + wg, bar_other = 3 - wg;
#pragma unroll 1
        for (int rd = 0; rd < 4; rd++) {
            const int h = 8 * rd + cb, p = item_p(ca, rd);
            const int role = wg ^ (rd & 1);
            const int nrest = 2 * p + role;
            Slot kfirst;
            {
                auto qstep = [&](auto zero, int ks) {
                    const Slot sl = c.next();
                    BP(2, 4 + 3 * ks);
                    c.wait(sl);
                    BP(2, 5 + 3 * ks);
                    wgmma_fence();
                    gemm_q<zero.value>(s, sl.dl, role);
                    wgmma_commit();
                    wgmma_wait<1>();
                    BP(2, 6 + 3 * ks);
                    c.release(pend);
                    pend = sl.bo;
                };
                qstep(TrueT{}, 0);
                if (rd == 0) c.release(slot_a(3) * 8);
                fence_regs(o);
#pragma unroll 1
                for (int ks = 1; ks < QST; ks++) qstep(FalseT{}, ks);
                for4([&](auto i) {
                    qstep(FalseT{}, QST + i.value);
                    if (i.value == 0) {
                        l0 += __shfl_xor_sync(0xffffffffu, l0, 1); l1 += __shfl_xor_sync(0xffffffffu, l1, 1);
                        l0 += __shfl_xor_sync(0xffffffffu, l0, 2); l1 += __shfl_xor_sync(0xffffffffu, l1, 2);
                        l0 = rcp(l0); l1 = rcp(l1);
                    }
                    store_chunk<i.value>(o, ep_ptr, ep_ptr + ep_step, l0, l1, policy_sel(((EFMASK & 4) && rd == 1) || ((EFMASK & 8) && rd == 2)));
                });
                signal(bars, wg, 4 + rd, lane);
                PROF(11 + rd * 4);
#pragma unroll 1
                for (int ks = QST + 4; ks < 10; ks++) qstep(FalseT{}, ks);
                if (!role) { const Slot sl = c.next(); c.wait(sl); c.release(sl.bo); }
                kfirst = c.next();
                c.wait(kfirst);
                wgmma_wait<0>();
                BP(2, 34);
                c.release(pend);
                fence_regs(s);
                pack_tile(s, qf);
            }
            PROF(8 + rd * 4);
            fence_regs(qf);
            BP(2, 35);
            if (PINGPONG && !role) named_sync(bar_me, 256);
            BP(2, 36);
            wgmma_fence();
            gemm_rs<true>(s, qf, kfirst.dl);
            wgmma_commit();
            if (PINGPONG) named_arrive(bar_other, 256);
            BP(2, 37);
            if (!role) { const Slot sl = c.next(); c.wait(sl); c.release(sl.bo); }
            const int dg = __reduce_or_sync(0xffffffffu, 2 * (role ^ rank) + (w >> 1));
            wgmma_wait<0>();
            BP(2, 38);
            fence_regs(s);
            c.release(kfirst.bo);
            float n0, n1;
            l0 = 0.f; l1 = 0.f;
            for4([&](auto a) {
                constexpr int B = 16 * a.value;
                if (a.value == dg) {
                    const int lim = 16 * (w & 1) + lr - 8 * q;
#pragma unroll
                    for (int i = 0; i < 16; i++)
                        if (2 * (i >> 2) + (i & 1) > lim + 4 * (i & 2)) s[B + i] = -INFINITY;
                }
                if (a.value == 0) {
                    n0 = fmaxf(fmaxf(fmaxf(s[0], s[1]), fmaxf(s[4], s[5])), fmaxf(fmaxf(s[8], s[9]), fmaxf(s[12], s[13])));
                    n1 = fmaxf(fmaxf(fmaxf(s[2], s[3]), fmaxf(s[6], s[7])), fmaxf(fmaxf(s[10], s[11]), fmaxf(s[14], s[15])));
                    n0 = fmaxf(n0, __shfl_xor_sync(0xffffffffu, n0, 1)); n1 = fmaxf(n1, __shfl_xor_sync(0xffffffffu, n1, 1));
                    n0 = fmaxf(n0, __shfl_xor_sync(0xffffffffu, n0, 2)); n1 = fmaxf(n1, __shfl_xor_sync(0xffffffffu, n1, 2));
                    n0 *= -SM_SCALE; n1 *= -SM_SCALE;
                }
                if (a.value <= dg) {
                    exp_part<4 * a.value, 4 * a.value + 4>(s, n0, n1, l0, l1);
#pragma unroll
                    for (int i = 0; i < 8; i++) pf[8 * a.value + i] = pack_bf16(s[B + 2 * i], s[B + 2 * i + 1]);
                } else {
#pragma unroll
                    for (int i = 0; i < 8; i++) pf[8 * a.value + i] = 0u;
                }
            });
            PROF(9 + rd * 4);
#pragma unroll 1
            for (int it = 0; it < nrest; it++) {
                const Slot sk = c.next(), sv = c.next();
                LP(0);
                if (it < 3) BP(2, 40 + 4 * it);
                if (it >= nrest - 2) BP(1, 60 + 4 * (it - nrest + 2));
                c.wait(sk);
                c.wait(sv);
                fence_regs(o); fence_regs(pf);
                LP(1);
                if (it < 3) BP(2, 41 + 4 * it);
                if (it >= nrest - 2) BP(1, 61 + 4 * (it - nrest + 2));
                if (PINGPONG) named_sync(bar_me, 256);
                LP(2);
                if (it < 3) BP(2, 42 + 4 * it);
                if (it >= nrest - 2) BP(1, 62 + 4 * (it - nrest + 2));
                wgmma_fence();
                gemm_rs<true>(s, qf, sk.dl);
                wgmma_commit();
                gemm_rs<false>(o, pf, sv.dl, it);
                wgmma_commit();
                if (PINGPONG) named_arrive(bar_other, 256);
                LP(3);
                if (it < 3) BP(2, 43 + 4 * it);
                if (it >= nrest - 2) BP(1, 63 + 4 * (it - nrest + 2));
                wgmma_wait<1>();
                LP(4);
                c.release(sk.bo);
                fence_regs(s);
                exp_part<0, SPLITJ>(s, n0, n1, l0, l1);
                sched_barrier(l0, l1, bars + MISC_OFF + 16);
                LP(5);
                wgmma_wait<0>();
                LP(6);
                c.release(sv.bo);
                fence_regs(o); fence_regs(pf);
                exp_part<SPLITJ, 16>(s, n0, n1, l0, l1);
                pack_tile(s, pf);
            }
            PROF(10 + rd * 4);
            PROFG(183 + rd);
            const Slot sv = c.next();
            BP(1, 0);
            c.wait(sv);
            if (nrest == 0) {
#pragma unroll
                for (int i = 0; i < 64; i++) o[i] = 0.f;
            }
            if (__builtin_expect(__any_sync(0xffffffffu, !(l0 < 0x1p60f && l1 < 0x1p60f)), 0)) {
                attention_exact(o, qf, l0, l1, h, nrest + 1, 64 * (role ^ rank) + 16 * w + lr - 8 * q, lane);
#pragma unroll
                for (int i = 0; i < 32; i++) pf[i] = 0u;
            }
            fence_regs(o); fence_regs(pf);
            BP(1, 1);
            if (PINGPONG && !role) named_sync(bar_me, 256);
            BP(1, 2);
            wgmma_fence();
            gemm_rs<false>(o, pf, sv.dl);
            wgmma_commit();
            BP(1, 3);
            pend = sv.bo;
            ep_ptr = g_ctx + (size_t)(h * SEQ + 256 * p + 128 * rank + 64 * role + 16 * w + lr) * HD + 8 * q;
            ep_step = 8 * HD;
        }
        l0 += __shfl_xor_sync(0xffffffffu, l0, 1); l1 += __shfl_xor_sync(0xffffffffu, l1, 1);
        l0 += __shfl_xor_sync(0xffffffffu, l0, 2); l1 += __shfl_xor_sync(0xffffffffu, l1, 2);
        l0 = rcp(l0); l1 = rcp(l1);
        wgmma_wait<0>();
        c.release(pend);
        fence_regs(o); fence_regs(pf);
#pragma unroll
        for (int i = 0; i < 32; i++) pf[i] = pack_bf16(o[2 * i] * ((i & 1) ? l1 : l0), o[2 * i + 1] * ((i & 1) ? l1 : l0));
    }
    PROFG(187);
    PROF(3);
    {
        float a1[64], a2[96];
        uint32_t px = 0, py = 0;
        auto mma1 = [&](const Slot& x, int acc) {
#pragma unroll
            for (int k = 0; k < 4; k++) wgmma_ss_n128<0, 1>(a1, x.dl + wg * 512 + lbo(16) + k * 2, x.dl + 1024 + lbo(4096) + (k >> 1) * 512 + (k & 1) * 128, k ? 1 : acc);
        };
        auto mma2 = [&](const Slot& x, const Slot& y, int acc) {
#pragma unroll
            for (int k = 0; k < 4; k++) wgmma_ss_n192<0, 1>(a2, x.dl + wg * 512 + lbo(16) + k * 2, y.dl + lbo(4096) + (k >> 1) * 768 + (k & 1) * 128, k ? 1 : acc);
        };
#pragma unroll 1
        for (int t = 0; t < (EARLYSEND ? 14 : 16); t++) {
            const Slot sx = c.next(), sy = c.next();
            c.wait(sx);
            wgmma_fence();
            mma1(sx, t);
            wgmma_commit();
            wgmma_wait<1>();
            if (t > 0) { c.release(px); c.release(py); }
            px = sx.bo; py = sy.bo;
            c.wait(sy);
            wgmma_fence();
            mma2(sx, sy, t);
            wgmma_commit();
            if (t == 0) {
#pragma unroll
                for (int i = 0; i < 4; i++) stg128(ep_ptr + 32 * i, pf[8 * i], pf[8 * i + 2], pf[8 * i + 4], pf[8 * i + 6]);
            }
            if (t == 1) {
#pragma unroll
                for (int i = 0; i < 4; i++) stg128(ep_ptr + 8 * HD + 32 * i, pf[8 * i + 1], pf[8 * i + 3], pf[8 * i + 5], pf[8 * i + 7]);
                signal(bars, wg, 8, lane);
            }
        }
        if (EARLYSEND) {
            const Slot x0 = c.next(), y0 = c.next(), x1 = c.next(), y1 = c.next();
            c.wait(x0);
            c.wait(y0);
            wgmma_fence();
            mma2(x0, y0, 1);
            wgmma_commit();
            wgmma_wait<1>();
            c.release(px); c.release(py);
            c.wait(x1);
            c.wait(y1);
            wgmma_fence();
            mma2(x1, y1, 1);
            wgmma_commit();
            mma1(x0, 1);
            mma1(x1, 1);
            wgmma_commit();
        }
        const int cw = __reduce_or_sync(0xffffffffu, wg * 4 + w);
        Slot st = c.next();
        if (cw >= 3) st = c.next();
        if (cw >= 6) st = c.next();
        const uint32_t stage = smem + st.bo * (SLOT / 8) + (cw % 3) * 10240;
        const int orow = unperm_row(256 * ca + 128 * rank + 16 * cw), ocol = 320 * (cb & 1);
        const uint32_t sa = stage + ((lane & 7) + (lane & 8)) * 128, sx = (lane >> 4) ^ (lane & 7);
        auto send = [&](auto c0, auto c1) {
#pragma unroll
            for (int ch = c0.value; ch < c1.value; ch++) {
#pragma unroll
                for (int i = 0; i < 4; i++) {
                    uint32_t r[4];
#pragma unroll
                    for (int e = 0; e < 4; e++) {
                        const int k = 32 * ch + 8 * i + 2 * e;
                        r[e] = (ch < 2) ? pack_bf16(a1[k & 63], a1[(k & 63) + 1]) : pack_bf16(a2[ch < 2 ? 0 : k - 64], a2[ch < 2 ? 1 : k - 63]);
                    }
                    asm volatile("stmatrix.sync.aligned.m8n8.x4.shared.b16 [%0], {%1, %2, %3, %4};"
                                 ::"r"(sa + ch * 2048 + ((sx ^ (2 * i)) << 4)), "r"(r[0]), "r"(r[1]), "r"(r[2]), "r"(r[3]) : "memory");
                }
                if (FENCE_EACH || ch == c1.value - 1) {
                    asm volatile("fence.proxy.async.shared::cta;" ::: "memory");
                    __syncwarp();
#pragma unroll
                    for (int b = FENCE_EACH ? ch : c0.value; b <= ch; b++)
                        asm volatile(ELECT "cp.reduce.async.bulk.tensor.2d.global.shared::cta.add.bulk_group [%0, {%2, %3}], [%1];\n}\n"
                                     ::"l"(&P.outm), "r"(stage + b * 2048), "r"(ocol + 64 * b), "r"(orow) : "memory");
                }
            }
        };
        mbar_wait(bars + BAR_EMPTY + st.bo, st.par ^ 1);
        mbar_wait(bars + BAR_DEP + 13 * 8, 0);
        wgmma_wait<EARLYSEND>();
        fence_regs(a2);
        send(IntT<2>{}, IntT<5>{});
        wgmma_wait<0>();
        fence_regs(a1);
        PROFG(188);
        PROF(4);
        send(IntT<0>{}, IntT<2>{});
        PROF(5);
        asm volatile("cp.async.bulk.commit_group;\ncp.async.bulk.wait_group.read 0;" ::: "memory");
    }
    PROF(6);
}

__device__ __forceinline__ void mma_rows(float (&acc)[8][4], uint32_t a0, uint32_t a2, const uint4& w0, const uint4& w1, const uint4& w2, const uint4& w3) {
    const uint32_t r0[4] = {w0.x, w0.y, w0.z, w0.w}, r1[4] = {w1.x, w1.y, w1.z, w1.w};
    const uint32_t r2[4] = {w2.x, w2.y, w2.z, w2.w}, r3[4] = {w3.x, w3.y, w3.z, w3.w};
#pragma unroll
    for (int i = 0; i < 4; i++) {
        mma16816(acc[2 * i][0], acc[2 * i][1], acc[2 * i][2], acc[2 * i][3], a0, 0u, a2, 0u, __byte_perm(r0[i], r1[i], 0x5410), __byte_perm(r2[i], r3[i], 0x5410));
        mma16816(acc[2 * i + 1][0], acc[2 * i + 1][1], acc[2 * i + 1][2], acc[2 * i + 1][3], a0, 0u, a2, 0u, __byte_perm(r0[i], r1[i], 0x7632), __byte_perm(r2[i], r3[i], 0x7632));
    }
}

__device__ __forceinline__ void mod_ffn(const Params& P, uint8_t* sm, int mc  ) {
    const uint32_t epoch = read_epoch();
    const int tid = threadIdx.x - 128, lane = tid & 31, cw = tid >> 5, q = lane & 3, lr = lane >> 2;
    uint32_t* xs = reinterpret_cast<uint32_t*>(sm);
    uint32_t* wmax = xs + 8 * 324;
    int* sidx = reinterpret_cast<int*>(wmax + 16);
    const int fg = cw * 4 + mc;
    const uint32_t ring = smem_u32(sm) + 16384 + cw * 24576, rbar = smem_u32(sm) + 12288 + cw * 32;
    auto issue = [&](int u, int st) {
        if (lane == 0 && u < 30) {
            mbar_expect_tx(rbar + st * 8, 8192);
            if (u < 20) {
                tma_load_stream(ring + st * 8192, &P.wg, fg * 64, u * 32, rbar + st * 8);
                tma_load_stream(ring + st * 8192 + 4096, &P.wu, fg * 64, u * 32, rbar + st * 8);
            } else {
                tma_load_stream(ring + st * 8192, &P.wd, (u - 20) * 64, fg * 64, rbar + st * 8);
            }
        }
    };
    if (lane == 0) {
        mbar_init(rbar, 1); mbar_init(rbar + 8, 1); mbar_init(rbar + 16, 1);
        asm volatile("fence.mbarrier_init.release.cluster;" ::: "memory");
    }
    if (tid == 0) flag_wait<100>(F_LN, 256u * (epoch + 1));
    named_sync(1, 256);
    PROF(1);
    if (fg < 27) {
#pragma unroll 1
        for (int u = 0; u < 3; u++) issue(u, u);
    }
    PROF(2);
    uint32_t key[8];
#pragma unroll
    for (int i = 0; i < 8; i++) {
        const int t = tid + 256 * i;
        uint32_t b = __float_as_uint(__ldcg(g_r + t) + 0.f) >> 16;
        b = (b & 0x8000u) ? (~b & 0xffffu) : (b | 0x8000u);
        key[i] = (b << 16) | (uint32_t)(0xffff - t);
    }
#pragma unroll 1
    for (int rnd = 0; rnd < 8; rnd++) {
        uint32_t mx = key[0];
#pragma unroll
        for (int i = 1; i < 8; i++) mx = max(mx, key[i]);
        mx = __reduce_max_sync(0xffffffffu, mx);
        if (lane == 0) wmax[(rnd & 1) * 8 + cw] = mx;
        named_sync(1, 256);
        mx = __reduce_max_sync(0xffffffffu, wmax[(rnd & 1) * 8 + (lane & 7)]);
#pragma unroll
        for (int i = 0; i < 8; i++) if (key[i] == mx) key[i] = 0;
        if (tid == 0) sidx[rnd] = 0xffff - (int)(mx & 0xffffu);
    }
    named_sync(1, 256);
    {
        const uint32_t* src = reinterpret_cast<const uint32_t*>(g_xn + (size_t)perm_row(sidx[cw]) * DM);
#pragma unroll 2
        for (int i = lane; i < 320; i += 32) xs[cw * 324 + i] = __ldcg(src + i);
    }
    named_sync(1, 256);
    PROF(3);
    if (fg < 27) {
        float g[8][4], v[8][4];
        uint32_t hp[8];
#pragma unroll
        for (int i = 0; i < 8; i++)
#pragma unroll
            for (int e = 0; e < 4; e++) { g[i][e] = 0.f; v[i][e] = 0.f; }
        int st = 0, ph = 0;
#pragma unroll 1
        for (int u = 0; u < 60; u++) {
            if (!(u & 1)) mbar_wait(rbar + st * 8, ph);
            uint4 a[8];
#pragma unroll
            for (int r = 0; r < 8; r++) {
                const int row = (u < 40) ? 32 * (r >> 2) + 16 * (u & 1) + 2 * q + (r & 1) + 4 * (r & 2) : 16 * q + 8 * (u & 1) + r;
                asm volatile("ld.shared.v4.b32 {%0, %1, %2, %3}, [%4];" : "=r"(a[r].x), "=r"(a[r].y), "=r"(a[r].z), "=r"(a[r].w)
                             : "r"(ring + st * 8192 + row * 128 + ((lr ^ row) & 7) * 16) : "memory");
            }
            uint32_t f0, f1, f2, f3;
            if (u < 40) { f0 = f2 = xs[lr * 324 + u * 8 + q]; f1 = f3 = xs[lr * 324 + u * 8 + 4 + q]; }
            else if (u & 1) { f0 = hp[4]; f1 = hp[5]; f2 = hp[6]; f3 = hp[7]; }
            else { f0 = hp[0]; f1 = hp[1]; f2 = hp[2]; f3 = hp[3]; }
            mma_rows(g, f0, f1, a[0], a[1], a[2], a[3]);
            mma_rows(v, f2, f3, a[4], a[5], a[6], a[7]);
            if (u & 1) {
                __syncwarp();
                issue((u >> 1) + 3, st);
                if (++st == 3) { st = 0; ph ^= 1; }
                if (u >= 39) {
                    if (u == 39) {
                        float hv[16];
#pragma unroll
                        for (int i = 0; i < 16; i++) {
                            const float gp = round_bf16(g[i & 7][i >> 3]);
                            hv[i] = round_bf16(__fdividef(gp, 1.0f + __expf(fminf(-gp, 80.f)))) * round_bf16(v[i & 7][i >> 3]);
                        }
#pragma unroll
                        for (int i = 0; i < 8; i++) hp[i] = pack_bf16(hv[2 * i], hv[2 * i + 1]);
                    } else {
                        float4* dst = reinterpret_cast<float4*>(g_ypart + (fg * 8 + lr) * DM + ((u - 40) >> 1) * 64 + 16 * q);
#pragma unroll
                        for (int i = 0; i < 4; i++) {
                            const int j = 4 * (i & 1), e = i >> 1;
                            dst[i] = make_float4(g[j][e] + v[j][e], g[j + 1][e] + v[j + 1][e], g[j + 2][e] + v[j + 2][e], g[j + 3][e] + v[j + 3][e]);
                        }
                    }
#pragma unroll
                    for (int i = 0; i < 8; i++) { g[i][0] = 0.f; g[i][1] = 0.f; v[i][0] = 0.f; v[i][1] = 0.f; }
                }
            }
        }
    }
    PROF(5);
    named_sync(1, 256);
    if (tid == 0) {
        flag_add(F_MODP);
        flag_wait<100>(F_MODP, 4u * (epoch + 1));
    }
    named_sync(1, 256);
    PROF(6);
#pragma unroll 1
    for (int i = tid; i < 2 * DM; i += 256) {
        const int c = 2 * mc + (i >= DM), col = i - (i >= DM) * DM, t = sidx[c];
        float y = 0.f;
#pragma unroll 9
        for (int k = 0; k < 27; k++) y += __ldcg(g_ypart + (k * 8 + c) * DM + col);
        const float rs = round_bf16(__fdividef(1.0f, 1.0f + __expf(fminf(-__ldcg(g_r + t), 80.f))));
        const float xn = __bfloat162float(reinterpret_cast<const __nv_bfloat16*>(xs + c * 324)[col]);
        P.out[(size_t)t * DM + col] = __float2bfloat16_rn(__bfloat162float(P.x[(size_t)t * DM + col]) + round_bf16(xn + round_bf16(round_bf16(y) * rs)));
    }
    named_sync(1, 256);
    if (tid == 0) flag_add(F_MOD);
    PROF(7);
}

__global__ void __cluster_dims__(2, 1, 1) __launch_bounds__(384, 1) fused_kernel(const __grid_constant__ Params P) {
    extern __shared__ __align__(1024) uint8_t smem_raw[];
    const uint32_t smem = (smem_u32(smem_raw) + 1023u) & ~1023u;
    uint8_t* smem_gen = smem_raw + (smem - smem_u32(smem_raw));
    const uint32_t bars = smem + NSLOT * SLOT;
    const int wgi = __reduce_or_sync(0xffffffffu, threadIdx.x >> 7);
    const int cl = blockIdx.x >> 1, rank = blockIdx.x & 1, ca = cl & 7, cb = cl >> 3;
    PROFG(30);
    PROF(0);
    if (threadIdx.x == 0) {
#pragma unroll
        for (int i = 0; i < NSLOT; i++) { mbar_init(bars + BAR_FULL + i * 8, 1); mbar_init(bars + BAR_EMPTY + i * 8, 16); }
        mbar_arrive(bars + BAR_FULL + 16);
        asm volatile("mbarrier.arrive.shared::cta.b64 _, [%0], 16;" ::"r"(bars + BAR_EMPTY + 16) : "memory");
        asm volatile("fence.mbarrier_init.release.cluster;" ::: "memory");
        PROF(24);
    } else if (threadIdx.x == 32) {
#pragma unroll
        for (int i = 0; i < 18; i++) mbar_init(bars + BAR_SIG + i * 8, 4);
#pragma unroll
        for (int i = 0; i < 14; i++) mbar_init(bars + BAR_DEP + i * 8, 1);
    } else if (threadIdx.x >= 64 && threadIdx.x < 128 && cl < 64) {
        const int i = threadIdx.x - 64;
        if (i == 0) { prefetch_map(&P.ckv); prefetch_map(&P.wuk); }
        if (i < 32) asm volatile("prefetch.global.L2 [%0];" ::"l"(P.ckv_ptr + ((2 * ca + rank) * 128 + cb * 16 + (i >> 1)) * DC + (i & 1) * 64));
        else if (i < 48) asm volatile("prefetch.global.L2 [%0];" ::"l"(P.wuk_ptr + (size_t)((i - 32) * 8 + ca) * (NH * HD) + (cb + 8 * kv_round(0)) * 128 + rank * 64));
    }
    __syncthreads();
    PROF(29);
    cluster_arrive();
    if (wgi > 0) {
        asm volatile("setmaxnreg.inc.sync.aligned.u32 232;");
        if (cl >= 64) {
            cluster_wait();
            mod_ffn(P, smem_gen, blockIdx.x - 128);
        } else {
            consumer(P, smem, bars, ca, cb, rank, wgi - 1);
        }
        cluster_arrive();
        PROFG(31);
        PROFDUMP();
    } else {
        asm volatile("setmaxnreg.dec.sync.aligned.u32 40;");
        const int w = __reduce_or_sync(0xffffffffu, threadIdx.x >> 5), lane = threadIdx.x & 31;
        if (threadIdx.x == 32 && cl < 64) {
            mbar_expect_tx(bars + BAR_FULL, SLOT);
            tma_load(smem, &P.ckv, 0, (2 * ca + rank) * 128, bars + BAR_FULL);
            tma_load(smem + 16384, &P.ckv, 64, (2 * ca + rank) * 128, bars + BAR_FULL);
        }
        if (threadIdx.x == 64) {
            prefetch_map(&P.wuv); prefetch_map(&P.xn); prefetch_map(&P.wq); prefetch_map(&P.kv); prefetch_map(&P.ctx); prefetch_map(&P.wo); prefetch_map(&P.outm);
        }
        __syncwarp();
        cluster_wait();
        PROF(27);
        if (cl < 64) {
            if (w == 0) {
                producer(P, smem, bars, ca, cb, rank);
            } else if (w < 3 && lane == 0) {
                const int wg = w - 1;
#pragma unroll 1
                for (int i = 0; i < 9; i++) {
                    const int e = (i < wg * LNSTAG + 1) ? i + 1 : (i == wg * LNSTAG + 1) ? 0 : i;
                    mbar_wait_sleep(bars + BAR_SIG + (wg * 9 + e) * 8, 0);
                    int f;
                    if (e == 0) f = F_LN;
                    else if (e < 5) f = F_KV + cb + 8 * kv_round(e - 1);
                    else { const int rd = e - 5; f = F_CTX + (8 * rd + cb) * 16 + item_p(ca, rd) * 2 + rank; }
                    flag_add(f);
                }
            } else if (lane == 0) {
                const uint32_t epoch = read_epoch();
#pragma unroll 1
                for (int i = 0; i < 14; i++) {
                    const int e = (i < 11) ? i : (i == 11) ? 13 : i - 1;
                    int f;
                    uint32_t n;
                    if (e == 0) { f = F_LN; n = 256; }
                    else if (e < 5) { f = F_KV + cb + 8 * (e - 1); n = 32; }
                    else if (e < 13) { f = F_CTX + (8 * ((e - 5) >> 1) + (cb & 6) + ((e - 5) & 1)) * 16 + ca * 2 + rank; n = 2; }
                    else { f = F_MOD; n = 4; }
                    flag_wait<200>(f, n * (epoch + 1));
                    fence_proxy_async();
                    mbar_arrive(bars + BAR_DEP + e * 8);
                }
            }
        }
        __syncwarp();
        cluster_arrive();
        cluster_wait();
        if (threadIdx.x == 0) atomicAdd(g_flags + F_EXIT * 8, 1u);
        PROFG(31);
        PROFDUMP();
    }
}

typedef CUresult (*EncodeFn)(CUtensorMap*, CUtensorMapDataType, cuuint32_t, void*, const cuuint64_t*, const cuuint64_t*, const cuuint32_t*,
                             const cuuint32_t*, CUtensorMapInterleave, CUtensorMapSwizzle, CUtensorMapL2promotion, CUtensorMapFloatOOBfill);

void make_map(EncodeFn fn, CUtensorMap* m, const void* ptr, uint64_t rows, uint64_t cols, uint32_t box_rows) {
    cuuint64_t dims[2] = {cols, rows};
    cuuint64_t strides[1] = {cols * 2};
    cuuint32_t box[2] = {64, box_rows};
    cuuint32_t es[2] = {1, 1};
    fn(m, CU_TENSOR_MAP_DATA_TYPE_BFLOAT16, 2, const_cast<void*>(ptr), dims, strides, box, es, CU_TENSOR_MAP_INTERLEAVE_NONE,
       CU_TENSOR_MAP_SWIZZLE_128B, CU_TENSOR_MAP_L2_PROMOTION_L2_128B, CU_TENSOR_MAP_FLOAT_OOB_FILL_NONE);
}

}

extern "C" void kernel_launch(void* const* d_in, const int* in_sizes, int n_in, void* d_out, int out_size) {
    (void)in_sizes; (void)n_in; (void)out_size;
    void* fnp = nullptr;
    cudaDriverEntryPointQueryResult qr;
    cudaGetDriverEntryPoint("cuTensorMapEncodeTiled", &fnp, cudaEnableDefault, &qr);
    EncodeFn fn = (EncodeFn)fnp;
    void *xn, *kv, *ctx;
    cudaGetSymbolAddress(&xn, g_xn);
    cudaGetSymbolAddress(&kv, g_kv);
    cudaGetSymbolAddress(&ctx, g_ctx);
    Params P;
    make_map(fn, &P.ckv, d_in[1], SEQ, DC, 128);
    make_map(fn, &P.wq, d_in[2], DM, NH * HD, 64);
    make_map(fn, &P.wuk, d_in[3], DC, NH * HD, 128);
    make_map(fn, &P.wuv, d_in[4], DC, NH * HD, 128);
    make_map(fn, &P.wo, d_in[5], NH * HD, DM, 32);
    make_map(fn, &P.xn, xn, SEQ, DM, 128);
    make_map(fn, &P.kv, kv, NH * 16 * 2 * 128, 128, 128);
    make_map(fn, &P.ctx, ctx, NH * SEQ, HD, 128);
    P.x = (const __nv_bfloat16*)d_in[0];
    P.wr = (const __nv_bfloat16*)d_in[7];
    make_map(fn, &P.wg, d_in[8], DM, FF, 32);
    make_map(fn, &P.wu, d_in[9], DM, FF, 32);
    make_map(fn, &P.wd, d_in[10], FF, DM, 64);
    P.ckv_ptr = (const __nv_bfloat16*)d_in[1];
    P.wuk_ptr = (const __nv_bfloat16*)d_in[3];
    make_map(fn, &P.outm, d_out, SEQ, DM, 16);
    P.out = (__nv_bfloat16*)d_out;
    cudaFuncSetAttribute(fused_kernel, cudaFuncAttributeMaxDynamicSharedMemorySize, SMEM_BYTES);
    fused_kernel<<<NCTA, 384, SMEM_BYTES>>>(P);
}
```

```cpp
#include <cuda_runtime.h>
#include <cuda_bf16.h>
#include <cuda.h>
#include <stdint.h>

namespace {

constexpr int SEQ = 2048, DM = 640, DC = 512, NH = 32, HD = 128, FF = 1728;
constexpr int NSLOT = 7, SLOT = 32768;
constexpr int NCTA = 132;
#define PINGPONG 1
#define SIGMA 1
#define KVORDER 0x1023
#define KVSPLIT 1
#define LNSTAG 1
#define EARLYPF 1
#define EARLYSEND 1
#define FENCE_EACH 1
#define LATEST 1
#define LASTRD 7
#define LASTN 2
#define EFMASK 13
#define SPLITJ 8
constexpr uint32_t DESC_HI = (1024u >> 4) | (1u << 30);
constexpr int SMEM_BYTES = NSLOT * SLOT + 3072;

constexpr int BAR_FULL = 0, BAR_EMPTY = 64, BAR_SIG = 128  , BAR_DEP = 320  , MISC_OFF = 512;

constexpr int F_EXIT = 0, F_LN = 1, F_MOD = 2, F_MODP = 3, F_KV = 4  , F_CTX = 36  , F_NUM = 548;

__device__ __align__(1024) __nv_bfloat16 g_xn[SEQ * DM];
__device__ __align__(1024) __nv_bfloat16 g_kv[NH * 16 * 2 * 128 * 128];
__device__ __align__(1024) __nv_bfloat16 g_ctx[NH * SEQ * HD];
__device__ __align__(16) float g_r[SEQ];
__device__ __align__(16) float g_ypart[27 * 8 * DM];
__device__ uint32_t g_flags[F_NUM * 8];

struct TrueT { static constexpr bool value = true; };
struct FalseT { static constexpr bool value = false; };

struct Params {
    CUtensorMap ckv, wuk, wuv, xn, wq, kv, ctx, wo, wg, wu, wd, outm;
    const __nv_bfloat16 *x, *wr, *ckv_ptr, *wuk_ptr;
    __nv_bfloat16* out;
};

__device__ __forceinline__ uint32_t smem_u32(const void* p) { return (uint32_t)__cvta_generic_to_shared(p); }
__device__ __forceinline__ void mbar_init(uint32_t bar, uint32_t cnt) {
    asm volatile("mbarrier.init.shared::cta.b64 [%0], %1;" ::"r"(bar), "r"(cnt) : "memory");
}
__device__ __forceinline__ void mbar_expect_tx(uint32_t bar, uint32_t bytes) {
    asm volatile("mbarrier.arrive.expect_tx.shared::cta.b64 _, [%0], %1;" ::"r"(bar), "r"(bytes) : "memory");
}
__device__ __forceinline__ void mbar_arrive(uint32_t bar) {
    asm volatile("mbarrier.arrive.shared::cta.b64 _, [%0];" ::"r"(bar) : "memory");
}
__device__ __forceinline__ uint32_t mapa(uint32_t addr, uint32_t cta) {
    uint32_t r;
    asm("mapa.shared::cluster.u32 %0, %1, %2;" : "=r"(r) : "r"(addr), "r"(cta));
    return r;
}
__device__ __forceinline__ void mbar_wait(uint32_t bar, uint32_t parity) {
    asm volatile(
        "{\n.reg .pred p;\n.reg .b32 c;\n"
        "mov.b32 c, 0;\n"
        "WLOOP:\n"
        "mbarrier.try_wait.parity.shared::cta.b64 p, [%0], %1;\n"
        "@p bra.uni WDONE;\n"
        "add.u32 c, c, 1;\n"
        "setp.lt.u32 p, c, 0x400000;\n"
        "@p bra.uni WLOOP;\n"
        "trap;\n"
        "WDONE:\n}\n" ::"r"(bar), "r"(parity) : "memory");
}
__device__ __forceinline__ void mbar_wait_sleep(uint32_t bar, uint32_t parity) {
    asm volatile(
        "{\n.reg .pred p;\n.reg .b32 c;\n"
        "mov.b32 c, 0;\n"
        "WLOOP:\n"
        "mbarrier.try_wait.parity.shared::cta.b64 p, [%0], %1, 20000;\n"
        "@p bra.uni WDONE;\n"
        "add.u32 c, c, 1;\n"
        "setp.lt.u32 p, c, 0x40000;\n"
        "@p bra.uni WLOOP;\n"
        "trap;\n"
        "WDONE:\n}\n" ::"r"(bar), "r"(parity) : "memory");
}
__device__ __forceinline__ void tma_load(uint32_t dst, const CUtensorMap* m, int c0, int c1, uint32_t bar) {
    asm volatile("cp.async.bulk.tensor.2d.shared::cluster.global.mbarrier::complete_tx::bytes [%0], [%1, {%3, %4}], [%2];"
                 ::"r"(dst), "l"(m), "r"(bar), "r"(c0), "r"(c1) : "memory");
}
#define ELECT "{\n.reg .pred e;\nelect.sync _|e, 0xffffffff;\n@e "
__device__ __forceinline__ void w_expect_tx(uint32_t bar, uint32_t bytes) {
    asm volatile(ELECT "mbarrier.arrive.expect_tx.shared::cta.b64 _, [%0], %1;\n}\n" ::"r"(bar), "r"(bytes) : "memory");
}
__device__ __forceinline__ void w_tma_load(uint32_t dst, const CUtensorMap* m, int c0, int c1, uint32_t bar) {
    asm volatile(ELECT "cp.async.bulk.tensor.2d.shared::cluster.global.mbarrier::complete_tx::bytes [%0], [%1, {%3, %4}], [%2];\n}\n"
                 ::"r"(dst), "l"(m), "r"(bar), "r"(c0), "r"(c1) : "memory");
}
__device__ __forceinline__ void w_tma_load_mc(uint32_t dst, const CUtensorMap* m, int c0, int c1, uint32_t bar) {
    asm volatile(ELECT "cp.async.bulk.tensor.2d.shared::cluster.global.mbarrier::complete_tx::bytes.multicast::cluster [%0], [%1, {%3, %4}], [%2], %5;\n}\n"
                 ::"r"(dst), "l"(m), "r"(bar), "r"(c0), "r"(c1), "h"((uint16_t)3) : "memory");
}
__device__ __forceinline__ void w_tma_prefetch(const CUtensorMap* m, int c0, int c1) {
    asm volatile(ELECT "cp.async.bulk.prefetch.tensor.2d.L2.global [%0, {%1, %2}];\n}\n" ::"l"(m), "r"(c0), "r"(c1) : "memory");
}
__device__ __forceinline__ uint64_t policy_evict_first() {
    uint64_t p;
    asm("createpolicy.fractional.L2::evict_first.b64 %0, 1.0;" : "=l"(p));
    return p;
}
__device__ __forceinline__ void w_tma_load_mc_last(uint32_t dst, const CUtensorMap* m, int c0, int c1, uint32_t bar) {
    asm volatile(ELECT "cp.async.bulk.tensor.2d.shared::cluster.global.mbarrier::complete_tx::bytes.multicast::cluster.L2::cache_hint [%0], [%1, {%3, %4}], [%2], %5, %6;\n}\n"
                 ::"r"(dst), "l"(m), "r"(bar), "r"(c0), "r"(c1), "h"((uint16_t)3), "l"(policy_evict_first()) : "memory");
}
__device__ __forceinline__ void tma_load_stream(uint32_t dst, const CUtensorMap* m, int c0, int c1, uint32_t bar) {
    asm volatile("cp.async.bulk.tensor.2d.shared::cluster.global.mbarrier::complete_tx::bytes.L2::cache_hint [%0], [%1, {%3, %4}], [%2], %5;"
                 ::"r"(dst), "l"(m), "r"(bar), "r"(c0), "r"(c1), "l"(policy_evict_first()) : "memory");
}
__device__ __forceinline__ uint4 ldg_stream(const void* p) {
    uint4 v;
    asm volatile("ld.global.nc.L2::cache_hint.v4.b32 {%0, %1, %2, %3}, [%4], %5;" : "=r"(v.x), "=r"(v.y), "=r"(v.z), "=r"(v.w) : "l"(p), "l"(policy_evict_first()));
    return v;
}
__device__ __forceinline__ void prefetch_map(const CUtensorMap* m) {
    asm volatile("prefetch.tensormap [%0];" ::"l"(m) : "memory");
}
__device__ __forceinline__ void cluster_arrive() { asm volatile("barrier.cluster.arrive.relaxed.aligned;" ::: "memory"); }
__device__ __forceinline__ void cluster_wait() { asm volatile("barrier.cluster.wait.aligned;" ::: "memory"); }
__device__ __forceinline__ void named_sync(int id, int n) { asm volatile("bar.sync %0, %1;" ::"r"(id), "r"(n) : "memory"); }
__device__ __forceinline__ void named_arrive(int id, int n) { asm volatile("bar.arrive %0, %1;" ::"r"(id), "r"(n) : "memory"); }

__device__ __forceinline__ void flag_add(int f) {
    asm volatile("fence.acq_rel.gpu;\nred.relaxed.gpu.global.add.u32 [%0], 1;" ::"l"(g_flags + f * 8) : "memory");
}
template <int SLEEP>
__device__ __forceinline__ void flag_wait(int f, uint32_t target) {
    asm volatile(
        "{\n.reg .pred p;\n.reg .b32 c, v;\n"
        "mov.b32 c, 0;\n"
        "FLOOP:\n"
        "ld.acquire.gpu.global.u32 v, [%0];\n"
        "sub.u32 v, v, %1;\n"
        "setp.ge.s32 p, v, 0;\n"
        "@p bra FDONE;\n"
        "nanosleep.u32 %2;\n"
        "add.u32 c, c, 1;\n"
        "setp.lt.u32 p, c, 0x400000;\n"
        "@p bra FLOOP;\n"
        "trap;\n"
        "FDONE:\n}\n" ::"l"(g_flags + f * 8), "r"(target), "n"(SLEEP) : "memory");
}
__device__ __forceinline__ uint32_t read_epoch() {
    uint32_t e;
    asm volatile("ld.relaxed.gpu.global.u32 %0, [%1];" : "=r"(e) : "l"(g_flags + F_EXIT * 8) : "memory");
    return e / NCTA;
}
__device__ __forceinline__ void fence_proxy_async() { asm volatile("fence.proxy.async;" ::: "memory"); }

__device__ __forceinline__ void wgmma_fence() { asm volatile("wgmma.fence.sync.aligned;" ::: "memory"); }
__device__ __forceinline__ void wgmma_commit() { asm volatile("wgmma.commit_group.sync.aligned;" ::: "memory"); }
template <int N>
__device__ __forceinline__ void wgmma_wait() { asm volatile("wgmma.wait_group.sync.aligned %0;" ::"n"(N) : "memory"); }
template <int N>
__device__ __forceinline__ void fence_regs(float (&d)[N]) {
#pragma unroll
    for (int i = 0; i < N; i++) asm volatile("" : "+f"(d[i])::"memory");
}
template <int N>
__device__ __forceinline__ void fence_regs(uint32_t (&d)[N]) {
#pragma unroll
    for (int i = 0; i < N; i++) asm volatile("" : "+r"(d[i])::"memory");
}

template <int TA, int TB>
__device__ __forceinline__ void wgmma_ss_n128(float (&d)[64], uint32_t alo, uint32_t blo, int scale_d) {
    asm volatile("{\n.reg .pred p;\n.reg .b64 da, db;\nsetp.ne.b32 p, %66, 0;\n"
        "mov.b64 da, {%64, %69};\nmov.b64 db, {%65, %69};\n"
        "wgmma.mma_async.sync.aligned.m64n128k16.f32.bf16.bf16 "
        "{%0, %1, %2, %3, %4, %5, %6, %7, %8, %9, %10, %11, %12, %13, %14, %15, %16, %17, %18, %19, %20, %21, %22, %23, %24, %25, %26, %27, %28, %29, %30, %31, %32, %33, %34, %35, %36, %37, %38, %39, %40, %41, %42, %43, %44, %45, %46, %47, %48, %49, %50, %51, %52, %53, %54, %55, %56, %57, %58, %59, %60, %61, %62, %63}, da, db, p, 1, 1, %67, %68;\n}\n"
        :
          "+f"(d[0]), "+f"(d[1]), "+f"(d[2]), "+f"(d[3]), "+f"(d[4]), "+f"(d[5]), "+f"(d[6]), "+f"(d[7]),
          "+f"(d[8]), "+f"(d[9]), "+f"(d[10]), "+f"(d[11]), "+f"(d[12]), "+f"(d[13]), "+f"(d[14]), "+f"(d[15]),
          "+f"(d[16]), "+f"(d[17]), "+f"(d[18]), "+f"(d[19]), "+f"(d[20]), "+f"(d[21]), "+f"(d[22]), "+f"(d[23]),
          "+f"(d[24]), "+f"(d[25]), "+f"(d[26]), "+f"(d[27]), "+f"(d[28]), "+f"(d[29]), "+f"(d[30]), "+f"(d[31]),
          "+f"(d[32]), "+f"(d[33]), "+f"(d[34]), "+f"(d[35]), "+f"(d[36]), "+f"(d[37]), "+f"(d[38]), "+f"(d[39]),
          "+f"(d[40]), "+f"(d[41]), "+f"(d[42]), "+f"(d[43]), "+f"(d[44]), "+f"(d[45]), "+f"(d[46]), "+f"(d[47]),
          "+f"(d[48]), "+f"(d[49]), "+f"(d[50]), "+f"(d[51]), "+f"(d[52]), "+f"(d[53]), "+f"(d[54]), "+f"(d[55]),
          "+f"(d[56]), "+f"(d[57]), "+f"(d[58]), "+f"(d[59]), "+f"(d[60]), "+f"(d[61]), "+f"(d[62]), "+f"(d[63])
        : "r"(alo), "r"(blo), "r"(scale_d), "n"(TA), "n"(TB), "r"(DESC_HI));
}
template <int TA, int TB>
__device__ __forceinline__ void wgmma_ss_n192(float (&d)[96], uint32_t alo, uint32_t blo, int scale_d) {
    asm volatile("{\n.reg .pred p;\n.reg .b64 da, db;\nsetp.ne.b32 p, %98, 0;\n"
        "mov.b64 da, {%96, %101};\nmov.b64 db, {%97, %101};\n"
        "wgmma.mma_async.sync.aligned.m64n192k16.f32.bf16.bf16 "
        "{%0, %1, %2, %3, %4, %5, %6, %7, %8, %9, %10, %11, %12, %13, %14, %15, %16, %17, %18, %19, %20, %21, %22, %23, %24, %25, %26, %27, %28, %29, %30, %31, %32, %33, %34, %35, %36, %37, %38, %39, %40, %41, %42, %43, %44, %45, %46, %47, %48, %49, %50, %51, %52, %53, %54, %55, %56, %57, %58, %59, %60, %61, %62, %63, %64, %65, %66, %67, %68, %69, %70, %71, %72, %73, %74, %75, %76, %77, %78, %79, %80, %81, %82, %83, %84, %85, %86, %87, %88, %89, %90, %91, %92, %93, %94, %95}, da, db, p, 1, 1, %99, %100;\n}\n"
        :
          "+f"(d[0]), "+f"(d[1]), "+f"(d[2]), "+f"(d[3]), "+f"(d[4]), "+f"(d[5]), "+f"(d[6]), "+f"(d[7]),
          "+f"(d[8]), "+f"(d[9]), "+f"(d[10]), "+f"(d[11]), "+f"(d[12]), "+f"(d[13]), "+f"(d[14]), "+f"(d[15]),
          "+f"(d[16]), "+f"(d[17]), "+f"(d[18]), "+f"(d[19]), "+f"(d[20]), "+f"(d[21]), "+f"(d[22]), "+f"(d[23]),
          "+f"(d[24]), "+f"(d[25]), "+f"(d[26]), "+f"(d[27]), "+f"(d[28]), "+f"(d[29]), "+f"(d[30]), "+f"(d[31]),
          "+f"(d[32]), "+f"(d[33]), "+f"(d[34]), "+f"(d[35]), "+f"(d[36]), "+f"(d[37]), "+f"(d[38]), "+f"(d[39]),
          "+f"(d[40]), "+f"(d[41]), "+f"(d[42]), "+f"(d[43]), "+f"(d[44]), "+f"(d[45]), "+f"(d[46]), "+f"(d[47]),
          "+f"(d[48]), "+f"(d[49]), "+f"(d[50]), "+f"(d[51]), "+f"(d[52]), "+f"(d[53]), "+f"(d[54]), "+f"(d[55]),
          "+f"(d[56]), "+f"(d[57]), "+f"(d[58]), "+f"(d[59]), "+f"(d[60]), "+f"(d[61]), "+f"(d[62]), "+f"(d[63]),
          "+f"(d[64]), "+f"(d[65]), "+f"(d[66]), "+f"(d[67]), "+f"(d[68]), "+f"(d[69]), "+f"(d[70]), "+f"(d[71]),
          "+f"(d[72]), "+f"(d[73]), "+f"(d[74]), "+f"(d[75]), "+f"(d[76]), "+f"(d[77]), "+f"(d[78]), "+f"(d[79]),
          "+f"(d[80]), "+f"(d[81]), "+f"(d[82]), "+f"(d[83]), "+f"(d[84]), "+f"(d[85]), "+f"(d[86]), "+f"(d[87]),
          "+f"(d[88]), "+f"(d[89]), "+f"(d[90]), "+f"(d[91]), "+f"(d[92]), "+f"(d[93]), "+f"(d[94]), "+f"(d[95])
        : "r"(alo), "r"(blo), "r"(scale_d), "n"(TA), "n"(TB), "r"(DESC_HI));
}
template <int TB>
__device__ __forceinline__ void wgmma_rs_n128(float (&d)[64], uint32_t a0, uint32_t a1, uint32_t a2, uint32_t a3, uint32_t blo, int scale_d) {
    asm volatile("{\n.reg .pred p;\n.reg .b64 db;\nsetp.ne.b32 p, %69, 0;\n"
        "mov.b64 db, {%68, %71};\n"
        "wgmma.mma_async.sync.aligned.m64n128k16.f32.bf16.bf16 "
        "{%0, %1, %2, %3, %4, %5, %6, %7, %8, %9, %10, %11, %12, %13, %14, %15, %16, %17, %18, %19, %20, %21, %22, %23, %24, %25, %26, %27, %28, %29, %30, %31, %32, %33, %34, %35, %36, %37, %38, %39, %40, %41, %42, %43, %44, %45, %46, %47, %48, %49, %50, %51, %52, %53, %54, %55, %56, %57, %58, %59, %60, %61, %62, %63}, {%64, %65, %66, %67}, db, p, 1, 1, %70;\n}\n"
        :
          "+f"(d[0]), "+f"(d[1]), "+f"(d[2]), "+f"(d[3]), "+f"(d[4]), "+f"(d[5]), "+f"(d[6]), "+f"(d[7]),
          "+f"(d[8]), "+f"(d[9]), "+f"(d[10]), "+f"(d[11]), "+f"(d[12]), "+f"(d[13]), "+f"(d[14]), "+f"(d[15]),
          "+f"(d[16]), "+f"(d[17]), "+f"(d[18]), "+f"(d[19]), "+f"(d[20]), "+f"(d[21]), "+f"(d[22]), "+f"(d[23]),
          "+f"(d[24]), "+f"(d[25]), "+f"(d[26]), "+f"(d[27]), "+f"(d[28]), "+f"(d[29]), "+f"(d[30]), "+f"(d[31]),
          "+f"(d[32]), "+f"(d[33]), "+f"(d[34]), "+f"(d[35]), "+f"(d[36]), "+f"(d[37]), "+f"(d[38]), "+f"(d[39]),
          "+f"(d[40]), "+f"(d[41]), "+f"(d[42]), "+f"(d[43]), "+f"(d[44]), "+f"(d[45]), "+f"(d[46]), "+f"(d[47]),
          "+f"(d[48]), "+f"(d[49]), "+f"(d[50]), "+f"(d[51]), "+f"(d[52]), "+f"(d[53]), "+f"(d[54]), "+f"(d[55]),
          "+f"(d[56]), "+f"(d[57]), "+f"(d[58]), "+f"(d[59]), "+f"(d[60]), "+f"(d[61]), "+f"(d[62]), "+f"(d[63])
        : "r"(a0), "r"(a1), "r"(a2), "r"(a3), "r"(blo), "r"(scale_d), "n"(TB), "r"(DESC_HI));
}
template <int TB>
__device__ __forceinline__ void wgmma_rs_n128_z(float (&d)[64], uint32_t a0, uint32_t a1, uint32_t a2, uint32_t a3, uint32_t blo) {
    asm volatile("{\n.reg .pred p;\n.reg .b64 db;\nsetp.ne.b32 p, %69, 0;\n"
        "mov.b64 db, {%68, %71};\n"
        "wgmma.mma_async.sync.aligned.m64n128k16.f32.bf16.bf16 "
        "{%0, %1, %2, %3, %4, %5, %6, %7, %8, %9, %10, %11, %12, %13, %14, %15, %16, %17, %18, %19, %20, %21, %22, %23, %24, %25, %26, %27, %28, %29, %30, %31, %32, %33, %34, %35, %36, %37, %38, %39, %40, %41, %42, %43, %44, %45, %46, %47, %48, %49, %50, %51, %52, %53, %54, %55, %56, %57, %58, %59, %60, %61, %62, %63}, {%64, %65, %66, %67}, db, p, 1, 1, %70;\n}\n"
        :
          "=f"(d[0]), "=f"(d[1]), "=f"(d[2]), "=f"(d[3]), "=f"(d[4]), "=f"(d[5]), "=f"(d[6]), "=f"(d[7]),
          "=f"(d[8]), "=f"(d[9]), "=f"(d[10]), "=f"(d[11]), "=f"(d[12]), "=f"(d[13]), "=f"(d[14]), "=f"(d[15]),
          "=f"(d[16]), "=f"(d[17]), "=f"(d[18]), "=f"(d[19]), "=f"(d[20]), "=f"(d[21]), "=f"(d[22]), "=f"(d[23]),
          "=f"(d[24]), "=f"(d[25]), "=f"(d[26]), "=f"(d[27]), "=f"(d[28]), "=f"(d[29]), "=f"(d[30]), "=f"(d[31]),
          "=f"(d[32]), "=f"(d[33]), "=f"(d[34]), "=f"(d[35]), "=f"(d[36]), "=f"(d[37]), "=f"(d[38]), "=f"(d[39]),
          "=f"(d[40]), "=f"(d[41]), "=f"(d[42]), "=f"(d[43]), "=f"(d[44]), "=f"(d[45]), "=f"(d[46]), "=f"(d[47]),
          "=f"(d[48]), "=f"(d[49]), "=f"(d[50]), "=f"(d[51]), "=f"(d[52]), "=f"(d[53]), "=f"(d[54]), "=f"(d[55]),
          "=f"(d[56]), "=f"(d[57]), "=f"(d[58]), "=f"(d[59]), "=f"(d[60]), "=f"(d[61]), "=f"(d[62]), "=f"(d[63])
        : "r"(a0), "r"(a1), "r"(a2), "r"(a3), "r"(blo), "n"(0), "n"(TB), "r"(DESC_HI));
}
template <int TA, int TB>
__device__ __forceinline__ void wgmma_ss_n128_z(float (&d)[64], uint32_t alo, uint32_t blo) {
    asm volatile("{\n.reg .pred p;\n.reg .b64 da, db;\nsetp.ne.b32 p, %66, 0;\n"
        "mov.b64 da, {%64, %69};\nmov.b64 db, {%65, %69};\n"
        "wgmma.mma_async.sync.aligned.m64n128k16.f32.bf16.bf16 "
        "{%0, %1, %2, %3, %4, %5, %6, %7, %8, %9, %10, %11, %12, %13, %14, %15, %16, %17, %18, %19, %20, %21, %22, %23, %24, %25, %26, %27, %28, %29, %30, %31, %32, %33, %34, %35, %36, %37, %38, %39, %40, %41, %42, %43, %44, %45, %46, %47, %48, %49, %50, %51, %52, %53, %54, %55, %56, %57, %58, %59, %60, %61, %62, %63}, da, db, p, 1, 1, %67, %68;\n}\n"
        :
          "=f"(d[0]), "=f"(d[1]), "=f"(d[2]), "=f"(d[3]), "=f"(d[4]), "=f"(d[5]), "=f"(d[6]), "=f"(d[7]),
          "=f"(d[8]), "=f"(d[9]), "=f"(d[10]), "=f"(d[11]), "=f"(d[12]), "=f"(d[13]), "=f"(d[14]), "=f"(d[15]),
          "=f"(d[16]), "=f"(d[17]), "=f"(d[18]), "=f"(d[19]), "=f"(d[20]), "=f"(d[21]), "=f"(d[22]), "=f"(d[23]),
          "=f"(d[24]), "=f"(d[25]), "=f"(d[26]), "=f"(d[27]), "=f"(d[28]), "=f"(d[29]), "=f"(d[30]), "=f"(d[31]),
          "=f"(d[32]), "=f"(d[33]), "=f"(d[34]), "=f"(d[35]), "=f"(d[36]), "=f"(d[37]), "=f"(d[38]), "=f"(d[39]),
          "=f"(d[40]), "=f"(d[41]), "=f"(d[42]), "=f"(d[43]), "=f"(d[44]), "=f"(d[45]), "=f"(d[46]), "=f"(d[47]),
          "=f"(d[48]), "=f"(d[49]), "=f"(d[50]), "=f"(d[51]), "=f"(d[52]), "=f"(d[53]), "=f"(d[54]), "=f"(d[55]),
          "=f"(d[56]), "=f"(d[57]), "=f"(d[58]), "=f"(d[59]), "=f"(d[60]), "=f"(d[61]), "=f"(d[62]), "=f"(d[63])
        : "r"(alo), "r"(blo), "n"(0), "n"(TA), "n"(TB), "r"(DESC_HI));
}

__device__ __forceinline__ uint32_t pack_bf16(float lo, float hi) {
    uint32_t r;
    asm("cvt.rn.bf16x2.f32 %0, %1, %2;" : "=r"(r) : "f"(hi), "f"(lo));
    return r;
}
__device__ __forceinline__ uint32_t add_bf16x2(uint32_t a, uint32_t b) {
    uint32_t r;
    asm("add.rn.bf16x2 %0, %1, %2;" : "=r"(r) : "r"(a), "r"(b));
    return r;
}
__device__ __forceinline__ float bf_lo(uint32_t v) { return __uint_as_float(v << 16); }
__device__ __forceinline__ float bf_hi(uint32_t v) { return __uint_as_float(v & 0xffff0000u); }
__device__ __forceinline__ float round_bf16(float v) { return __bfloat162float(__float2bfloat16_rn(v)); }
__device__ __forceinline__ float ex2(float x) {
    float y;
    asm("ex2.approx.ftz.f32 %0, %1;" : "=f"(y) : "f"(x));
    return y;
}
__device__ __forceinline__ float rcp(float x) {
    float y;
    asm("rcp.approx.ftz.f32 %0, %1;" : "=f"(y) : "f"(x));
    return y;
}
__device__ __forceinline__ void stg128(void* p, uint32_t a, uint32_t b, uint32_t c, uint32_t d) {
    asm volatile("st.global.v4.b32 [%0], {%1, %2, %3, %4};" ::"l"(p), "r"(a), "r"(b), "r"(c), "r"(d) : "memory");
}
__device__ __forceinline__ void stg128p(void* p, uint32_t a, uint32_t b, uint32_t c, uint32_t d, uint64_t pol) {
    asm volatile("st.global.L2::cache_hint.v4.b32 [%0], {%1, %2, %3, %4}, %5;" ::"l"(p), "r"(a), "r"(b), "r"(c), "r"(d), "l"(pol) : "memory");
}
__device__ __forceinline__ uint64_t policy_sel(bool first) {
    uint64_t p;
    asm("createpolicy.fractional.L2::evict_normal.b64 %0, 1.0;" : "=l"(p));
    return first ? policy_evict_first() : p;
}
__device__ __forceinline__ int perm_row(int t) { return (t & ~255) | (((0x78 >> (((t >> 6) & 3) * 2)) & 3) << 6) | (t & 63); }
__device__ __forceinline__ int unperm_row(int t) { return (t & ~255) | (((0x9C >> (((t >> 6) & 3) * 2)) & 3) << 6) | (t & 63); }

#define PROF(i)
#define PROFG(i)
#define PROFDUMP()
#define TR(i)
#define BP(r, i)
#define LP(i)

template <int I>
__device__ __forceinline__ void store_chunk(const float (&a)[64], __nv_bfloat16* row0, __nv_bfloat16* row1, float s0, float s1, uint64_t pol) {
    stg128p(row0 + 32 * I, pack_bf16(a[16 * I + 0] * s0, a[16 * I + 1] * s0), pack_bf16(a[16 * I + 4] * s0, a[16 * I + 5] * s0),
           pack_bf16(a[16 * I + 8] * s0, a[16 * I + 9] * s0), pack_bf16(a[16 * I + 12] * s0, a[16 * I + 13] * s0), pol);
    stg128p(row1 + 32 * I, pack_bf16(a[16 * I + 2] * s1, a[16 * I + 3] * s1), pack_bf16(a[16 * I + 6] * s1, a[16 * I + 7] * s1),
           pack_bf16(a[16 * I + 10] * s1, a[16 * I + 11] * s1), pack_bf16(a[16 * I + 14] * s1, a[16 * I + 15] * s1), pol);
}
template <int I>
struct IntT { static constexpr int value = I; };
template <class F>
__device__ __forceinline__ void for4(F f) { f(IntT<0>{}); f(IntT<1>{}); f(IntT<2>{}); f(IntT<3>{}); }

struct Prod {
    uint32_t smem, bars;
    uint32_t bo, par;
    uint32_t dst, fb;
    __device__ __forceinline__ void acquire(uint32_t o, uint32_t parity, uint32_t bytes) {
        mbar_wait(bars + BAR_EMPTY + o, parity);
        fb = bars + BAR_FULL + o;
        dst = smem + o * (SLOT / 8);
        w_expect_tx(fb, bytes);
    }
    __device__ __forceinline__ void next(uint32_t bytes) {
        acquire(bo, par, bytes);
        const bool wrap = bo == (NSLOT - 1) * 8;
        bo = wrap ? 0u : bo + 8;
        par ^= wrap ? 1u : 0u;
    }
};

__device__ __forceinline__ int item_p(int ca, int rd) {
    const int v = (rd & 1) ? (ca + 4) & 7 : ca;
    return (rd & 2) ? 7 - v : v;
}
__device__ __forceinline__ int kv_round(int i) { return (KVORDER >> (4 * i)) & 3; }
__device__ __forceinline__ int slot_a(int i) { return (0x5310 >> (4 * i)) & 15; }
__device__ __forceinline__ int slot_w(int m) { return (0x264 >> (4 * m)) & 15; }

__device__ __forceinline__ void producer(const Params& P, uint32_t smem, uint32_t bars, int ca, int cb, int rank) {
    Prod pr{smem, bars, 0u, 0u, 0u, 0u};
    {
        int m = 0;
        uint32_t lap = 1;
#pragma unroll 1
        for (int u = 0; u < 32; u++) {
            if (u >= 3) {
                const int v = (u == 3) ? 3 + ca : u + 7;
                if (v < 32 && (u == 3 || (v & 7) == ca)) w_tma_prefetch((v & 4) ? &P.wuv : &P.wuk, (cb + 8 * kv_round(v >> 3)) * 128 + rank * 64, (v & 3) * 128);
                if (u == 24) {
                    w_tma_prefetch(&P.wq, cb * 128 + rank * 64, ca * 64);
                    if (ca < 2) w_tma_prefetch(&P.wq, cb * 128 + rank * 64, (ca + 8) * 64);
                }
            }
            pr.acquire(slot_w(m) * 8, lap ^ (m >> 1), SLOT);
            lap ^= m >> 1;
            m = (m == 2) ? 0 : m + 1;
            TR(1 + u);
            w_tma_load_mc(pr.dst + rank * 16384, (u & 4) ? &P.wuv : &P.wuk, (cb + 8 * kv_round(u >> 3)) * 128 + rank * 64, (u & 3) * 128, pr.fb);
            if (u < 3) {
                pr.acquire(slot_a(u + 1) * 8, 1, SLOT);
                w_tma_load(pr.dst, &P.ckv, u * 128 + 128, (2 * ca + rank) * 128, pr.fb);
                w_tma_load(pr.dst + 16384, &P.ckv, u * 128 + 192, (2 * ca + rank) * 128, pr.fb);
            }
        }
    }
    PROF(1);
    mbar_wait(bars + BAR_DEP, 0);
#pragma unroll 1
    for (int rd = 0; rd < 4; rd++) {
        const int h = 8 * rd + cb, p = item_p(ca, rd);
#pragma unroll 1
        for (int ks = 0; ks < 10; ks++) {
            pr.next(SLOT);
            w_tma_load_mc(pr.dst + 16384 + rank * 8192, &P.wq, h * 128 + rank * 64, ks * 64, pr.fb);
            w_tma_load(pr.dst, &P.xn, ks * 64, 256 * p + 128 * rank, pr.fb);
        }
        PROF(8 + rd * 4);
        mbar_wait(bars + BAR_DEP + (1 + rd) * 8, 0);
        const int last = 4 * p + 3, top = h * 32 + last;
#pragma unroll 1
        for (int i = 0; i <= last; i++) {
            const int t = (i == 0) ? top - 1 : (i == last) ? h * 32 + 1 : (i & 1) ? top - 2 - i : top + 2 - i;
            pr.next(SLOT);
            const bool lastrd = (rd == 0) ? ((LASTRD & 1) && ca >= 8 - LASTN) : (rd == 1) ? ((LASTRD & 2) && (ca & 3) >= 4 - LASTN) : (rd == 2) ? ((LASTRD & 4) && (ca == 3 || (ca < 3 && (t & 31) >= 4 * p))) : (LASTRD & 8) != 0;
            if (lastrd) w_tma_load_mc_last(pr.dst + rank * 16384, &P.kv, rank * 64, t * 128, pr.fb);
            else w_tma_load_mc(pr.dst + rank * 16384, &P.kv, rank * 64, t * 128, pr.fb);
            if (i == 2) {
                if (rd < 3) {
                    w_tma_prefetch(&P.wq, (h + 8) * 128 + rank * 64, ca * 64);
                    if (ca < 2) w_tma_prefetch(&P.wq, (h + 8) * 128 + rank * 64, (ca + 8) * 64);
                } else {
#pragma unroll 1
                    for (int j = 0; j < 10; j++) {
                        const int tt = ca + (j >= 5 ? 8 : 0);
                        w_tma_prefetch(&P.wo, 320 * (cb & 1) + 64 * (j >= 5 ? j - 5 : j), (8 * (tt >> 2) + (cb & 6) + ((tt >> 1) & 1)) * 128 + (tt & 1) * 64 + rank * 32);
                    }
                }
            }
        }
        PROF(9 + rd * 4);
    }
    {
        const int n0 = 320 * (cb & 1), kg = cb >> 1;
#pragma unroll 1
        for (int t = 0; t < 16; t++) {
            const int h = 8 * (t >> 2) + 2 * kg + ((t >> 1) & 1), ks = t & 1;
            const int krow = h * 128 + ks * 64 + rank * 32;
            pr.next(SLOT);
            w_tma_load_mc(pr.dst + 16384 + rank * 8192, &P.wo, n0, krow, pr.fb);
            w_tma_load_mc(pr.dst + 16384 + rank * 8192 + 4096, &P.wo, n0 + 64, krow, pr.fb);
            mbar_wait(bars + BAR_DEP + (5 + (t >> 1)) * 8, 0);
            w_tma_load(pr.dst, &P.ctx, ks * 64, h * SEQ + 256 * ca + 128 * rank, pr.fb);
            pr.next(24576);
#pragma unroll
            for (int c = 0; c < 3; c++) w_tma_load_mc(pr.dst + rank * 12288 + c * 4096, &P.wo, n0 + 128 + 64 * c, krow, pr.fb);
        }
    }
}

struct Slot {
    uint32_t bo, dl, par;
};
struct Cons {
    uint32_t bars, rel;
    uint32_t dl0;
    uint32_t lane;
    Slot cur;
    __device__ __forceinline__ Slot slot(int s, uint32_t par) const { return Slot{(uint32_t)s * 8, dl0 + (uint32_t)s * (SLOT >> 4), par}; }
    __device__ __forceinline__ void wait(const Slot& s) const { mbar_wait(bars + BAR_FULL + s.bo, s.par); }
    __device__ __forceinline__ void release(uint32_t bo) const {
        asm volatile("{\n.reg .pred p;\nsetp.lt.u32 p, %1, 2;\n@p mbarrier.arrive.shared::cluster.b64 _, [%0];\n}\n" ::"r"(rel + bo), "r"(lane) : "memory");
    }
    __device__ __forceinline__ Slot next() {
        const Slot s = cur;
        const bool wrap = s.bo == (NSLOT - 1) * 8;
        cur.bo = wrap ? 0u : s.bo + 8;
        cur.dl = wrap ? dl0 : s.dl + (SLOT >> 4);
        cur.par = s.par ^ (wrap ? 1u : 0u);
        return s;
    }
};
__host__ __device__ constexpr uint32_t lbo(uint32_t bytes) { return (bytes >> 4) << 16; }

__device__ __forceinline__ float div640(float x) {
    const float q = x * (1.0f / DM);
    return fmaf(fmaf(-q, (float)DM, x), 1.0f / DM, q);
}
__device__ __forceinline__ float sqrt_approx(float x) {
    float y;
    asm("sqrt.approx.ftz.f32 %0, %1;" : "=f"(y) : "f"(x));
    return y;
}
struct LayerNorm {
    uint4 xv[5], wv[5];
    float mean, inv, r;
    static __device__ __forceinline__ float half_sum(float v) {
#pragma unroll
        for (int o = 8; o > 0; o >>= 1) v += __shfl_xor_sync(0xffffffffu, v, o);
        return v;
    }
    __device__ __forceinline__ void load(const __nv_bfloat16* x, const __nv_bfloat16* wr, int t, int l) {
#pragma unroll
        for (int i = 0; i < 5; i++) {
            xv[i] = ldg_stream(reinterpret_cast<const uint4*>(x + t * DM) + l + 16 * i);
            wv[i] = __ldg(reinterpret_cast<const uint4*>(wr) + l + 16 * i);
        }
    }
    __device__ __forceinline__ void stat1() {
        float a[4] = {0.f, 0.f, 0.f, 0.f};
#pragma unroll
        for (int i = 0; i < 20; i++) { const uint32_t u = (&xv[i >> 2].x)[i & 3]; a[i & 3] += bf_lo(u) + bf_hi(u); }
        mean = div640(half_sum((a[0] + a[1]) + (a[2] + a[3])));
        r = 0.f;
    }
    template <int H>
    __device__ __forceinline__ void stat2() {
        float a[4] = {r, 0.f, 0.f, 0.f};
#pragma unroll
        for (int i = H ? 12 : 0; i < (H ? 20 : 12); i++) {
            uint32_t u = (&xv[i >> 2].x)[i & 3];
            asm volatile("" : "+r"(u));
            const float d0 = bf_lo(u) - mean, d1 = bf_hi(u) - mean;
            a[i & 3] = fmaf(d0, d0, fmaf(d1, d1, a[i & 3]));
        }
        r = (a[0] + a[1]) + (a[2] + a[3]);
        if (H) {
            inv = rcp(round_bf16(sqrt_approx(round_bf16(round_bf16(div640(half_sum(r))) + 1e-5f))));
            r = 0.f;
        }
    }
    template <int I>
    __device__ __forceinline__ void piece(__nv_bfloat16* out, int t, int l) {
        const uint32_t nmb = pack_bf16(-mean, -mean);
        uint32_t o[4], z[4];
        float a[4];
#pragma unroll
        for (int j = 0; j < 4; j++) {
            const uint32_t u = (&xv[I].x)[j], w = (&wv[I].x)[j];
            const uint32_t d = add_bf16x2(u, nmb);
            o[j] = pack_bf16(bf_lo(d) * inv, bf_hi(d) * inv);
            z[j] = add_bf16x2(u, o[j]);
            a[j] = fmaf(bf_hi(o[j]), bf_hi(w), bf_lo(o[j]) * bf_lo(w));
        }
        r += (a[0] + a[1]) + (a[2] + a[3]);
        stg128(g_xn + perm_row(t) * DM + 8 * (l + 16 * I), o[0], o[1], o[2], o[3]);
        stg128p(out + t * DM + 8 * (l + 16 * I), z[0], z[1], z[2], z[3], policy_sel(EFMASK & 1));
        if (I == 4) {
            r = half_sum(r);
            if (l == 0) g_r[t] = round_bf16(r);
        }
    }
};

constexpr float SM_SCALE = 0.08838834764831845f * 1.4426950408889634f;

template <int J0, int J1>
__device__ __forceinline__ void exp_part(float (&s)[64], float n0, float n1, float& r0, float& r1) {
    float a1 = 0.f, b1 = 0.f;
#pragma unroll
    for (int j = J0; j < J1; j++) {
        s[4 * j + 0] = ex2(fmaf(s[4 * j + 0], SM_SCALE, n0));
        s[4 * j + 1] = ex2(fmaf(s[4 * j + 1], SM_SCALE, n0));
        s[4 * j + 2] = ex2(fmaf(s[4 * j + 2], SM_SCALE, n1));
        s[4 * j + 3] = ex2(fmaf(s[4 * j + 3], SM_SCALE, n1));
        r0 += s[4 * j + 0]; r1 += s[4 * j + 2];
        if (j == J0) { a1 = s[4 * j + 1]; b1 = s[4 * j + 3]; } else { a1 += s[4 * j + 1]; b1 += s[4 * j + 3]; }
    }
    r0 += a1;
    r1 += b1;
}
__device__ __forceinline__ void sched_barrier(float x, float y, uint32_t scratch) {
    asm volatile("{\n.reg .pred p;\nsetp.lt.f32 p, %0, 0f00000000;\n@p st.shared.f32 [%2], %1;\n}\n" ::"f"(x), "f"(y), "r"(scratch) : "memory");
}
__device__ __forceinline__ void pack_tile(const float (&s)[64], uint32_t (&p)[32]) {
#pragma unroll
    for (int i = 0; i < 32; i++) p[i] = pack_bf16(s[2 * i], s[2 * i + 1]);
}
template <bool ZERO>
__device__ __forceinline__ void gemm_rs(float (&d)[64], const uint32_t (&a)[32], uint32_t dl, int acc = 1) {
    const uint32_t b = dl + lbo(16384);
    if (ZERO) wgmma_rs_n128_z<1>(d, a[0], a[1], a[2], a[3], b);
#pragma unroll
    for (int k = ZERO ? 1 : 0; k < 8; k++) wgmma_rs_n128<1>(d, a[4 * k], a[4 * k + 1], a[4 * k + 2], a[4 * k + 3], b + k * 128, k ? 1 : acc);
}
template <int ZERO>
__device__ __forceinline__ void gemm_q(float (&d)[64], uint32_t dl, int role) {
    const uint32_t a = dl + role * 512 + lbo(16), b = dl + 1024 + lbo(8192);
    if (ZERO) wgmma_ss_n128_z<0, 1>(d, a, b);
#pragma unroll
    for (int k = ZERO ? 1 : 0; k < 4; k++) wgmma_ss_n128<0, 1>(d, a + k * 2, b + k * 128, 1);
}
template <bool KT, bool ZERO, int K0, int K1>
__device__ __forceinline__ void gemm_kv(float (&d)[64], uint32_t ckv, uint32_t wt, int wg) {
    if (KT) {
        const uint32_t a = wt + wg * 1024 + lbo(16), b = ckv + lbo(16);
        if (ZERO) wgmma_ss_n128_z<1, 0>(d, a, b);
#pragma unroll
        for (int k = ZERO ? 1 : K0; k < K1; k++) wgmma_ss_n128<1, 0>(d, a + k * 128, b + (k >> 2) * 1024 + (k & 3) * 2, 1);
    } else {
        const uint32_t a = ckv + wg * 512 + lbo(16), b = wt + lbo(16384);
        if (ZERO) wgmma_ss_n128_z<0, 1>(d, a, b);
#pragma unroll
        for (int k = ZERO ? 1 : K0; k < K1; k++) wgmma_ss_n128<0, 1>(d, a + (k >> 2) * 1024 + (k & 3) * 2, b + k * 128, 1);
    }
}
__device__ __forceinline__ void mma16816(float& d0, float& d1, float& d2, float& d3, uint32_t a0, uint32_t a1, uint32_t a2, uint32_t a3, uint32_t b0, uint32_t b1) {
    asm volatile("mma.sync.aligned.m16n8k16.row.col.f32.bf16.bf16.f32 {%0,%1,%2,%3}, {%4,%5,%6,%7}, {%8,%9}, {%0,%1,%2,%3};"
                 : "+f"(d0), "+f"(d1), "+f"(d2), "+f"(d3) : "r"(a0), "r"(a1), "r"(a2), "r"(a3), "r"(b0), "r"(b1));
}
__device__ __forceinline__ uint32_t ld_pair(const __nv_bfloat16* p) {
    const unsigned short* u = reinterpret_cast<const unsigned short*>(p);
    return (uint32_t)__ldcg(u) | ((uint32_t)__ldcg(u + 128) << 16);
}
__device__ __forceinline__ void attention_exact(float (&o)[64], const uint32_t (&qf)[32], float& l0, float& l1, int h, int nblk, int rr, int lane) {
    const int q = lane & 3, lr = lane >> 2;
    float m0 = -INFINITY, m1 = -INFINITY;
    l0 = 0.f; l1 = 0.f;
#pragma unroll
    for (int i = 0; i < 64; i++) o[i] = 0.f;
#pragma unroll 1
    for (int cidx = 0; cidx < nblk * 8; cidx++) {
        const int kc = cidx & 7;
        const __nv_bfloat16* kt = g_kv + (size_t)((h * 16 + (cidx >> 3)) * 2) * 16384;
        float sc[8];
#pragma unroll
        for (int i = 0; i < 8; i++) sc[i] = 0.f;
#pragma unroll
        for (int kk = 0; kk < 8; kk++)
#pragma unroll
            for (int nt = 0; nt < 2; nt++) {
                const __nv_bfloat16* b = kt + (16 * kk + 2 * q) * 128 + 16 * kc + 8 * nt + lr;
                mma16816(sc[4 * nt], sc[4 * nt + 1], sc[4 * nt + 2], sc[4 * nt + 3], qf[4 * kk], qf[4 * kk + 1], qf[4 * kk + 2], qf[4 * kk + 3],
                         ld_pair(b), ld_pair(b + 8 * 128));
            }
        const int lim = rr + ((nblk - 1) - (cidx >> 3)) * 128 - 32 * (kc >> 1) - 4 * (kc & 1);
#pragma unroll
        for (int i = 0; i < 8; i++)
            if (2 * (i >> 2) + (i & 1) > lim + 4 * (i & 2)) sc[i] = -INFINITY;
        float x0 = fmaxf(fmaxf(sc[0], sc[1]), fmaxf(sc[4], sc[5])), x1 = fmaxf(fmaxf(sc[2], sc[3]), fmaxf(sc[6], sc[7]));
        x0 = fmaxf(x0, __shfl_xor_sync(0xffffffffu, x0, 1)); x1 = fmaxf(x1, __shfl_xor_sync(0xffffffffu, x1, 1));
        x0 = fmaxf(x0, __shfl_xor_sync(0xffffffffu, x0, 2)); x1 = fmaxf(x1, __shfl_xor_sync(0xffffffffu, x1, 2));
        x0 = fmaxf(x0, m0); x1 = fmaxf(x1, m1);
        const float a0 = ex2((m0 - x0) * SM_SCALE), a1 = ex2((m1 - x1) * SM_SCALE);
        m0 = x0; m1 = x1;
#pragma unroll
        for (int i = 0; i < 8; i++) sc[i] = ex2((sc[i] - ((i & 2) ? m1 : m0)) * SM_SCALE);
        l0 = l0 * a0 + (sc[0] + sc[1]) + (sc[4] + sc[5]);
        l1 = l1 * a1 + (sc[2] + sc[3]) + (sc[6] + sc[7]);
        const uint32_t p0 = pack_bf16(sc[0], sc[1]), p1 = pack_bf16(sc[2], sc[3]), p2 = pack_bf16(sc[4], sc[5]), p3 = pack_bf16(sc[6], sc[7]);
        const __nv_bfloat16* vb = kt + 16384 + (16 * kc + 2 * q) * 128 + lr;
#pragma unroll
        for (int nt = 0; nt < 16; nt++) {
            o[4 * nt] *= a0; o[4 * nt + 1] *= a0; o[4 * nt + 2] *= a1; o[4 * nt + 3] *= a1;
            mma16816(o[4 * nt], o[4 * nt + 1], o[4 * nt + 2], o[4 * nt + 3], p0, p1, p2, p3, ld_pair(vb + 8 * nt), ld_pair(vb + 8 * nt + 8 * 128));
        }
    }
}

__device__ __forceinline__ void signal(uint32_t bars, int wg, int e, int lane) {
    __syncwarp();
    asm volatile("{\n.reg .pred p;\nsetp.eq.u32 p, %1, 0;\n@p mbarrier.arrive.shared::cta.b64 _, [%0];\n}\n" ::"r"(bars + BAR_SIG + (wg * 9 + e) * 8), "r"(lane) : "memory");
}

__device__ __forceinline__ void consumer(const Params& P, uint32_t smem, uint32_t bars, int ca, int cb, int rank, int wg) {
    const int lane = threadIdx.x & 31, w = (threadIdx.x >> 5) & 3, q = lane & 3, lr = lane >> 2;
    PROF(7);
    cluster_wait();
    Cons c{bars, mapa(bars + BAR_EMPTY, lane & 1), (smem & 0x3FFFF) >> 4, (uint32_t)lane, Slot{0u, (smem & 0x3FFFF) >> 4, 1u}};
    PROFG(180);
    PROF(1);
    float o[64], s[64];
    uint32_t pend;
    __nv_bfloat16* ep_ptr;
    int ep_step;
    {
        const int ln_t = blockIdx.x * 16 + wg * 8 + w * 2 + (lane >> 4);
        const int krow = 64 * wg + 16 * w + lr;
        const int vrow = 64 * wg + 32 * (w >> 1) + 8 * (lr >> 1) + 4 * (w & 1) + (lr & 1);
        ep_step = 2 * 128;
        int m = 0;
        uint32_t lap = 0;
        LayerNorm ln;
        auto step = [&](auto kt, auto kc, float (&d)[64], int hh) {
            const Slot sa = c.slot(slot_a(kc.value), 0), sw = c.slot(slot_w(m), lap ^ (m >> 1));
            lap ^= m >> 1;
            m = (m == 2) ? 0 : m + 1;
            TR(1 + (hh * 8 + (kt.value ? 0 : 4) + kc.value) * 2);
            if (kt.value && hh == 0) c.wait(sa);
            c.wait(sw);
            TR(2 + (hh * 8 + (kt.value ? 0 : 4) + kc.value) * 2);
            wgmma_fence();
            gemm_kv<kt.value, kc.value == 0, 0, KVSPLIT>(d, sa.dl, sw.dl, wg);
            wgmma_commit();
            wgmma_wait<1>();
            if (!(kt.value && kc.value == 0 && hh == 0)) c.release(pend);
            if (!kt.value && kc.value > 0 && hh == 3) c.release(slot_a(kc.value - 1) * 8);
            pend = sw.bo;
            wgmma_fence();
            gemm_kv<kt.value, false, KVSPLIT, 8>(d, sa.dl, sw.dl, wg);
            wgmma_commit();
        };
#pragma unroll 1
        for (int hh = 0; hh < 4; hh++) {
            __nv_bfloat16* base = g_kv + (size_t)(((cb + 8 * kv_round(hh)) * 16 + 2 * ca + rank) * 2) * 16384 + 8 * q;
            const bool do_ln = hh == wg * LNSTAG + 1;
            for4([&](auto kc) {
                step(TrueT{}, kc, s, hh);
                if (hh > 0) {
                    if (kc.value == 0) fence_regs(o);
                    store_chunk<kc.value>(o, ep_ptr, ep_ptr + ep_step, 1.f, 1.f, policy_sel((EFMASK & 2) && hh == 1));
                }
                if (do_ln) {
                    if (kc.value == 0) ln.stat1();
                    if (kc.value == 1) ln.template stat2<0>();
                    if (kc.value == 2) ln.template stat2<1>();
                    if (kc.value == 3) ln.template piece<0>(P.out, ln_t, lane & 15);
                }
            });
            if (hh > 0) signal(bars, wg, hh, lane);
            for4([&](auto kc) {
                step(FalseT{}, kc, o, hh);
                if (kc.value == 0) fence_regs(s);
                store_chunk<kc.value>(s, base + krow * 128, base + (krow + 8) * 128, 1.f, 1.f, policy_sel((EFMASK & 2) && hh == 0));
                if (do_ln) ln.template piece<kc.value + 1>(P.out, ln_t, lane & 15);
                if (kc.value == 1 && hh == wg * LNSTAG) ln.load(P.x, P.wr, ln_t, lane & 15);
            });
            if (do_ln) signal(bars, wg, 0, lane);
            PROF(24 + hh);
            if (hh == 1) PROFG(181);
            ep_ptr = base + 16384 + vrow * 128;
        }
    }
    PROFG(182);
    PROF(2);
    uint32_t pf[32];
    {
        uint32_t qf[32];
        float l0 = 0.25f, l1 = 0.25f;
        const int bar_me = 2 + wg, bar_other = 3 - wg;
#pragma unroll 1
        for (int rd = 0; rd < 4; rd++) {
            const int h = 8 * rd + cb, p = item_p(ca, rd);
            const int role = wg ^ (rd & 1);
            const int nrest = 2 * p + role;
            Slot kfirst;
            const int lim = 64 * (role ^ rank) + 16 * w + lr - 8 * q;
            const uint64_t pol = policy_sel(((EFMASK & 4) && rd == 1) || ((EFMASK & 8) && rd == 2));
            {
                auto qstep = [&](auto zero, int ks) {
                    const Slot sl = c.next();
                    c.wait(sl);
                    BP(2, 5 + 3 * ks);
                    wgmma_fence();
                    gemm_q<zero.value>(s, sl.dl, role);
                    wgmma_commit();
                    wgmma_wait<1>();
                    c.release(pend);
                    pend = sl.bo;
                };
                qstep(TrueT{}, 0);
                if (rd == 0) c.release(slot_a(3) * 8);
                fence_regs(o);
                l0 += __shfl_xor_sync(0xffffffffu, l0, 1); l1 += __shfl_xor_sync(0xffffffffu, l1, 1);
                l0 += __shfl_xor_sync(0xffffffffu, l0, 2); l1 += __shfl_xor_sync(0xffffffffu, l1, 2);
                l0 = rcp(l0); l1 = rcp(l1);
                for4([&](auto i) {
                    constexpr int B = 16 * i.value;
#pragma unroll
                    for (int r = 0; r < 2; r++) {
                        qstep(FalseT{}, 1 + 2 * i.value + r);
                        const float f = r ? l1 : l0;
                        stg128p(ep_ptr + r * ep_step + 2 * B, pack_bf16(o[B + 2 * r] * f, o[B + 2 * r + 1] * f), pack_bf16(o[B + 2 * r + 4] * f, o[B + 2 * r + 5] * f),
                                pack_bf16(o[B + 2 * r + 8] * f, o[B + 2 * r + 9] * f), pack_bf16(o[B + 2 * r + 12] * f, o[B + 2 * r + 13] * f), pol);
#pragma unroll
                        for (int k = 0; k < 8; k++) {
                            float& v = o[B + 4 * (k >> 1) + 2 * r + (k & 1)];
                            v = (2 * B + k > lim + 8 * r) ? -1e30f : 0.f;
                            asm volatile("" : "+f"(v));
                        }
                    }
                });
                signal(bars, wg, 4 + rd, lane);
                PROF(11 + rd * 4);
                qstep(FalseT{}, 9);
                if (!role) { const Slot sl = c.next(); c.wait(sl); c.release(sl.bo); }
                kfirst = c.next();
                c.wait(kfirst);
                wgmma_wait<0>();
                BP(2, 34);
                c.release(pend);
                fence_regs(s);
                pack_tile(s, qf);
            }
            PROF(8 + rd * 4);
            fence_regs(qf); fence_regs(o);
            if (PINGPONG && !role) named_sync(bar_me, 256);
            BP(2, 36);
            wgmma_fence();
            gemm_rs<false>(o, qf, kfirst.dl);
            wgmma_commit();
            if (PINGPONG) named_arrive(bar_other, 256);
            if (!role) { const Slot sl = c.next(); c.wait(sl); c.release(sl.bo); }
            wgmma_wait<0>();
            BP(2, 38);
            fence_regs(o);
            c.release(kfirst.bo);
            float n0 = fmaxf(fmaxf(fmaxf(o[0], o[1]), fmaxf(o[4], o[5])), fmaxf(fmaxf(o[8], o[9]), fmaxf(o[12], o[13])));
            float n1 = fmaxf(fmaxf(fmaxf(o[2], o[3]), fmaxf(o[6], o[7])), fmaxf(fmaxf(o[10], o[11]), fmaxf(o[14], o[15])));
            n0 = __shfl_sync(0xffffffffu, n0, lane & 28); n1 = __shfl_sync(0xffffffffu, n1, lane & 28);
            n0 *= -SM_SCALE; n1 *= -SM_SCALE;
            l0 = 0.f; l1 = 0.f;
#pragma unroll
            for (int i = 0; i < 64; i++) s[i] = o[i];
            exp_part<0, 8>(s, n0, n1, l0, l1);
#pragma unroll
            for (int i = 0; i < 16; i++) pf[i] = pack_bf16(s[2 * i], s[2 * i + 1]);
            if (role != rank) {
                exp_part<8, 16>(s, n0, n1, l0, l1);
#pragma unroll
                for (int i = 16; i < 32; i++) pf[i] = pack_bf16(s[2 * i], s[2 * i + 1]);
            } else {
#pragma unroll
                for (int i = 16; i < 32; i++) pf[i] = 0u;
            }
            PROF(9 + rd * 4);
#pragma unroll 1
            for (int it = 0; it < nrest; it++) {
                const Slot sk = c.next(), sv = c.next();
                LP(0);
                c.wait(sk);
                c.wait(sv);
                fence_regs(o); fence_regs(pf);
                LP(1);
                if (PINGPONG) named_sync(bar_me, 256);
                LP(2);
                if (it < 3) BP(2, 42 + 4 * it);
                if (it >= nrest - 2) BP(1, 62 + 4 * (it - nrest + 2));
                wgmma_fence();
                gemm_rs<true>(s, qf, sk.dl);
                wgmma_commit();
                gemm_rs<false>(o, pf, sv.dl, it);
                wgmma_commit();
                if (PINGPONG) named_arrive(bar_other, 256);
                LP(3);
                wgmma_wait<1>();
                LP(4);
                c.release(sk.bo);
                fence_regs(s);
                exp_part<0, SPLITJ>(s, n0, n1, l0, l1);
                sched_barrier(l0, l1, bars + MISC_OFF + 16);
                LP(5);
                wgmma_wait<0>();
                LP(6);
                c.release(sv.bo);
                fence_regs(o); fence_regs(pf);
                exp_part<SPLITJ, 16>(s, n0, n1, l0, l1);
                pack_tile(s, pf);
            }
            PROF(10 + rd * 4);
            PROFG(183 + rd);
            const Slot sv = c.next();
            BP(1, 0);
            c.wait(sv);
            if (nrest == 0) {
#pragma unroll
                for (int i = 0; i < 64; i++) o[i] = 0.f;
            }
            if (__builtin_expect(__any_sync(0xffffffffu, !(l0 < 0x1p60f && l1 < 0x1p60f)), 0)) {
                attention_exact(o, qf, l0, l1, h, nrest + 1, lim, lane);
#pragma unroll
                for (int i = 0; i < 32; i++) pf[i] = 0u;
            }
            fence_regs(o); fence_regs(pf);
            if (PINGPONG && !role) named_sync(bar_me, 256);
            BP(1, 2);
            wgmma_fence();
            gemm_rs<false>(o, pf, sv.dl);
            wgmma_commit();
            pend = sv.bo;
            ep_ptr = g_ctx + (size_t)(h * SEQ + 256 * p + 128 * rank + 64 * role + 16 * w + lr) * HD + 8 * q;
            ep_step = 8 * HD;
        }
        l0 += __shfl_xor_sync(0xffffffffu, l0, 1); l1 += __shfl_xor_sync(0xffffffffu, l1, 1);
        l0 += __shfl_xor_sync(0xffffffffu, l0, 2); l1 += __shfl_xor_sync(0xffffffffu, l1, 2);
        l0 = rcp(l0); l1 = rcp(l1);
        wgmma_wait<0>();
        c.release(pend);
        fence_regs(o); fence_regs(pf);
#pragma unroll
        for (int i = 0; i < 32; i++) pf[i] = pack_bf16(o[2 * i] * ((i & 1) ? l1 : l0), o[2 * i + 1] * ((i & 1) ? l1 : l0));
    }
    PROFG(187);
    PROF(3);
    {
        float a1[64], a2[96];
        uint32_t px = 0, py = 0;
        auto mma1 = [&](const Slot& x, int acc) {
#pragma unroll
            for (int k = 0; k < 4; k++) wgmma_ss_n128<0, 1>(a1, x.dl + wg * 512 + lbo(16) + k * 2, x.dl + 1024 + lbo(4096) + (k >> 1) * 512 + (k & 1) * 128, k ? 1 : acc);
        };
        auto mma2 = [&](const Slot& x, const Slot& y, int acc) {
#pragma unroll
            for (int k = 0; k < 4; k++) wgmma_ss_n192<0, 1>(a2, x.dl + wg * 512 + lbo(16) + k * 2, y.dl + lbo(4096) + (k >> 1) * 768 + (k & 1) * 128, k ? 1 : acc);
        };
#pragma unroll 1
        for (int t = 0; t < (EARLYSEND ? 14 : 16); t++) {
            const Slot sx = c.next(), sy = c.next();
            c.wait(sx);
            wgmma_fence();
            mma1(sx, t);
            wgmma_commit();
            wgmma_wait<1>();
            if (t > 0) { c.release(px); c.release(py); }
            px = sx.bo; py = sy.bo;
            c.wait(sy);
            wgmma_fence();
            mma2(sx, sy, t);
            wgmma_commit();
            if (t == 0) {
#pragma unroll
                for (int i = 0; i < 4; i++) stg128(ep_ptr + 32 * i, pf[8 * i], pf[8 * i + 2], pf[8 * i + 4], pf[8 * i + 6]);
            }
            if (t == 1) {
#pragma unroll
                for (int i = 0; i < 4; i++) stg128(ep_ptr + 8 * HD + 32 * i, pf[8 * i + 1], pf[8 * i + 3], pf[8 * i + 5], pf[8 * i + 7]);
                signal(bars, wg, 8, lane);
            }
        }
        if (EARLYSEND) {
            const Slot x0 = c.next(), y0 = c.next(), x1 = c.next(), y1 = c.next();
            c.wait(x0);
            c.wait(y0);
            wgmma_fence();
            mma2(x0, y0, 1);
            wgmma_commit();
            wgmma_wait<1>();
            c.release(px); c.release(py);
            c.wait(x1);
            c.wait(y1);
            wgmma_fence();
            mma2(x1, y1, 1);
            wgmma_commit();
            mma1(x0, 1);
            mma1(x1, 1);
            wgmma_commit();
        }
        const int cw = __reduce_or_sync(0xffffffffu, wg * 4 + w);
        Slot st = c.next();
        if (cw >= 3) st = c.next();
        if (cw >= 6) st = c.next();
        const uint32_t stage = smem + st.bo * (SLOT / 8) + (cw % 3) * 10240;
        const int orow = unperm_row(256 * ca + 128 * rank + 16 * cw), ocol = 320 * (cb & 1);
        const uint32_t sa = stage + ((lane & 7) + (lane & 8)) * 128, sx = (lane >> 4) ^ (lane & 7);
        auto send = [&](auto c0, auto c1) {
#pragma unroll
            for (int ch = c0.value; ch < c1.value; ch++) {
#pragma unroll
                for (int i = 0; i < 4; i++) {
                    uint32_t r[4];
#pragma unroll
                    for (int e = 0; e < 4; e++) {
                        const int k = 32 * ch + 8 * i + 2 * e;
                        r[e] = (ch < 2) ? pack_bf16(a1[k & 63], a1[(k & 63) + 1]) : pack_bf16(a2[ch < 2 ? 0 : k - 64], a2[ch < 2 ? 1 : k - 63]);
                    }
                    asm volatile("stmatrix.sync.aligned.m8n8.x4.shared.b16 [%0], {%1, %2, %3, %4};"
                                 ::"r"(sa + ch * 2048 + ((sx ^ (2 * i)) << 4)), "r"(r[0]), "r"(r[1]), "r"(r[2]), "r"(r[3]) : "memory");
                }
                if (FENCE_EACH || ch == c1.value - 1) {
                    asm volatile("fence.proxy.async.shared::cta;" ::: "memory");
                    __syncwarp();
#pragma unroll
                    for (int b = FENCE_EACH ? ch : c0.value; b <= ch; b++)
                        asm volatile(ELECT "cp.reduce.async.bulk.tensor.2d.global.shared::cta.add.bulk_group [%0, {%2, %3}], [%1];\n}\n"
                                     ::"l"(&P.outm), "r"(stage + b * 2048), "r"(ocol + 64 * b), "r"(orow) : "memory");
                }
            }
        };
        mbar_wait(bars + BAR_EMPTY + st.bo, st.par ^ 1);
        mbar_wait(bars + BAR_DEP + 13 * 8, 0);
        wgmma_wait<EARLYSEND>();
        fence_regs(a2);
        send(IntT<2>{}, IntT<5>{});
        wgmma_wait<0>();
        fence_regs(a1);
        PROFG(188);
        PROF(4);
        send(IntT<0>{}, IntT<2>{});
        PROF(5);
        asm volatile("cp.async.bulk.commit_group;\ncp.async.bulk.wait_group.read 0;" ::: "memory");
    }
    PROF(6);
}

__device__ __forceinline__ void mma_rows(float (&acc)[8][4], uint32_t a0, uint32_t a2, const uint4& w0, const uint4& w1, const uint4& w2, const uint4& w3) {
    const uint32_t r0[4] = {w0.x, w0.y, w0.z, w0.w}, r1[4] = {w1.x, w1.y, w1.z, w1.w};
    const uint32_t r2[4] = {w2.x, w2.y, w2.z, w2.w}, r3[4] = {w3.x, w3.y, w3.z, w3.w};
#pragma unroll
    for (int i = 0; i < 4; i++) {
        mma16816(acc[2 * i][0], acc[2 * i][1], acc[2 * i][2], acc[2 * i][3], a0, 0u, a2, 0u, __byte_perm(r0[i], r1[i], 0x5410), __byte_perm(r2[i], r3[i], 0x5410));
        mma16816(acc[2 * i + 1][0], acc[2 * i + 1][1], acc[2 * i + 1][2], acc[2 * i + 1][3], a0, 0u, a2, 0u, __byte_perm(r0[i], r1[i], 0x7632), __byte_perm(r2[i], r3[i], 0x7632));
    }
}

__device__ __forceinline__ void mod_ffn(const Params& P, uint8_t* sm, int mc  ) {
    const uint32_t epoch = read_epoch();
    const int tid = threadIdx.x - 128, lane = tid & 31, cw = tid >> 5, q = lane & 3, lr = lane >> 2;
    uint32_t* xs = reinterpret_cast<uint32_t*>(sm);
    uint32_t* wmax = xs + 8 * 324;
    int* sidx = reinterpret_cast<int*>(wmax + 16);
    const int fg = cw * 4 + mc;
    const uint32_t ring = smem_u32(sm) + 16384 + cw * 24576, rbar = smem_u32(sm) + 12288 + cw * 32;
    auto issue = [&](int u, int st) {
        if (lane == 0 && u < 30) {
            mbar_expect_tx(rbar + st * 8, 8192);
            if (u < 20) {
                tma_load_stream(ring + st * 8192, &P.wg, fg * 64, u * 32, rbar + st * 8);
                tma_load_stream(ring + st * 8192 + 4096, &P.wu, fg * 64, u * 32, rbar + st * 8);
            } else {
                tma_load_stream(ring + st * 8192, &P.wd, (u - 20) * 64, fg * 64, rbar + st * 8);
            }
        }
    };
    if (lane == 0) {
        mbar_init(rbar, 1); mbar_init(rbar + 8, 1); mbar_init(rbar + 16, 1);
        asm volatile("fence.mbarrier_init.release.cluster;" ::: "memory");
    }
    if (tid == 0) flag_wait<100>(F_LN, 256u * (epoch + 1));
    named_sync(1, 256);
    PROF(1);
    if (fg < 27) {
#pragma unroll 1
        for (int u = 0; u < 3; u++) issue(u, u);
    }
    PROF(2);
    uint32_t key[8];
#pragma unroll
    for (int i = 0; i < 8; i++) {
        const int t = tid + 256 * i;
        uint32_t b = __float_as_uint(__ldcg(g_r + t) + 0.f) >> 16;
        b = (b & 0x8000u) ? (~b & 0xffffu) : (b | 0x8000u);
        key[i] = (b << 16) | (uint32_t)(0xffff - t);
    }
#pragma unroll 1
    for (int rnd = 0; rnd < 8; rnd++) {
        uint32_t mx = key[0];
#pragma unroll
        for (int i = 1; i < 8; i++) mx = max(mx, key[i]);
        mx = __reduce_max_sync(0xffffffffu, mx);
        if (lane == 0) wmax[(rnd & 1) * 8 + cw] = mx;
        named_sync(1, 256);
        mx = __reduce_max_sync(0xffffffffu, wmax[(rnd & 1) * 8 + (lane & 7)]);
#pragma unroll
        for (int i = 0; i < 8; i++) if (key[i] == mx) key[i] = 0;
        if (tid == 0) sidx[rnd] = 0xffff - (int)(mx & 0xffffu);
    }
    named_sync(1, 256);
    {
        const uint32_t* src = reinterpret_cast<const uint32_t*>(g_xn + (size_t)perm_row(sidx[cw]) * DM);
#pragma unroll 2
        for (int i = lane; i < 320; i += 32) xs[cw * 324 + i] = __ldcg(src + i);
    }
    named_sync(1, 256);
    PROF(3);
    if (fg < 27) {
        float g[8][4], v[8][4];
        uint32_t hp[8];
#pragma unroll
        for (int i = 0; i < 8; i++)
#pragma unroll
            for (int e = 0; e < 4; e++) { g[i][e] = 0.f; v[i][e] = 0.f; }
        int st = 0, ph = 0;
#pragma unroll 1
        for (int u = 0; u < 60; u++) {
            if (!(u & 1)) mbar_wait(rbar + st * 8, ph);
            uint4 a[8];
#pragma unroll
            for (int r = 0; r < 8; r++) {
                const int row = (u < 40) ? 32 * (r >> 2) + 16 * (u & 1) + 2 * q + (r & 1) + 4 * (r & 2) : 16 * q + 8 * (u & 1) + r;
                asm volatile("ld.shared.v4.b32 {%0, %1, %2, %3}, [%4];" : "=r"(a[r].x), "=r"(a[r].y), "=r"(a[r].z), "=r"(a[r].w)
                             : "r"(ring + st * 8192 + row * 128 + ((lr ^ row) & 7) * 16) : "memory");
            }
            uint32_t f0, f1, f2, f3;
            if (u < 40) { f0 = f2 = xs[lr * 324 + u * 8 + q]; f1 = f3 = xs[lr * 324 + u * 8 + 4 + q]; }
            else if (u & 1) { f0 = hp[4]; f1 = hp[5]; f2 = hp[6]; f3 = hp[7]; }
            else { f0 = hp[0]; f1 = hp[1]; f2 = hp[2]; f3 = hp[3]; }
            mma_rows(g, f0, f1, a[0], a[1], a[2], a[3]);
            mma_rows(v, f2, f3, a[4], a[5], a[6], a[7]);
            if (u & 1) {
                __syncwarp();
                issue((u >> 1) + 3, st);
                if (++st == 3) { st = 0; ph ^= 1; }
                if (u >= 39) {
                    if (u == 39) {
                        float hv[16];
#pragma unroll
                        for (int i = 0; i < 16; i++) {
                            const float gp = round_bf16(g[i & 7][i >> 3]);
                            hv[i] = round_bf16(__fdividef(gp, 1.0f + __expf(fminf(-gp, 80.f)))) * round_bf16(v[i & 7][i >> 3]);
                        }
#pragma unroll
                        for (int i = 0; i < 8; i++) hp[i] = pack_bf16(hv[2 * i], hv[2 * i + 1]);
                    } else {
                        float4* dst = reinterpret_cast<float4*>(g_ypart + (fg * 8 + lr) * DM + ((u - 40) >> 1) * 64 + 16 * q);
#pragma unroll
                        for (int i = 0; i < 4; i++) {
                            const int j = 4 * (i & 1), e = i >> 1;
                            dst[i] = make_float4(g[j][e] + v[j][e], g[j + 1][e] + v[j + 1][e], g[j + 2][e] + v[j + 2][e], g[j + 3][e] + v[j + 3][e]);
                        }
                    }
#pragma unroll
                    for (int i = 0; i < 8; i++) { g[i][0] = 0.f; g[i][1] = 0.f; v[i][0] = 0.f; v[i][1] = 0.f; }
                }
            }
        }
    }
    PROF(5);
    named_sync(1, 256);
    if (tid == 0) {
        flag_add(F_MODP);
        flag_wait<100>(F_MODP, 4u * (epoch + 1));
    }
    named_sync(1, 256);
    PROF(6);
#pragma unroll 1
    for (int i = tid; i < 2 * DM; i += 256) {
        const int c = 2 * mc + (i >= DM), col = i - (i >= DM) * DM, t = sidx[c];
        float y = 0.f;
#pragma unroll 9
        for (int k = 0; k < 27; k++) y += __ldcg(g_ypart + (k * 8 + c) * DM + col);
        const float rs = round_bf16(__fdividef(1.0f, 1.0f + __expf(fminf(-__ldcg(g_r + t), 80.f))));
        const float xn = __bfloat162float(reinterpret_cast<const __nv_bfloat16*>(xs + c * 324)[col]);
        P.out[(size_t)t * DM + col] = __float2bfloat16_rn(__bfloat162float(P.x[(size_t)t * DM + col]) + round_bf16(xn + round_bf16(round_bf16(y) * rs)));
    }
    named_sync(1, 256);
    if (tid == 0) flag_add(F_MOD);
    PROF(7);
}

__global__ void __cluster_dims__(2, 1, 1) __launch_bounds__(384, 1) fused_kernel(const __grid_constant__ Params P) {
    extern __shared__ __align__(1024) uint8_t smem_raw[];
    const uint32_t smem = (smem_u32(smem_raw) + 1023u) & ~1023u;
    uint8_t* smem_gen = smem_raw + (smem - smem_u32(smem_raw));
    const uint32_t bars = smem + NSLOT * SLOT;
    const int wgi = __reduce_or_sync(0xffffffffu, threadIdx.x >> 7);
    const int cl = blockIdx.x >> 1, rank = blockIdx.x & 1, ca = cl & 7, cb = cl >> 3;
    PROFG(30);
    PROF(0);
    if (threadIdx.x == 0) {
#pragma unroll
        for (int i = 0; i < NSLOT; i++) { mbar_init(bars + BAR_FULL + i * 8, 1); mbar_init(bars + BAR_EMPTY + i * 8, 16); }
        mbar_arrive(bars + BAR_FULL + 16);
        asm volatile("mbarrier.arrive.shared::cta.b64 _, [%0], 16;" ::"r"(bars + BAR_EMPTY + 16) : "memory");
        asm volatile("fence.mbarrier_init.release.cluster;" ::: "memory");
        PROF(24);
    } else if (threadIdx.x == 32) {
#pragma unroll
        for (int i = 0; i < 18; i++) mbar_init(bars + BAR_SIG + i * 8, 4);
#pragma unroll
        for (int i = 0; i < 14; i++) mbar_init(bars + BAR_DEP + i * 8, 1);
    } else if (threadIdx.x >= 64 && threadIdx.x < 128 && cl < 64) {
        const int i = threadIdx.x - 64;
        if (i == 0) { prefetch_map(&P.ckv); prefetch_map(&P.wuk); }
        if (i < 32) asm volatile("prefetch.global.L2 [%0];" ::"l"(P.ckv_ptr + ((2 * ca + rank) * 128 + cb * 16 + (i >> 1)) * DC + (i & 1) * 64));
        else if (i < 48) asm volatile("prefetch.global.L2 [%0];" ::"l"(P.wuk_ptr + (size_t)((i - 32) * 8 + ca) * (NH * HD) + (cb + 8 * kv_round(0)) * 128 + rank * 64));
    }
    __syncthreads();
    PROF(29);
    cluster_arrive();
    if (wgi > 0) {
        asm volatile("setmaxnreg.inc.sync.aligned.u32 232;");
        if (cl >= 64) {
            cluster_wait();
            mod_ffn(P, smem_gen, blockIdx.x - 128);
        } else {
            consumer(P, smem, bars, ca, cb, rank, wgi - 1);
        }
        cluster_arrive();
        PROFG(31);
        PROFDUMP();
    } else {
        asm volatile("setmaxnreg.dec.sync.aligned.u32 40;");
        const int w = __reduce_or_sync(0xffffffffu, threadIdx.x >> 5), lane = threadIdx.x & 31;
        if (threadIdx.x == 32 && cl < 64) {
            mbar_expect_tx(bars + BAR_FULL, SLOT);
            tma_load(smem, &P.ckv, 0, (2 * ca + rank) * 128, bars + BAR_FULL);
            tma_load(smem + 16384, &P.ckv, 64, (2 * ca + rank) * 128, bars + BAR_FULL);
        }
        if (threadIdx.x == 64) {
            prefetch_map(&P.wuv); prefetch_map(&P.xn); prefetch_map(&P.wq); prefetch_map(&P.kv); prefetch_map(&P.ctx); prefetch_map(&P.wo); prefetch_map(&P.outm);
        }
        __syncwarp();
        cluster_wait();
        PROF(27);
        if (cl < 64) {
            if (w == 0) {
                producer(P, smem, bars, ca, cb, rank);
            } else if (w < 3 && lane == 0) {
                const int wg = w - 1;
#pragma unroll 1
                for (int i = 0; i < 9; i++) {
                    const int e = (i < wg * LNSTAG + 1) ? i + 1 : (i == wg * LNSTAG + 1) ? 0 : i;
                    mbar_wait_sleep(bars + BAR_SIG + (wg * 9 + e) * 8, 0);
                    int f;
                    if (e == 0) f = F_LN;
                    else if (e < 5) f = F_KV + cb + 8 * kv_round(e - 1);
                    else { const int rd = e - 5; f = F_CTX + (8 * rd + cb) * 16 + item_p(ca, rd) * 2 + rank; }
                    flag_add(f);
                }
            } else if (lane == 0) {
                const uint32_t epoch = read_epoch();
#pragma unroll 1
                for (int i = 0; i < 14; i++) {
                    const int e = (i < 11) ? i : (i == 11) ? 13 : i - 1;
                    int f;
                    uint32_t n;
                    if (e == 0) { f = F_LN; n = 256; }
                    else if (e < 5) { f = F_KV + cb + 8 * (e - 1); n = 32; }
                    else if (e < 13) { f = F_CTX + (8 * ((e - 5) >> 1) + (cb & 6) + ((e - 5) & 1)) * 16 + ca * 2 + rank; n = 2; }
                    else { f = F_MOD; n = 4; }
                    flag_wait<200>(f, n * (epoch + 1));
                    fence_proxy_async();
                    mbar_arrive(bars + BAR_DEP + e * 8);
                }
            }
        }
        __syncwarp();
        cluster_arrive();
        cluster_wait();
        if (threadIdx.x == 0) atomicAdd(g_flags + F_EXIT * 8, 1u);
        PROFG(31);
        PROFDUMP();
    }
}

typedef CUresult (*EncodeFn)(CUtensorMap*, CUtensorMapDataType, cuuint32_t, void*, const cuuint64_t*, const cuuint64_t*, const cuuint32_t*,
                             const cuuint32_t*, CUtensorMapInterleave, CUtensorMapSwizzle, CUtensorMapL2promotion, CUtensorMapFloatOOBfill);

void make_map(EncodeFn fn, CUtensorMap* m, const void* ptr, uint64_t rows, uint64_t cols, uint32_t box_rows) {
    cuuint64_t dims[2] = {cols, rows};
    cuuint64_t strides[1] = {cols * 2};
    cuuint32_t box[2] = {64, box_rows};
    cuuint32_t es[2] = {1, 1};
    fn(m, CU_TENSOR_MAP_DATA_TYPE_BFLOAT16, 2, const_cast<void*>(ptr), dims, strides, box, es, CU_TENSOR_MAP_INTERLEAVE_NONE,
       CU_TENSOR_MAP_SWIZZLE_128B, CU_TENSOR_MAP_L2_PROMOTION_L2_128B, CU_TENSOR_MAP_FLOAT_OOB_FILL_NONE);
}

}

extern "C" void kernel_launch(void* const* d_in, const int* in_sizes, int n_in, void* d_out, int out_size) {
    (void)in_sizes; (void)n_in; (void)out_size;
    void* fnp = nullptr;
    cudaDriverEntryPointQueryResult qr;
    cudaGetDriverEntryPoint("cuTensorMapEncodeTiled", &fnp, cudaEnableDefault, &qr);
    EncodeFn fn = (EncodeFn)fnp;
    void *xn, *kv, *ctx;
    cudaGetSymbolAddress(&xn, g_xn);
    cudaGetSymbolAddress(&kv, g_kv);
    cudaGetSymbolAddress(&ctx, g_ctx);
    Params P;
    make_map(fn, &P.ckv, d_in[1], SEQ, DC, 128);
    make_map(fn, &P.wq, d_in[2], DM, NH * HD, 64);
    make_map(fn, &P.wuk, d_in[3], DC, NH * HD, 128);
    make_map(fn, &P.wuv, d_in[4], DC, NH * HD, 128);
    make_map(fn, &P.wo, d_in[5], NH * HD, DM, 32);
    make_map(fn, &P.xn, xn, SEQ, DM, 128);
    make_map(fn, &P.kv, kv, NH * 16 * 2 * 128, 128, 128);
    make_map(fn, &P.ctx, ctx, NH * SEQ, HD, 128);
    P.x = (const __nv_bfloat16*)d_in[0];
    P.wr = (const __nv_bfloat16*)d_in[7];
    make_map(fn, &P.wg, d_in[8], DM, FF, 32);
    make_map(fn, &P.wu, d_in[9], DM, FF, 32);
    make_map(fn, &P.wd, d_in[10], FF, DM, 64);
    P.ckv_ptr = (const __nv_bfloat16*)d_in[1];
    P.wuk_ptr = (const __nv_bfloat16*)d_in[3];
    make_map(fn, &P.outm, d_out, SEQ, DM, 16);
    P.out = (__nv_bfloat16*)d_out;
    cudaFuncSetAttribute(fused_kernel, cudaFuncAttributeMaxDynamicSharedMemorySize, SMEM_BYTES);
    fused_kernel<<<NCTA, 384, SMEM_BYTES>>>(P);
}
```

```cpp
#include <cuda_runtime.h>
#include <cuda_bf16.h>
#include <cuda.h>
#include <stdint.h>

namespace {

constexpr int SEQ = 2048, DM = 640, DC = 512, NH = 32, HD = 128, FF = 1728;
constexpr int NSLOT = 7, SLOT = 32768;
constexpr int NCTA = 132;
#define PINGPONG 1
#define SIGMA 1
#define KVORDER 0x1023
#define KVSPLIT 1
#define LNSTAG 1
#define EARLYPF 1
#define EARLYSEND 1
#define FENCE_EACH 1
#define LATEST 1
#define LASTRD 7
#define LASTN 2
#define EFMASK 13
#define LNOFF 4
#define LNLEAD 2
#define FASTSTART 1
#define SPLITJ 8
constexpr uint32_t DESC_HI = (1024u >> 4) | (1u << 30);
constexpr int SMEM_BYTES = NSLOT * SLOT + 3072;

constexpr int BAR_FULL = 0, BAR_EMPTY = 64, BAR_SIG = 128  , BAR_DEP = 320  , MISC_OFF = 512;

constexpr int F_EXIT = 0, F_LN = 1, F_MOD = 2, F_MODP = 3, F_KV = 4  , F_CTX = 36  , F_NUM = 548;

__device__ __align__(1024) __nv_bfloat16 g_xn[SEQ * DM];
__device__ __align__(1024) __nv_bfloat16 g_kv[NH * 16 * 2 * 128 * 128];
__device__ __align__(1024) __nv_bfloat16 g_ctx[NH * SEQ * HD];
__device__ __align__(16) float g_r[SEQ];
__device__ __align__(16) float g_ypart[27 * 8 * DM];
__device__ uint32_t g_flags[F_NUM * 8];

struct TrueT { static constexpr bool value = true; };
struct FalseT { static constexpr bool value = false; };

struct Params {
    CUtensorMap ckv, wuk, wuv, xn, wq, kv, ctx, wo, wg, wu, wd, outm;
    const __nv_bfloat16 *x, *wr, *ckv_ptr, *wuk_ptr;
    __nv_bfloat16* out;
};

__device__ __forceinline__ uint32_t smem_u32(const void* p) { return (uint32_t)__cvta_generic_to_shared(p); }
__device__ __forceinline__ void mbar_init(uint32_t bar, uint32_t cnt) {
    asm volatile("mbarrier.init.shared::cta.b64 [%0], %1;" ::"r"(bar), "r"(cnt) : "memory");
}
__device__ __forceinline__ void mbar_expect_tx(uint32_t bar, uint32_t bytes) {
    asm volatile("mbarrier.arrive.expect_tx.shared::cta.b64 _, [%0], %1;" ::"r"(bar), "r"(bytes) : "memory");
}
__device__ __forceinline__ void mbar_arrive(uint32_t bar) {
    asm volatile("mbarrier.arrive.shared::cta.b64 _, [%0];" ::"r"(bar) : "memory");
}
__device__ __forceinline__ uint32_t mapa(uint32_t addr, uint32_t cta) {
    uint32_t r;
    asm("mapa.shared::cluster.u32 %0, %1, %2;" : "=r"(r) : "r"(addr), "r"(cta));
    return r;
}
__device__ __forceinline__ void mbar_wait(uint32_t bar, uint32_t parity) {
    asm volatile(
        "{\n.reg .pred p;\n.reg .b32 c;\n"
        "mov.b32 c, 0;\n"
        "WLOOP:\n"
        "mbarrier.try_wait.parity.shared::cta.b64 p, [%0], %1;\n"
        "@p bra.uni WDONE;\n"
        "add.u32 c, c, 1;\n"
        "setp.lt.u32 p, c, 0x400000;\n"
        "@p bra.uni WLOOP;\n"
        "trap;\n"
        "WDONE:\n}\n" ::"r"(bar), "r"(parity) : "memory");
}
__device__ __forceinline__ void mbar_wait_sleep(uint32_t bar, uint32_t parity) {
    asm volatile(
        "{\n.reg .pred p;\n.reg .b32 c;\n"
        "mov.b32 c, 0;\n"
        "WLOOP:\n"
        "mbarrier.try_wait.parity.shared::cta.b64 p, [%0], %1, 20000;\n"
        "@p bra.uni WDONE;\n"
        "add.u32 c, c, 1;\n"
        "setp.lt.u32 p, c, 0x40000;\n"
        "@p bra.uni WLOOP;\n"
        "trap;\n"
        "WDONE:\n}\n" ::"r"(bar), "r"(parity) : "memory");
}
__device__ __forceinline__ void tma_load(uint32_t dst, const CUtensorMap* m, int c0, int c1, uint32_t bar) {
    asm volatile("cp.async.bulk.tensor.2d.shared::cluster.global.mbarrier::complete_tx::bytes [%0], [%1, {%3, %4}], [%2];"
                 ::"r"(dst), "l"(m), "r"(bar), "r"(c0), "r"(c1) : "memory");
}
#define ELECT "{\n.reg .pred e;\nelect.sync _|e, 0xffffffff;\n@e "
__device__ __forceinline__ void w_expect_tx(uint32_t bar, uint32_t bytes) {
    asm volatile(ELECT "mbarrier.arrive.expect_tx.shared::cta.b64 _, [%0], %1;\n}\n" ::"r"(bar), "r"(bytes) : "memory");
}
__device__ __forceinline__ void w_tma_load(uint32_t dst, const CUtensorMap* m, int c0, int c1, uint32_t bar) {
    asm volatile(ELECT "cp.async.bulk.tensor.2d.shared::cluster.global.mbarrier::complete_tx::bytes [%0], [%1, {%3, %4}], [%2];\n}\n"
                 ::"r"(dst), "l"(m), "r"(bar), "r"(c0), "r"(c1) : "memory");
}
__device__ __forceinline__ void w_tma_load_mc(uint32_t dst, const CUtensorMap* m, int c0, int c1, uint32_t bar) {
    asm volatile(ELECT "cp.async.bulk.tensor.2d.shared::cluster.global.mbarrier::complete_tx::bytes.multicast::cluster [%0], [%1, {%3, %4}], [%2], %5;\n}\n"
                 ::"r"(dst), "l"(m), "r"(bar), "r"(c0), "r"(c1), "h"((uint16_t)3) : "memory");
}
__device__ __forceinline__ void w_tma_prefetch(const CUtensorMap* m, int c0, int c1) {
    asm volatile(ELECT "cp.async.bulk.prefetch.tensor.2d.L2.global [%0, {%1, %2}];\n}\n" ::"l"(m), "r"(c0), "r"(c1) : "memory");
}
__device__ __forceinline__ uint64_t policy_evict_first() {
    uint64_t p;
    asm("createpolicy.fractional.L2::evict_first.b64 %0, 1.0;" : "=l"(p));
    return p;
}
__device__ __forceinline__ void w_tma_load_mc_last(uint32_t dst, const CUtensorMap* m, int c0, int c1, uint32_t bar) {
    asm volatile(ELECT "cp.async.bulk.tensor.2d.shared::cluster.global.mbarrier::complete_tx::bytes.multicast::cluster.L2::cache_hint [%0], [%1, {%3, %4}], [%2], %5, %6;\n}\n"
                 ::"r"(dst), "l"(m), "r"(bar), "r"(c0), "r"(c1), "h"((uint16_t)3), "l"(policy_evict_first()) : "memory");
}
__device__ __forceinline__ void tma_load_stream(uint32_t dst, const CUtensorMap* m, int c0, int c1, uint32_t bar) {
    asm volatile("cp.async.bulk.tensor.2d.shared::cluster.global.mbarrier::complete_tx::bytes.L2::cache_hint [%0], [%1, {%3, %4}], [%2], %5;"
                 ::"r"(dst), "l"(m), "r"(bar), "r"(c0), "r"(c1), "l"(policy_evict_first()) : "memory");
}
__device__ __forceinline__ uint4 ldg_stream(const void* p) {
    uint4 v;
    asm volatile("ld.global.nc.L2::cache_hint.v4.b32 {%0, %1, %2, %3}, [%4], %5;" : "=r"(v.x), "=r"(v.y), "=r"(v.z), "=r"(v.w) : "l"(p), "l"(policy_evict_first()));
    return v;
}
__device__ __forceinline__ void prefetch_map(const CUtensorMap* m) {
    asm volatile("prefetch.tensormap [%0];" ::"l"(m) : "memory");
}
__device__ __forceinline__ void cluster_arrive() { asm volatile("barrier.cluster.arrive.relaxed.aligned;" ::: "memory"); }
__device__ __forceinline__ void cluster_wait() { asm volatile("barrier.cluster.wait.aligned;" ::: "memory"); }
__device__ __forceinline__ void named_sync(int id, int n) { asm volatile("bar.sync %0, %1;" ::"r"(id), "r"(n) : "memory"); }
__device__ __forceinline__ void named_arrive(int id, int n) { asm volatile("bar.arrive %0, %1;" ::"r"(id), "r"(n) : "memory"); }

__device__ __forceinline__ void flag_add(int f) {
    asm volatile("fence.acq_rel.gpu;\nred.relaxed.gpu.global.add.u32 [%0], 1;" ::"l"(g_flags + f * 8) : "memory");
}
template <int SLEEP>
__device__ __forceinline__ void flag_wait(int f, uint32_t target) {
    asm volatile(
        "{\n.reg .pred p;\n.reg .b32 c, v;\n"
        "mov.b32 c, 0;\n"
        "FLOOP:\n"
        "ld.acquire.gpu.global.u32 v, [%0];\n"
        "sub.u32 v, v, %1;\n"
        "setp.ge.s32 p, v, 0;\n"
        "@p bra FDONE;\n"
        "nanosleep.u32 %2;\n"
        "add.u32 c, c, 1;\n"
        "setp.lt.u32 p, c, 0x400000;\n"
        "@p bra FLOOP;\n"
        "trap;\n"
        "FDONE:\n}\n" ::"l"(g_flags + f * 8), "r"(target), "n"(SLEEP) : "memory");
}
__device__ __forceinline__ uint32_t read_epoch() {
    uint32_t e;
    asm volatile("ld.relaxed.gpu.global.u32 %0, [%1];" : "=r"(e) : "l"(g_flags + F_EXIT * 8) : "memory");
    return e / NCTA;
}
__device__ __forceinline__ void fence_proxy_async() { asm volatile("fence.proxy.async;" ::: "memory"); }

__device__ __forceinline__ void wgmma_fence() { asm volatile("wgmma.fence.sync.aligned;" ::: "memory"); }
__device__ __forceinline__ void wgmma_commit() { asm volatile("wgmma.commit_group.sync.aligned;" ::: "memory"); }
template <int N>
__device__ __forceinline__ void wgmma_wait() { asm volatile("wgmma.wait_group.sync.aligned %0;" ::"n"(N) : "memory"); }
template <int N>
__device__ __forceinline__ void fence_regs(float (&d)[N]) {
#pragma unroll
    for (int i = 0; i < N; i++) asm volatile("" : "+f"(d[i])::"memory");
}
template <int N>
__device__ __forceinline__ void fence_regs(uint32_t (&d)[N]) {
#pragma unroll
    for (int i = 0; i < N; i++) asm volatile("" : "+r"(d[i])::"memory");
}

template <int TA, int TB>
__device__ __forceinline__ void wgmma_ss_n128(float (&d)[64], uint32_t alo, uint32_t blo, int scale_d) {
    asm volatile("{\n.reg .pred p;\n.reg .b64 da, db;\nsetp.ne.b32 p, %66, 0;\n"
        "mov.b64 da, {%64, %69};\nmov.b64 db, {%65, %69};\n"
        "wgmma.mma_async.sync.aligned.m64n128k16.f32.bf16.bf16 "
        "{%0, %1, %2, %3, %4, %5, %6, %7, %8, %9, %10, %11, %12, %13, %14, %15, %16, %17, %18, %19, %20, %21, %22, %23, %24, %25, %26, %27, %28, %29, %30, %31, %32, %33, %34, %35, %36, %37, %38, %39, %40, %41, %42, %43, %44, %45, %46, %47, %48, %49, %50, %51, %52, %53, %54, %55, %56, %57, %58, %59, %60, %61, %62, %63}, da, db, p, 1, 1, %67, %68;\n}\n"
        :
          "+f"(d[0]), "+f"(d[1]), "+f"(d[2]), "+f"(d[3]), "+f"(d[4]), "+f"(d[5]), "+f"(d[6]), "+f"(d[7]),
          "+f"(d[8]), "+f"(d[9]), "+f"(d[10]), "+f"(d[11]), "+f"(d[12]), "+f"(d[13]), "+f"(d[14]), "+f"(d[15]),
          "+f"(d[16]), "+f"(d[17]), "+f"(d[18]), "+f"(d[19]), "+f"(d[20]), "+f"(d[21]), "+f"(d[22]), "+f"(d[23]),
          "+f"(d[24]), "+f"(d[25]), "+f"(d[26]), "+f"(d[27]), "+f"(d[28]), "+f"(d[29]), "+f"(d[30]), "+f"(d[31]),
          "+f"(d[32]), "+f"(d[33]), "+f"(d[34]), "+f"(d[35]), "+f"(d[36]), "+f"(d[37]), "+f"(d[38]), "+f"(d[39]),
          "+f"(d[40]), "+f"(d[41]), "+f"(d[42]), "+f"(d[43]), "+f"(d[44]), "+f"(d[45]), "+f"(d[46]), "+f"(d[47]),
          "+f"(d[48]), "+f"(d[49]), "+f"(d[50]), "+f"(d[51]), "+f"(d[52]), "+f"(d[53]), "+f"(d[54]), "+f"(d[55]),
          "+f"(d[56]), "+f"(d[57]), "+f"(d[58]), "+f"(d[59]), "+f"(d[60]), "+f"(d[61]), "+f"(d[62]), "+f"(d[63])
        : "r"(alo), "r"(blo), "r"(scale_d), "n"(TA), "n"(TB), "r"(DESC_HI));
}
template <int TA, int TB>
__device__ __forceinline__ void wgmma_ss_n192(float (&d)[96], uint32_t alo, uint32_t blo, int scale_d) {
    asm volatile("{\n.reg .pred p;\n.reg .b64 da, db;\nsetp.ne.b32 p, %98, 0;\n"
        "mov.b64 da, {%96, %101};\nmov.b64 db, {%97, %101};\n"
        "wgmma.mma_async.sync.aligned.m64n192k16.f32.bf16.bf16 "
        "{%0, %1, %2, %3, %4, %5, %6, %7, %8, %9, %10, %11, %12, %13, %14, %15, %16, %17, %18, %19, %20, %21, %22, %23, %24, %25, %26, %27, %28, %29, %30, %31, %32, %33, %34, %35, %36, %37, %38, %39, %40, %41, %42, %43, %44, %45, %46, %47, %48, %49, %50, %51, %52, %53, %54, %55, %56, %57, %58, %59, %60, %61, %62, %63, %64, %65, %66, %67, %68, %69, %70, %71, %72, %73, %74, %75, %76, %77, %78, %79, %80, %81, %82, %83, %84, %85, %86, %87, %88, %89, %90, %91, %92, %93, %94, %95}, da, db, p, 1, 1, %99, %100;\n}\n"
        :
          "+f"(d[0]), "+f"(d[1]), "+f"(d[2]), "+f"(d[3]), "+f"(d[4]), "+f"(d[5]), "+f"(d[6]), "+f"(d[7]),
          "+f"(d[8]), "+f"(d[9]), "+f"(d[10]), "+f"(d[11]), "+f"(d[12]), "+f"(d[13]), "+f"(d[14]), "+f"(d[15]),
          "+f"(d[16]), "+f"(d[17]), "+f"(d[18]), "+f"(d[19]), "+f"(d[20]), "+f"(d[21]), "+f"(d[22]), "+f"(d[23]),
          "+f"(d[24]), "+f"(d[25]), "+f"(d[26]), "+f"(d[27]), "+f"(d[28]), "+f"(d[29]), "+f"(d[30]), "+f"(d[31]),
          "+f"(d[32]), "+f"(d[33]), "+f"(d[34]), "+f"(d[35]), "+f"(d[36]), "+f"(d[37]), "+f"(d[38]), "+f"(d[39]),
          "+f"(d[40]), "+f"(d[41]), "+f"(d[42]), "+f"(d[43]), "+f"(d[44]), "+f"(d[45]), "+f"(d[46]), "+f"(d[47]),
          "+f"(d[48]), "+f"(d[49]), "+f"(d[50]), "+f"(d[51]), "+f"(d[52]), "+f"(d[53]), "+f"(d[54]), "+f"(d[55]),
          "+f"(d[56]), "+f"(d[57]), "+f"(d[58]), "+f"(d[59]), "+f"(d[60]), "+f"(d[61]), "+f"(d[62]), "+f"(d[63]),
          "+f"(d[64]), "+f"(d[65]), "+f"(d[66]), "+f"(d[67]), "+f"(d[68]), "+f"(d[69]), "+f"(d[70]), "+f"(d[71]),
          "+f"(d[72]), "+f"(d[73]), "+f"(d[74]), "+f"(d[75]), "+f"(d[76]), "+f"(d[77]), "+f"(d[78]), "+f"(d[79]),
          "+f"(d[80]), "+f"(d[81]), "+f"(d[82]), "+f"(d[83]), "+f"(d[84]), "+f"(d[85]), "+f"(d[86]), "+f"(d[87]),
          "+f"(d[88]), "+f"(d[89]), "+f"(d[90]), "+f"(d[91]), "+f"(d[92]), "+f"(d[93]), "+f"(d[94]), "+f"(d[95])
        : "r"(alo), "r"(blo), "r"(scale_d), "n"(TA), "n"(TB), "r"(DESC_HI));
}
template <int TB>
__device__ __forceinline__ void wgmma_rs_n128(float (&d)[64], uint32_t a0, uint32_t a1, uint32_t a2, uint32_t a3, uint32_t blo, int scale_d) {
    asm volatile("{\n.reg .pred p;\n.reg .b64 db;\nsetp.ne.b32 p, %69, 0;\n"
        "mov.b64 db, {%68, %71};\n"
        "wgmma.mma_async.sync.aligned.m64n128k16.f32.bf16.bf16 "
        "{%0, %1, %2, %3, %4, %5, %6, %7, %8, %9, %10, %11, %12, %13, %14, %15, %16, %17, %18, %19, %20, %21, %22, %23, %24, %25, %26, %27, %28, %29, %30, %31, %32, %33, %34, %35, %36, %37, %38, %39, %40, %41, %42, %43, %44, %45, %46, %47, %48, %49, %50, %51, %52, %53, %54, %55, %56, %57, %58, %59, %60, %61, %62, %63}, {%64, %65, %66, %67}, db, p, 1, 1, %70;\n}\n"
        :
          "+f"(d[0]), "+f"(d[1]), "+f"(d[2]), "+f"(d[3]), "+f"(d[4]), "+f"(d[5]), "+f"(d[6]), "+f"(d[7]),
          "+f"(d[8]), "+f"(d[9]), "+f"(d[10]), "+f"(d[11]), "+f"(d[12]), "+f"(d[13]), "+f"(d[14]), "+f"(d[15]),
          "+f"(d[16]), "+f"(d[17]), "+f"(d[18]), "+f"(d[19]), "+f"(d[20]), "+f"(d[21]), "+f"(d[22]), "+f"(d[23]),
          "+f"(d[24]), "+f"(d[25]), "+f"(d[26]), "+f"(d[27]), "+f"(d[28]), "+f"(d[29]), "+f"(d[30]), "+f"(d[31]),
          "+f"(d[32]), "+f"(d[33]), "+f"(d[34]), "+f"(d[35]), "+f"(d[36]), "+f"(d[37]), "+f"(d[38]), "+f"(d[39]),
          "+f"(d[40]), "+f"(d[41]), "+f"(d[42]), "+f"(d[43]), "+f"(d[44]), "+f"(d[45]), "+f"(d[46]), "+f"(d[47]),
          "+f"(d[48]), "+f"(d[49]), "+f"(d[50]), "+f"(d[51]), "+f"(d[52]), "+f"(d[53]), "+f"(d[54]), "+f"(d[55]),
          "+f"(d[56]), "+f"(d[57]), "+f"(d[58]), "+f"(d[59]), "+f"(d[60]), "+f"(d[61]), "+f"(d[62]), "+f"(d[63])
        : "r"(a0), "r"(a1), "r"(a2), "r"(a3), "r"(blo), "r"(scale_d), "n"(TB), "r"(DESC_HI));
}
template <int TB>
__device__ __forceinline__ void wgmma_rs_n128_z(float (&d)[64], uint32_t a0, uint32_t a1, uint32_t a2, uint32_t a3, uint32_t blo) {
    asm volatile("{\n.reg .pred p;\n.reg .b64 db;\nsetp.ne.b32 p, %69, 0;\n"
        "mov.b64 db, {%68, %71};\n"
        "wgmma.mma_async.sync.aligned.m64n128k16.f32.bf16.bf16 "
        "{%0, %1, %2, %3, %4, %5, %6, %7, %8, %9, %10, %11, %12, %13, %14, %15, %16, %17, %18, %19, %20, %21, %22, %23, %24, %25, %26, %27, %28, %29, %30, %31, %32, %33, %34, %35, %36, %37, %38, %39, %40, %41, %42, %43, %44, %45, %46, %47, %48, %49, %50, %51, %52, %53, %54, %55, %56, %57, %58, %59, %60, %61, %62, %63}, {%64, %65, %66, %67}, db, p, 1, 1, %70;\n}\n"
        :
          "=f"(d[0]), "=f"(d[1]), "=f"(d[2]), "=f"(d[3]), "=f"(d[4]), "=f"(d[5]), "=f"(d[6]), "=f"(d[7]),
          "=f"(d[8]), "=f"(d[9]), "=f"(d[10]), "=f"(d[11]), "=f"(d[12]), "=f"(d[13]), "=f"(d[14]), "=f"(d[15]),
          "=f"(d[16]), "=f"(d[17]), "=f"(d[18]), "=f"(d[19]), "=f"(d[20]), "=f"(d[21]), "=f"(d[22]), "=f"(d[23]),
          "=f"(d[24]), "=f"(d[25]), "=f"(d[26]), "=f"(d[27]), "=f"(d[28]), "=f"(d[29]), "=f"(d[30]), "=f"(d[31]),
          "=f"(d[32]), "=f"(d[33]), "=f"(d[34]), "=f"(d[35]), "=f"(d[36]), "=f"(d[37]), "=f"(d[38]), "=f"(d[39]),
          "=f"(d[40]), "=f"(d[41]), "=f"(d[42]), "=f"(d[43]), "=f"(d[44]), "=f"(d[45]), "=f"(d[46]), "=f"(d[47]),
          "=f"(d[48]), "=f"(d[49]), "=f"(d[50]), "=f"(d[51]), "=f"(d[52]), "=f"(d[53]), "=f"(d[54]), "=f"(d[55]),
          "=f"(d[56]), "=f"(d[57]), "=f"(d[58]), "=f"(d[59]), "=f"(d[60]), "=f"(d[61]), "=f"(d[62]), "=f"(d[63])
        : "r"(a0), "r"(a1), "r"(a2), "r"(a3), "r"(blo), "n"(0), "n"(TB), "r"(DESC_HI));
}
template <int TA, int TB>
__device__ __forceinline__ void wgmma_ss_n128_z(float (&d)[64], uint32_t alo, uint32_t blo) {
    asm volatile("{\n.reg .pred p;\n.reg .b64 da, db;\nsetp.ne.b32 p, %66, 0;\n"
        "mov.b64 da, {%64, %69};\nmov.b64 db, {%65, %69};\n"
        "wgmma.mma_async.sync.aligned.m64n128k16.f32.bf16.bf16 "
        "{%0, %1, %2, %3, %4, %5, %6, %7, %8, %9, %10, %11, %12, %13, %14, %15, %16, %17, %18, %19, %20, %21, %22, %23, %24, %25, %26, %27, %28, %29, %30, %31, %32, %33, %34, %35, %36, %37, %38, %39, %40, %41, %42, %43, %44, %45, %46, %47, %48, %49, %50, %51, %52, %53, %54, %55, %56, %57, %58, %59, %60, %61, %62, %63}, da, db, p, 1, 1, %67, %68;\n}\n"
        :
          "=f"(d[0]), "=f"(d[1]), "=f"(d[2]), "=f"(d[3]), "=f"(d[4]), "=f"(d[5]), "=f"(d[6]), "=f"(d[7]),
          "=f"(d[8]), "=f"(d[9]), "=f"(d[10]), "=f"(d[11]), "=f"(d[12]), "=f"(d[13]), "=f"(d[14]), "=f"(d[15]),
          "=f"(d[16]), "=f"(d[17]), "=f"(d[18]), "=f"(d[19]), "=f"(d[20]), "=f"(d[21]), "=f"(d[22]), "=f"(d[23]),
          "=f"(d[24]), "=f"(d[25]), "=f"(d[26]), "=f"(d[27]), "=f"(d[28]), "=f"(d[29]), "=f"(d[30]), "=f"(d[31]),
          "=f"(d[32]), "=f"(d[33]), "=f"(d[34]), "=f"(d[35]), "=f"(d[36]), "=f"(d[37]), "=f"(d[38]), "=f"(d[39]),
          "=f"(d[40]), "=f"(d[41]), "=f"(d[42]), "=f"(d[43]), "=f"(d[44]), "=f"(d[45]), "=f"(d[46]), "=f"(d[47]),
          "=f"(d[48]), "=f"(d[49]), "=f"(d[50]), "=f"(d[51]), "=f"(d[52]), "=f"(d[53]), "=f"(d[54]), "=f"(d[55]),
          "=f"(d[56]), "=f"(d[57]), "=f"(d[58]), "=f"(d[59]), "=f"(d[60]), "=f"(d[61]), "=f"(d[62]), "=f"(d[63])
        : "r"(alo), "r"(blo), "n"(0), "n"(TA), "n"(TB), "r"(DESC_HI));
}

__device__ __forceinline__ uint32_t pack_bf16(float lo, float hi) {
    uint32_t r;
    asm("cvt.rn.bf16x2.f32 %0, %1, %2;" : "=r"(r) : "f"(hi), "f"(lo));
    return r;
}
__device__ __forceinline__ uint32_t add_bf16x2(uint32_t a, uint32_t b) {
    uint32_t r;
    asm("add.rn.bf16x2 %0, %1, %2;" : "=r"(r) : "r"(a), "r"(b));
    return r;
}
__device__ __forceinline__ float bf_lo(uint32_t v) { return __uint_as_float(v << 16); }
__device__ __forceinline__ float bf_hi(uint32_t v) { return __uint_as_float(v & 0xffff0000u); }
__device__ __forceinline__ float round_bf16(float v) { return __bfloat162float(__float2bfloat16_rn(v)); }
__device__ __forceinline__ float ex2(float x) {
    float y;
    asm("ex2.approx.ftz.f32 %0, %1;" : "=f"(y) : "f"(x));
    return y;
}
__device__ __forceinline__ float rcp(float x) {
    float y;
    asm("rcp.approx.ftz.f32 %0, %1;" : "=f"(y) : "f"(x));
    return y;
}
__device__ __forceinline__ void stg128(void* p, uint32_t a, uint32_t b, uint32_t c, uint32_t d) {
    asm volatile("st.global.v4.b32 [%0], {%1, %2, %3, %4};" ::"l"(p), "r"(a), "r"(b), "r"(c), "r"(d) : "memory");
}
__device__ __forceinline__ void stg128p(void* p, uint32_t a, uint32_t b, uint32_t c, uint32_t d, uint64_t pol) {
    asm volatile("st.global.L2::cache_hint.v4.b32 [%0], {%1, %2, %3, %4}, %5;" ::"l"(p), "r"(a), "r"(b), "r"(c), "r"(d), "l"(pol) : "memory");
}
__device__ __forceinline__ uint64_t policy_sel(bool first) {
    uint64_t p;
    asm("createpolicy.fractional.L2::evict_normal.b64 %0, 1.0;" : "=l"(p));
    return first ? policy_evict_first() : p;
}
__device__ __forceinline__ int perm_row(int t) { return (t & ~255) | (((0x78 >> (((t >> 6) & 3) * 2)) & 3) << 6) | (t & 63); }
__device__ __forceinline__ int unperm_row(int t) { return (t & ~255) | (((0x9C >> (((t >> 6) & 3) * 2)) & 3) << 6) | (t & 63); }

#define PROF(i)
#define PROFG(i)
#define PROFDUMP()
#define TR(i)
#define BP(r, i)
#define LP(i)

template <int I>
__device__ __forceinline__ void store_chunk(const float (&a)[64], __nv_bfloat16* row0, __nv_bfloat16* row1, float s0, float s1, uint64_t pol) {
    stg128p(row0 + 32 * I, pack_bf16(a[16 * I + 0] * s0, a[16 * I + 1] * s0), pack_bf16(a[16 * I + 4] * s0, a[16 * I + 5] * s0),
           pack_bf16(a[16 * I + 8] * s0, a[16 * I + 9] * s0), pack_bf16(a[16 * I + 12] * s0, a[16 * I + 13] * s0), pol);
    stg128p(row1 + 32 * I, pack_bf16(a[16 * I + 2] * s1, a[16 * I + 3] * s1), pack_bf16(a[16 * I + 6] * s1, a[16 * I + 7] * s1),
           pack_bf16(a[16 * I + 10] * s1, a[16 * I + 11] * s1), pack_bf16(a[16 * I + 14] * s1, a[16 * I + 15] * s1), pol);
}
template <int I>
struct IntT { static constexpr int value = I; };
template <class F>
__device__ __forceinline__ void for4(F f) { f(IntT<0>{}); f(IntT<1>{}); f(IntT<2>{}); f(IntT<3>{}); }

struct Prod {
    uint32_t smem, bars;
    uint32_t bo, par;
    uint32_t dst, fb;
    __device__ __forceinline__ void acquire(uint32_t o, uint32_t parity, uint32_t bytes) {
        mbar_wait(bars + BAR_EMPTY + o, parity);
        fb = bars + BAR_FULL + o;
        dst = smem + o * (SLOT / 8);
        w_expect_tx(fb, bytes);
    }
    __device__ __forceinline__ void next(uint32_t bytes) {
        acquire(bo, par, bytes);
        const bool wrap = bo == (NSLOT - 1) * 8;
        bo = wrap ? 0u : bo + 8;
        par ^= wrap ? 1u : 0u;
    }
};

__device__ __forceinline__ int item_p(int ca, int rd) {
    const int v = (rd & 1) ? (ca + 4) & 7 : ca;
    return (rd & 2) ? 7 - v : v;
}
__device__ __forceinline__ int kv_round(int i) { return (KVORDER >> (4 * i)) & 3; }
__device__ __forceinline__ int slot_a(int i) { return (0x5310 >> (4 * i)) & 15; }
__device__ __forceinline__ int slot_w(int m) { return (0x264 >> (4 * m)) & 15; }

__device__ __forceinline__ void producer(const Params& P, uint32_t smem, uint32_t bars, int ca, int cb, int rank) {
    Prod pr{smem, bars, 0u, 0u, 0u, 0u};
    {
        int m = 0;
        uint32_t lap = 1;
#pragma unroll 1
        for (int u = 0; u < 32; u++) {
            if (u >= 3) {
                const int v = (u == 3) ? 3 + ca : u + 7;
                if (v < 32 && (u == 3 || (v & 7) == ca)) w_tma_prefetch((v & 4) ? &P.wuv : &P.wuk, (cb + 8 * kv_round(v >> 3)) * 128 + rank * 64, (v & 3) * 128);
                if (u == 24) {
                    w_tma_prefetch(&P.wq, cb * 128 + rank * 64, ca * 64);
                    if (ca < 2) w_tma_prefetch(&P.wq, cb * 128 + rank * 64, (ca + 8) * 64);
                }
            }
            if (!FASTSTART || u > 0) pr.acquire(slot_w(m) * 8, lap ^ (m >> 1), SLOT);
            lap ^= m >> 1;
            m = (m == 2) ? 0 : m + 1;
            TR(1 + u);
            if (!FASTSTART || u > 0) w_tma_load_mc(pr.dst + rank * 16384, (u & 4) ? &P.wuv : &P.wuk, (cb + 8 * kv_round(u >> 3)) * 128 + rank * 64, (u & 3) * 128, pr.fb);
            if (u < 3) {
                pr.acquire(slot_a(u + 1) * 8, 1, SLOT);
                w_tma_load(pr.dst, &P.ckv, u * 128 + 128, (2 * ca + rank) * 128, pr.fb);
                w_tma_load(pr.dst + 16384, &P.ckv, u * 128 + 192, (2 * ca + rank) * 128, pr.fb);
            }
        }
    }
    PROF(1);
    mbar_wait(bars + BAR_DEP, 0);
#pragma unroll 1
    for (int rd = 0; rd < 4; rd++) {
        const int h = 8 * rd + cb, p = item_p(ca, rd);
#pragma unroll 1
        for (int ks = 0; ks < 10; ks++) {
            pr.next(SLOT);
            w_tma_load_mc(pr.dst + 16384 + rank * 8192, &P.wq, h * 128 + rank * 64, ks * 64, pr.fb);
            w_tma_load(pr.dst, &P.xn, ks * 64, 256 * p + 128 * rank, pr.fb);
        }
        PROF(8 + rd * 4);
        mbar_wait(bars + BAR_DEP + (1 + rd) * 8, 0);
        const int last = 4 * p + 3, top = h * 32 + last;
#pragma unroll 1
        for (int i = 0; i <= last; i++) {
            const int t = (i == 0) ? top - 1 : (i == last) ? h * 32 + 1 : (i & 1) ? top - 2 - i : top + 2 - i;
            pr.next(SLOT);
            const bool lastrd = (rd == 0) ? ((LASTRD & 1) && ca >= 8 - LASTN) : (rd == 1) ? ((LASTRD & 2) && (ca & 3) >= 4 - LASTN) : (rd == 2) ? ((LASTRD & 4) && (ca == 3 || (ca < 3 && (t & 31) >= 4 * p))) : (LASTRD & 8) != 0;
            if (lastrd) w_tma_load_mc_last(pr.dst + rank * 16384, &P.kv, rank * 64, t * 128, pr.fb);
            else w_tma_load_mc(pr.dst + rank * 16384, &P.kv, rank * 64, t * 128, pr.fb);
            if (i == 2) {
                if (rd < 3) {
                    w_tma_prefetch(&P.wq, (h + 8) * 128 + rank * 64, ca * 64);
                    if (ca < 2) w_tma_prefetch(&P.wq, (h + 8) * 128 + rank * 64, (ca + 8) * 64);
                } else {
#pragma unroll 1
                    for (int j = 0; j < 10; j++) {
                        const int tt = ca + (j >= 5 ? 8 : 0);
                        w_tma_prefetch(&P.wo, 320 * (cb & 1) + 64 * (j >= 5 ? j - 5 : j), (8 * (tt >> 2) + (cb & 6) + ((tt >> 1) & 1)) * 128 + (tt & 1) * 64 + rank * 32);
                    }
                }
            }
        }
        PROF(9 + rd * 4);
    }
    {
        const int n0 = 320 * (cb & 1), kg = cb >> 1;
#pragma unroll 1
        for (int t = 0; t < 16; t++) {
            const int h = 8 * (t >> 2) + 2 * kg + ((t >> 1) & 1), ks = t & 1;
            const int krow = h * 128 + ks * 64 + rank * 32;
            pr.next(SLOT);
            w_tma_load_mc(pr.dst + 16384 + rank * 8192, &P.wo, n0, krow, pr.fb);
            w_tma_load_mc(pr.dst + 16384 + rank * 8192 + 4096, &P.wo, n0 + 64, krow, pr.fb);
            mbar_wait(bars + BAR_DEP + (5 + (t >> 1)) * 8, 0);
            w_tma_load(pr.dst, &P.ctx, ks * 64, h * SEQ + 256 * ca + 128 * rank, pr.fb);
            pr.next(24576);
#pragma unroll
            for (int c = 0; c < 3; c++) w_tma_load_mc(pr.dst + rank * 12288 + c * 4096, &P.wo, n0 + 128 + 64 * c, krow, pr.fb);
        }
    }
}

struct Slot {
    uint32_t bo, dl, par;
};
struct Cons {
    uint32_t bars, rel;
    uint32_t dl0;
    uint32_t lane;
    Slot cur;
    __device__ __forceinline__ Slot slot(int s, uint32_t par) const { return Slot{(uint32_t)s * 8, dl0 + (uint32_t)s * (SLOT >> 4), par}; }
    __device__ __forceinline__ void wait(const Slot& s) const { mbar_wait(bars + BAR_FULL + s.bo, s.par); }
    __device__ __forceinline__ void release(uint32_t bo) const {
        asm volatile("{\n.reg .pred p;\nsetp.lt.u32 p, %1, 2;\n@p mbarrier.arrive.shared::cluster.b64 _, [%0];\n}\n" ::"r"(rel + bo), "r"(lane) : "memory");
    }
    __device__ __forceinline__ Slot next() {
        const Slot s = cur;
        const bool wrap = s.bo == (NSLOT - 1) * 8;
        cur.bo = wrap ? 0u : s.bo + 8;
        cur.dl = wrap ? dl0 : s.dl + (SLOT >> 4);
        cur.par = s.par ^ (wrap ? 1u : 0u);
        return s;
    }
};
__host__ __device__ constexpr uint32_t lbo(uint32_t bytes) { return (bytes >> 4) << 16; }

__device__ __forceinline__ float div640(float x) {
    const float q = x * (1.0f / DM);
    return fmaf(fmaf(-q, (float)DM, x), 1.0f / DM, q);
}
__device__ __forceinline__ float sqrt_approx(float x) {
    float y;
    asm("sqrt.approx.ftz.f32 %0, %1;" : "=f"(y) : "f"(x));
    return y;
}
struct LayerNorm {
    uint4 xv[5], wv[5];
    float mean, inv, r;
    static __device__ __forceinline__ float half_sum(float v) {
#pragma unroll
        for (int o = 8; o > 0; o >>= 1) v += __shfl_xor_sync(0xffffffffu, v, o);
        return v;
    }
    __device__ __forceinline__ void load(const __nv_bfloat16* x, const __nv_bfloat16* wr, int t, int l) {
#pragma unroll
        for (int i = 0; i < 5; i++) {
            xv[i] = ldg_stream(reinterpret_cast<const uint4*>(x + t * DM) + l + 16 * i);
            wv[i] = __ldg(reinterpret_cast<const uint4*>(wr) + l + 16 * i);
        }
    }
    __device__ __forceinline__ void stat1() {
        float a[4] = {0.f, 0.f, 0.f, 0.f};
#pragma unroll
        for (int i = 0; i < 20; i++) { const uint32_t u = (&xv[i >> 2].x)[i & 3]; a[i & 3] += bf_lo(u) + bf_hi(u); }
        mean = div640(half_sum((a[0] + a[1]) + (a[2] + a[3])));
        r = 0.f;
    }
    template <int H>
    __device__ __forceinline__ void stat2() {
        float a[4] = {r, 0.f, 0.f, 0.f};
#pragma unroll
        for (int i = H ? 12 : 0; i < (H ? 20 : 12); i++) {
            uint32_t u = (&xv[i >> 2].x)[i & 3];
            asm volatile("" : "+r"(u));
            const float d0 = bf_lo(u) - mean, d1 = bf_hi(u) - mean;
            a[i & 3] = fmaf(d0, d0, fmaf(d1, d1, a[i & 3]));
        }
        r = (a[0] + a[1]) + (a[2] + a[3]);
        if (H) {
            inv = rcp(round_bf16(sqrt_approx(round_bf16(round_bf16(div640(half_sum(r))) + 1e-5f))));
            r = 0.f;
        }
    }
    template <int I>
    __device__ __forceinline__ void piece(__nv_bfloat16* out, int t, int l) {
        const uint32_t nmb = pack_bf16(-mean, -mean);
        uint32_t o[4], z[4];
        float a[4];
#pragma unroll
        for (int j = 0; j < 4; j++) {
            const uint32_t u = (&xv[I].x)[j], w = (&wv[I].x)[j];
            const uint32_t d = add_bf16x2(u, nmb);
            o[j] = pack_bf16(bf_lo(d) * inv, bf_hi(d) * inv);
            z[j] = add_bf16x2(u, o[j]);
            a[j] = fmaf(bf_hi(o[j]), bf_hi(w), bf_lo(o[j]) * bf_lo(w));
        }
        r += (a[0] + a[1]) + (a[2] + a[3]);
        stg128(g_xn + perm_row(t) * DM + 8 * (l + 16 * I), o[0], o[1], o[2], o[3]);
        stg128p(out + t * DM + 8 * (l + 16 * I), z[0], z[1], z[2], z[3], policy_sel(EFMASK & 1));
        if (I == 4) {
            r = half_sum(r);
            if (l == 0) g_r[t] = round_bf16(r);
        }
    }
};

constexpr float SM_SCALE = 0.08838834764831845f * 1.4426950408889634f;

template <int J0, int J1>
__device__ __forceinline__ void exp_part(float (&s)[64], float n0, float n1, float& r0, float& r1) {
    float a1 = 0.f, b1 = 0.f;
#pragma unroll
    for (int j = J0; j < J1; j++) {
        s[4 * j + 0] = ex2(fmaf(s[4 * j + 0], SM_SCALE, n0));
        s[4 * j + 1] = ex2(fmaf(s[4 * j + 1], SM_SCALE, n0));
        s[4 * j + 2] = ex2(fmaf(s[4 * j + 2], SM_SCALE, n1));
        s[4 * j + 3] = ex2(fmaf(s[4 * j + 3], SM_SCALE, n1));
        r0 += s[4 * j + 0]; r1 += s[4 * j + 2];
        if (j == J0) { a1 = s[4 * j + 1]; b1 = s[4 * j + 3]; } else { a1 += s[4 * j + 1]; b1 += s[4 * j + 3]; }
    }
    r0 += a1;
    r1 += b1;
}
__device__ __forceinline__ void sched_barrier(float x, float y, uint32_t scratch) {
    asm volatile("{\n.reg .pred p;\nsetp.lt.f32 p, %0, 0f00000000;\n@p st.shared.f32 [%2], %1;\n}\n" ::"f"(x), "f"(y), "r"(scratch) : "memory");
}
__device__ __forceinline__ void pack_tile(const float (&s)[64], uint32_t (&p)[32]) {
#pragma unroll
    for (int i = 0; i < 32; i++) p[i] = pack_bf16(s[2 * i], s[2 * i + 1]);
}
template <bool ZERO>
__device__ __forceinline__ void gemm_rs(float (&d)[64], const uint32_t (&a)[32], uint32_t dl, int acc = 1) {
    const uint32_t b = dl + lbo(16384);
    if (ZERO) wgmma_rs_n128_z<1>(d, a[0], a[1], a[2], a[3], b);
#pragma unroll
    for (int k = ZERO ? 1 : 0; k < 8; k++) wgmma_rs_n128<1>(d, a[4 * k], a[4 * k + 1], a[4 * k + 2], a[4 * k + 3], b + k * 128, k ? 1 : acc);
}
template <int ZERO>
__device__ __forceinline__ void gemm_q(float (&d)[64], uint32_t dl, int role) {
    const uint32_t a = dl + role * 512 + lbo(16), b = dl + 1024 + lbo(8192);
    if (ZERO) wgmma_ss_n128_z<0, 1>(d, a, b);
#pragma unroll
    for (int k = ZERO ? 1 : 0; k < 4; k++) wgmma_ss_n128<0, 1>(d, a + k * 2, b + k * 128, 1);
}
template <bool KT, bool ZERO, int K0, int K1>
__device__ __forceinline__ void gemm_kv(float (&d)[64], uint32_t ckv, uint32_t wt, int wg) {
    if (KT) {
        const uint32_t a = wt + wg * 1024 + lbo(16), b = ckv + lbo(16);
        if (ZERO) wgmma_ss_n128_z<1, 0>(d, a, b);
#pragma unroll
        for (int k = ZERO ? 1 : K0; k < K1; k++) wgmma_ss_n128<1, 0>(d, a + k * 128, b + (k >> 2) * 1024 + (k & 3) * 2, 1);
    } else {
        const uint32_t a = ckv + wg * 512 + lbo(16), b = wt + lbo(16384);
        if (ZERO) wgmma_ss_n128_z<0, 1>(d, a, b);
#pragma unroll
        for (int k = ZERO ? 1 : K0; k < K1; k++) wgmma_ss_n128<0, 1>(d, a + (k >> 2) * 1024 + (k & 3) * 2, b + k * 128, 1);
    }
}
__device__ __forceinline__ void mma16816(float& d0, float& d1, float& d2, float& d3, uint32_t a0, uint32_t a1, uint32_t a2, uint32_t a3, uint32_t b0, uint32_t b1) {
    asm volatile("mma.sync.aligned.m16n8k16.row.col.f32.bf16.bf16.f32 {%0,%1,%2,%3}, {%4,%5,%6,%7}, {%8,%9}, {%0,%1,%2,%3};"
                 : "+f"(d0), "+f"(d1), "+f"(d2), "+f"(d3) : "r"(a0), "r"(a1), "r"(a2), "r"(a3), "r"(b0), "r"(b1));
}
__device__ __forceinline__ uint32_t ld_pair(const __nv_bfloat16* p) {
    const unsigned short* u = reinterpret_cast<const unsigned short*>(p);
    return (uint32_t)__ldcg(u) | ((uint32_t)__ldcg(u + 128) << 16);
}
__device__ __forceinline__ void attention_exact(float (&o)[64], const uint32_t (&qf)[32], float& l0, float& l1, int h, int nblk, int rr, int lane) {
    const int q = lane & 3, lr = lane >> 2;
    float m0 = -INFINITY, m1 = -INFINITY;
    l0 = 0.f; l1 = 0.f;
#pragma unroll
    for (int i = 0; i < 64; i++) o[i] = 0.f;
#pragma unroll 1
    for (int cidx = 0; cidx < nblk * 8; cidx++) {
        const int kc = cidx & 7;
        const __nv_bfloat16* kt = g_kv + (size_t)((h * 16 + (cidx >> 3)) * 2) * 16384;
        float sc[8];
#pragma unroll
        for (int i = 0; i < 8; i++) sc[i] = 0.f;
#pragma unroll
        for (int kk = 0; kk < 8; kk++)
#pragma unroll
            for (int nt = 0; nt < 2; nt++) {
                const __nv_bfloat16* b = kt + (16 * kk + 2 * q) * 128 + 16 * kc + 8 * nt + lr;
                mma16816(sc[4 * nt], sc[4 * nt + 1], sc[4 * nt + 2], sc[4 * nt + 3], qf[4 * kk], qf[4 * kk + 1], qf[4 * kk + 2], qf[4 * kk + 3],
                         ld_pair(b), ld_pair(b + 8 * 128));
            }
        const int lim = rr + ((nblk - 1) - (cidx >> 3)) * 128 - 32 * (kc >> 1) - 4 * (kc & 1);
#pragma unroll
        for (int i = 0; i < 8; i++)
            if (2 * (i >> 2) + (i & 1) > lim + 4 * (i & 2)) sc[i] = -INFINITY;
        float x0 = fmaxf(fmaxf(sc[0], sc[1]), fmaxf(sc[4], sc[5])), x1 = fmaxf(fmaxf(sc[2], sc[3]), fmaxf(sc[6], sc[7]));
        x0 = fmaxf(x0, __shfl_xor_sync(0xffffffffu, x0, 1)); x1 = fmaxf(x1, __shfl_xor_sync(0xffffffffu, x1, 1));
        x0 = fmaxf(x0, __shfl_xor_sync(0xffffffffu, x0, 2)); x1 = fmaxf(x1, __shfl_xor_sync(0xffffffffu, x1, 2));
        x0 = fmaxf(x0, m0); x1 = fmaxf(x1, m1);
        const float a0 = ex2((m0 - x0) * SM_SCALE), a1 = ex2((m1 - x1) * SM_SCALE);
        m0 = x0; m1 = x1;
#pragma unroll
        for (int i = 0; i < 8; i++) sc[i] = ex2((sc[i] - ((i & 2) ? m1 : m0)) * SM_SCALE);
        l0 = l0 * a0 + (sc[0] + sc[1]) + (sc[4] + sc[5]);
        l1 = l1 * a1 + (sc[2] + sc[3]) + (sc[6] + sc[7]);
        const uint32_t p0 = pack_bf16(sc[0], sc[1]), p1 = pack_bf16(sc[2], sc[3]), p2 = pack_bf16(sc[4], sc[5]), p3 = pack_bf16(sc[6], sc[7]);
        const __nv_bfloat16* vb = kt + 16384 + (16 * kc + 2 * q) * 128 + lr;
#pragma unroll
        for (int nt = 0; nt < 16; nt++) {
            o[4 * nt] *= a0; o[4 * nt + 1] *= a0; o[4 * nt + 2] *= a1; o[4 * nt + 3] *= a1;
            mma16816(o[4 * nt], o[4 * nt + 1], o[4 * nt + 2], o[4 * nt + 3], p0, p1, p2, p3, ld_pair(vb + 8 * nt), ld_pair(vb + 8 * nt + 8 * 128));
        }
    }
}

__device__ __forceinline__ void signal(uint32_t bars, int wg, int e, int lane) {
    __syncwarp();
    asm volatile("{\n.reg .pred p;\nsetp.eq.u32 p, %1, 0;\n@p mbarrier.arrive.shared::cta.b64 _, [%0];\n}\n" ::"r"(bars + BAR_SIG + (wg * 9 + e) * 8), "r"(lane) : "memory");
}

__device__ __forceinline__ void consumer(const Params& P, uint32_t smem, uint32_t bars, int ca, int cb, int rank, int wg) {
    const int lane = threadIdx.x & 31, w = (threadIdx.x >> 5) & 3, q = lane & 3, lr = lane >> 2;
    PROF(7);
    cluster_wait();
    Cons c{bars, mapa(bars + BAR_EMPTY, lane & 1), (smem & 0x3FFFF) >> 4, (uint32_t)lane, Slot{0u, (smem & 0x3FFFF) >> 4, 1u}};
    PROFG(180);
    PROF(1);
    float o[64], s[64];
    uint32_t pend;
    __nv_bfloat16* ep_ptr;
    int ep_step;
    {
        const int ln_t = blockIdx.x * 16 + wg * 8 + w * 2 + (lane >> 4);
        const int krow = 64 * wg + 16 * w + lr;
        const int vrow = 64 * wg + 32 * (w >> 1) + 8 * (lr >> 1) + 4 * (w & 1) + (lr & 1);
        ep_step = 2 * 128;
        int m = 0;
        uint32_t lap = 0;
        LayerNorm ln;
        auto step = [&](auto kt, auto kc, float (&d)[64], int hh) {
            const Slot sa = c.slot(slot_a(kc.value), 0), sw = c.slot(slot_w(m), lap ^ (m >> 1));
            lap ^= m >> 1;
            m = (m == 2) ? 0 : m + 1;
            TR(1 + (hh * 8 + (kt.value ? 0 : 4) + kc.value) * 2);
            if (kt.value && hh == 0) c.wait(sa);
            c.wait(sw);
            TR(2 + (hh * 8 + (kt.value ? 0 : 4) + kc.value) * 2);
            wgmma_fence();
            gemm_kv<kt.value, kc.value == 0, 0, KVSPLIT>(d, sa.dl, sw.dl, wg);
            wgmma_commit();
            wgmma_wait<1>();
            if (!(kt.value && kc.value == 0 && hh == 0)) c.release(pend);
            if (!kt.value && kc.value > 0 && hh == 3) c.release(slot_a(kc.value - 1) * 8);
            pend = sw.bo;
            wgmma_fence();
            gemm_kv<kt.value, false, KVSPLIT, 8>(d, sa.dl, sw.dl, wg);
            wgmma_commit();
        };
#pragma unroll 1
        for (int hh = 0; hh < 4; hh++) {
            __nv_bfloat16* base = g_kv + (size_t)(((cb + 8 * kv_round(hh)) * 16 + 2 * ca + rank) * 2) * 16384 + 8 * q;
            auto ln_stage = [&](auto pos) {
                constexpr int j = (pos.value + 8 - LNOFF % 8) % 8;
                if (hh == wg * LNSTAG + (LNOFF + j) / 8) {
                    if (j == 0) ln.stat1();
                    if (j == 1) ln.template stat2<0>();
                    if (j == 2) ln.template stat2<1>();
                    if constexpr (j >= 3) ln.template piece<j - 3>(P.out, ln_t, lane & 15);
                    if (j == 7) signal(bars, wg, 0, lane);
                }
                if (pos.value == (LNOFF - LNLEAD) % 8 && hh == wg * LNSTAG + (LNOFF - LNLEAD) / 8) ln.load(P.x, P.wr, ln_t, lane & 15);
            };
            for4([&](auto kc) {
                step(TrueT{}, kc, s, hh);
                if (hh > 0) {
                    if (kc.value == 0) fence_regs(o);
                    store_chunk<kc.value>(o, ep_ptr, ep_ptr + ep_step, 1.f, 1.f, policy_sel(false));
                    if (kc.value == 3) signal(bars, wg, hh, lane);
                }
                ln_stage(kc);
            });
            for4([&](auto kc) {
                step(FalseT{}, kc, o, hh);
                if (kc.value == 0) fence_regs(s);
                store_chunk<kc.value>(s, base + krow * 128, base + (krow + 8) * 128, 1.f, 1.f, policy_sel(false));
                ln_stage(IntT<kc.value + 4>{});
            });
            PROF(24 + hh);
            if (hh == 1) PROFG(181);
            ep_ptr = base + 16384 + vrow * 128;
        }
    }
    PROFG(182);
    PROF(2);
    uint32_t pf[32];
    {
        uint32_t qf[32];
        float l0 = 0.25f, l1 = 0.25f;
        const int bar_me = 2 + wg, bar_other = 3 - wg;
#pragma unroll 1
        for (int rd = 0; rd < 4; rd++) {
            const int h = 8 * rd + cb, p = item_p(ca, rd);
            const int role = wg ^ (rd & 1);
            const int nrest = 2 * p + role;
            Slot kfirst;
            const int lim = 64 * (role ^ rank) + 16 * w + lr - 8 * q;
            const uint64_t pol = policy_sel(((EFMASK & 4) && rd == 1) || ((EFMASK & 8) && rd == 2));
            {
                auto qstep = [&](auto zero, int ks) {
                    const Slot sl = c.next();
                    c.wait(sl);
                    BP(2, 5 + 3 * ks);
                    wgmma_fence();
                    gemm_q<zero.value>(s, sl.dl, role);
                    wgmma_commit();
                    wgmma_wait<1>();
                    c.release(pend);
                    pend = sl.bo;
                };
                qstep(TrueT{}, 0);
                if (rd == 0) c.release(slot_a(3) * 8);
                fence_regs(o);
                l0 += __shfl_xor_sync(0xffffffffu, l0, 1); l1 += __shfl_xor_sync(0xffffffffu, l1, 1);
                l0 += __shfl_xor_sync(0xffffffffu, l0, 2); l1 += __shfl_xor_sync(0xffffffffu, l1, 2);
                l0 = rcp(l0); l1 = rcp(l1);
                for4([&](auto i) {
                    constexpr int B = 16 * i.value;
#pragma unroll
                    for (int r = 0; r < 2; r++) {
                        qstep(FalseT{}, 1 + 2 * i.value + r);
                        const float f = r ? l1 : l0;
                        stg128p(ep_ptr + r * ep_step + 2 * B, pack_bf16(o[B + 2 * r] * f, o[B + 2 * r + 1] * f), pack_bf16(o[B + 2 * r + 4] * f, o[B + 2 * r + 5] * f),
                                pack_bf16(o[B + 2 * r + 8] * f, o[B + 2 * r + 9] * f), pack_bf16(o[B + 2 * r + 12] * f, o[B + 2 * r + 13] * f), pol);
#pragma unroll
                        for (int k = 0; k < 8; k++) {
                            float& v = o[B + 4 * (k >> 1) + 2 * r + (k & 1)];
                            v = (2 * B + k > lim + 8 * r) ? -1e30f : 0.f;
                            asm volatile("" : "+f"(v));
                        }
                    }
                });
                signal(bars, wg, 4 + rd, lane);
                PROF(11 + rd * 4);
                qstep(FalseT{}, 9);
                if (!role) { const Slot sl = c.next(); c.wait(sl); c.release(sl.bo); }
                kfirst = c.next();
                c.wait(kfirst);
                wgmma_wait<0>();
                BP(2, 34);
                c.release(pend);
                fence_regs(s);
                pack_tile(s, qf);
            }
            PROF(8 + rd * 4);
            fence_regs(qf); fence_regs(o);
            if (PINGPONG && !role) named_sync(bar_me, 256);
            BP(2, 36);
            wgmma_fence();
            gemm_rs<false>(o, qf, kfirst.dl);
            wgmma_commit();
            if (PINGPONG) named_arrive(bar_other, 256);
            if (!role) { const Slot sl = c.next(); c.wait(sl); c.release(sl.bo); }
            wgmma_wait<0>();
            BP(2, 38);
            fence_regs(o);
            c.release(kfirst.bo);
            float n0 = fmaxf(fmaxf(fmaxf(o[0], o[1]), fmaxf(o[4], o[5])), fmaxf(fmaxf(o[8], o[9]), fmaxf(o[12], o[13])));
            float n1 = fmaxf(fmaxf(fmaxf(o[2], o[3]), fmaxf(o[6], o[7])), fmaxf(fmaxf(o[10], o[11]), fmaxf(o[14], o[15])));
            n0 = __shfl_sync(0xffffffffu, n0, lane & 28); n1 = __shfl_sync(0xffffffffu, n1, lane & 28);
            n0 *= -SM_SCALE; n1 *= -SM_SCALE;
            l0 = 0.f; l1 = 0.f;
#pragma unroll
            for (int i = 0; i < 64; i++) s[i] = o[i];
            exp_part<0, 8>(s, n0, n1, l0, l1);
#pragma unroll
            for (int i = 0; i < 16; i++) pf[i] = pack_bf16(s[2 * i], s[2 * i + 1]);
            if (role != rank) {
                exp_part<8, 16>(s, n0, n1, l0, l1);
#pragma unroll
                for (int i = 16; i < 32; i++) pf[i] = pack_bf16(s[2 * i], s[2 * i + 1]);
            } else {
#pragma unroll
                for (int i = 16; i < 32; i++) pf[i] = 0u;
            }
            PROF(9 + rd * 4);
#pragma unroll 1
            for (int it = 0; it < nrest; it++) {
                const Slot sk = c.next(), sv = c.next();
                LP(0);
                c.wait(sk);
                c.wait(sv);
                fence_regs(o); fence_regs(pf);
                LP(1);
                if (PINGPONG) named_sync(bar_me, 256);
                LP(2);
                if (it < 3) BP(2, 42 + 4 * it);
                if (it >= nrest - 2) BP(1, 62 + 4 * (it - nrest + 2));
                wgmma_fence();
                gemm_rs<true>(s, qf, sk.dl);
                wgmma_commit();
                gemm_rs<false>(o, pf, sv.dl, it);
                wgmma_commit();
                if (PINGPONG) named_arrive(bar_other, 256);
                LP(3);
                wgmma_wait<1>();
                LP(4);
                c.release(sk.bo);
                fence_regs(s);
                exp_part<0, SPLITJ>(s, n0, n1, l0, l1);
                sched_barrier(l0, l1, bars + MISC_OFF + 16);
                LP(5);
                wgmma_wait<0>();
                LP(6);
                c.release(sv.bo);
                fence_regs(o); fence_regs(pf);
                exp_part<SPLITJ, 16>(s, n0, n1, l0, l1);
                pack_tile(s, pf);
            }
            PROF(10 + rd * 4);
            PROFG(183 + rd);
            const Slot sv = c.next();
            BP(1, 0);
            c.wait(sv);
            if (nrest == 0) {
#pragma unroll
                for (int i = 0; i < 64; i++) o[i] = 0.f;
            }
            if (__builtin_expect(__any_sync(0xffffffffu, !(l0 < 0x1p60f && l1 < 0x1p60f)), 0)) {
                attention_exact(o, qf, l0, l1, h, nrest + 1, lim, lane);
#pragma unroll
                for (int i = 0; i < 32; i++) pf[i] = 0u;
            }
            fence_regs(o); fence_regs(pf);
            if (PINGPONG && !role) named_sync(bar_me, 256);
            BP(1, 2);
            wgmma_fence();
            gemm_rs<false>(o, pf, sv.dl);
            wgmma_commit();
            pend = sv.bo;
            ep_ptr = g_ctx + (size_t)(h * SEQ + 256 * p + 128 * rank + 64 * role + 16 * w + lr) * HD + 8 * q;
            ep_step = 8 * HD;
        }
        l0 += __shfl_xor_sync(0xffffffffu, l0, 1); l1 += __shfl_xor_sync(0xffffffffu, l1, 1);
        l0 += __shfl_xor_sync(0xffffffffu, l0, 2); l1 += __shfl_xor_sync(0xffffffffu, l1, 2);
        l0 = rcp(l0); l1 = rcp(l1);
        wgmma_wait<0>();
        c.release(pend);
        fence_regs(o); fence_regs(pf);
#pragma unroll
        for (int i = 0; i < 32; i++) pf[i] = pack_bf16(o[2 * i] * ((i & 1) ? l1 : l0), o[2 * i + 1] * ((i & 1) ? l1 : l0));
    }
    PROFG(187);
    PROF(3);
    {
        float a1[64], a2[96];
        uint32_t px = 0, py = 0;
        auto mma1 = [&](const Slot& x, int acc) {
#pragma unroll
            for (int k = 0; k < 4; k++) wgmma_ss_n128<0, 1>(a1, x.dl + wg * 512 + lbo(16) + k * 2, x.dl + 1024 + lbo(4096) + (k >> 1) * 512 + (k & 1) * 128, k ? 1 : acc);
        };
        auto mma2 = [&](const Slot& x, const Slot& y, int acc) {
#pragma unroll
            for (int k = 0; k < 4; k++) wgmma_ss_n192<0, 1>(a2, x.dl + wg * 512 + lbo(16) + k * 2, y.dl + lbo(4096) + (k >> 1) * 768 + (k & 1) * 128, k ? 1 : acc);
        };
#pragma unroll 1
        for (int t = 0; t < (EARLYSEND ? 14 : 16); t++) {
            const Slot sx = c.next(), sy = c.next();
            c.wait(sx);
            wgmma_fence();
            mma1(sx, t);
            wgmma_commit();
            wgmma_wait<1>();
            if (t > 0) { c.release(px); c.release(py); }
            px = sx.bo; py = sy.bo;
            c.wait(sy);
            wgmma_fence();
            mma2(sx, sy, t);
            wgmma_commit();
            if (t == 0) {
#pragma unroll
                for (int i = 0; i < 4; i++) stg128(ep_ptr + 32 * i, pf[8 * i], pf[8 * i + 2], pf[8 * i + 4], pf[8 * i + 6]);
            }
            if (t == 1) {
#pragma unroll
                for (int i = 0; i < 4; i++) stg128(ep_ptr + 8 * HD + 32 * i, pf[8 * i + 1], pf[8 * i + 3], pf[8 * i + 5], pf[8 * i + 7]);
                signal(bars, wg, 8, lane);
            }
        }
        if (EARLYSEND) {
            const Slot x0 = c.next(), y0 = c.next(), x1 = c.next(), y1 = c.next();
            c.wait(x0);
            c.wait(y0);
            wgmma_fence();
            mma2(x0, y0, 1);
            wgmma_commit();
            wgmma_wait<1>();
            c.release(px); c.release(py);
            c.wait(x1);
            c.wait(y1);
            wgmma_fence();
            mma2(x1, y1, 1);
            wgmma_commit();
            mma1(x0, 1);
            mma1(x1, 1);
            wgmma_commit();
        }
        const int cw = __reduce_or_sync(0xffffffffu, wg * 4 + w);
        Slot st = c.next();
        if (cw >= 3) st = c.next();
        if (cw >= 6) st = c.next();
        const uint32_t stage = smem + st.bo * (SLOT / 8) + (cw % 3) * 10240;
        const int orow = unperm_row(256 * ca + 128 * rank + 16 * cw), ocol = 320 * (cb & 1);
        const uint32_t sa = stage + ((lane & 7) + (lane & 8)) * 128, sx = (lane >> 4) ^ (lane & 7);
        auto send = [&](auto c0, auto c1) {
#pragma unroll
            for (int ch = c0.value; ch < c1.value; ch++) {
#pragma unroll
                for (int i = 0; i < 4; i++) {
                    uint32_t r[4];
#pragma unroll
                    for (int e = 0; e < 4; e++) {
                        const int k = 32 * ch + 8 * i + 2 * e;
                        r[e] = (ch < 2) ? pack_bf16(a1[k & 63], a1[(k & 63) + 1]) : pack_bf16(a2[ch < 2 ? 0 : k - 64], a2[ch < 2 ? 1 : k - 63]);
                    }
                    asm volatile("stmatrix.sync.aligned.m8n8.x4.shared.b16 [%0], {%1, %2, %3, %4};"
                                 ::"r"(sa + ch * 2048 + ((sx ^ (2 * i)) << 4)), "r"(r[0]), "r"(r[1]), "r"(r[2]), "r"(r[3]) : "memory");
                }
                if (FENCE_EACH || ch == c1.value - 1) {
                    asm volatile("fence.proxy.async.shared::cta;" ::: "memory");
                    __syncwarp();
#pragma unroll
                    for (int b = FENCE_EACH ? ch : c0.value; b <= ch; b++)
                        asm volatile(ELECT "cp.reduce.async.bulk.tensor.2d.global.shared::cta.add.bulk_group [%0, {%2, %3}], [%1];\n}\n"
                                     ::"l"(&P.outm), "r"(stage + b * 2048), "r"(ocol + 64 * b), "r"(orow) : "memory");
                }
            }
        };
        mbar_wait(bars + BAR_EMPTY + st.bo, st.par ^ 1);
        mbar_wait(bars + BAR_DEP + 13 * 8, 0);
        wgmma_wait<EARLYSEND>();
        fence_regs(a2);
        send(IntT<2>{}, IntT<5>{});
        wgmma_wait<0>();
        fence_regs(a1);
        PROFG(188);
        PROF(4);
        send(IntT<0>{}, IntT<2>{});
        PROF(5);
        asm volatile("cp.async.bulk.commit_group;\ncp.async.bulk.wait_group.read 0;" ::: "memory");
    }
    PROF(6);
}

__device__ __forceinline__ void mma_rows(float (&acc)[8][4], uint32_t a0, uint32_t a2, const uint4& w0, const uint4& w1, const uint4& w2, const uint4& w3) {
    const uint32_t r0[4] = {w0.x, w0.y, w0.z, w0.w}, r1[4] = {w1.x, w1.y, w1.z, w1.w};
    const uint32_t r2[4] = {w2.x, w2.y, w2.z, w2.w}, r3[4] = {w3.x, w3.y, w3.z, w3.w};
#pragma unroll
    for (int i = 0; i < 4; i++) {
        mma16816(acc[2 * i][0], acc[2 * i][1], acc[2 * i][2], acc[2 * i][3], a0, 0u, a2, 0u, __byte_perm(r0[i], r1[i], 0x5410), __byte_perm(r2[i], r3[i], 0x5410));
        mma16816(acc[2 * i + 1][0], acc[2 * i + 1][1], acc[2 * i + 1][2], acc[2 * i + 1][3], a0, 0u, a2, 0u, __byte_perm(r0[i], r1[i], 0x7632), __byte_perm(r2[i], r3[i], 0x7632));
    }
}

__device__ __forceinline__ void mod_ffn(const Params& P, uint8_t* sm, int mc  ) {
    const uint32_t epoch = read_epoch();
    const int tid = threadIdx.x - 128, lane = tid & 31, cw = tid >> 5, q = lane & 3, lr = lane >> 2;
    uint32_t* xs = reinterpret_cast<uint32_t*>(sm);
    uint32_t* wmax = xs + 8 * 324;
    int* sidx = reinterpret_cast<int*>(wmax + 16);
    const int fg = cw * 4 + mc;
    const uint32_t ring = smem_u32(sm) + 16384 + cw * 24576, rbar = smem_u32(sm) + 12288 + cw * 32;
    auto issue = [&](int u, int st) {
        if (lane == 0 && u < 30) {
            mbar_expect_tx(rbar + st * 8, 8192);
            if (u < 20) {
                tma_load_stream(ring + st * 8192, &P.wg, fg * 64, u * 32, rbar + st * 8);
                tma_load_stream(ring + st * 8192 + 4096, &P.wu, fg * 64, u * 32, rbar + st * 8);
            } else {
                tma_load_stream(ring + st * 8192, &P.wd, (u - 20) * 64, fg * 64, rbar + st * 8);
            }
        }
    };
    if (lane == 0) {
        mbar_init(rbar, 1); mbar_init(rbar + 8, 1); mbar_init(rbar + 16, 1);
        asm volatile("fence.mbarrier_init.release.cluster;" ::: "memory");
    }
    if (tid == 0) flag_wait<100>(F_LN, 256u * (epoch + 1));
    named_sync(1, 256);
    PROF(1);
    if (fg < 27) {
#pragma unroll 1
        for (int u = 0; u < 3; u++) issue(u, u);
    }
    PROF(2);
    uint32_t key[8];
#pragma unroll
    for (int i = 0; i < 8; i++) {
        const int t = tid + 256 * i;
        uint32_t b = __float_as_uint(__ldcg(g_r + t) + 0.f) >> 16;
        b = (b & 0x8000u) ? (~b & 0xffffu) : (b | 0x8000u);
        key[i] = (b << 16) | (uint32_t)(0xffff - t);
    }
#pragma unroll 1
    for (int rnd = 0; rnd < 8; rnd++) {
        uint32_t mx = key[0];
#pragma unroll
        for (int i = 1; i < 8; i++) mx = max(mx, key[i]);
        mx = __reduce_max_sync(0xffffffffu, mx);
        if (lane == 0) wmax[(rnd & 1) * 8 + cw] = mx;
        named_sync(1, 256);
        mx = __reduce_max_sync(0xffffffffu, wmax[(rnd & 1) * 8 + (lane & 7)]);
#pragma unroll
        for (int i = 0; i < 8; i++) if (key[i] == mx) key[i] = 0;
        if (tid == 0) sidx[rnd] = 0xffff - (int)(mx & 0xffffu);
    }
    named_sync(1, 256);
    {
        const uint32_t* src = reinterpret_cast<const uint32_t*>(g_xn + (size_t)perm_row(sidx[cw]) * DM);
#pragma unroll 2
        for (int i = lane; i < 320; i += 32) xs[cw * 324 + i] = __ldcg(src + i);
    }
    named_sync(1, 256);
    PROF(3);
    if (fg < 27) {
        float g[8][4], v[8][4];
        uint32_t hp[8];
#pragma unroll
        for (int i = 0; i < 8; i++)
#pragma unroll
            for (int e = 0; e < 4; e++) { g[i][e] = 0.f; v[i][e] = 0.f; }
        int st = 0, ph = 0;
#pragma unroll 1
        for (int u = 0; u < 60; u++) {
            if (!(u & 1)) mbar_wait(rbar + st * 8, ph);
            uint4 a[8];
#pragma unroll
            for (int r = 0; r < 8; r++) {
                const int row = (u < 40) ? 32 * (r >> 2) + 16 * (u & 1) + 2 * q + (r & 1) + 4 * (r & 2) : 16 * q + 8 * (u & 1) + r;
                asm volatile("ld.shared.v4.b32 {%0, %1, %2, %3}, [%4];" : "=r"(a[r].x), "=r"(a[r].y), "=r"(a[r].z), "=r"(a[r].w)
                             : "r"(ring + st * 8192 + row * 128 + ((lr ^ row) & 7) * 16) : "memory");
            }
            uint32_t f0, f1, f2, f3;
            if (u < 40) { f0 = f2 = xs[lr * 324 + u * 8 + q]; f1 = f3 = xs[lr * 324 + u * 8 + 4 + q]; }
            else if (u & 1) { f0 = hp[4]; f1 = hp[5]; f2 = hp[6]; f3 = hp[7]; }
            else { f0 = hp[0]; f1 = hp[1]; f2 = hp[2]; f3 = hp[3]; }
            mma_rows(g, f0, f1, a[0], a[1], a[2], a[3]);
            mma_rows(v, f2, f3, a[4], a[5], a[6], a[7]);
            if (u & 1) {
                __syncwarp();
                issue((u >> 1) + 3, st);
                if (++st == 3) { st = 0; ph ^= 1; }
                if (u >= 39) {
                    if (u == 39) {
                        float hv[16];
#pragma unroll
                        for (int i = 0; i < 16; i++) {
                            const float gp = round_bf16(g[i & 7][i >> 3]);
                            hv[i] = round_bf16(__fdividef(gp, 1.0f + __expf(fminf(-gp, 80.f)))) * round_bf16(v[i & 7][i >> 3]);
                        }
#pragma unroll
                        for (int i = 0; i < 8; i++) hp[i] = pack_bf16(hv[2 * i], hv[2 * i + 1]);
                    } else {
                        float4* dst = reinterpret_cast<float4*>(g_ypart + (fg * 8 + lr) * DM + ((u - 40) >> 1) * 64 + 16 * q);
#pragma unroll
                        for (int i = 0; i < 4; i++) {
                            const int j = 4 * (i & 1), e = i >> 1;
                            dst[i] = make_float4(g[j][e] + v[j][e], g[j + 1][e] + v[j + 1][e], g[j + 2][e] + v[j + 2][e], g[j + 3][e] + v[j + 3][e]);
                        }
                    }
#pragma unroll
                    for (int i = 0; i < 8; i++) { g[i][0] = 0.f; g[i][1] = 0.f; v[i][0] = 0.f; v[i][1] = 0.f; }
                }
            }
        }
    }
    PROF(5);
    named_sync(1, 256);
    if (tid == 0) {
        flag_add(F_MODP);
        flag_wait<100>(F_MODP, 4u * (epoch + 1));
    }
    named_sync(1, 256);
    PROF(6);
#pragma unroll 1
    for (int i = tid; i < 2 * DM; i += 256) {
        const int c = 2 * mc + (i >= DM), col = i - (i >= DM) * DM, t = sidx[c];
        float y = 0.f;
#pragma unroll 9
        for (int k = 0; k < 27; k++) y += __ldcg(g_ypart + (k * 8 + c) * DM + col);
        const float rs = round_bf16(__fdividef(1.0f, 1.0f + __expf(fminf(-__ldcg(g_r + t), 80.f))));
        const float xn = __bfloat162float(reinterpret_cast<const __nv_bfloat16*>(xs + c * 324)[col]);
        P.out[(size_t)t * DM + col] = __float2bfloat16_rn(__bfloat162float(P.x[(size_t)t * DM + col]) + round_bf16(xn + round_bf16(round_bf16(y) * rs)));
    }
    named_sync(1, 256);
    if (tid == 0) flag_add(F_MOD);
    PROF(7);
}

__global__ void __cluster_dims__(2, 1, 1) __launch_bounds__(384, 1) fused_kernel(const __grid_constant__ Params P) {
    extern __shared__ __align__(1024) uint8_t smem_raw[];
    const uint32_t smem = (smem_u32(smem_raw) + 1023u) & ~1023u;
    uint8_t* smem_gen = smem_raw + (smem - smem_u32(smem_raw));
    const uint32_t bars = smem + NSLOT * SLOT;
    const int wgi = __reduce_or_sync(0xffffffffu, threadIdx.x >> 7);
    const int cl = blockIdx.x >> 1, rank = blockIdx.x & 1, ca = cl & 7, cb = cl >> 3;
    PROFG(30);
    PROF(0);
    if (FASTSTART && threadIdx.x == 96) {
        const uint32_t fa = bars + BAR_FULL, fw = bars + BAR_FULL + slot_w(0) * 8;
        mbar_init(fa, 1); mbar_init(fw, 1);
        asm volatile("fence.mbarrier_init.release.cluster;" ::: "memory");
        if (cl < 64) {
            mbar_expect_tx(fa, SLOT);
            mbar_expect_tx(fw, SLOT);
            tma_load(smem, &P.ckv, 0, (2 * ca + rank) * 128, fa);
            tma_load(smem + slot_w(0) * SLOT, &P.wuk, (cb + 8 * kv_round(0)) * 128, 0, fw);
            tma_load(smem + slot_w(0) * SLOT + 16384, &P.wuk, (cb + 8 * kv_round(0)) * 128 + 64, 0, fw);
            tma_load(smem + 16384, &P.ckv, 64, (2 * ca + rank) * 128, fa);
        }
    } else if (threadIdx.x == 0) {
#pragma unroll
        for (int i = 0; i < NSLOT; i++) {
            if (!FASTSTART || (i != 0 && i != 4)) mbar_init(bars + BAR_FULL + i * 8, 1);
            mbar_init(bars + BAR_EMPTY + i * 8, 16);
        }
        mbar_arrive(bars + BAR_FULL + 16);
        asm volatile("mbarrier.arrive.shared::cta.b64 _, [%0], 16;" ::"r"(bars + BAR_EMPTY + 16) : "memory");
        asm volatile("fence.mbarrier_init.release.cluster;" ::: "memory");
        PROF(24);
    } else if (threadIdx.x == 32) {
#pragma unroll
        for (int i = 0; i < 18; i++) mbar_init(bars + BAR_SIG + i * 8, 4);
#pragma unroll
        for (int i = 0; i < 14; i++) mbar_init(bars + BAR_DEP + i * 8, 1);
    } else if (!FASTSTART && threadIdx.x >= 64 && threadIdx.x < 128 && cl < 64) {
        const int i = threadIdx.x - 64;
        if (i == 0) { prefetch_map(&P.ckv); prefetch_map(&P.wuk); }
        if (i < 32) asm volatile("prefetch.global.L2 [%0];" ::"l"(P.ckv_ptr + ((2 * ca + rank) * 128 + cb * 16 + (i >> 1)) * DC + (i & 1) * 64));
        else if (i < 48) asm volatile("prefetch.global.L2 [%0];" ::"l"(P.wuk_ptr + (size_t)((i - 32) * 8 + ca) * (NH * HD) + (cb + 8 * kv_round(0)) * 128 + rank * 64));
    }
    __syncthreads();
    PROF(29);
    cluster_arrive();
    if (wgi > 0) {
        asm volatile("setmaxnreg.inc.sync.aligned.u32 232;");
        if (cl >= 64) {
            cluster_wait();
            mod_ffn(P, smem_gen, blockIdx.x - 128);
        } else {
            consumer(P, smem, bars, ca, cb, rank, wgi - 1);
        }
        cluster_arrive();
        PROFG(31);
        PROFDUMP();
    } else {
        asm volatile("setmaxnreg.dec.sync.aligned.u32 40;");
        const int w = __reduce_or_sync(0xffffffffu, threadIdx.x >> 5), lane = threadIdx.x & 31;
        if (!FASTSTART && threadIdx.x == 32 && cl < 64) {
            mbar_expect_tx(bars + BAR_FULL, SLOT);
            tma_load(smem, &P.ckv, 0, (2 * ca + rank) * 128, bars + BAR_FULL);
            tma_load(smem + 16384, &P.ckv, 64, (2 * ca + rank) * 128, bars + BAR_FULL);
        }
        if (threadIdx.x == 64) {
            prefetch_map(&P.wuv); prefetch_map(&P.xn); prefetch_map(&P.wq); prefetch_map(&P.kv); prefetch_map(&P.ctx); prefetch_map(&P.wo); prefetch_map(&P.outm);
        }
        __syncwarp();
        cluster_wait();
        PROF(27);
        if (cl < 64) {
            if (w == 0) {
                producer(P, smem, bars, ca, cb, rank);
            } else if (w < 3 && lane == 0) {
                const int wg = w - 1;
#pragma unroll 1
                for (int i = 0; i < 9; i++) {
                    const int nb = wg * LNSTAG + (LNOFF + 7 - 3) / 8;
                    const int e = (i < nb) ? i + 1 : (i == nb) ? 0 : i;
                    mbar_wait_sleep(bars + BAR_SIG + (wg * 9 + e) * 8, 0);
                    int f;
                    if (e == 0) f = F_LN;
                    else if (e < 5) f = F_KV + cb + 8 * kv_round(e - 1);
                    else { const int rd = e - 5; f = F_CTX + (8 * rd + cb) * 16 + item_p(ca, rd) * 2 + rank; }
                    flag_add(f);
                }
            } else if (lane == 0) {
                const uint32_t epoch = read_epoch();
#pragma unroll 1
                for (int i = 0; i < 14; i++) {
                    const int e = (i < 11) ? i : (i == 11) ? 13 : i - 1;
                    int f;
                    uint32_t n;
                    if (e == 0) { f = F_LN; n = 256; }
                    else if (e < 5) { f = F_KV + cb + 8 * (e - 1); n = 32; }
                    else if (e < 13) { f = F_CTX + (8 * ((e - 5) >> 1) + (cb & 6) + ((e - 5) & 1)) * 16 + ca * 2 + rank; n = 2; }
                    else { f = F_MOD; n = 4; }
                    flag_wait<200>(f, n * (epoch + 1));
                    fence_proxy_async();
                    mbar_arrive(bars + BAR_DEP + e * 8);
                }
            }
        }
        __syncwarp();
        cluster_arrive();
        cluster_wait();
        if (threadIdx.x == 0) atomicAdd(g_flags + F_EXIT * 8, 1u);
        PROFG(31);
        PROFDUMP();
    }
}

typedef CUresult (*EncodeFn)(CUtensorMap*, CUtensorMapDataType, cuuint32_t, void*, const cuuint64_t*, const cuuint64_t*, const cuuint32_t*,
                             const cuuint32_t*, CUtensorMapInterleave, CUtensorMapSwizzle, CUtensorMapL2promotion, CUtensorMapFloatOOBfill);

void make_map(EncodeFn fn, CUtensorMap* m, const void* ptr, uint64_t rows, uint64_t cols, uint32_t box_rows) {
    cuuint64_t dims[2] = {cols, rows};
    cuuint64_t strides[1] = {cols * 2};
    cuuint32_t box[2] = {64, box_rows};
    cuuint32_t es[2] = {1, 1};
    fn(m, CU_TENSOR_MAP_DATA_TYPE_BFLOAT16, 2, const_cast<void*>(ptr), dims, strides, box, es, CU_TENSOR_MAP_INTERLEAVE_NONE,
       CU_TENSOR_MAP_SWIZZLE_128B, CU_TENSOR_MAP_L2_PROMOTION_L2_128B, CU_TENSOR_MAP_FLOAT_OOB_FILL_NONE);
}

}

extern "C" void kernel_launch(void* const* d_in, const int* in_sizes, int n_in, void* d_out, int out_size) {
    (void)in_sizes; (void)n_in; (void)out_size;
    void* fnp = nullptr;
    cudaDriverEntryPointQueryResult qr;
    cudaGetDriverEntryPoint("cuTensorMapEncodeTiled", &fnp, cudaEnableDefault, &qr);
    EncodeFn fn = (EncodeFn)fnp;
    void *xn, *kv, *ctx;
    cudaGetSymbolAddress(&xn, g_xn);
    cudaGetSymbolAddress(&kv, g_kv);
    cudaGetSymbolAddress(&ctx, g_ctx);
    Params P;
    make_map(fn, &P.ckv, d_in[1], SEQ, DC, 128);
    make_map(fn, &P.wq, d_in[2], DM, NH * HD, 64);
    make_map(fn, &P.wuk, d_in[3], DC, NH * HD, 128);
    make_map(fn, &P.wuv, d_in[4], DC, NH * HD, 128);
    make_map(fn, &P.wo, d_in[5], NH * HD, DM, 32);
    make_map(fn, &P.xn, xn, SEQ, DM, 128);
    make_map(fn, &P.kv, kv, NH * 16 * 2 * 128, 128, 128);
    make_map(fn, &P.ctx, ctx, NH * SEQ, HD, 128);
    P.x = (const __nv_bfloat16*)d_in[0];
    P.wr = (const __nv_bfloat16*)d_in[7];
    make_map(fn, &P.wg, d_in[8], DM, FF, 32);
    make_map(fn, &P.wu, d_in[9], DM, FF, 32);
    make_map(fn, &P.wd, d_in[10], FF, DM, 64);
    P.ckv_ptr = (const __nv_bfloat16*)d_in[1];
    P.wuk_ptr = (const __nv_bfloat16*)d_in[3];
    make_map(fn, &P.outm, d_out, SEQ, DM, 16);
    P.out = (__nv_bfloat16*)d_out;
    cudaFuncSetAttribute(fused_kernel, cudaFuncAttributeMaxDynamicSharedMemorySize, SMEM_BYTES);
    fused_kernel<<<NCTA, 384, SMEM_BYTES>>>(P);
}
```

```cpp
#include <cuda_runtime.h>
#include <cuda_bf16.h>
#include <cuda.h>
#include <stdint.h>

namespace {

constexpr int SEQ = 2048, DM = 640, DC = 512, NH = 32, HD = 128, FF = 1728;
constexpr int NSLOT = 7, SLOT = 32768;
constexpr int NCTA = 132;
#define PINGPONG 1
#define SIGMA 1
#define KVORDER 0x1023
#define KVSPLIT 1
#define LNSTAG 1
#define EARLYSEND 1
#define FENCE_EACH 1
#define LATEST 1
#define LASTRD 7
#define LASTN 2
#define EFMASK 13
#define LNOFF 4
#define LNLEAD 2
#define FASTSTART 1
#define ENDBAR 0
#define SPLITJ 8
constexpr uint32_t DESC_HI = (1024u >> 4) | (1u << 30);
constexpr int SMEM_BYTES = NSLOT * SLOT + 3072;

constexpr int BAR_FULL = 0, BAR_EMPTY = 64, BAR_SIG = 128  , BAR_DEP = 320  , MISC_OFF = 512;

constexpr int F_EPOCH = 0, F_LN = 1, F_MOD = 2, F_MODP = 3, F_KV = 4  , F_CTX = 36  , F_NUM = 548;

__device__ __align__(1024) __nv_bfloat16 g_xn[SEQ * DM];
__device__ __align__(1024) __nv_bfloat16 g_kv[NH * 16 * 2 * 128 * 128];
__device__ __align__(1024) __nv_bfloat16 g_ctx[NH * SEQ * HD];
__device__ __align__(16) float g_r[SEQ];
__device__ __align__(16) float g_ypart[27 * 8 * DM];
__device__ uint32_t g_flags[F_NUM * 8];

struct TrueT { static constexpr bool value = true; };
struct FalseT { static constexpr bool value = false; };

struct Params {
    CUtensorMap ckv, wuk, wuv, xn, wq, kv, ctx, wo, wg, wu, wd, outm;
    const __nv_bfloat16 *x, *wr;
    __nv_bfloat16* out;
};

__device__ __forceinline__ uint32_t smem_u32(const void* p) { return (uint32_t)__cvta_generic_to_shared(p); }
__device__ __forceinline__ void mbar_init(uint32_t bar, uint32_t cnt) {
    asm volatile("mbarrier.init.shared::cta.b64 [%0], %1;" ::"r"(bar), "r"(cnt) : "memory");
}
__device__ __forceinline__ void mbar_expect_tx(uint32_t bar, uint32_t bytes) {
    asm volatile("mbarrier.arrive.expect_tx.shared::cta.b64 _, [%0], %1;" ::"r"(bar), "r"(bytes) : "memory");
}
__device__ __forceinline__ void mbar_arrive(uint32_t bar) {
    asm volatile("mbarrier.arrive.shared::cta.b64 _, [%0];" ::"r"(bar) : "memory");
}
__device__ __forceinline__ uint32_t mapa(uint32_t addr, uint32_t cta) {
    uint32_t r;
    asm("mapa.shared::cluster.u32 %0, %1, %2;" : "=r"(r) : "r"(addr), "r"(cta));
    return r;
}
__device__ __forceinline__ void mbar_wait(uint32_t bar, uint32_t parity) {
    asm volatile(
        "{\n.reg .pred p;\n.reg .b32 c;\n"
        "mov.b32 c, 0;\n"
        "WLOOP:\n"
        "mbarrier.try_wait.parity.shared::cta.b64 p, [%0], %1;\n"
        "@p bra.uni WDONE;\n"
        "add.u32 c, c, 1;\n"
        "setp.lt.u32 p, c, 0x400000;\n"
        "@p bra.uni WLOOP;\n"
        "trap;\n"
        "WDONE:\n}\n" ::"r"(bar), "r"(parity) : "memory");
}
__device__ __forceinline__ void mbar_wait_sleep(uint32_t bar, uint32_t parity) {
    asm volatile(
        "{\n.reg .pred p;\n.reg .b32 c;\n"
        "mov.b32 c, 0;\n"
        "WLOOP:\n"
        "mbarrier.try_wait.parity.shared::cta.b64 p, [%0], %1, 20000;\n"
        "@p bra.uni WDONE;\n"
        "add.u32 c, c, 1;\n"
        "setp.lt.u32 p, c, 0x40000;\n"
        "@p bra.uni WLOOP;\n"
        "trap;\n"
        "WDONE:\n}\n" ::"r"(bar), "r"(parity) : "memory");
}
__device__ __forceinline__ void tma_load(uint32_t dst, const CUtensorMap* m, int c0, int c1, uint32_t bar) {
    asm volatile("cp.async.bulk.tensor.2d.shared::cluster.global.mbarrier::complete_tx::bytes [%0], [%1, {%3, %4}], [%2];"
                 ::"r"(dst), "l"(m), "r"(bar), "r"(c0), "r"(c1) : "memory");
}
#define ELECT "{\n.reg .pred e;\nelect.sync _|e, 0xffffffff;\n@e "
__device__ __forceinline__ void w_expect_tx(uint32_t bar, uint32_t bytes) {
    asm volatile(ELECT "mbarrier.arrive.expect_tx.shared::cta.b64 _, [%0], %1;\n}\n" ::"r"(bar), "r"(bytes) : "memory");
}
__device__ __forceinline__ void w_tma_load(uint32_t dst, const CUtensorMap* m, int c0, int c1, uint32_t bar) {
    asm volatile(ELECT "cp.async.bulk.tensor.2d.shared::cluster.global.mbarrier::complete_tx::bytes [%0], [%1, {%3, %4}], [%2];\n}\n"
                 ::"r"(dst), "l"(m), "r"(bar), "r"(c0), "r"(c1) : "memory");
}
__device__ __forceinline__ void w_tma_load_mc(uint32_t dst, const CUtensorMap* m, int c0, int c1, uint32_t bar) {
    asm volatile(ELECT "cp.async.bulk.tensor.2d.shared::cluster.global.mbarrier::complete_tx::bytes.multicast::cluster [%0], [%1, {%3, %4}], [%2], %5;\n}\n"
                 ::"r"(dst), "l"(m), "r"(bar), "r"(c0), "r"(c1), "h"((uint16_t)3) : "memory");
}
__device__ __forceinline__ void w_tma_prefetch(const CUtensorMap* m, int c0, int c1) {
    asm volatile(ELECT "cp.async.bulk.prefetch.tensor.2d.L2.global [%0, {%1, %2}];\n}\n" ::"l"(m), "r"(c0), "r"(c1) : "memory");
}
__device__ __forceinline__ uint64_t policy_evict_first() {
    uint64_t p;
    asm("createpolicy.fractional.L2::evict_first.b64 %0, 1.0;" : "=l"(p));
    return p;
}
__device__ __forceinline__ void w_tma_load_mc_last(uint32_t dst, const CUtensorMap* m, int c0, int c1, uint32_t bar) {
    asm volatile(ELECT "cp.async.bulk.tensor.2d.shared::cluster.global.mbarrier::complete_tx::bytes.multicast::cluster.L2::cache_hint [%0], [%1, {%3, %4}], [%2], %5, %6;\n}\n"
                 ::"r"(dst), "l"(m), "r"(bar), "r"(c0), "r"(c1), "h"((uint16_t)3), "l"(policy_evict_first()) : "memory");
}
__device__ __forceinline__ void tma_load_stream(uint32_t dst, const CUtensorMap* m, int c0, int c1, uint32_t bar) {
    asm volatile("cp.async.bulk.tensor.2d.shared::cluster.global.mbarrier::complete_tx::bytes.L2::cache_hint [%0], [%1, {%3, %4}], [%2], %5;"
                 ::"r"(dst), "l"(m), "r"(bar), "r"(c0), "r"(c1), "l"(policy_evict_first()) : "memory");
}
__device__ __forceinline__ uint4 ldg_stream(const void* p) {
    uint4 v;
    asm volatile("ld.global.nc.L2::cache_hint.v4.b32 {%0, %1, %2, %3}, [%4], %5;" : "=r"(v.x), "=r"(v.y), "=r"(v.z), "=r"(v.w) : "l"(p), "l"(policy_evict_first()));
    return v;
}
__device__ __forceinline__ void prefetch_map(const CUtensorMap* m) {
    asm volatile("prefetch.tensormap [%0];" ::"l"(m) : "memory");
}
__device__ __forceinline__ void cluster_arrive() { asm volatile("barrier.cluster.arrive.relaxed.aligned;" ::: "memory"); }
__device__ __forceinline__ void cluster_wait() { asm volatile("barrier.cluster.wait.aligned;" ::: "memory"); }
__device__ __forceinline__ void named_sync(int id, int n) { asm volatile("bar.sync %0, %1;" ::"r"(id), "r"(n) : "memory"); }
__device__ __forceinline__ void named_arrive(int id, int n) { asm volatile("bar.arrive %0, %1;" ::"r"(id), "r"(n) : "memory"); }

__device__ __forceinline__ void flag_add(int f) {
    asm volatile("fence.acq_rel.gpu;\nred.relaxed.gpu.global.add.u32 [%0], 1;" ::"l"(g_flags + f * 8) : "memory");
}
template <int SLEEP>
__device__ __forceinline__ void flag_wait(int f, uint32_t target) {
    asm volatile(
        "{\n.reg .pred p;\n.reg .b32 c, v;\n"
        "mov.b32 c, 0;\n"
        "FLOOP:\n"
        "ld.acquire.gpu.global.u32 v, [%0];\n"
        "sub.u32 v, v, %1;\n"
        "setp.ge.s32 p, v, 0;\n"
        "@p bra FDONE;\n"
        "nanosleep.u32 %2;\n"
        "add.u32 c, c, 1;\n"
        "setp.lt.u32 p, c, 0x400000;\n"
        "@p bra FLOOP;\n"
        "trap;\n"
        "FDONE:\n}\n" ::"l"(g_flags + f * 8), "r"(target), "n"(SLEEP) : "memory");
}
__device__ __forceinline__ uint32_t read_epoch() { return atomicAdd(g_flags + F_EPOCH * 8, 1u) / NCTA; }
__device__ __forceinline__ void fence_proxy_async() { asm volatile("fence.proxy.async;" ::: "memory"); }

__device__ __forceinline__ void wgmma_fence() { asm volatile("wgmma.fence.sync.aligned;" ::: "memory"); }
__device__ __forceinline__ void wgmma_commit() { asm volatile("wgmma.commit_group.sync.aligned;" ::: "memory"); }
template <int N>
__device__ __forceinline__ void wgmma_wait() { asm volatile("wgmma.wait_group.sync.aligned %0;" ::"n"(N) : "memory"); }
template <int N>
__device__ __forceinline__ void fence_regs(float (&d)[N]) {
#pragma unroll
    for (int i = 0; i < N; i++) asm volatile("" : "+f"(d[i])::"memory");
}
template <int N>
__device__ __forceinline__ void fence_regs(uint32_t (&d)[N]) {
#pragma unroll
    for (int i = 0; i < N; i++) asm volatile("" : "+r"(d[i])::"memory");
}

template <int TA, int TB>
__device__ __forceinline__ void wgmma_ss_n128(float (&d)[64], uint32_t alo, uint32_t blo, int scale_d) {
    asm volatile("{\n.reg .pred p;\n.reg .b64 da, db;\nsetp.ne.b32 p, %66, 0;\n"
        "mov.b64 da, {%64, %69};\nmov.b64 db, {%65, %69};\n"
        "wgmma.mma_async.sync.aligned.m64n128k16.f32.bf16.bf16 "
        "{%0, %1, %2, %3, %4, %5, %6, %7, %8, %9, %10, %11, %12, %13, %14, %15, %16, %17, %18, %19, %20, %21, %22, %23, %24, %25, %26, %27, %28, %29, %30, %31, %32, %33, %34, %35, %36, %37, %38, %39, %40, %41, %42, %43, %44, %45, %46, %47, %48, %49, %50, %51, %52, %53, %54, %55, %56, %57, %58, %59, %60, %61, %62, %63}, da, db, p, 1, 1, %67, %68;\n}\n"
        :
          "+f"(d[0]), "+f"(d[1]), "+f"(d[2]), "+f"(d[3]), "+f"(d[4]), "+f"(d[5]), "+f"(d[6]), "+f"(d[7]),
          "+f"(d[8]), "+f"(d[9]), "+f"(d[10]), "+f"(d[11]), "+f"(d[12]), "+f"(d[13]), "+f"(d[14]), "+f"(d[15]),
          "+f"(d[16]), "+f"(d[17]), "+f"(d[18]), "+f"(d[19]), "+f"(d[20]), "+f"(d[21]), "+f"(d[22]), "+f"(d[23]),
          "+f"(d[24]), "+f"(d[25]), "+f"(d[26]), "+f"(d[27]), "+f"(d[28]), "+f"(d[29]), "+f"(d[30]), "+f"(d[31]),
          "+f"(d[32]), "+f"(d[33]), "+f"(d[34]), "+f"(d[35]), "+f"(d[36]), "+f"(d[37]), "+f"(d[38]), "+f"(d[39]),
          "+f"(d[40]), "+f"(d[41]), "+f"(d[42]), "+f"(d[43]), "+f"(d[44]), "+f"(d[45]), "+f"(d[46]), "+f"(d[47]),
          "+f"(d[48]), "+f"(d[49]), "+f"(d[50]), "+f"(d[51]), "+f"(d[52]), "+f"(d[53]), "+f"(d[54]), "+f"(d[55]),
          "+f"(d[56]), "+f"(d[57]), "+f"(d[58]), "+f"(d[59]), "+f"(d[60]), "+f"(d[61]), "+f"(d[62]), "+f"(d[63])
        : "r"(alo), "r"(blo), "r"(scale_d), "n"(TA), "n"(TB), "r"(DESC_HI));
}
template <int TA, int TB>
__device__ __forceinline__ void wgmma_ss_n192(float (&d)[96], uint32_t alo, uint32_t blo, int scale_d) {
    asm volatile("{\n.reg .pred p;\n.reg .b64 da, db;\nsetp.ne.b32 p, %98, 0;\n"
        "mov.b64 da, {%96, %101};\nmov.b64 db, {%97, %101};\n"
        "wgmma.mma_async.sync.aligned.m64n192k16.f32.bf16.bf16 "
        "{%0, %1, %2, %3, %4, %5, %6, %7, %8, %9, %10, %11, %12, %13, %14, %15, %16, %17, %18, %19, %20, %21, %22, %23, %24, %25, %26, %27, %28, %29, %30, %31, %32, %33, %34, %35, %36, %37, %38, %39, %40, %41, %42, %43, %44, %45, %46, %47, %48, %49, %50, %51, %52, %53, %54, %55, %56, %57, %58, %59, %60, %61, %62, %63, %64, %65, %66, %67, %68, %69, %70, %71, %72, %73, %74, %75, %76, %77, %78, %79, %80, %81, %82, %83, %84, %85, %86, %87, %88, %89, %90, %91, %92, %93, %94, %95}, da, db, p, 1, 1, %99, %100;\n}\n"
        :
          "+f"(d[0]), "+f"(d[1]), "+f"(d[2]), "+f"(d[3]), "+f"(d[4]), "+f"(d[5]), "+f"(d[6]), "+f"(d[7]),
          "+f"(d[8]), "+f"(d[9]), "+f"(d[10]), "+f"(d[11]), "+f"(d[12]), "+f"(d[13]), "+f"(d[14]), "+f"(d[15]),
          "+f"(d[16]), "+f"(d[17]), "+f"(d[18]), "+f"(d[19]), "+f"(d[20]), "+f"(d[21]), "+f"(d[22]), "+f"(d[23]),
          "+f"(d[24]), "+f"(d[25]), "+f"(d[26]), "+f"(d[27]), "+f"(d[28]), "+f"(d[29]), "+f"(d[30]), "+f"(d[31]),
          "+f"(d[32]), "+f"(d[33]), "+f"(d[34]), "+f"(d[35]), "+f"(d[36]), "+f"(d[37]), "+f"(d[38]), "+f"(d[39]),
          "+f"(d[40]), "+f"(d[41]), "+f"(d[42]), "+f"(d[43]), "+f"(d[44]), "+f"(d[45]), "+f"(d[46]), "+f"(d[47]),
          "+f"(d[48]), "+f"(d[49]), "+f"(d[50]), "+f"(d[51]), "+f"(d[52]), "+f"(d[53]), "+f"(d[54]), "+f"(d[55]),
          "+f"(d[56]), "+f"(d[57]), "+f"(d[58]), "+f"(d[59]), "+f"(d[60]), "+f"(d[61]), "+f"(d[62]), "+f"(d[63]),
          "+f"(d[64]), "+f"(d[65]), "+f"(d[66]), "+f"(d[67]), "+f"(d[68]), "+f"(d[69]), "+f"(d[70]), "+f"(d[71]),
          "+f"(d[72]), "+f"(d[73]), "+f"(d[74]), "+f"(d[75]), "+f"(d[76]), "+f"(d[77]), "+f"(d[78]), "+f"(d[79]),
          "+f"(d[80]), "+f"(d[81]), "+f"(d[82]), "+f"(d[83]), "+f"(d[84]), "+f"(d[85]), "+f"(d[86]), "+f"(d[87]),
          "+f"(d[88]), "+f"(d[89]), "+f"(d[90]), "+f"(d[91]), "+f"(d[92]), "+f"(d[93]), "+f"(d[94]), "+f"(d[95])
        : "r"(alo), "r"(blo), "r"(scale_d), "n"(TA), "n"(TB), "r"(DESC_HI));
}
template <int TB>
__device__ __forceinline__ void wgmma_rs_n128(float (&d)[64], uint32_t a0, uint32_t a1, uint32_t a2, uint32_t a3, uint32_t blo, int scale_d) {
    asm volatile("{\n.reg .pred p;\n.reg .b64 db;\nsetp.ne.b32 p, %69, 0;\n"
        "mov.b64 db, {%68, %71};\n"
        "wgmma.mma_async.sync.aligned.m64n128k16.f32.bf16.bf16 "
        "{%0, %1, %2, %3, %4, %5, %6, %7, %8, %9, %10, %11, %12, %13, %14, %15, %16, %17, %18, %19, %20, %21, %22, %23, %24, %25, %26, %27, %28, %29, %30, %31, %32, %33, %34, %35, %36, %37, %38, %39, %40, %41, %42, %43, %44, %45, %46, %47, %48, %49, %50, %51, %52, %53, %54, %55, %56, %57, %58, %59, %60, %61, %62, %63}, {%64, %65, %66, %67}, db, p, 1, 1, %70;\n}\n"
        :
          "+f"(d[0]), "+f"(d[1]), "+f"(d[2]), "+f"(d[3]), "+f"(d[4]), "+f"(d[5]), "+f"(d[6]), "+f"(d[7]),
          "+f"(d[8]), "+f"(d[9]), "+f"(d[10]), "+f"(d[11]), "+f"(d[12]), "+f"(d[13]), "+f"(d[14]), "+f"(d[15]),
          "+f"(d[16]), "+f"(d[17]), "+f"(d[18]), "+f"(d[19]), "+f"(d[20]), "+f"(d[21]), "+f"(d[22]), "+f"(d[23]),
          "+f"(d[24]), "+f"(d[25]), "+f"(d[26]), "+f"(d[27]), "+f"(d[28]), "+f"(d[29]), "+f"(d[30]), "+f"(d[31]),
          "+f"(d[32]), "+f"(d[33]), "+f"(d[34]), "+f"(d[35]), "+f"(d[36]), "+f"(d[37]), "+f"(d[38]), "+f"(d[39]),
          "+f"(d[40]), "+f"(d[41]), "+f"(d[42]), "+f"(d[43]), "+f"(d[44]), "+f"(d[45]), "+f"(d[46]), "+f"(d[47]),
          "+f"(d[48]), "+f"(d[49]), "+f"(d[50]), "+f"(d[51]), "+f"(d[52]), "+f"(d[53]), "+f"(d[54]), "+f"(d[55]),
          "+f"(d[56]), "+f"(d[57]), "+f"(d[58]), "+f"(d[59]), "+f"(d[60]), "+f"(d[61]), "+f"(d[62]), "+f"(d[63])
        : "r"(a0), "r"(a1), "r"(a2), "r"(a3), "r"(blo), "r"(scale_d), "n"(TB), "r"(DESC_HI));
}
template <int TB>
__device__ __forceinline__ void wgmma_rs_n128_z(float (&d)[64], uint32_t a0, uint32_t a1, uint32_t a2, uint32_t a3, uint32_t blo) {
    asm volatile("{\n.reg .pred p;\n.reg .b64 db;\nsetp.ne.b32 p, %69, 0;\n"
        "mov.b64 db, {%68, %71};\n"
        "wgmma.mma_async.sync.aligned.m64n128k16.f32.bf16.bf16 "
        "{%0, %1, %2, %3, %4, %5, %6, %7, %8, %9, %10, %11, %12, %13, %14, %15, %16, %17, %18, %19, %20, %21, %22, %23, %24, %25, %26, %27, %28, %29, %30, %31, %32, %33, %34, %35, %36, %37, %38, %39, %40, %41, %42, %43, %44, %45, %46, %47, %48, %49, %50, %51, %52, %53, %54, %55, %56, %57, %58, %59, %60, %61, %62, %63}, {%64, %65, %66, %67}, db, p, 1, 1, %70;\n}\n"
        :
          "=f"(d[0]), "=f"(d[1]), "=f"(d[2]), "=f"(d[3]), "=f"(d[4]), "=f"(d[5]), "=f"(d[6]), "=f"(d[7]),
          "=f"(d[8]), "=f"(d[9]), "=f"(d[10]), "=f"(d[11]), "=f"(d[12]), "=f"(d[13]), "=f"(d[14]), "=f"(d[15]),
          "=f"(d[16]), "=f"(d[17]), "=f"(d[18]), "=f"(d[19]), "=f"(d[20]), "=f"(d[21]), "=f"(d[22]), "=f"(d[23]),
          "=f"(d[24]), "=f"(d[25]), "=f"(d[26]), "=f"(d[27]), "=f"(d[28]), "=f"(d[29]), "=f"(d[30]), "=f"(d[31]),
          "=f"(d[32]), "=f"(d[33]), "=f"(d[34]), "=f"(d[35]), "=f"(d[36]), "=f"(d[37]), "=f"(d[38]), "=f"(d[39]),
          "=f"(d[40]), "=f"(d[41]), "=f"(d[42]), "=f"(d[43]), "=f"(d[44]), "=f"(d[45]), "=f"(d[46]), "=f"(d[47]),
          "=f"(d[48]), "=f"(d[49]), "=f"(d[50]), "=f"(d[51]), "=f"(d[52]), "=f"(d[53]), "=f"(d[54]), "=f"(d[55]),
          "=f"(d[56]), "=f"(d[57]), "=f"(d[58]), "=f"(d[59]), "=f"(d[60]), "=f"(d[61]), "=f"(d[62]), "=f"(d[63])
        : "r"(a0), "r"(a1), "r"(a2), "r"(a3), "r"(blo), "n"(0), "n"(TB), "r"(DESC_HI));
}
template <int TA, int TB>
__device__ __forceinline__ void wgmma_ss_n128_z(float (&d)[64], uint32_t alo, uint32_t blo) {
    asm volatile("{\n.reg .pred p;\n.reg .b64 da, db;\nsetp.ne.b32 p, %66, 0;\n"
        "mov.b64 da, {%64, %69};\nmov.b64 db, {%65, %69};\n"
        "wgmma.mma_async.sync.aligned.m64n128k16.f32.bf16.bf16 "
        "{%0, %1, %2, %3, %4, %5, %6, %7, %8, %9, %10, %11, %12, %13, %14, %15, %16, %17, %18, %19, %20, %21, %22, %23, %24, %25, %26, %27, %28, %29, %30, %31, %32, %33, %34, %35, %36, %37, %38, %39, %40, %41, %42, %43, %44, %45, %46, %47, %48, %49, %50, %51, %52, %53, %54, %55, %56, %57, %58, %59, %60, %61, %62, %63}, da, db, p, 1, 1, %67, %68;\n}\n"
        :
          "=f"(d[0]), "=f"(d[1]), "=f"(d[2]), "=f"(d[3]), "=f"(d[4]), "=f"(d[5]), "=f"(d[6]), "=f"(d[7]),
          "=f"(d[8]), "=f"(d[9]), "=f"(d[10]), "=f"(d[11]), "=f"(d[12]), "=f"(d[13]), "=f"(d[14]), "=f"(d[15]),
          "=f"(d[16]), "=f"(d[17]), "=f"(d[18]), "=f"(d[19]), "=f"(d[20]), "=f"(d[21]), "=f"(d[22]), "=f"(d[23]),
          "=f"(d[24]), "=f"(d[25]), "=f"(d[26]), "=f"(d[27]), "=f"(d[28]), "=f"(d[29]), "=f"(d[30]), "=f"(d[31]),
          "=f"(d[32]), "=f"(d[33]), "=f"(d[34]), "=f"(d[35]), "=f"(d[36]), "=f"(d[37]), "=f"(d[38]), "=f"(d[39]),
          "=f"(d[40]), "=f"(d[41]), "=f"(d[42]), "=f"(d[43]), "=f"(d[44]), "=f"(d[45]), "=f"(d[46]), "=f"(d[47]),
          "=f"(d[48]), "=f"(d[49]), "=f"(d[50]), "=f"(d[51]), "=f"(d[52]), "=f"(d[53]), "=f"(d[54]), "=f"(d[55]),
          "=f"(d[56]), "=f"(d[57]), "=f"(d[58]), "=f"(d[59]), "=f"(d[60]), "=f"(d[61]), "=f"(d[62]), "=f"(d[63])
        : "r"(alo), "r"(blo), "n"(0), "n"(TA), "n"(TB), "r"(DESC_HI));
}

__device__ __forceinline__ uint32_t pack_bf16(float lo, float hi) {
    uint32_t r;
    asm("cvt.rn.bf16x2.f32 %0, %1, %2;" : "=r"(r) : "f"(hi), "f"(lo));
    return r;
}
__device__ __forceinline__ uint32_t add_bf16x2(uint32_t a, uint32_t b) {
    uint32_t r;
    asm("add.rn.bf16x2 %0, %1, %2;" : "=r"(r) : "r"(a), "r"(b));
    return r;
}
__device__ __forceinline__ float bf_lo(uint32_t v) { return __uint_as_float(v << 16); }
__device__ __forceinline__ float bf_hi(uint32_t v) { return __uint_as_float(v & 0xffff0000u); }
__device__ __forceinline__ float round_bf16(float v) { return __bfloat162float(__float2bfloat16_rn(v)); }
__device__ __forceinline__ float ex2(float x) {
    float y;
    asm("ex2.approx.ftz.f32 %0, %1;" : "=f"(y) : "f"(x));
    return y;
}
__device__ __forceinline__ float rcp(float x) {
    float y;
    asm("rcp.approx.ftz.f32 %0, %1;" : "=f"(y) : "f"(x));
    return y;
}
__device__ __forceinline__ void stg128(void* p, uint32_t a, uint32_t b, uint32_t c, uint32_t d) {
    asm volatile("st.global.v4.b32 [%0], {%1, %2, %3, %4};" ::"l"(p), "r"(a), "r"(b), "r"(c), "r"(d) : "memory");
}
__device__ __forceinline__ void stg128p(void* p, uint32_t a, uint32_t b, uint32_t c, uint32_t d, uint64_t pol) {
    asm volatile("st.global.L2::cache_hint.v4.b32 [%0], {%1, %2, %3, %4}, %5;" ::"l"(p), "r"(a), "r"(b), "r"(c), "r"(d), "l"(pol) : "memory");
}
__device__ __forceinline__ uint64_t policy_sel(bool first) {
    uint64_t p;
    asm("createpolicy.fractional.L2::evict_normal.b64 %0, 1.0;" : "=l"(p));
    return first ? policy_evict_first() : p;
}
__device__ __forceinline__ int perm_row(int t) { return (t & ~255) | (((0x78 >> (((t >> 6) & 3) * 2)) & 3) << 6) | (t & 63); }
__device__ __forceinline__ int unperm_row(int t) { return (t & ~255) | (((0x9C >> (((t >> 6) & 3) * 2)) & 3) << 6) | (t & 63); }

#define PROF(i)
#define PROFG(i)
#define PROFDUMP()
#define TR(i)
#define BP(r, i)
#define LP(i)

template <int I>
__device__ __forceinline__ void store_chunk(const float (&a)[64], __nv_bfloat16* row0, __nv_bfloat16* row1, float s0, float s1, uint64_t pol) {
    stg128p(row0 + 32 * I, pack_bf16(a[16 * I + 0] * s0, a[16 * I + 1] * s0), pack_bf16(a[16 * I + 4] * s0, a[16 * I + 5] * s0),
           pack_bf16(a[16 * I + 8] * s0, a[16 * I + 9] * s0), pack_bf16(a[16 * I + 12] * s0, a[16 * I + 13] * s0), pol);
    stg128p(row1 + 32 * I, pack_bf16(a[16 * I + 2] * s1, a[16 * I + 3] * s1), pack_bf16(a[16 * I + 6] * s1, a[16 * I + 7] * s1),
           pack_bf16(a[16 * I + 10] * s1, a[16 * I + 11] * s1), pack_bf16(a[16 * I + 14] * s1, a[16 * I + 15] * s1), pol);
}
template <int I>
struct IntT { static constexpr int value = I; };
template <class F>
__device__ __forceinline__ void for4(F f) { f(IntT<0>{}); f(IntT<1>{}); f(IntT<2>{}); f(IntT<3>{}); }

struct Prod {
    uint32_t smem, bars;
    uint32_t bo, par;
    uint32_t dst, fb;
    __device__ __forceinline__ void acquire(uint32_t o, uint32_t parity, uint32_t bytes) {
        mbar_wait(bars + BAR_EMPTY + o, parity);
        fb = bars + BAR_FULL + o;
        dst = smem + o * (SLOT / 8);
        w_expect_tx(fb, bytes);
    }
    __device__ __forceinline__ void next(uint32_t bytes) {
        acquire(bo, par, bytes);
        const bool wrap = bo == (NSLOT - 1) * 8;
        bo = wrap ? 0u : bo + 8;
        par ^= wrap ? 1u : 0u;
    }
};

__device__ __forceinline__ int item_p(int ca, int rd) {
    const int v = (rd & 1) ? (ca + 4) & 7 : ca;
    return (rd & 2) ? 7 - v : v;
}
__device__ __forceinline__ int kv_round(int i) { return (KVORDER >> (4 * i)) & 3; }
__device__ __forceinline__ int slot_a(int i) { return (0x5310 >> (4 * i)) & 15; }
__device__ __forceinline__ int slot_w(int m) { return (0x264 >> (4 * m)) & 15; }

__device__ __forceinline__ void producer(const Params& P, uint32_t smem, uint32_t bars, int ca, int cb, int rank) {
    Prod pr{smem, bars, 0u, 0u, 0u, 0u};
    {
        int m = 0;
        uint32_t lap = 1;
#pragma unroll 1
        for (int u = 0; u < 32; u++) {
            if (u >= 3) {
                const int v = (u == 3) ? 3 + ca : u + 7;
                if (v < 32 && (u == 3 || (v & 7) == ca)) w_tma_prefetch((v & 4) ? &P.wuv : &P.wuk, (cb + 8 * kv_round(v >> 3)) * 128 + rank * 64, (v & 3) * 128);
                if (u == 24) {
                    w_tma_prefetch(&P.wq, cb * 128 + rank * 64, ca * 64);
                    if (ca < 2) w_tma_prefetch(&P.wq, cb * 128 + rank * 64, (ca + 8) * 64);
                }
            }
            if (u >= FASTSTART) pr.acquire(slot_w(m) * 8, lap ^ (m >> 1), SLOT);
            lap ^= m >> 1;
            m = (m == 2) ? 0 : m + 1;
            TR(1 + u);
            if (u >= FASTSTART) w_tma_load_mc(pr.dst + rank * 16384, (u & 4) ? &P.wuv : &P.wuk, (cb + 8 * kv_round(u >> 3)) * 128 + rank * 64, (u & 3) * 128, pr.fb);
            if (u < 3 && u + 1 >= FASTSTART) {
                pr.acquire(slot_a(u + 1) * 8, 1, SLOT);
                w_tma_load(pr.dst, &P.ckv, u * 128 + 128, (2 * ca + rank) * 128, pr.fb);
                w_tma_load(pr.dst + 16384, &P.ckv, u * 128 + 192, (2 * ca + rank) * 128, pr.fb);
            }
        }
    }
    PROF(1);
    mbar_wait(bars + BAR_DEP, 0);
#pragma unroll 1
    for (int rd = 0; rd < 4; rd++) {
        const int h = 8 * rd + cb, p = item_p(ca, rd);
#pragma unroll 1
        for (int ks = 0; ks < 10; ks++) {
            pr.next(SLOT);
            w_tma_load_mc(pr.dst + 16384 + rank * 8192, &P.wq, h * 128 + rank * 64, ks * 64, pr.fb);
            w_tma_load(pr.dst, &P.xn, ks * 64, 256 * p + 128 * rank, pr.fb);
        }
        PROF(8 + rd * 4);
        mbar_wait(bars + BAR_DEP + (1 + rd) * 8, 0);
        const int last = 4 * p + 3, top = h * 32 + last;
#pragma unroll 1
        for (int i = 0; i <= last; i++) {
            const int t = (i == 0) ? top - 1 : (i == last) ? h * 32 + 1 : (i & 1) ? top - 2 - i : top + 2 - i;
            pr.next(SLOT);
            const bool lastrd = (rd == 0) ? ((LASTRD & 1) && ca >= 8 - LASTN) : (rd == 1) ? ((LASTRD & 2) && (ca & 3) >= 4 - LASTN) : (rd == 2) ? ((LASTRD & 4) && (ca == 3 || (ca < 3 && (t & 31) >= 4 * p))) : (LASTRD & 8) != 0;
            if (lastrd) w_tma_load_mc_last(pr.dst + rank * 16384, &P.kv, rank * 64, t * 128, pr.fb);
            else w_tma_load_mc(pr.dst + rank * 16384, &P.kv, rank * 64, t * 128, pr.fb);
            if (i == 2) {
                if (rd < 3) {
                    w_tma_prefetch(&P.wq, (h + 8) * 128 + rank * 64, ca * 64);
                    if (ca < 2) w_tma_prefetch(&P.wq, (h + 8) * 128 + rank * 64, (ca + 8) * 64);
                } else {
#pragma unroll 1
                    for (int j = 0; j < 10; j++) {
                        const int tt = ca + (j >= 5 ? 8 : 0);
                        w_tma_prefetch(&P.wo, 320 * (cb & 1) + 64 * (j >= 5 ? j - 5 : j), (8 * (tt >> 2) + (cb & 6) + ((tt >> 1) & 1)) * 128 + (tt & 1) * 64 + rank * 32);
                    }
                }
            }
        }
        PROF(9 + rd * 4);
    }
    {
        const int n0 = 320 * (cb & 1), kg = cb >> 1;
#pragma unroll 1
        for (int t = 0; t < 16; t++) {
            const int h = 8 * (t >> 2) + 2 * kg + ((t >> 1) & 1), ks = t & 1;
            const int krow = h * 128 + ks * 64 + rank * 32;
            pr.next(SLOT);
            w_tma_load_mc(pr.dst + 16384 + rank * 8192, &P.wo, n0, krow, pr.fb);
            w_tma_load_mc(pr.dst + 16384 + rank * 8192 + 4096, &P.wo, n0 + 64, krow, pr.fb);
            mbar_wait(bars + BAR_DEP + (5 + (t >> 1)) * 8, 0);
            w_tma_load(pr.dst, &P.ctx, ks * 64, h * SEQ + 256 * ca + 128 * rank, pr.fb);
            pr.next(24576);
#pragma unroll
            for (int c = 0; c < 3; c++) w_tma_load_mc(pr.dst + rank * 12288 + c * 4096, &P.wo, n0 + 128 + 64 * c, krow, pr.fb);
        }
    }
}

struct Slot {
    uint32_t bo, dl, par;
};
struct Cons {
    uint32_t bars, rel;
    uint32_t dl0;
    uint32_t lane;
    Slot cur;
    __device__ __forceinline__ Slot slot(int s, uint32_t par) const { return Slot{(uint32_t)s * 8, dl0 + (uint32_t)s * (SLOT >> 4), par}; }
    __device__ __forceinline__ void wait(const Slot& s) const { mbar_wait(bars + BAR_FULL + s.bo, s.par); }
    __device__ __forceinline__ void release(uint32_t bo) const {
        asm volatile("{\n.reg .pred p;\nsetp.lt.u32 p, %1, 2;\n@p mbarrier.arrive.shared::cluster.b64 _, [%0];\n}\n" ::"r"(rel + bo), "r"(lane) : "memory");
    }
    __device__ __forceinline__ Slot next() {
        const Slot s = cur;
        const bool wrap = s.bo == (NSLOT - 1) * 8;
        cur.bo = wrap ? 0u : s.bo + 8;
        cur.dl = wrap ? dl0 : s.dl + (SLOT >> 4);
        cur.par = s.par ^ (wrap ? 1u : 0u);
        return s;
    }
};
__host__ __device__ constexpr uint32_t lbo(uint32_t bytes) { return (bytes >> 4) << 16; }

__device__ __forceinline__ float div640(float x) {
    const float q = x * (1.0f / DM);
    return fmaf(fmaf(-q, (float)DM, x), 1.0f / DM, q);
}
__device__ __forceinline__ float sqrt_approx(float x) {
    float y;
    asm("sqrt.approx.ftz.f32 %0, %1;" : "=f"(y) : "f"(x));
    return y;
}
struct LayerNorm {
    uint4 xv[5], wv[5];
    float mean, inv, r;
    static __device__ __forceinline__ float half_sum(float v) {
#pragma unroll
        for (int o = 8; o > 0; o >>= 1) v += __shfl_xor_sync(0xffffffffu, v, o);
        return v;
    }
    __device__ __forceinline__ void load(const __nv_bfloat16* x, const __nv_bfloat16* wr, int t, int l) {
#pragma unroll
        for (int i = 0; i < 5; i++) {
            xv[i] = ldg_stream(reinterpret_cast<const uint4*>(x + t * DM) + l + 16 * i);
            wv[i] = __ldg(reinterpret_cast<const uint4*>(wr) + l + 16 * i);
        }
    }
    __device__ __forceinline__ void stat1() {
        float a[4] = {0.f, 0.f, 0.f, 0.f};
#pragma unroll
        for (int i = 0; i < 20; i++) { const uint32_t u = (&xv[i >> 2].x)[i & 3]; a[i & 3] += bf_lo(u) + bf_hi(u); }
        mean = div640(half_sum((a[0] + a[1]) + (a[2] + a[3])));
        r = 0.f;
    }
    template <int H>
    __device__ __forceinline__ void stat2() {
        float a[4] = {r, 0.f, 0.f, 0.f};
#pragma unroll
        for (int i = H ? 12 : 0; i < (H ? 20 : 12); i++) {
            uint32_t u = (&xv[i >> 2].x)[i & 3];
            asm volatile("" : "+r"(u));
            const float d0 = bf_lo(u) - mean, d1 = bf_hi(u) - mean;
            a[i & 3] = fmaf(d0, d0, fmaf(d1, d1, a[i & 3]));
        }
        r = (a[0] + a[1]) + (a[2] + a[3]);
        if (H) {
            inv = rcp(round_bf16(sqrt_approx(round_bf16(round_bf16(div640(half_sum(r))) + 1e-5f))));
            r = 0.f;
        }
    }
    template <int I>
    __device__ __forceinline__ void piece(__nv_bfloat16* out, int t, int l) {
        const uint32_t nmb = pack_bf16(-mean, -mean);
        uint32_t o[4], z[4];
        float a[4];
#pragma unroll
        for (int j = 0; j < 4; j++) {
            const uint32_t u = (&xv[I].x)[j], w = (&wv[I].x)[j];
            const uint32_t d = add_bf16x2(u, nmb);
            o[j] = pack_bf16(bf_lo(d) * inv, bf_hi(d) * inv);
            z[j] = add_bf16x2(u, o[j]);
            a[j] = fmaf(bf_hi(o[j]), bf_hi(w), bf_lo(o[j]) * bf_lo(w));
        }
        r += (a[0] + a[1]) + (a[2] + a[3]);
        stg128(g_xn + perm_row(t) * DM + 8 * (l + 16 * I), o[0], o[1], o[2], o[3]);
        stg128p(out + t * DM + 8 * (l + 16 * I), z[0], z[1], z[2], z[3], policy_sel(EFMASK & 1));
        if (I == 4) {
            r = half_sum(r);
            if (l == 0) g_r[t] = round_bf16(r);
        }
    }
};

constexpr float SM_SCALE = 0.08838834764831845f * 1.4426950408889634f;

template <int J0, int J1>
__device__ __forceinline__ void exp_part(float (&s)[64], float n0, float n1, float& r0, float& r1) {
    float a1 = 0.f, b1 = 0.f;
#pragma unroll
    for (int j = J0; j < J1; j++) {
        s[4 * j + 0] = ex2(fmaf(s[4 * j + 0], SM_SCALE, n0));
        s[4 * j + 1] = ex2(fmaf(s[4 * j + 1], SM_SCALE, n0));
        s[4 * j + 2] = ex2(fmaf(s[4 * j + 2], SM_SCALE, n1));
        s[4 * j + 3] = ex2(fmaf(s[4 * j + 3], SM_SCALE, n1));
        r0 += s[4 * j + 0]; r1 += s[4 * j + 2];
        if (j == J0) { a1 = s[4 * j + 1]; b1 = s[4 * j + 3]; } else { a1 += s[4 * j + 1]; b1 += s[4 * j + 3]; }
    }
    r0 += a1;
    r1 += b1;
}
__device__ __forceinline__ void sched_barrier(float x, float y, uint32_t scratch) {
    asm volatile("{\n.reg .pred p;\nsetp.lt.f32 p, %0, 0f00000000;\n@p st.shared.f32 [%2], %1;\n}\n" ::"f"(x), "f"(y), "r"(scratch) : "memory");
}
__device__ __forceinline__ void pack_tile(const float (&s)[64], uint32_t (&p)[32]) {
#pragma unroll
    for (int i = 0; i < 32; i++) p[i] = pack_bf16(s[2 * i], s[2 * i + 1]);
}
template <bool ZERO>
__device__ __forceinline__ void gemm_rs(float (&d)[64], const uint32_t (&a)[32], uint32_t dl, int acc = 1) {
    const uint32_t b = dl + lbo(16384);
    if (ZERO) wgmma_rs_n128_z<1>(d, a[0], a[1], a[2], a[3], b);
#pragma unroll
    for (int k = ZERO ? 1 : 0; k < 8; k++) wgmma_rs_n128<1>(d, a[4 * k], a[4 * k + 1], a[4 * k + 2], a[4 * k + 3], b + k * 128, k ? 1 : acc);
}
template <int ZERO>
__device__ __forceinline__ void gemm_q(float (&d)[64], uint32_t dl, int role) {
    const uint32_t a = dl + role * 512 + lbo(16), b = dl + 1024 + lbo(8192);
    if (ZERO) wgmma_ss_n128_z<0, 1>(d, a, b);
#pragma unroll
    for (int k = ZERO ? 1 : 0; k < 4; k++) wgmma_ss_n128<0, 1>(d, a + k * 2, b + k * 128, 1);
}
template <bool KT, bool ZERO, int K0, int K1>
__device__ __forceinline__ void gemm_kv(float (&d)[64], uint32_t ckv, uint32_t wt, int wg) {
    if (KT) {
        const uint32_t a = wt + wg * 1024 + lbo(16), b = ckv + lbo(16);
        if (ZERO) wgmma_ss_n128_z<1, 0>(d, a, b);
#pragma unroll
        for (int k = ZERO ? 1 : K0; k < K1; k++) wgmma_ss_n128<1, 0>(d, a + k * 128, b + (k >> 2) * 1024 + (k & 3) * 2, 1);
    } else {
        const uint32_t a = ckv + wg * 512 + lbo(16), b = wt + lbo(16384);
        if (ZERO) wgmma_ss_n128_z<0, 1>(d, a, b);
#pragma unroll
        for (int k = ZERO ? 1 : K0; k < K1; k++) wgmma_ss_n128<0, 1>(d, a + (k >> 2) * 1024 + (k & 3) * 2, b + k * 128, 1);
    }
}
__device__ __forceinline__ void mma16816(float& d0, float& d1, float& d2, float& d3, uint32_t a0, uint32_t a1, uint32_t a2, uint32_t a3, uint32_t b0, uint32_t b1) {
    asm volatile("mma.sync.aligned.m16n8k16.row.col.f32.bf16.bf16.f32 {%0,%1,%2,%3}, {%4,%5,%6,%7}, {%8,%9}, {%0,%1,%2,%3};"
                 : "+f"(d0), "+f"(d1), "+f"(d2), "+f"(d3) : "r"(a0), "r"(a1), "r"(a2), "r"(a3), "r"(b0), "r"(b1));
}
__device__ __forceinline__ uint32_t ld_pair(const __nv_bfloat16* p) {
    const unsigned short* u = reinterpret_cast<const unsigned short*>(p);
    return (uint32_t)__ldcg(u) | ((uint32_t)__ldcg(u + 128) << 16);
}
__device__ __forceinline__ void attention_exact(float (&o)[64], const uint32_t (&qf)[32], float& l0, float& l1, int h, int nblk, int rr, int lane) {
    const int q = lane & 3, lr = lane >> 2;
    float m0 = -INFINITY, m1 = -INFINITY;
    l0 = 0.f; l1 = 0.f;
#pragma unroll
    for (int i = 0; i < 64; i++) o[i] = 0.f;
#pragma unroll 1
    for (int cidx = 0; cidx < nblk * 8; cidx++) {
        const int kc = cidx & 7;
        const __nv_bfloat16* kt = g_kv + (size_t)((h * 16 + (cidx >> 3)) * 2) * 16384;
        float sc[8];
#pragma unroll
        for (int i = 0; i < 8; i++) sc[i] = 0.f;
#pragma unroll
        for (int kk = 0; kk < 8; kk++)
#pragma unroll
            for (int nt = 0; nt < 2; nt++) {
                const __nv_bfloat16* b = kt + (16 * kk + 2 * q) * 128 + 16 * kc + 8 * nt + lr;
                mma16816(sc[4 * nt], sc[4 * nt + 1], sc[4 * nt + 2], sc[4 * nt + 3], qf[4 * kk], qf[4 * kk + 1], qf[4 * kk + 2], qf[4 * kk + 3],
                         ld_pair(b), ld_pair(b + 8 * 128));
            }
        const int lim = rr + ((nblk - 1) - (cidx >> 3)) * 128 - 32 * (kc >> 1) - 4 * (kc & 1);
#pragma unroll
        for (int i = 0; i < 8; i++)
            if (2 * (i >> 2) + (i & 1) > lim + 4 * (i & 2)) sc[i] = -INFINITY;
        float x0 = fmaxf(fmaxf(sc[0], sc[1]), fmaxf(sc[4], sc[5])), x1 = fmaxf(fmaxf(sc[2], sc[3]), fmaxf(sc[6], sc[7]));
        x0 = fmaxf(x0, __shfl_xor_sync(0xffffffffu, x0, 1)); x1 = fmaxf(x1, __shfl_xor_sync(0xffffffffu, x1, 1));
        x0 = fmaxf(x0, __shfl_xor_sync(0xffffffffu, x0, 2)); x1 = fmaxf(x1, __shfl_xor_sync(0xffffffffu, x1, 2));
        x0 = fmaxf(x0, m0); x1 = fmaxf(x1, m1);
        const float a0 = ex2((m0 - x0) * SM_SCALE), a1 = ex2((m1 - x1) * SM_SCALE);
        m0 = x0; m1 = x1;
#pragma unroll
        for (int i = 0; i < 8; i++) sc[i] = ex2((sc[i] - ((i & 2) ? m1 : m0)) * SM_SCALE);
        l0 = l0 * a0 + (sc[0] + sc[1]) + (sc[4] + sc[5]);
        l1 = l1 * a1 + (sc[2] + sc[3]) + (sc[6] + sc[7]);
        const uint32_t p0 = pack_bf16(sc[0], sc[1]), p1 = pack_bf16(sc[2], sc[3]), p2 = pack_bf16(sc[4], sc[5]), p3 = pack_bf16(sc[6], sc[7]);
        const __nv_bfloat16* vb = kt + 16384 + (16 * kc + 2 * q) * 128 + lr;
#pragma unroll
        for (int nt = 0; nt < 16; nt++) {
            o[4 * nt] *= a0; o[4 * nt + 1] *= a0; o[4 * nt + 2] *= a1; o[4 * nt + 3] *= a1;
            mma16816(o[4 * nt], o[4 * nt + 1], o[4 * nt + 2], o[4 * nt + 3], p0, p1, p2, p3, ld_pair(vb + 8 * nt), ld_pair(vb + 8 * nt + 8 * 128));
        }
    }
}

__device__ __forceinline__ void signal(uint32_t bars, int wg, int e, int lane) {
    __syncwarp();
    asm volatile("{\n.reg .pred p;\nsetp.eq.u32 p, %1, 0;\n@p mbarrier.arrive.shared::cta.b64 _, [%0];\n}\n" ::"r"(bars + BAR_SIG + (wg * 9 + e) * 8), "r"(lane) : "memory");
}

__device__ __forceinline__ void consumer(const Params& P, uint32_t smem, uint32_t bars, int ca, int cb, int rank, int wg) {
    const int lane = threadIdx.x & 31, w = (threadIdx.x >> 5) & 3, q = lane & 3, lr = lane >> 2;
    PROF(7);
    cluster_wait();
    Cons c{bars, mapa(bars + BAR_EMPTY, lane & 1), (smem & 0x3FFFF) >> 4, (uint32_t)lane, Slot{0u, (smem & 0x3FFFF) >> 4, 1u}};
    PROFG(180);
    PROF(1);
    float o[64], s[64];
    uint32_t pend;
    __nv_bfloat16* ep_ptr;
    int ep_step;
    {
        const int ln_t = blockIdx.x * 16 + wg * 8 + w * 2 + (lane >> 4);
        const int krow = 64 * wg + 16 * w + lr;
        const int vrow = 64 * wg + 32 * (w >> 1) + 8 * (lr >> 1) + 4 * (w & 1) + (lr & 1);
        ep_step = 2 * 128;
        int m = 0;
        uint32_t lap = 0;
        LayerNorm ln;
        auto step = [&](auto kt, auto kc, float (&d)[64], int hh) {
            const Slot sa = c.slot(slot_a(kc.value), 0), sw = c.slot(slot_w(m), lap ^ (m >> 1));
            lap ^= m >> 1;
            m = (m == 2) ? 0 : m + 1;
            TR(1 + (hh * 8 + (kt.value ? 0 : 4) + kc.value) * 2);
            if (kt.value && hh == 0) c.wait(sa);
            c.wait(sw);
            TR(2 + (hh * 8 + (kt.value ? 0 : 4) + kc.value) * 2);
            wgmma_fence();
            gemm_kv<kt.value, kc.value == 0, 0, KVSPLIT>(d, sa.dl, sw.dl, wg);
            wgmma_commit();
            wgmma_wait<1>();
            if (!(kt.value && kc.value == 0 && hh == 0)) c.release(pend);
            if (!kt.value && kc.value > 0 && hh == 3) c.release(slot_a(kc.value - 1) * 8);
            pend = sw.bo;
            wgmma_fence();
            gemm_kv<kt.value, false, KVSPLIT, 8>(d, sa.dl, sw.dl, wg);
            wgmma_commit();
        };
#pragma unroll 1
        for (int hh = 0; hh < 4; hh++) {
            __nv_bfloat16* base = g_kv + (size_t)(((cb + 8 * kv_round(hh)) * 16 + 2 * ca + rank) * 2) * 16384 + 8 * q;
            auto ln_stage = [&](auto pos) {
                constexpr int j = (pos.value + 8 - LNOFF % 8) % 8;
                if (hh == wg * LNSTAG + (LNOFF + j) / 8) {
                    if (j == 0) ln.stat1();
                    if (j == 1) ln.template stat2<0>();
                    if (j == 2) ln.template stat2<1>();
                    if constexpr (j >= 3) ln.template piece<j - 3>(P.out, ln_t, lane & 15);
                    if (j == 7) signal(bars, wg, 0, lane);
                }
                if (pos.value == (LNOFF - LNLEAD) % 8 && hh == wg * LNSTAG + (LNOFF - LNLEAD) / 8) ln.load(P.x, P.wr, ln_t, lane & 15);
            };
            for4([&](auto kc) {
                step(TrueT{}, kc, s, hh);
                if (hh > 0) {
                    if (kc.value == 0) fence_regs(o);
                    store_chunk<kc.value>(o, ep_ptr, ep_ptr + ep_step, 1.f, 1.f, policy_sel(false));
                    if (kc.value == 3) signal(bars, wg, hh, lane);
                }
                ln_stage(kc);
            });
            for4([&](auto kc) {
                step(FalseT{}, kc, o, hh);
                if (kc.value == 0) fence_regs(s);
                store_chunk<kc.value>(s, base + krow * 128, base + (krow + 8) * 128, 1.f, 1.f, policy_sel(false));
                ln_stage(IntT<kc.value + 4>{});
            });
            PROF(24 + hh);
            if (hh == 1) PROFG(181);
            ep_ptr = base + 16384 + vrow * 128;
        }
    }
    PROFG(182);
    PROF(2);
    uint32_t pf[32];
    {
        uint32_t qf[32];
        float l0 = 0.25f, l1 = 0.25f;
        const int bar_me = 2 + wg, bar_other = 3 - wg;
#pragma unroll 1
        for (int rd = 0; rd < 4; rd++) {
            const int h = 8 * rd + cb, p = item_p(ca, rd);
            const int role = wg ^ (rd & 1);
            const int nrest = 2 * p + role;
            Slot kfirst;
            const int lim = 64 * (role ^ rank) + 16 * w + lr - 8 * q;
            const uint64_t pol = policy_sel(((EFMASK & 4) && rd == 1) || ((EFMASK & 8) && rd == 2));
            {
                auto qstep = [&](auto zero, int ks) {
                    const Slot sl = c.next();
                    c.wait(sl);
                    BP(2, 5 + 3 * ks);
                    wgmma_fence();
                    gemm_q<zero.value>(s, sl.dl, role);
                    wgmma_commit();
                    wgmma_wait<1>();
                    c.release(pend);
                    pend = sl.bo;
                };
                qstep(TrueT{}, 0);
                if (rd == 0) c.release(slot_a(3) * 8);
                fence_regs(o);
                l0 += __shfl_xor_sync(0xffffffffu, l0, 1); l1 += __shfl_xor_sync(0xffffffffu, l1, 1);
                l0 += __shfl_xor_sync(0xffffffffu, l0, 2); l1 += __shfl_xor_sync(0xffffffffu, l1, 2);
                l0 = rcp(l0); l1 = rcp(l1);
                for4([&](auto i) {
                    constexpr int B = 16 * i.value;
#pragma unroll
                    for (int r = 0; r < 2; r++) {
                        qstep(FalseT{}, 1 + 2 * i.value + r);
                        const float f = r ? l1 : l0;
                        stg128p(ep_ptr + r * ep_step + 2 * B, pack_bf16(o[B + 2 * r] * f, o[B + 2 * r + 1] * f), pack_bf16(o[B + 2 * r + 4] * f, o[B + 2 * r + 5] * f),
                                pack_bf16(o[B + 2 * r + 8] * f, o[B + 2 * r + 9] * f), pack_bf16(o[B + 2 * r + 12] * f, o[B + 2 * r + 13] * f), pol);
#pragma unroll
                        for (int k = 0; k < 8; k++) {
                            float& v = o[B + 4 * (k >> 1) + 2 * r + (k & 1)];
                            v = (2 * B + k > lim + 8 * r) ? -1e30f : 0.f;
                            asm volatile("" : "+f"(v));
                        }
                    }
                });
                signal(bars, wg, 4 + rd, lane);
                PROF(11 + rd * 4);
                qstep(FalseT{}, 9);
                if (!role) { const Slot sl = c.next(); c.wait(sl); c.release(sl.bo); }
                kfirst = c.next();
                c.wait(kfirst);
                wgmma_wait<0>();
                BP(2, 34);
                c.release(pend);
                fence_regs(s);
                pack_tile(s, qf);
            }
            PROF(8 + rd * 4);
            fence_regs(qf); fence_regs(o);
            if (PINGPONG && !role) named_sync(bar_me, 256);
            BP(2, 36);
            wgmma_fence();
            gemm_rs<false>(o, qf, kfirst.dl);
            wgmma_commit();
            if (PINGPONG) named_arrive(bar_other, 256);
            if (!role) { const Slot sl = c.next(); c.wait(sl); c.release(sl.bo); }
            wgmma_wait<0>();
            BP(2, 38);
            fence_regs(o);
            c.release(kfirst.bo);
            float n0 = fmaxf(fmaxf(fmaxf(o[0], o[1]), fmaxf(o[4], o[5])), fmaxf(fmaxf(o[8], o[9]), fmaxf(o[12], o[13])));
            float n1 = fmaxf(fmaxf(fmaxf(o[2], o[3]), fmaxf(o[6], o[7])), fmaxf(fmaxf(o[10], o[11]), fmaxf(o[14], o[15])));
            n0 = __shfl_sync(0xffffffffu, n0, lane & 28); n1 = __shfl_sync(0xffffffffu, n1, lane & 28);
            n0 *= -SM_SCALE; n1 *= -SM_SCALE;
            l0 = 0.f; l1 = 0.f;
#pragma unroll
            for (int i = 0; i < 64; i++) s[i] = o[i];
            exp_part<0, 8>(s, n0, n1, l0, l1);
#pragma unroll
            for (int i = 0; i < 16; i++) pf[i] = pack_bf16(s[2 * i], s[2 * i + 1]);
            if (role != rank) {
                exp_part<8, 16>(s, n0, n1, l0, l1);
#pragma unroll
                for (int i = 16; i < 32; i++) pf[i] = pack_bf16(s[2 * i], s[2 * i + 1]);
            } else {
#pragma unroll
                for (int i = 16; i < 32; i++) pf[i] = 0u;
            }
            PROF(9 + rd * 4);
#pragma unroll 1
            for (int it = 0; it < nrest; it++) {
                const Slot sk = c.next(), sv = c.next();
                LP(0);
                c.wait(sk);
                c.wait(sv);
                fence_regs(o); fence_regs(pf);
                LP(1);
                if (PINGPONG) named_sync(bar_me, 256);
                LP(2);
                if (it < 3) BP(2, 42 + 4 * it);
                if (it >= nrest - 2) BP(1, 62 + 4 * (it - nrest + 2));
                wgmma_fence();
                gemm_rs<true>(s, qf, sk.dl);
                wgmma_commit();
                gemm_rs<false>(o, pf, sv.dl, it);
                wgmma_commit();
                if (PINGPONG) named_arrive(bar_other, 256);
                LP(3);
                wgmma_wait<1>();
                LP(4);
                c.release(sk.bo);
                fence_regs(s);
                exp_part<0, SPLITJ>(s, n0, n1, l0, l1);
                sched_barrier(l0, l1, bars + MISC_OFF + 16);
                LP(5);
                wgmma_wait<0>();
                LP(6);
                c.release(sv.bo);
                fence_regs(o); fence_regs(pf);
                exp_part<SPLITJ, 16>(s, n0, n1, l0, l1);
                pack_tile(s, pf);
            }
            PROF(10 + rd * 4);
            PROFG(183 + rd);
            const Slot sv = c.next();
            BP(1, 0);
            c.wait(sv);
            if (nrest == 0) {
#pragma unroll
                for (int i = 0; i < 64; i++) o[i] = 0.f;
            }
            if (__builtin_expect(__any_sync(0xffffffffu, !(l0 < 0x1p60f && l1 < 0x1p60f)), 0)) {
                attention_exact(o, qf, l0, l1, h, nrest + 1, lim, lane);
#pragma unroll
                for (int i = 0; i < 32; i++) pf[i] = 0u;
            }
            fence_regs(o); fence_regs(pf);
            if (PINGPONG && !role) named_sync(bar_me, 256);
            BP(1, 2);
            wgmma_fence();
            gemm_rs<false>(o, pf, sv.dl);
            wgmma_commit();
            pend = sv.bo;
            ep_ptr = g_ctx + (size_t)(h * SEQ + 256 * p + 128 * rank + 64 * role + 16 * w + lr) * HD + 8 * q;
            ep_step = 8 * HD;
        }
        l0 += __shfl_xor_sync(0xffffffffu, l0, 1); l1 += __shfl_xor_sync(0xffffffffu, l1, 1);
        l0 += __shfl_xor_sync(0xffffffffu, l0, 2); l1 += __shfl_xor_sync(0xffffffffu, l1, 2);
        l0 = rcp(l0); l1 = rcp(l1);
        wgmma_wait<0>();
        c.release(pend);
        fence_regs(o); fence_regs(pf);
#pragma unroll
        for (int i = 0; i < 32; i++) pf[i] = pack_bf16(o[2 * i] * ((i & 1) ? l1 : l0), o[2 * i + 1] * ((i & 1) ? l1 : l0));
    }
    PROFG(187);
    PROF(3);
    {
        float a1[64], a2[96];
        uint32_t px = 0, py = 0;
        auto mma1 = [&](const Slot& x, int acc) {
#pragma unroll
            for (int k = 0; k < 4; k++) wgmma_ss_n128<0, 1>(a1, x.dl + wg * 512 + lbo(16) + k * 2, x.dl + 1024 + lbo(4096) + (k >> 1) * 512 + (k & 1) * 128, k ? 1 : acc);
        };
        auto mma2 = [&](const Slot& x, const Slot& y, int acc) {
#pragma unroll
            for (int k = 0; k < 4; k++) wgmma_ss_n192<0, 1>(a2, x.dl + wg * 512 + lbo(16) + k * 2, y.dl + lbo(4096) + (k >> 1) * 768 + (k & 1) * 128, k ? 1 : acc);
        };
#pragma unroll 1
        for (int t = 0; t < (EARLYSEND ? 14 : 16); t++) {
            const Slot sx = c.next(), sy = c.next();
            c.wait(sx);
            wgmma_fence();
            mma1(sx, t);
            wgmma_commit();
            wgmma_wait<1>();
            if (t > 0) { c.release(px); c.release(py); }
            px = sx.bo; py = sy.bo;
            c.wait(sy);
            wgmma_fence();
            mma2(sx, sy, t);
            wgmma_commit();
            if (t == 0) {
#pragma unroll
                for (int i = 0; i < 4; i++) stg128(ep_ptr + 32 * i, pf[8 * i], pf[8 * i + 2], pf[8 * i + 4], pf[8 * i + 6]);
            }
            if (t == 1) {
#pragma unroll
                for (int i = 0; i < 4; i++) stg128(ep_ptr + 8 * HD + 32 * i, pf[8 * i + 1], pf[8 * i + 3], pf[8 * i + 5], pf[8 * i + 7]);
                signal(bars, wg, 8, lane);
            }
        }
        if (EARLYSEND) {
            const Slot x0 = c.next(), y0 = c.next(), x1 = c.next(), y1 = c.next();
            c.wait(x0);
            c.wait(y0);
            wgmma_fence();
            mma2(x0, y0, 1);
            wgmma_commit();
            wgmma_wait<1>();
            c.release(px); c.release(py);
            c.wait(x1);
            c.wait(y1);
            wgmma_fence();
            mma2(x1, y1, 1);
            wgmma_commit();
            mma1(x0, 1);
            mma1(x1, 1);
            wgmma_commit();
        }
        const int cw = __reduce_or_sync(0xffffffffu, wg * 4 + w);
        Slot st = c.next();
        if (cw >= 3) st = c.next();
        if (cw >= 6) st = c.next();
        const uint32_t stage = smem + st.bo * (SLOT / 8) + (cw % 3) * 10240;
        const int orow = unperm_row(256 * ca + 128 * rank + 16 * cw), ocol = 320 * (cb & 1);
        const uint32_t sa = stage + ((lane & 7) + (lane & 8)) * 128, sx = (lane >> 4) ^ (lane & 7);
        auto send = [&](auto c0, auto c1) {
#pragma unroll
            for (int ch = c0.value; ch < c1.value; ch++) {
#pragma unroll
                for (int i = 0; i < 4; i++) {
                    uint32_t r[4];
#pragma unroll
                    for (int e = 0; e < 4; e++) {
                        const int k = 32 * ch + 8 * i + 2 * e;
                        r[e] = (ch < 2) ? pack_bf16(a1[k & 63], a1[(k & 63) + 1]) : pack_bf16(a2[ch < 2 ? 0 : k - 64], a2[ch < 2 ? 1 : k - 63]);
                    }
                    asm volatile("stmatrix.sync.aligned.m8n8.x4.shared.b16 [%0], {%1, %2, %3, %4};"
                                 ::"r"(sa + ch * 2048 + ((sx ^ (2 * i)) << 4)), "r"(r[0]), "r"(r[1]), "r"(r[2]), "r"(r[3]) : "memory");
                }
                if (FENCE_EACH || ch == c1.value - 1) {
                    asm volatile("fence.proxy.async.shared::cta;" ::: "memory");
                    __syncwarp();
#pragma unroll
                    for (int b = FENCE_EACH ? ch : c0.value; b <= ch; b++)
                        asm volatile(ELECT "cp.reduce.async.bulk.tensor.2d.global.shared::cta.add.bulk_group [%0, {%2, %3}], [%1];\n}\n"
                                     ::"l"(&P.outm), "r"(stage + b * 2048), "r"(ocol + 64 * b), "r"(orow) : "memory");
                }
            }
        };
        mbar_wait(bars + BAR_EMPTY + st.bo, st.par ^ 1);
        mbar_wait(bars + BAR_DEP + 13 * 8, 0);
        wgmma_wait<EARLYSEND>();
        fence_regs(a2);
        send(IntT<2>{}, IntT<5>{});
        wgmma_wait<0>();
        fence_regs(a1);
        PROFG(188);
        PROF(4);
        send(IntT<0>{}, IntT<2>{});
        PROF(5);
        asm volatile("cp.async.bulk.commit_group;\ncp.async.bulk.wait_group.read 0;" ::: "memory");
    }
    PROF(6);
}

__device__ __forceinline__ void mma_rows(float (&acc)[8][4], uint32_t a0, uint32_t a2, const uint4& w0, const uint4& w1, const uint4& w2, const uint4& w3) {
    const uint32_t r0[4] = {w0.x, w0.y, w0.z, w0.w}, r1[4] = {w1.x, w1.y, w1.z, w1.w};
    const uint32_t r2[4] = {w2.x, w2.y, w2.z, w2.w}, r3[4] = {w3.x, w3.y, w3.z, w3.w};
#pragma unroll
    for (int i = 0; i < 4; i++) {
        mma16816(acc[2 * i][0], acc[2 * i][1], acc[2 * i][2], acc[2 * i][3], a0, 0u, a2, 0u, __byte_perm(r0[i], r1[i], 0x5410), __byte_perm(r2[i], r3[i], 0x5410));
        mma16816(acc[2 * i + 1][0], acc[2 * i + 1][1], acc[2 * i + 1][2], acc[2 * i + 1][3], a0, 0u, a2, 0u, __byte_perm(r0[i], r1[i], 0x7632), __byte_perm(r2[i], r3[i], 0x7632));
    }
}

__device__ __forceinline__ void mod_ffn(const Params& P, uint8_t* sm, int mc  ) {
    const int tid = threadIdx.x - 128, lane = tid & 31, cw = tid >> 5, q = lane & 3, lr = lane >> 2;
    const uint32_t epoch = (tid == 0) ? read_epoch() : 0u;
    uint32_t* xs = reinterpret_cast<uint32_t*>(sm);
    uint32_t* wmax = xs + 8 * 324;
    int* sidx = reinterpret_cast<int*>(wmax + 16);
    const int fg = cw * 4 + mc;
    const uint32_t ring = smem_u32(sm) + 16384 + cw * 24576, rbar = smem_u32(sm) + 12288 + cw * 32;
    auto issue = [&](int u, int st) {
        if (lane == 0 && u < 30) {
            mbar_expect_tx(rbar + st * 8, 8192);
            if (u < 20) {
                tma_load_stream(ring + st * 8192, &P.wg, fg * 64, u * 32, rbar + st * 8);
                tma_load_stream(ring + st * 8192 + 4096, &P.wu, fg * 64, u * 32, rbar + st * 8);
            } else {
                tma_load_stream(ring + st * 8192, &P.wd, (u - 20) * 64, fg * 64, rbar + st * 8);
            }
        }
    };
    if (lane == 0) {
        mbar_init(rbar, 1); mbar_init(rbar + 8, 1); mbar_init(rbar + 16, 1);
        asm volatile("fence.mbarrier_init.release.cluster;" ::: "memory");
    }
    if (tid == 0) flag_wait<100>(F_LN, 256u * (epoch + 1));
    named_sync(1, 256);
    PROF(1);
    if (fg < 27) {
#pragma unroll 1
        for (int u = 0; u < 3; u++) issue(u, u);
    }
    PROF(2);
    uint32_t key[8];
#pragma unroll
    for (int i = 0; i < 8; i++) {
        const int t = tid + 256 * i;
        uint32_t b = __float_as_uint(__ldcg(g_r + t) + 0.f) >> 16;
        b = (b & 0x8000u) ? (~b & 0xffffu) : (b | 0x8000u);
        key[i] = (b << 16) | (uint32_t)(0xffff - t);
    }
#pragma unroll 1
    for (int rnd = 0; rnd < 8; rnd++) {
        uint32_t mx = key[0];
#pragma unroll
        for (int i = 1; i < 8; i++) mx = max(mx, key[i]);
        mx = __reduce_max_sync(0xffffffffu, mx);
        if (lane == 0) wmax[(rnd & 1) * 8 + cw] = mx;
        named_sync(1, 256);
        mx = __reduce_max_sync(0xffffffffu, wmax[(rnd & 1) * 8 + (lane & 7)]);
#pragma unroll
        for (int i = 0; i < 8; i++) if (key[i] == mx) key[i] = 0;
        if (tid == 0) sidx[rnd] = 0xffff - (int)(mx & 0xffffu);
    }
    named_sync(1, 256);
    {
        const uint32_t* src = reinterpret_cast<const uint32_t*>(g_xn + (size_t)perm_row(sidx[cw]) * DM);
#pragma unroll 2
        for (int i = lane; i < 320; i += 32) xs[cw * 324 + i] = __ldcg(src + i);
    }
    named_sync(1, 256);
    PROF(3);
    if (fg < 27) {
        float g[8][4], v[8][4];
        uint32_t hp[8];
#pragma unroll
        for (int i = 0; i < 8; i++)
#pragma unroll
            for (int e = 0; e < 4; e++) { g[i][e] = 0.f; v[i][e] = 0.f; }
        int st = 0, ph = 0;
#pragma unroll 1
        for (int u = 0; u < 60; u++) {
            if (!(u & 1)) mbar_wait(rbar + st * 8, ph);
            uint4 a[8];
#pragma unroll
            for (int r = 0; r < 8; r++) {
                const int row = (u < 40) ? 32 * (r >> 2) + 16 * (u & 1) + 2 * q + (r & 1) + 4 * (r & 2) : 16 * q + 8 * (u & 1) + r;
                asm volatile("ld.shared.v4.b32 {%0, %1, %2, %3}, [%4];" : "=r"(a[r].x), "=r"(a[r].y), "=r"(a[r].z), "=r"(a[r].w)
                             : "r"(ring + st * 8192 + row * 128 + ((lr ^ row) & 7) * 16) : "memory");
            }
            uint32_t f0, f1, f2, f3;
            if (u < 40) { f0 = f2 = xs[lr * 324 + u * 8 + q]; f1 = f3 = xs[lr * 324 + u * 8 + 4 + q]; }
            else if (u & 1) { f0 = hp[4]; f1 = hp[5]; f2 = hp[6]; f3 = hp[7]; }
            else { f0 = hp[0]; f1 = hp[1]; f2 = hp[2]; f3 = hp[3]; }
            mma_rows(g, f0, f1, a[0], a[1], a[2], a[3]);
            mma_rows(v, f2, f3, a[4], a[5], a[6], a[7]);
            if (u & 1) {
                __syncwarp();
                issue((u >> 1) + 3, st);
                if (++st == 3) { st = 0; ph ^= 1; }
                if (u >= 39) {
                    if (u == 39) {
                        float hv[16];
#pragma unroll
                        for (int i = 0; i < 16; i++) {
                            const float gp = round_bf16(g[i & 7][i >> 3]);
                            hv[i] = round_bf16(__fdividef(gp, 1.0f + __expf(fminf(-gp, 80.f)))) * round_bf16(v[i & 7][i >> 3]);
                        }
#pragma unroll
                        for (int i = 0; i < 8; i++) hp[i] = pack_bf16(hv[2 * i], hv[2 * i + 1]);
                    } else {
                        float4* dst = reinterpret_cast<float4*>(g_ypart + (fg * 8 + lr) * DM + ((u - 40) >> 1) * 64 + 16 * q);
#pragma unroll
                        for (int i = 0; i < 4; i++) {
                            const int j = 4 * (i & 1), e = i >> 1;
                            dst[i] = make_float4(g[j][e] + v[j][e], g[j + 1][e] + v[j + 1][e], g[j + 2][e] + v[j + 2][e], g[j + 3][e] + v[j + 3][e]);
                        }
                    }
#pragma unroll
                    for (int i = 0; i < 8; i++) { g[i][0] = 0.f; g[i][1] = 0.f; v[i][0] = 0.f; v[i][1] = 0.f; }
                }
            }
        }
    }
    PROF(5);
    named_sync(1, 256);
    if (tid == 0) {
        flag_add(F_MODP);
        flag_wait<100>(F_MODP, 4u * (epoch + 1));
    }
    named_sync(1, 256);
    PROF(6);
#pragma unroll 1
    for (int i = tid; i < 2 * DM; i += 256) {
        const int c = 2 * mc + (i >= DM), col = i - (i >= DM) * DM, t = sidx[c];
        float y = 0.f;
#pragma unroll 9
        for (int k = 0; k < 27; k++) y += __ldcg(g_ypart + (k * 8 + c) * DM + col);
        const float rs = round_bf16(__fdividef(1.0f, 1.0f + __expf(fminf(-__ldcg(g_r + t), 80.f))));
        const float xn = __bfloat162float(reinterpret_cast<const __nv_bfloat16*>(xs + c * 324)[col]);
        P.out[(size_t)t * DM + col] = __float2bfloat16_rn(__bfloat162float(P.x[(size_t)t * DM + col]) + round_bf16(xn + round_bf16(round_bf16(y) * rs)));
    }
    named_sync(1, 256);
    if (tid == 0) flag_add(F_MOD);
    PROF(7);
}

__global__ void __cluster_dims__(2, 1, 1) __launch_bounds__(384, 1) fused_kernel(const __grid_constant__ Params P) {
    extern __shared__ __align__(1024) uint8_t smem_raw[];
    const uint32_t smem = (smem_u32(smem_raw) + 1023u) & ~1023u;
    uint8_t* smem_gen = smem_raw + (smem - smem_u32(smem_raw));
    const uint32_t bars = smem + NSLOT * SLOT;
    const int wgi = __reduce_or_sync(0xffffffffu, threadIdx.x >> 7);
    const int cl = blockIdx.x >> 1, rank = blockIdx.x & 1, ca = cl & 7, cb = cl >> 3;
    PROFG(30);
    PROF(0);
    if (threadIdx.x >= 64 && threadIdx.x < 64 + 32 * FASTSTART && (threadIdx.x & 31) == 0) {
        const int u = (threadIdx.x >> 5) - 2;
        const uint32_t fa = bars + BAR_FULL + slot_a(u) * 8, fw = bars + BAR_FULL + slot_w(u) * 8;
        mbar_init(fa, 1); mbar_init(fw, 1);
        asm volatile("fence.mbarrier_init.release.cluster;" ::: "memory");
        if (cl < 64) {
            mbar_expect_tx(fa, SLOT);
            mbar_expect_tx(fw, SLOT);
            tma_load(smem + slot_a(u) * SLOT, &P.ckv, u * 128, (2 * ca + rank) * 128, fa);
            tma_load(smem + slot_w(u) * SLOT, &P.wuk, (cb + 8 * kv_round(0)) * 128, u * 128, fw);
            tma_load(smem + slot_w(u) * SLOT + 16384, &P.wuk, (cb + 8 * kv_round(0)) * 128 + 64, u * 128, fw);
            tma_load(smem + slot_a(u) * SLOT + 16384, &P.ckv, u * 128 + 64, (2 * ca + rank) * 128, fa);
        }
    } else if (threadIdx.x == 0) {
#pragma unroll
        for (int i = 0; i < NSLOT; i++) {
            if (i != 0 && i != 4 && (FASTSTART < 2 || (i != 1 && i != 6))) mbar_init(bars + BAR_FULL + i * 8, 1);
            mbar_init(bars + BAR_EMPTY + i * 8, 16);
        }
        mbar_arrive(bars + BAR_FULL + 16);
        asm volatile("mbarrier.arrive.shared::cta.b64 _, [%0], 16;" ::"r"(bars + BAR_EMPTY + 16) : "memory");
        asm volatile("fence.mbarrier_init.release.cluster;" ::: "memory");
        PROF(24);
    } else if (threadIdx.x == 32) {
#pragma unroll
        for (int i = 0; i < 18; i++) mbar_init(bars + BAR_SIG + i * 8, 4);
#pragma unroll
        for (int i = 0; i < 14; i++) mbar_init(bars + BAR_DEP + i * 8, 1);
    }
    __syncthreads();
    PROF(29);
    cluster_arrive();
    if (wgi > 0) {
        asm volatile("setmaxnreg.inc.sync.aligned.u32 232;");
        if (cl >= 64) {
            cluster_wait();
            mod_ffn(P, smem_gen, blockIdx.x - 128);
        } else {
            consumer(P, smem, bars, ca, cb, rank, wgi - 1);
        }
        if (ENDBAR) cluster_arrive();
        PROFG(31);
        PROFDUMP();
    } else {
        asm volatile("setmaxnreg.dec.sync.aligned.u32 40;");
        const int w = __reduce_or_sync(0xffffffffu, threadIdx.x >> 5), lane = threadIdx.x & 31;
        if (threadIdx.x == 32) {
            prefetch_map(&P.wuv); prefetch_map(&P.xn); prefetch_map(&P.wq); prefetch_map(&P.kv); prefetch_map(&P.ctx); prefetch_map(&P.wo); prefetch_map(&P.outm);
        }
        __syncwarp();
        cluster_wait();
        PROF(27);
        if (cl < 64) {
            if (w == 0) {
                producer(P, smem, bars, ca, cb, rank);
            } else if (w < 3 && lane == 0) {
                const int wg = w - 1;
#pragma unroll 1
                for (int i = 0; i < 9; i++) {
                    const int nb = wg * LNSTAG + (LNOFF + 7 - 3) / 8;
                    const int e = (i < nb) ? i + 1 : (i == nb) ? 0 : i;
                    mbar_wait_sleep(bars + BAR_SIG + (wg * 9 + e) * 8, 0);
                    int f;
                    if (e == 0) f = F_LN;
                    else if (e < 5) f = F_KV + cb + 8 * kv_round(e - 1);
                    else { const int rd = e - 5; f = F_CTX + (8 * rd + cb) * 16 + item_p(ca, rd) * 2 + rank; }
                    flag_add(f);
                }
            } else if (lane == 0) {
                const uint32_t epoch = read_epoch();
#pragma unroll 1
                for (int i = 0; i < 14; i++) {
                    const int e = (i < 11) ? i : (i == 11) ? 13 : i - 1;
                    int f;
                    uint32_t n;
                    if (e == 0) { f = F_LN; n = 256; }
                    else if (e < 5) { f = F_KV + cb + 8 * (e - 1); n = 32; }
                    else if (e < 13) { f = F_CTX + (8 * ((e - 5) >> 1) + (cb & 6) + ((e - 5) & 1)) * 16 + ca * 2 + rank; n = 2; }
                    else { f = F_MOD; n = 4; }
                    flag_wait<200>(f, n * (epoch + 1));
                    fence_proxy_async();
                    mbar_arrive(bars + BAR_DEP + e * 8);
                }
            }
        }
        if (ENDBAR) { __syncwarp(); cluster_arrive(); cluster_wait(); }
        PROFG(31);
        PROFDUMP();
    }
}

typedef CUresult (*EncodeFn)(CUtensorMap*, CUtensorMapDataType, cuuint32_t, void*, const cuuint64_t*, const cuuint64_t*, const cuuint32_t*,
                             const cuuint32_t*, CUtensorMapInterleave, CUtensorMapSwizzle, CUtensorMapL2promotion, CUtensorMapFloatOOBfill);

void make_map(EncodeFn fn, CUtensorMap* m, const void* ptr, uint64_t rows, uint64_t cols, uint32_t box_rows) {
    cuuint64_t dims[2] = {cols, rows};
    cuuint64_t strides[1] = {cols * 2};
    cuuint32_t box[2] = {64, box_rows};
    cuuint32_t es[2] = {1, 1};
    fn(m, CU_TENSOR_MAP_DATA_TYPE_BFLOAT16, 2, const_cast<void*>(ptr), dims, strides, box, es, CU_TENSOR_MAP_INTERLEAVE_NONE,
       CU_TENSOR_MAP_SWIZZLE_128B, CU_TENSOR_MAP_L2_PROMOTION_L2_128B, CU_TENSOR_MAP_FLOAT_OOB_FILL_NONE);
}

}

extern "C" void kernel_launch(void* const* d_in, const int* in_sizes, int n_in, void* d_out, int out_size) {
    (void)in_sizes; (void)n_in; (void)out_size;
    void* fnp = nullptr;
    cudaDriverEntryPointQueryResult qr;
    cudaGetDriverEntryPoint("cuTensorMapEncodeTiled", &fnp, cudaEnableDefault, &qr);
    EncodeFn fn = (EncodeFn)fnp;
    void *xn, *kv, *ctx;
    cudaGetSymbolAddress(&xn, g_xn);
    cudaGetSymbolAddress(&kv, g_kv);
    cudaGetSymbolAddress(&ctx, g_ctx);
    Params P;
    make_map(fn, &P.ckv, d_in[1], SEQ, DC, 128);
    make_map(fn, &P.wq, d_in[2], DM, NH * HD, 64);
    make_map(fn, &P.wuk, d_in[3], DC, NH * HD, 128);
    make_map(fn, &P.wuv, d_in[4], DC, NH * HD, 128);
    make_map(fn, &P.wo, d_in[5], NH * HD, DM, 32);
    make_map(fn, &P.xn, xn, SEQ, DM, 128);
    make_map(fn, &P.kv, kv, NH * 16 * 2 * 128, 128, 128);
    make_map(fn, &P.ctx, ctx, NH * SEQ, HD, 128);
    P.x = (const __nv_bfloat16*)d_in[0];
    P.wr = (const __nv_bfloat16*)d_in[7];
    make_map(fn, &P.wg, d_in[8], DM, FF, 32);
    make_map(fn, &P.wu, d_in[9], DM, FF, 32);
    make_map(fn, &P.wd, d_in[10], FF, DM, 64);
    make_map(fn, &P.outm, d_out, SEQ, DM, 16);
    P.out = (__nv_bfloat16*)d_out;
    cudaFuncSetAttribute(fused_kernel, cudaFuncAttributeMaxDynamicSharedMemorySize, SMEM_BYTES);
    fused_kernel<<<NCTA, 384, SMEM_BYTES>>>(P);
}
```

```cpp
#include <cuda_runtime.h>
#include <cuda_bf16.h>
#include <cuda.h>
#include <stdint.h>

namespace {

constexpr int SEQ = 2048, DM = 640, DC = 512, NH = 32, HD = 128, FF = 1728;
constexpr int NSLOT = 7, SLOT = 32768;
constexpr int NCTA = 132;
#define PINGPONG 1
#define SIGMA 1
#define KVORDER 0x1023
#define KVSPLIT 1
#define LNSTAG 1
#define NPOOL 44
#define LATEST 1
#define LASTRD 7
#define LASTN 2
#define EFMASK 13
#define LNOFF 4
#define LNLEAD 2
#define FASTSTART 1
#define ENDBAR 0
#define SPLITJ 8
constexpr uint32_t DESC_HI = (1024u >> 4) | (1u << 30);
constexpr int SMEM_BYTES = NSLOT * SLOT + 3072;

constexpr int BAR_FULL = 0, BAR_EMPTY = 64, BAR_SIG = 128  , BAR_DEP = 320  , BAR_MAIL = 400  ;
constexpr int MISC_OFF = 512  , MAIL_OFF = 544  , CTL_OFF = 576  ;

constexpr int F_EPOCH = 0, F_LN = 1, F_MOD = 2, F_MODP = 3, F_KV = 4  , F_CTX = 36  , F_POOL = 100  , F_NUM = 116;

__device__ __align__(1024) __nv_bfloat16 g_xn[SEQ * DM];
__device__ __align__(1024) __nv_bfloat16 g_kv[NH * 16 * 2 * 128 * 128];
__device__ __align__(1024) __nv_bfloat16 g_ctx[NH * SEQ * HD];
__device__ __align__(16) float g_r[SEQ];
__device__ __align__(16) float g_ypart[27 * 8 * DM];
__device__ uint32_t g_flags[F_NUM * 8];

struct TrueT { static constexpr bool value = true; };
struct FalseT { static constexpr bool value = false; };

struct Params {
    CUtensorMap ckv, wuk, wuv, xn, wq, kv, ctx, wo, wg, wu, wd, outm;
    const __nv_bfloat16 *x, *wr;
    __nv_bfloat16* out;
};

__device__ __forceinline__ uint32_t smem_u32(const void* p) { return (uint32_t)__cvta_generic_to_shared(p); }
__device__ __forceinline__ void mbar_init(uint32_t bar, uint32_t cnt) {
    asm volatile("mbarrier.init.shared::cta.b64 [%0], %1;" ::"r"(bar), "r"(cnt) : "memory");
}
__device__ __forceinline__ void mbar_expect_tx(uint32_t bar, uint32_t bytes) {
    asm volatile("mbarrier.arrive.expect_tx.shared::cta.b64 _, [%0], %1;" ::"r"(bar), "r"(bytes) : "memory");
}
__device__ __forceinline__ void mbar_arrive(uint32_t bar) {
    asm volatile("mbarrier.arrive.shared::cta.b64 _, [%0];" ::"r"(bar) : "memory");
}
__device__ __forceinline__ uint32_t mapa(uint32_t addr, uint32_t cta) {
    uint32_t r;
    asm("mapa.shared::cluster.u32 %0, %1, %2;" : "=r"(r) : "r"(addr), "r"(cta));
    return r;
}
__device__ __forceinline__ void mbar_wait(uint32_t bar, uint32_t parity) {
    asm volatile(
        "{\n.reg .pred p;\n.reg .b32 c;\n"
        "mov.b32 c, 0;\n"
        "WLOOP:\n"
        "mbarrier.try_wait.parity.shared::cta.b64 p, [%0], %1;\n"
        "@p bra.uni WDONE;\n"
        "add.u32 c, c, 1;\n"
        "setp.lt.u32 p, c, 0x400000;\n"
        "@p bra.uni WLOOP;\n"
        "trap;\n"
        "WDONE:\n}\n" ::"r"(bar), "r"(parity) : "memory");
}
__device__ __forceinline__ void mbar_wait_sleep(uint32_t bar, uint32_t parity) {
    asm volatile(
        "{\n.reg .pred p;\n.reg .b32 c;\n"
        "mov.b32 c, 0;\n"
        "WLOOP:\n"
        "mbarrier.try_wait.parity.shared::cta.b64 p, [%0], %1, 20000;\n"
        "@p bra.uni WDONE;\n"
        "add.u32 c, c, 1;\n"
        "setp.lt.u32 p, c, 0x40000;\n"
        "@p bra.uni WLOOP;\n"
        "trap;\n"
        "WDONE:\n}\n" ::"r"(bar), "r"(parity) : "memory");
}
__device__ __forceinline__ void tma_load(uint32_t dst, const CUtensorMap* m, int c0, int c1, uint32_t bar) {
    asm volatile("cp.async.bulk.tensor.2d.shared::cluster.global.mbarrier::complete_tx::bytes [%0], [%1, {%3, %4}], [%2];"
                 ::"r"(dst), "l"(m), "r"(bar), "r"(c0), "r"(c1) : "memory");
}
#define ELECT "{\n.reg .pred e;\nelect.sync _|e, 0xffffffff;\n@e "
__device__ __forceinline__ void w_expect_tx(uint32_t bar, uint32_t bytes) {
    asm volatile(ELECT "mbarrier.arrive.expect_tx.shared::cta.b64 _, [%0], %1;\n}\n" ::"r"(bar), "r"(bytes) : "memory");
}
__device__ __forceinline__ void w_tma_load(uint32_t dst, const CUtensorMap* m, int c0, int c1, uint32_t bar) {
    asm volatile(ELECT "cp.async.bulk.tensor.2d.shared::cluster.global.mbarrier::complete_tx::bytes [%0], [%1, {%3, %4}], [%2];\n}\n"
                 ::"r"(dst), "l"(m), "r"(bar), "r"(c0), "r"(c1) : "memory");
}
__device__ __forceinline__ void w_tma_load_mc(uint32_t dst, const CUtensorMap* m, int c0, int c1, uint32_t bar) {
    asm volatile(ELECT "cp.async.bulk.tensor.2d.shared::cluster.global.mbarrier::complete_tx::bytes.multicast::cluster [%0], [%1, {%3, %4}], [%2], %5;\n}\n"
                 ::"r"(dst), "l"(m), "r"(bar), "r"(c0), "r"(c1), "h"((uint16_t)3) : "memory");
}
__device__ __forceinline__ void w_tma_prefetch(const CUtensorMap* m, int c0, int c1) {
    asm volatile(ELECT "cp.async.bulk.prefetch.tensor.2d.L2.global [%0, {%1, %2}];\n}\n" ::"l"(m), "r"(c0), "r"(c1) : "memory");
}
__device__ __forceinline__ uint64_t policy_evict_first() {
    uint64_t p;
    asm("createpolicy.fractional.L2::evict_first.b64 %0, 1.0;" : "=l"(p));
    return p;
}
__device__ __forceinline__ void w_tma_load_mc_last(uint32_t dst, const CUtensorMap* m, int c0, int c1, uint32_t bar) {
    asm volatile(ELECT "cp.async.bulk.tensor.2d.shared::cluster.global.mbarrier::complete_tx::bytes.multicast::cluster.L2::cache_hint [%0], [%1, {%3, %4}], [%2], %5, %6;\n}\n"
                 ::"r"(dst), "l"(m), "r"(bar), "r"(c0), "r"(c1), "h"((uint16_t)3), "l"(policy_evict_first()) : "memory");
}
__device__ __forceinline__ void tma_load_stream(uint32_t dst, const CUtensorMap* m, int c0, int c1, uint32_t bar) {
    asm volatile("cp.async.bulk.tensor.2d.shared::cluster.global.mbarrier::complete_tx::bytes.L2::cache_hint [%0], [%1, {%3, %4}], [%2], %5;"
                 ::"r"(dst), "l"(m), "r"(bar), "r"(c0), "r"(c1), "l"(policy_evict_first()) : "memory");
}
__device__ __forceinline__ uint4 ldg_stream(const void* p) {
    uint4 v;
    asm volatile("ld.global.nc.L2::cache_hint.v4.b32 {%0, %1, %2, %3}, [%4], %5;" : "=r"(v.x), "=r"(v.y), "=r"(v.z), "=r"(v.w) : "l"(p), "l"(policy_evict_first()));
    return v;
}
__device__ __forceinline__ void prefetch_map(const CUtensorMap* m) {
    asm volatile("prefetch.tensormap [%0];" ::"l"(m) : "memory");
}
__device__ __forceinline__ void cluster_arrive() { asm volatile("barrier.cluster.arrive.relaxed.aligned;" ::: "memory"); }
__device__ __forceinline__ void cluster_wait() { asm volatile("barrier.cluster.wait.aligned;" ::: "memory"); }
__device__ __forceinline__ void named_sync(int id, int n) { asm volatile("bar.sync %0, %1;" ::"r"(id), "r"(n) : "memory"); }
__device__ __forceinline__ void named_arrive(int id, int n) { asm volatile("bar.arrive %0, %1;" ::"r"(id), "r"(n) : "memory"); }

__device__ __forceinline__ void flag_add(int f) {
    asm volatile("fence.acq_rel.gpu;\nred.relaxed.gpu.global.add.u32 [%0], 1;" ::"l"(g_flags + f * 8) : "memory");
}
template <int SLEEP>
__device__ __forceinline__ void flag_wait(int f, uint32_t target) {
    asm volatile(
        "{\n.reg .pred p;\n.reg .b32 c, v;\n"
        "mov.b32 c, 0;\n"
        "FLOOP:\n"
        "ld.acquire.gpu.global.u32 v, [%0];\n"
        "sub.u32 v, v, %1;\n"
        "setp.ge.s32 p, v, 0;\n"
        "@p bra FDONE;\n"
        "nanosleep.u32 %2;\n"
        "add.u32 c, c, 1;\n"
        "setp.lt.u32 p, c, 0x400000;\n"
        "@p bra FLOOP;\n"
        "trap;\n"
        "FDONE:\n}\n" ::"l"(g_flags + f * 8), "r"(target), "n"(SLEEP) : "memory");
}
__device__ __forceinline__ uint32_t read_epoch() { return atomicAdd(g_flags + F_EPOCH * 8, 1u) / NCTA; }
__device__ __forceinline__ void fence_proxy_async() { asm volatile("fence.proxy.async;" ::: "memory"); }

__device__ __forceinline__ void wgmma_fence() { asm volatile("wgmma.fence.sync.aligned;" ::: "memory"); }
__device__ __forceinline__ void wgmma_commit() { asm volatile("wgmma.commit_group.sync.aligned;" ::: "memory"); }
template <int N>
__device__ __forceinline__ void wgmma_wait() { asm volatile("wgmma.wait_group.sync.aligned %0;" ::"n"(N) : "memory"); }
template <int N>
__device__ __forceinline__ void fence_regs(float (&d)[N]) {
#pragma unroll
    for (int i = 0; i < N; i++) asm volatile("" : "+f"(d[i])::"memory");
}
template <int N>
__device__ __forceinline__ void fence_regs(uint32_t (&d)[N]) {
#pragma unroll
    for (int i = 0; i < N; i++) asm volatile("" : "+r"(d[i])::"memory");
}

template <int TA, int TB>
__device__ __forceinline__ void wgmma_ss_n128(float (&d)[64], uint32_t alo, uint32_t blo, int scale_d) {
    asm volatile("{\n.reg .pred p;\n.reg .b64 da, db;\nsetp.ne.b32 p, %66, 0;\n"
        "mov.b64 da, {%64, %69};\nmov.b64 db, {%65, %69};\n"
        "wgmma.mma_async.sync.aligned.m64n128k16.f32.bf16.bf16 "
        "{%0, %1, %2, %3, %4, %5, %6, %7, %8, %9, %10, %11, %12, %13, %14, %15, %16, %17, %18, %19, %20, %21, %22, %23, %24, %25, %26, %27, %28, %29, %30, %31, %32, %33, %34, %35, %36, %37, %38, %39, %40, %41, %42, %43, %44, %45, %46, %47, %48, %49, %50, %51, %52, %53, %54, %55, %56, %57, %58, %59, %60, %61, %62, %63}, da, db, p, 1, 1, %67, %68;\n}\n"
        :
          "+f"(d[0]), "+f"(d[1]), "+f"(d[2]), "+f"(d[3]), "+f"(d[4]), "+f"(d[5]), "+f"(d[6]), "+f"(d[7]),
          "+f"(d[8]), "+f"(d[9]), "+f"(d[10]), "+f"(d[11]), "+f"(d[12]), "+f"(d[13]), "+f"(d[14]), "+f"(d[15]),
          "+f"(d[16]), "+f"(d[17]), "+f"(d[18]), "+f"(d[19]), "+f"(d[20]), "+f"(d[21]), "+f"(d[22]), "+f"(d[23]),
          "+f"(d[24]), "+f"(d[25]), "+f"(d[26]), "+f"(d[27]), "+f"(d[28]), "+f"(d[29]), "+f"(d[30]), "+f"(d[31]),
          "+f"(d[32]), "+f"(d[33]), "+f"(d[34]), "+f"(d[35]), "+f"(d[36]), "+f"(d[37]), "+f"(d[38]), "+f"(d[39]),
          "+f"(d[40]), "+f"(d[41]), "+f"(d[42]), "+f"(d[43]), "+f"(d[44]), "+f"(d[45]), "+f"(d[46]), "+f"(d[47]),
          "+f"(d[48]), "+f"(d[49]), "+f"(d[50]), "+f"(d[51]), "+f"(d[52]), "+f"(d[53]), "+f"(d[54]), "+f"(d[55]),
          "+f"(d[56]), "+f"(d[57]), "+f"(d[58]), "+f"(d[59]), "+f"(d[60]), "+f"(d[61]), "+f"(d[62]), "+f"(d[63])
        : "r"(alo), "r"(blo), "r"(scale_d), "n"(TA), "n"(TB), "r"(DESC_HI));
}
template <int TA, int TB>
__device__ __forceinline__ void wgmma_ss_n192(float (&d)[96], uint32_t alo, uint32_t blo, int scale_d) {
    asm volatile("{\n.reg .pred p;\n.reg .b64 da, db;\nsetp.ne.b32 p, %98, 0;\n"
        "mov.b64 da, {%96, %101};\nmov.b64 db, {%97, %101};\n"
        "wgmma.mma_async.sync.aligned.m64n192k16.f32.bf16.bf16 "
        "{%0, %1, %2, %3, %4, %5, %6, %7, %8, %9, %10, %11, %12, %13, %14, %15, %16, %17, %18, %19, %20, %21, %22, %23, %24, %25, %26, %27, %28, %29, %30, %31, %32, %33, %34, %35, %36, %37, %38, %39, %40, %41, %42, %43, %44, %45, %46, %47, %48, %49, %50, %51, %52, %53, %54, %55, %56, %57, %58, %59, %60, %61, %62, %63, %64, %65, %66, %67, %68, %69, %70, %71, %72, %73, %74, %75, %76, %77, %78, %79, %80, %81, %82, %83, %84, %85, %86, %87, %88, %89, %90, %91, %92, %93, %94, %95}, da, db, p, 1, 1, %99, %100;\n}\n"
        :
          "+f"(d[0]), "+f"(d[1]), "+f"(d[2]), "+f"(d[3]), "+f"(d[4]), "+f"(d[5]), "+f"(d[6]), "+f"(d[7]),
          "+f"(d[8]), "+f"(d[9]), "+f"(d[10]), "+f"(d[11]), "+f"(d[12]), "+f"(d[13]), "+f"(d[14]), "+f"(d[15]),
          "+f"(d[16]), "+f"(d[17]), "+f"(d[18]), "+f"(d[19]), "+f"(d[20]), "+f"(d[21]), "+f"(d[22]), "+f"(d[23]),
          "+f"(d[24]), "+f"(d[25]), "+f"(d[26]), "+f"(d[27]), "+f"(d[28]), "+f"(d[29]), "+f"(d[30]), "+f"(d[31]),
          "+f"(d[32]), "+f"(d[33]), "+f"(d[34]), "+f"(d[35]), "+f"(d[36]), "+f"(d[37]), "+f"(d[38]), "+f"(d[39]),
          "+f"(d[40]), "+f"(d[41]), "+f"(d[42]), "+f"(d[43]), "+f"(d[44]), "+f"(d[45]), "+f"(d[46]), "+f"(d[47]),
          "+f"(d[48]), "+f"(d[49]), "+f"(d[50]), "+f"(d[51]), "+f"(d[52]), "+f"(d[53]), "+f"(d[54]), "+f"(d[55]),
          "+f"(d[56]), "+f"(d[57]), "+f"(d[58]), "+f"(d[59]), "+f"(d[60]), "+f"(d[61]), "+f"(d[62]), "+f"(d[63]),
          "+f"(d[64]), "+f"(d[65]), "+f"(d[66]), "+f"(d[67]), "+f"(d[68]), "+f"(d[69]), "+f"(d[70]), "+f"(d[71]),
          "+f"(d[72]), "+f"(d[73]), "+f"(d[74]), "+f"(d[75]), "+f"(d[76]), "+f"(d[77]), "+f"(d[78]), "+f"(d[79]),
          "+f"(d[80]), "+f"(d[81]), "+f"(d[82]), "+f"(d[83]), "+f"(d[84]), "+f"(d[85]), "+f"(d[86]), "+f"(d[87]),
          "+f"(d[88]), "+f"(d[89]), "+f"(d[90]), "+f"(d[91]), "+f"(d[92]), "+f"(d[93]), "+f"(d[94]), "+f"(d[95])
        : "r"(alo), "r"(blo), "r"(scale_d), "n"(TA), "n"(TB), "r"(DESC_HI));
}
template <int TB>
__device__ __forceinline__ void wgmma_rs_n128(float (&d)[64], uint32_t a0, uint32_t a1, uint32_t a2, uint32_t a3, uint32_t blo, int scale_d) {
    asm volatile("{\n.reg .pred p;\n.reg .b64 db;\nsetp.ne.b32 p, %69, 0;\n"
        "mov.b64 db, {%68, %71};\n"
        "wgmma.mma_async.sync.aligned.m64n128k16.f32.bf16.bf16 "
        "{%0, %1, %2, %3, %4, %5, %6, %7, %8, %9, %10, %11, %12, %13, %14, %15, %16, %17, %18, %19, %20, %21, %22, %23, %24, %25, %26, %27, %28, %29, %30, %31, %32, %33, %34, %35, %36, %37, %38, %39, %40, %41, %42, %43, %44, %45, %46, %47, %48, %49, %50, %51, %52, %53, %54, %55, %56, %57, %58, %59, %60, %61, %62, %63}, {%64, %65, %66, %67}, db, p, 1, 1, %70;\n}\n"
        :
          "+f"(d[0]), "+f"(d[1]), "+f"(d[2]), "+f"(d[3]), "+f"(d[4]), "+f"(d[5]), "+f"(d[6]), "+f"(d[7]),
          "+f"(d[8]), "+f"(d[9]), "+f"(d[10]), "+f"(d[11]), "+f"(d[12]), "+f"(d[13]), "+f"(d[14]), "+f"(d[15]),
          "+f"(d[16]), "+f"(d[17]), "+f"(d[18]), "+f"(d[19]), "+f"(d[20]), "+f"(d[21]), "+f"(d[22]), "+f"(d[23]),
          "+f"(d[24]), "+f"(d[25]), "+f"(d[26]), "+f"(d[27]), "+f"(d[28]), "+f"(d[29]), "+f"(d[30]), "+f"(d[31]),
          "+f"(d[32]), "+f"(d[33]), "+f"(d[34]), "+f"(d[35]), "+f"(d[36]), "+f"(d[37]), "+f"(d[38]), "+f"(d[39]),
          "+f"(d[40]), "+f"(d[41]), "+f"(d[42]), "+f"(d[43]), "+f"(d[44]), "+f"(d[45]), "+f"(d[46]), "+f"(d[47]),
          "+f"(d[48]), "+f"(d[49]), "+f"(d[50]), "+f"(d[51]), "+f"(d[52]), "+f"(d[53]), "+f"(d[54]), "+f"(d[55]),
          "+f"(d[56]), "+f"(d[57]), "+f"(d[58]), "+f"(d[59]), "+f"(d[60]), "+f"(d[61]), "+f"(d[62]), "+f"(d[63])
        : "r"(a0), "r"(a1), "r"(a2), "r"(a3), "r"(blo), "r"(scale_d), "n"(TB), "r"(DESC_HI));
}
template <int TB>
__device__ __forceinline__ void wgmma_rs_n128_z(float (&d)[64], uint32_t a0, uint32_t a1, uint32_t a2, uint32_t a3, uint32_t blo) {
    asm volatile("{\n.reg .pred p;\n.reg .b64 db;\nsetp.ne.b32 p, %69, 0;\n"
        "mov.b64 db, {%68, %71};\n"
        "wgmma.mma_async.sync.aligned.m64n128k16.f32.bf16.bf16 "
        "{%0, %1, %2, %3, %4, %5, %6, %7, %8, %9, %10, %11, %12, %13, %14, %15, %16, %17, %18, %19, %20, %21, %22, %23, %24, %25, %26, %27, %28, %29, %30, %31, %32, %33, %34, %35, %36, %37, %38, %39, %40, %41, %42, %43, %44, %45, %46, %47, %48, %49, %50, %51, %52, %53, %54, %55, %56, %57, %58, %59, %60, %61, %62, %63}, {%64, %65, %66, %67}, db, p, 1, 1, %70;\n}\n"
        :
          "=f"(d[0]), "=f"(d[1]), "=f"(d[2]), "=f"(d[3]), "=f"(d[4]), "=f"(d[5]), "=f"(d[6]), "=f"(d[7]),
          "=f"(d[8]), "=f"(d[9]), "=f"(d[10]), "=f"(d[11]), "=f"(d[12]), "=f"(d[13]), "=f"(d[14]), "=f"(d[15]),
          "=f"(d[16]), "=f"(d[17]), "=f"(d[18]), "=f"(d[19]), "=f"(d[20]), "=f"(d[21]), "=f"(d[22]), "=f"(d[23]),
          "=f"(d[24]), "=f"(d[25]), "=f"(d[26]), "=f"(d[27]), "=f"(d[28]), "=f"(d[29]), "=f"(d[30]), "=f"(d[31]),
          "=f"(d[32]), "=f"(d[33]), "=f"(d[34]), "=f"(d[35]), "=f"(d[36]), "=f"(d[37]), "=f"(d[38]), "=f"(d[39]),
          "=f"(d[40]), "=f"(d[41]), "=f"(d[42]), "=f"(d[43]), "=f"(d[44]), "=f"(d[45]), "=f"(d[46]), "=f"(d[47]),
          "=f"(d[48]), "=f"(d[49]), "=f"(d[50]), "=f"(d[51]), "=f"(d[52]), "=f"(d[53]), "=f"(d[54]), "=f"(d[55]),
          "=f"(d[56]), "=f"(d[57]), "=f"(d[58]), "=f"(d[59]), "=f"(d[60]), "=f"(d[61]), "=f"(d[62]), "=f"(d[63])
        : "r"(a0), "r"(a1), "r"(a2), "r"(a3), "r"(blo), "n"(0), "n"(TB), "r"(DESC_HI));
}
template <int TA, int TB>
__device__ __forceinline__ void wgmma_ss_n128_z(float (&d)[64], uint32_t alo, uint32_t blo) {
    asm volatile("{\n.reg .pred p;\n.reg .b64 da, db;\nsetp.ne.b32 p, %66, 0;\n"
        "mov.b64 da, {%64, %69};\nmov.b64 db, {%65, %69};\n"
        "wgmma.mma_async.sync.aligned.m64n128k16.f32.bf16.bf16 "
        "{%0, %1, %2, %3, %4, %5, %6, %7, %8, %9, %10, %11, %12, %13, %14, %15, %16, %17, %18, %19, %20, %21, %22, %23, %24, %25, %26, %27, %28, %29, %30, %31, %32, %33, %34, %35, %36, %37, %38, %39, %40, %41, %42, %43, %44, %45, %46, %47, %48, %49, %50, %51, %52, %53, %54, %55, %56, %57, %58, %59, %60, %61, %62, %63}, da, db, p, 1, 1, %67, %68;\n}\n"
        :
          "=f"(d[0]), "=f"(d[1]), "=f"(d[2]), "=f"(d[3]), "=f"(d[4]), "=f"(d[5]), "=f"(d[6]), "=f"(d[7]),
          "=f"(d[8]), "=f"(d[9]), "=f"(d[10]), "=f"(d[11]), "=f"(d[12]), "=f"(d[13]), "=f"(d[14]), "=f"(d[15]),
          "=f"(d[16]), "=f"(d[17]), "=f"(d[18]), "=f"(d[19]), "=f"(d[20]), "=f"(d[21]), "=f"(d[22]), "=f"(d[23]),
          "=f"(d[24]), "=f"(d[25]), "=f"(d[26]), "=f"(d[27]), "=f"(d[28]), "=f"(d[29]), "=f"(d[30]), "=f"(d[31]),
          "=f"(d[32]), "=f"(d[33]), "=f"(d[34]), "=f"(d[35]), "=f"(d[36]), "=f"(d[37]), "=f"(d[38]), "=f"(d[39]),
          "=f"(d[40]), "=f"(d[41]), "=f"(d[42]), "=f"(d[43]), "=f"(d[44]), "=f"(d[45]), "=f"(d[46]), "=f"(d[47]),
          "=f"(d[48]), "=f"(d[49]), "=f"(d[50]), "=f"(d[51]), "=f"(d[52]), "=f"(d[53]), "=f"(d[54]), "=f"(d[55]),
          "=f"(d[56]), "=f"(d[57]), "=f"(d[58]), "=f"(d[59]), "=f"(d[60]), "=f"(d[61]), "=f"(d[62]), "=f"(d[63])
        : "r"(alo), "r"(blo), "n"(0), "n"(TA), "n"(TB), "r"(DESC_HI));
}

__device__ __forceinline__ uint32_t pack_bf16(float lo, float hi) {
    uint32_t r;
    asm("cvt.rn.bf16x2.f32 %0, %1, %2;" : "=r"(r) : "f"(hi), "f"(lo));
    return r;
}
__device__ __forceinline__ uint32_t add_bf16x2(uint32_t a, uint32_t b) {
    uint32_t r;
    asm("add.rn.bf16x2 %0, %1, %2;" : "=r"(r) : "r"(a), "r"(b));
    return r;
}
__device__ __forceinline__ float bf_lo(uint32_t v) { return __uint_as_float(v << 16); }
__device__ __forceinline__ float bf_hi(uint32_t v) { return __uint_as_float(v & 0xffff0000u); }
__device__ __forceinline__ float round_bf16(float v) { return __bfloat162float(__float2bfloat16_rn(v)); }
__device__ __forceinline__ float ex2(float x) {
    float y;
    asm("ex2.approx.ftz.f32 %0, %1;" : "=f"(y) : "f"(x));
    return y;
}
__device__ __forceinline__ float rcp(float x) {
    float y;
    asm("rcp.approx.ftz.f32 %0, %1;" : "=f"(y) : "f"(x));
    return y;
}
__device__ __forceinline__ void stg128(void* p, uint32_t a, uint32_t b, uint32_t c, uint32_t d) {
    asm volatile("st.global.v4.b32 [%0], {%1, %2, %3, %4};" ::"l"(p), "r"(a), "r"(b), "r"(c), "r"(d) : "memory");
}
__device__ __forceinline__ void stg128p(void* p, uint32_t a, uint32_t b, uint32_t c, uint32_t d, uint64_t pol) {
    asm volatile("st.global.L2::cache_hint.v4.b32 [%0], {%1, %2, %3, %4}, %5;" ::"l"(p), "r"(a), "r"(b), "r"(c), "r"(d), "l"(pol) : "memory");
}
__device__ __forceinline__ uint64_t policy_sel(bool first) {
    uint64_t p;
    asm("createpolicy.fractional.L2::evict_normal.b64 %0, 1.0;" : "=l"(p));
    return first ? policy_evict_first() : p;
}
__device__ __forceinline__ int perm_row(int t) { return (t & ~255) | (((0x78 >> (((t >> 6) & 3) * 2)) & 3) << 6) | (t & 63); }
__device__ __forceinline__ int unperm_row(int t) { return (t & ~255) | (((0x9C >> (((t >> 6) & 3) * 2)) & 3) << 6) | (t & 63); }

#define PROF(i)
#define PROFG(i)
#define PROFDUMP()
#define TR(i)
#define BP(r, i)
#define LP(i)

template <int I>
__device__ __forceinline__ void store_chunk(const float (&a)[64], __nv_bfloat16* row0, __nv_bfloat16* row1, float s0, float s1, uint64_t pol) {
    stg128p(row0 + 32 * I, pack_bf16(a[16 * I + 0] * s0, a[16 * I + 1] * s0), pack_bf16(a[16 * I + 4] * s0, a[16 * I + 5] * s0),
           pack_bf16(a[16 * I + 8] * s0, a[16 * I + 9] * s0), pack_bf16(a[16 * I + 12] * s0, a[16 * I + 13] * s0), pol);
    stg128p(row1 + 32 * I, pack_bf16(a[16 * I + 2] * s1, a[16 * I + 3] * s1), pack_bf16(a[16 * I + 6] * s1, a[16 * I + 7] * s1),
           pack_bf16(a[16 * I + 10] * s1, a[16 * I + 11] * s1), pack_bf16(a[16 * I + 14] * s1, a[16 * I + 15] * s1), pol);
}
template <int I>
struct IntT { static constexpr int value = I; };
template <class F>
__device__ __forceinline__ void for4(F f) { f(IntT<0>{}); f(IntT<1>{}); f(IntT<2>{}); f(IntT<3>{}); }

struct Prod {
    uint32_t smem, bars;
    uint32_t bo, par;
    uint32_t dst, fb;
    __device__ __forceinline__ void acquire(uint32_t o, uint32_t parity, uint32_t bytes) {
        mbar_wait(bars + BAR_EMPTY + o, parity);
        fb = bars + BAR_FULL + o;
        dst = smem + o * (SLOT / 8);
        w_expect_tx(fb, bytes);
    }
    __device__ __forceinline__ void next(uint32_t bytes) {
        acquire(bo, par, bytes);
        const bool wrap = bo == (NSLOT - 1) * 8;
        bo = wrap ? 0u : bo + 8;
        par ^= wrap ? 1u : 0u;
    }
};

__device__ __forceinline__ int item_p(int ca, int rd) {
    const int v = (rd & 1) ? (ca + 4) & 7 : ca;
    return (rd & 2) ? 7 - v : v;
}
__device__ __forceinline__ int out_p(int ca, int cb) { return (cb + 2 * (ca & 3)) & 7; }
__device__ __forceinline__ int kv_round(int i) { return (KVORDER >> (4 * i)) & 3; }
__device__ __forceinline__ int slot_a(int i) { return (0x5310 >> (4 * i)) & 15; }
__device__ __forceinline__ int slot_w(int m) { return (0x264 >> (4 * m)) & 15; }

__device__ __forceinline__ void producer(const Params& P, uint32_t smem, uint32_t bars, int ca, int cb, int rank) {
    Prod pr{smem, bars, 0u, 0u, 0u, 0u};
    {
        int m = 0;
        uint32_t lap = 1;
#pragma unroll 1
        for (int u = 0; u < 32; u++) {
            if (u >= 3) {
                const int v = (u == 3) ? 3 + ca : u + 7;
                if (v < 32 && (u == 3 || (v & 7) == ca)) w_tma_prefetch((v & 4) ? &P.wuv : &P.wuk, (cb + 8 * kv_round(v >> 3)) * 128 + rank * 64, (v & 3) * 128);
                if (u == 24) {
                    w_tma_prefetch(&P.wq, cb * 128 + rank * 64, ca * 64);
                    if (ca < 2) w_tma_prefetch(&P.wq, cb * 128 + rank * 64, (ca + 8) * 64);
                }
            }
            if (u >= FASTSTART) pr.acquire(slot_w(m) * 8, lap ^ (m >> 1), SLOT);
            lap ^= m >> 1;
            m = (m == 2) ? 0 : m + 1;
            TR(1 + u);
            if (u >= FASTSTART) w_tma_load_mc(pr.dst + rank * 16384, (u & 4) ? &P.wuv : &P.wuk, (cb + 8 * kv_round(u >> 3)) * 128 + rank * 64, (u & 3) * 128, pr.fb);
            if (u < 3 && u + 1 >= FASTSTART) {
                pr.acquire(slot_a(u + 1) * 8, 1, SLOT);
                w_tma_load(pr.dst, &P.ckv, u * 128 + 128, (2 * ca + rank) * 128, pr.fb);
                w_tma_load(pr.dst + 16384, &P.ckv, u * 128 + 192, (2 * ca + rank) * 128, pr.fb);
            }
        }
    }
    PROF(1);
    mbar_wait(bars + BAR_DEP, 0);
#pragma unroll 1
    for (int rd = 0; rd < 4; rd++) {
        const int h = 8 * rd + cb, p = item_p(ca, rd);
#pragma unroll 1
        for (int ks = 0; ks < 10; ks++) {
            pr.next(SLOT);
            w_tma_load_mc(pr.dst + 16384 + rank * 8192, &P.wq, h * 128 + rank * 64, ks * 64, pr.fb);
            w_tma_load(pr.dst, &P.xn, ks * 64, 256 * p + 128 * rank, pr.fb);
        }
        PROF(8 + rd * 4);
        mbar_wait(bars + BAR_DEP + (1 + rd) * 8, 0);
        const int last = 4 * p + 3, top = h * 32 + last;
#pragma unroll 1
        for (int i = 0; i <= last; i++) {
            const int t = (i == 0) ? top - 1 : (i == last) ? h * 32 + 1 : (i & 1) ? top - 2 - i : top + 2 - i;
            pr.next(SLOT);
            const bool lastrd = (rd == 0) ? ((LASTRD & 1) && ca >= 8 - LASTN) : (rd == 1) ? ((LASTRD & 2) && (ca & 3) >= 4 - LASTN) : (rd == 2) ? ((LASTRD & 4) && (ca == 3 || (ca < 3 && (t & 31) >= 4 * p))) : (LASTRD & 8) != 0;
            if (lastrd) w_tma_load_mc_last(pr.dst + rank * 16384, &P.kv, rank * 64, t * 128, pr.fb);
            else w_tma_load_mc(pr.dst + rank * 16384, &P.kv, rank * 64, t * 128, pr.fb);
            if (i == 2) {
                if (rd < 3) {
                    w_tma_prefetch(&P.wq, (h + 8) * 128 + rank * 64, ca * 64);
                    if (ca < 2) w_tma_prefetch(&P.wq, (h + 8) * 128 + rank * 64, (ca + 8) * 64);
                } else {
#pragma unroll 1
                    for (int j = 0; j < 10; j++) {
                        const int tt = cb * 4 + (ca & 3) + (j >= 5 ? 32 : 0);
                        w_tma_prefetch(&P.wo, 320 * (ca >> 2) + 64 * (j >= 5 ? j - 5 : j), tt * 64 + rank * 32);
                    }
                }
            }
        }
        PROF(9 + rd * 4);
    }
    {
        const int n0 = 320 * (ca >> 2), op = out_p(ca, cb);
        uint32_t* pool = g_flags + (F_POOL + op * 2 + (ca >> 2)) * 8;
        uint32_t base, nxt = 0;
        asm volatile("ld.shared.u32 %0, [%1];" : "=r"(base) : "r"(bars + MISC_OFF) : "memory");
        base *= NPOOL + 4;
        auto draw = [&]() {
            if (NPOOL && rank == 0) asm volatile(ELECT "atom.relaxed.gpu.global.add.u32 %0, [%1], 1;\n}\n" : "+r"(nxt) : "l"(pool) : "memory");
        };
        draw();
        int fixed = NPOOL ? -1 : 0;
#pragma unroll 1
        for (int i = 0; fixed < (64 - NPOOL) / 4; i++) {
            int st;
            if (fixed < 0) {
                const uint32_t mb = bars + BAR_MAIL + (i & 7) * 8, md = bars + MAIL_OFF + (i & 7) * 4;
                if (rank == 0) {
                    st = __reduce_add_sync(0xffffffffu, nxt) - base;
                    asm volatile(ELECT "st.async.shared::cluster.mbarrier::complete_tx::bytes.b32 [%0], %1, [%2];\n}\n" ::"r"(mapa(md, 1)), "r"(st), "r"(mapa(mb, 1)) : "memory");
                    if (st < NPOOL) draw();
                } else {
                    w_expect_tx(mb, 4);
                    mbar_wait(mb, (i >> 3) & 1);
                    asm volatile("ld.shared.u32 %0, [%1];" : "=r"(st) : "r"(md) : "memory");
                    st = __reduce_or_sync(0xffffffffu, st);
                }
                if (st >= NPOOL) fixed = 0;
            }
            if (fixed >= 0) { st = NPOOL + (ca & 3) + 4 * fixed; fixed++; }
            const int krow = st * 64 + rank * 32;
            mbar_wait(bars + BAR_EMPTY + pr.bo, pr.par);
            asm volatile("st.shared.u32 [%0], %1;" ::"r"(bars + CTL_OFF + pr.bo), "r"((int)(fixed == (64 - NPOOL) / 4 - 3)) : "memory");
            __syncwarp();
            pr.next(SLOT);
            w_tma_load_mc(pr.dst + 16384 + rank * 8192, &P.wo, n0, krow, pr.fb);
            w_tma_load_mc(pr.dst + 16384 + rank * 8192 + 4096, &P.wo, n0 + 64, krow, pr.fb);
            mbar_wait(bars + BAR_DEP + (5 + (st >> 4)) * 8, 0);
            w_tma_load(pr.dst, &P.ctx, (st & 1) * 64, (st >> 1) * SEQ + 256 * op + 128 * rank, pr.fb);
            pr.next(24576);
#pragma unroll
            for (int c = 0; c < 3; c++) w_tma_load_mc(pr.dst + rank * 12288 + c * 4096, &P.wo, n0 + 128 + 64 * c, krow, pr.fb);
        }
    }
}

struct Slot {
    uint32_t bo, dl, par;
};
struct Cons {
    uint32_t bars, rel;
    uint32_t dl0;
    uint32_t lane;
    Slot cur;
    __device__ __forceinline__ Slot slot(int s, uint32_t par) const { return Slot{(uint32_t)s * 8, dl0 + (uint32_t)s * (SLOT >> 4), par}; }
    __device__ __forceinline__ void wait(const Slot& s) const { mbar_wait(bars + BAR_FULL + s.bo, s.par); }
    __device__ __forceinline__ void release(uint32_t bo) const {
        asm volatile("{\n.reg .pred p;\nsetp.lt.u32 p, %1, 2;\n@p mbarrier.arrive.shared::cluster.b64 _, [%0];\n}\n" ::"r"(rel + bo), "r"(lane) : "memory");
    }
    __device__ __forceinline__ Slot next() {
        const Slot s = cur;
        const bool wrap = s.bo == (NSLOT - 1) * 8;
        cur.bo = wrap ? 0u : s.bo + 8;
        cur.dl = wrap ? dl0 : s.dl + (SLOT >> 4);
        cur.par = s.par ^ (wrap ? 1u : 0u);
        return s;
    }
};
__host__ __device__ constexpr uint32_t lbo(uint32_t bytes) { return (bytes >> 4) << 16; }

__device__ __forceinline__ float div640(float x) {
    const float q = x * (1.0f / DM);
    return fmaf(fmaf(-q, (float)DM, x), 1.0f / DM, q);
}
__device__ __forceinline__ float sqrt_approx(float x) {
    float y;
    asm("sqrt.approx.ftz.f32 %0, %1;" : "=f"(y) : "f"(x));
    return y;
}
struct LayerNorm {
    uint4 xv[5], wv[5];
    float mean, inv, r;
    static __device__ __forceinline__ float half_sum(float v) {
#pragma unroll
        for (int o = 8; o > 0; o >>= 1) v += __shfl_xor_sync(0xffffffffu, v, o);
        return v;
    }
    __device__ __forceinline__ void load(const __nv_bfloat16* x, const __nv_bfloat16* wr, int t, int l) {
#pragma unroll
        for (int i = 0; i < 5; i++) {
            xv[i] = ldg_stream(reinterpret_cast<const uint4*>(x + t * DM) + l + 16 * i);
            wv[i] = __ldg(reinterpret_cast<const uint4*>(wr) + l + 16 * i);
        }
    }
    __device__ __forceinline__ void stat1() {
        float a[4] = {0.f, 0.f, 0.f, 0.f};
#pragma unroll
        for (int i = 0; i < 20; i++) { const uint32_t u = (&xv[i >> 2].x)[i & 3]; a[i & 3] += bf_lo(u) + bf_hi(u); }
        mean = div640(half_sum((a[0] + a[1]) + (a[2] + a[3])));
        r = 0.f;
    }
    template <int H>
    __device__ __forceinline__ void stat2() {
        float a[4] = {r, 0.f, 0.f, 0.f};
#pragma unroll
        for (int i = H ? 12 : 0; i < (H ? 20 : 12); i++) {
            uint32_t u = (&xv[i >> 2].x)[i & 3];
            asm volatile("" : "+r"(u));
            const float d0 = bf_lo(u) - mean, d1 = bf_hi(u) - mean;
            a[i & 3] = fmaf(d0, d0, fmaf(d1, d1, a[i & 3]));
        }
        r = (a[0] + a[1]) + (a[2] + a[3]);
        if (H) {
            inv = rcp(round_bf16(sqrt_approx(round_bf16(round_bf16(div640(half_sum(r))) + 1e-5f))));
            r = 0.f;
        }
    }
    template <int I>
    __device__ __forceinline__ void piece(__nv_bfloat16* out, int t, int l) {
        const uint32_t nmb = pack_bf16(-mean, -mean);
        uint32_t o[4], z[4];
        float a[4];
#pragma unroll
        for (int j = 0; j < 4; j++) {
            const uint32_t u = (&xv[I].x)[j], w = (&wv[I].x)[j];
            const uint32_t d = add_bf16x2(u, nmb);
            o[j] = pack_bf16(bf_lo(d) * inv, bf_hi(d) * inv);
            z[j] = add_bf16x2(u, o[j]);
            a[j] = fmaf(bf_hi(o[j]), bf_hi(w), bf_lo(o[j]) * bf_lo(w));
        }
        r += (a[0] + a[1]) + (a[2] + a[3]);
        stg128(g_xn + perm_row(t) * DM + 8 * (l + 16 * I), o[0], o[1], o[2], o[3]);
        stg128p(out + t * DM + 8 * (l + 16 * I), z[0], z[1], z[2], z[3], policy_sel(EFMASK & 1));
        if (I == 4) {
            r = half_sum(r);
            if (l == 0) g_r[t] = round_bf16(r);
        }
    }
};

constexpr float SM_SCALE = 0.08838834764831845f * 1.4426950408889634f;

template <int J0, int J1>
__device__ __forceinline__ void exp_part(float (&s)[64], float n0, float n1, float& r0, float& r1) {
    float a1 = 0.f, b1 = 0.f;
#pragma unroll
    for (int j = J0; j < J1; j++) {
        s[4 * j + 0] = ex2(fmaf(s[4 * j + 0], SM_SCALE, n0));
        s[4 * j + 1] = ex2(fmaf(s[4 * j + 1], SM_SCALE, n0));
        s[4 * j + 2] = ex2(fmaf(s[4 * j + 2], SM_SCALE, n1));
        s[4 * j + 3] = ex2(fmaf(s[4 * j + 3], SM_SCALE, n1));
        r0 += s[4 * j + 0]; r1 += s[4 * j + 2];
        if (j == J0) { a1 = s[4 * j + 1]; b1 = s[4 * j + 3]; } else { a1 += s[4 * j + 1]; b1 += s[4 * j + 3]; }
    }
    r0 += a1;
    r1 += b1;
}
__device__ __forceinline__ void sched_barrier(float x, float y, uint32_t scratch) {
    asm volatile("{\n.reg .pred p;\nsetp.lt.f32 p, %0, 0f00000000;\n@p st.shared.f32 [%2], %1;\n}\n" ::"f"(x), "f"(y), "r"(scratch) : "memory");
}
__device__ __forceinline__ void pack_tile(const float (&s)[64], uint32_t (&p)[32]) {
#pragma unroll
    for (int i = 0; i < 32; i++) p[i] = pack_bf16(s[2 * i], s[2 * i + 1]);
}
template <bool ZERO>
__device__ __forceinline__ void gemm_rs(float (&d)[64], const uint32_t (&a)[32], uint32_t dl, int acc = 1) {
    const uint32_t b = dl + lbo(16384);
    if (ZERO) wgmma_rs_n128_z<1>(d, a[0], a[1], a[2], a[3], b);
#pragma unroll
    for (int k = ZERO ? 1 : 0; k < 8; k++) wgmma_rs_n128<1>(d, a[4 * k], a[4 * k + 1], a[4 * k + 2], a[4 * k + 3], b + k * 128, k ? 1 : acc);
}
template <int ZERO>
__device__ __forceinline__ void gemm_q(float (&d)[64], uint32_t dl, int role) {
    const uint32_t a = dl + role * 512 + lbo(16), b = dl + 1024 + lbo(8192);
    if (ZERO) wgmma_ss_n128_z<0, 1>(d, a, b);
#pragma unroll
    for (int k = ZERO ? 1 : 0; k < 4; k++) wgmma_ss_n128<0, 1>(d, a + k * 2, b + k * 128, 1);
}
template <bool KT, bool ZERO, int K0, int K1>
__device__ __forceinline__ void gemm_kv(float (&d)[64], uint32_t ckv, uint32_t wt, int wg) {
    if (KT) {
        const uint32_t a = wt + wg * 1024 + lbo(16), b = ckv + lbo(16);
        if (ZERO) wgmma_ss_n128_z<1, 0>(d, a, b);
#pragma unroll
        for (int k = ZERO ? 1 : K0; k < K1; k++) wgmma_ss_n128<1, 0>(d, a + k * 128, b + (k >> 2) * 1024 + (k & 3) * 2, 1);
    } else {
        const uint32_t a = ckv + wg * 512 + lbo(16), b = wt + lbo(16384);
        if (ZERO) wgmma_ss_n128_z<0, 1>(d, a, b);
#pragma unroll
        for (int k = ZERO ? 1 : K0; k < K1; k++) wgmma_ss_n128<0, 1>(d, a + (k >> 2) * 1024 + (k & 3) * 2, b + k * 128, 1);
    }
}
__device__ __forceinline__ void mma16816(float& d0, float& d1, float& d2, float& d3, uint32_t a0, uint32_t a1, uint32_t a2, uint32_t a3, uint32_t b0, uint32_t b1) {
    asm volatile("mma.sync.aligned.m16n8k16.row.col.f32.bf16.bf16.f32 {%0,%1,%2,%3}, {%4,%5,%6,%7}, {%8,%9}, {%0,%1,%2,%3};"
                 : "+f"(d0), "+f"(d1), "+f"(d2), "+f"(d3) : "r"(a0), "r"(a1), "r"(a2), "r"(a3), "r"(b0), "r"(b1));
}
__device__ __forceinline__ uint32_t ld_pair(const __nv_bfloat16* p) {
    const unsigned short* u = reinterpret_cast<const unsigned short*>(p);
    return (uint32_t)__ldcg(u) | ((uint32_t)__ldcg(u + 128) << 16);
}
__device__ __forceinline__ void attention_exact(float (&o)[64], const uint32_t (&qf)[32], float& l0, float& l1, int h, int nblk, int rr, int lane) {
    const int q = lane & 3, lr = lane >> 2;
    float m0 = -INFINITY, m1 = -INFINITY;
    l0 = 0.f; l1 = 0.f;
#pragma unroll
    for (int i = 0; i < 64; i++) o[i] = 0.f;
#pragma unroll 1
    for (int cidx = 0; cidx < nblk * 8; cidx++) {
        const int kc = cidx & 7;
        const __nv_bfloat16* kt = g_kv + (size_t)((h * 16 + (cidx >> 3)) * 2) * 16384;
        float sc[8];
#pragma unroll
        for (int i = 0; i < 8; i++) sc[i] = 0.f;
#pragma unroll
        for (int kk = 0; kk < 8; kk++)
#pragma unroll
            for (int nt = 0; nt < 2; nt++) {
                const __nv_bfloat16* b = kt + (16 * kk + 2 * q) * 128 + 16 * kc + 8 * nt + lr;
                mma16816(sc[4 * nt], sc[4 * nt + 1], sc[4 * nt + 2], sc[4 * nt + 3], qf[4 * kk], qf[4 * kk + 1], qf[4 * kk + 2], qf[4 * kk + 3],
                         ld_pair(b), ld_pair(b + 8 * 128));
            }
        const int lim = rr + ((nblk - 1) - (cidx >> 3)) * 128 - 32 * (kc >> 1) - 4 * (kc & 1);
#pragma unroll
        for (int i = 0; i < 8; i++)
            if (2 * (i >> 2) + (i & 1) > lim + 4 * (i & 2)) sc[i] = -INFINITY;
        float x0 = fmaxf(fmaxf(sc[0], sc[1]), fmaxf(sc[4], sc[5])), x1 = fmaxf(fmaxf(sc[2], sc[3]), fmaxf(sc[6], sc[7]));
        x0 = fmaxf(x0, __shfl_xor_sync(0xffffffffu, x0, 1)); x1 = fmaxf(x1, __shfl_xor_sync(0xffffffffu, x1, 1));
        x0 = fmaxf(x0, __shfl_xor_sync(0xffffffffu, x0, 2)); x1 = fmaxf(x1, __shfl_xor_sync(0xffffffffu, x1, 2));
        x0 = fmaxf(x0, m0); x1 = fmaxf(x1, m1);
        const float a0 = ex2((m0 - x0) * SM_SCALE), a1 = ex2((m1 - x1) * SM_SCALE);
        m0 = x0; m1 = x1;
#pragma unroll
        for (int i = 0; i < 8; i++) sc[i] = ex2((sc[i] - ((i & 2) ? m1 : m0)) * SM_SCALE);
        l0 = l0 * a0 + (sc[0] + sc[1]) + (sc[4] + sc[5]);
        l1 = l1 * a1 + (sc[2] + sc[3]) + (sc[6] + sc[7]);
        const uint32_t p0 = pack_bf16(sc[0], sc[1]), p1 = pack_bf16(sc[2], sc[3]), p2 = pack_bf16(sc[4], sc[5]), p3 = pack_bf16(sc[6], sc[7]);
        const __nv_bfloat16* vb = kt + 16384 + (16 * kc + 2 * q) * 128 + lr;
#pragma unroll
        for (int nt = 0; nt < 16; nt++) {
            o[4 * nt] *= a0; o[4 * nt + 1] *= a0; o[4 * nt + 2] *= a1; o[4 * nt + 3] *= a1;
            mma16816(o[4 * nt], o[4 * nt + 1], o[4 * nt + 2], o[4 * nt + 3], p0, p1, p2, p3, ld_pair(vb + 8 * nt), ld_pair(vb + 8 * nt + 8 * 128));
        }
    }
}

__device__ __forceinline__ void signal(uint32_t bars, int wg, int e, int lane) {
    __syncwarp();
    asm volatile("{\n.reg .pred p;\nsetp.eq.u32 p, %1, 0;\n@p mbarrier.arrive.shared::cta.b64 _, [%0];\n}\n" ::"r"(bars + BAR_SIG + (wg * 9 + e) * 8), "r"(lane) : "memory");
}

__device__ __forceinline__ void consumer(const Params& P, uint32_t smem, uint32_t bars, int ca, int cb, int rank, int wg) {
    const int lane = threadIdx.x & 31, w = (threadIdx.x >> 5) & 3, q = lane & 3, lr = lane >> 2;
    PROF(7);
    cluster_wait();
    Cons c{bars, mapa(bars + BAR_EMPTY, lane & 1), (smem & 0x3FFFF) >> 4, (uint32_t)lane, Slot{0u, (smem & 0x3FFFF) >> 4, 1u}};
    PROFG(180);
    PROF(1);
    float o[64], s[64];
    uint32_t pend;
    __nv_bfloat16* ep_ptr;
    int ep_step;
    {
        const int ln_t = blockIdx.x * 16 + wg * 8 + w * 2 + (lane >> 4);
        const int krow = 64 * wg + 16 * w + lr;
        const int vrow = 64 * wg + 32 * (w >> 1) + 8 * (lr >> 1) + 4 * (w & 1) + (lr & 1);
        ep_step = 2 * 128;
        int m = 0;
        uint32_t lap = 0;
        LayerNorm ln;
        auto step = [&](auto kt, auto kc, float (&d)[64], int hh) {
            const Slot sa = c.slot(slot_a(kc.value), 0), sw = c.slot(slot_w(m), lap ^ (m >> 1));
            lap ^= m >> 1;
            m = (m == 2) ? 0 : m + 1;
            TR(1 + (hh * 8 + (kt.value ? 0 : 4) + kc.value) * 2);
            if (kt.value && hh == 0) c.wait(sa);
            c.wait(sw);
            TR(2 + (hh * 8 + (kt.value ? 0 : 4) + kc.value) * 2);
            wgmma_fence();
            gemm_kv<kt.value, kc.value == 0, 0, KVSPLIT>(d, sa.dl, sw.dl, wg);
            wgmma_commit();
            wgmma_wait<1>();
            if (!(kt.value && kc.value == 0 && hh == 0)) c.release(pend);
            if (!kt.value && kc.value > 0 && hh == 3) c.release(slot_a(kc.value - 1) * 8);
            pend = sw.bo;
            wgmma_fence();
            gemm_kv<kt.value, false, KVSPLIT, 8>(d, sa.dl, sw.dl, wg);
            wgmma_commit();
        };
#pragma unroll 1
        for (int hh = 0; hh < 4; hh++) {
            __nv_bfloat16* base = g_kv + (size_t)(((cb + 8 * kv_round(hh)) * 16 + 2 * ca + rank) * 2) * 16384 + 8 * q;
            auto ln_stage = [&](auto pos) {
                constexpr int j = (pos.value + 8 - LNOFF % 8) % 8;
                if (hh == wg * LNSTAG + (LNOFF + j) / 8) {
                    if (j == 0) ln.stat1();
                    if (j == 1) ln.template stat2<0>();
                    if (j == 2) ln.template stat2<1>();
                    if constexpr (j >= 3) ln.template piece<j - 3>(P.out, ln_t, lane & 15);
                    if (j == 7) signal(bars, wg, 0, lane);
                }
                if (pos.value == (LNOFF - LNLEAD) % 8 && hh == wg * LNSTAG + (LNOFF - LNLEAD) / 8) ln.load(P.x, P.wr, ln_t, lane & 15);
            };
            for4([&](auto kc) {
                step(TrueT{}, kc, s, hh);
                if (hh > 0) {
                    if (kc.value == 0) fence_regs(o);
                    store_chunk<kc.value>(o, ep_ptr, ep_ptr + ep_step, 1.f, 1.f, policy_sel(false));
                    if (kc.value == 3) signal(bars, wg, hh, lane);
                }
                ln_stage(kc);
            });
            for4([&](auto kc) {
                step(FalseT{}, kc, o, hh);
                if (kc.value == 0) fence_regs(s);
                store_chunk<kc.value>(s, base + krow * 128, base + (krow + 8) * 128, 1.f, 1.f, policy_sel(false));
                ln_stage(IntT<kc.value + 4>{});
            });
            PROF(24 + hh);
            if (hh == 1) PROFG(181);
            ep_ptr = base + 16384 + vrow * 128;
        }
    }
    PROFG(182);
    PROF(2);
    uint32_t pf[32];
    {
        uint32_t qf[32];
        float l0 = 0.25f, l1 = 0.25f;
        const int bar_me = 2 + wg, bar_other = 3 - wg;
#pragma unroll 1
        for (int rd = 0; rd < 4; rd++) {
            const int h = 8 * rd + cb, p = item_p(ca, rd);
            const int role = wg ^ (rd & 1);
            const int nrest = 2 * p + role;
            Slot kfirst;
            const int lim = 64 * (role ^ rank) + 16 * w + lr - 8 * q;
            const uint64_t pol = policy_sel(((EFMASK & 4) && rd == 1) || ((EFMASK & 8) && rd == 2));
            {
                auto qstep = [&](auto zero, int ks) {
                    const Slot sl = c.next();
                    c.wait(sl);
                    BP(2, 5 + 3 * ks);
                    wgmma_fence();
                    gemm_q<zero.value>(s, sl.dl, role);
                    wgmma_commit();
                    wgmma_wait<1>();
                    c.release(pend);
                    pend = sl.bo;
                };
                qstep(TrueT{}, 0);
                if (rd == 0) c.release(slot_a(3) * 8);
                fence_regs(o);
                l0 += __shfl_xor_sync(0xffffffffu, l0, 1); l1 += __shfl_xor_sync(0xffffffffu, l1, 1);
                l0 += __shfl_xor_sync(0xffffffffu, l0, 2); l1 += __shfl_xor_sync(0xffffffffu, l1, 2);
                l0 = rcp(l0); l1 = rcp(l1);
                for4([&](auto i) {
                    constexpr int B = 16 * i.value;
#pragma unroll
                    for (int r = 0; r < 2; r++) {
                        qstep(FalseT{}, 1 + 2 * i.value + r);
                        const float f = r ? l1 : l0;
                        stg128p(ep_ptr + r * ep_step + 2 * B, pack_bf16(o[B + 2 * r] * f, o[B + 2 * r + 1] * f), pack_bf16(o[B + 2 * r + 4] * f, o[B + 2 * r + 5] * f),
                                pack_bf16(o[B + 2 * r + 8] * f, o[B + 2 * r + 9] * f), pack_bf16(o[B + 2 * r + 12] * f, o[B + 2 * r + 13] * f), pol);
#pragma unroll
                        for (int k = 0; k < 8; k++) {
                            float& v = o[B + 4 * (k >> 1) + 2 * r + (k & 1)];
                            v = (2 * B + k > lim + 8 * r) ? -1e30f : 0.f;
                            asm volatile("" : "+f"(v));
                        }
                    }
                });
                signal(bars, wg, 4 + rd, lane);
                PROF(11 + rd * 4);
                qstep(FalseT{}, 9);
                if (!role) { const Slot sl = c.next(); c.wait(sl); c.release(sl.bo); }
                kfirst = c.next();
                c.wait(kfirst);
                wgmma_wait<0>();
                BP(2, 34);
                c.release(pend);
                fence_regs(s);
                pack_tile(s, qf);
            }
            PROF(8 + rd * 4);
            fence_regs(qf); fence_regs(o);
            if (PINGPONG && !role) named_sync(bar_me, 256);
            BP(2, 36);
            wgmma_fence();
            gemm_rs<false>(o, qf, kfirst.dl);
            wgmma_commit();
            if (PINGPONG) named_arrive(bar_other, 256);
            if (!role) { const Slot sl = c.next(); c.wait(sl); c.release(sl.bo); }
            wgmma_wait<0>();
            BP(2, 38);
            fence_regs(o);
            c.release(kfirst.bo);
            float n0 = fmaxf(fmaxf(fmaxf(o[0], o[1]), fmaxf(o[4], o[5])), fmaxf(fmaxf(o[8], o[9]), fmaxf(o[12], o[13])));
            float n1 = fmaxf(fmaxf(fmaxf(o[2], o[3]), fmaxf(o[6], o[7])), fmaxf(fmaxf(o[10], o[11]), fmaxf(o[14], o[15])));
            n0 = __shfl_sync(0xffffffffu, n0, lane & 28); n1 = __shfl_sync(0xffffffffu, n1, lane & 28);
            n0 *= -SM_SCALE; n1 *= -SM_SCALE;
            l0 = 0.f; l1 = 0.f;
#pragma unroll
            for (int i = 0; i < 64; i++) s[i] = o[i];
            exp_part<0, 8>(s, n0, n1, l0, l1);
#pragma unroll
            for (int i = 0; i < 16; i++) pf[i] = pack_bf16(s[2 * i], s[2 * i + 1]);
            if (role != rank) {
                exp_part<8, 16>(s, n0, n1, l0, l1);
#pragma unroll
                for (int i = 16; i < 32; i++) pf[i] = pack_bf16(s[2 * i], s[2 * i + 1]);
            } else {
#pragma unroll
                for (int i = 16; i < 32; i++) pf[i] = 0u;
            }
            PROF(9 + rd * 4);
#pragma unroll 1
            for (int it = 0; it < nrest; it++) {
                const Slot sk = c.next(), sv = c.next();
                LP(0);
                c.wait(sk);
                c.wait(sv);
                fence_regs(o); fence_regs(pf);
                LP(1);
                if (PINGPONG) named_sync(bar_me, 256);
                LP(2);
                if (it < 3) BP(2, 42 + 4 * it);
                if (it >= nrest - 2) BP(1, 62 + 4 * (it - nrest + 2));
                wgmma_fence();
                gemm_rs<true>(s, qf, sk.dl);
                wgmma_commit();
                gemm_rs<false>(o, pf, sv.dl, it);
                wgmma_commit();
                if (PINGPONG) named_arrive(bar_other, 256);
                LP(3);
                wgmma_wait<1>();
                LP(4);
                c.release(sk.bo);
                fence_regs(s);
                exp_part<0, SPLITJ>(s, n0, n1, l0, l1);
                sched_barrier(l0, l1, bars + MISC_OFF + 16);
                LP(5);
                wgmma_wait<0>();
                LP(6);
                c.release(sv.bo);
                fence_regs(o); fence_regs(pf);
                exp_part<SPLITJ, 16>(s, n0, n1, l0, l1);
                pack_tile(s, pf);
            }
            PROF(10 + rd * 4);
            PROFG(183 + rd);
            const Slot sv = c.next();
            BP(1, 0);
            c.wait(sv);
            if (nrest == 0) {
#pragma unroll
                for (int i = 0; i < 64; i++) o[i] = 0.f;
            }
            if (__builtin_expect(__any_sync(0xffffffffu, !(l0 < 0x1p60f && l1 < 0x1p60f)), 0)) {
                attention_exact(o, qf, l0, l1, h, nrest + 1, lim, lane);
#pragma unroll
                for (int i = 0; i < 32; i++) pf[i] = 0u;
            }
            fence_regs(o); fence_regs(pf);
            if (PINGPONG && !role) named_sync(bar_me, 256);
            BP(1, 2);
            wgmma_fence();
            gemm_rs<false>(o, pf, sv.dl);
            wgmma_commit();
            pend = sv.bo;
            ep_ptr = g_ctx + (size_t)(h * SEQ + 256 * p + 128 * rank + 64 * role + 16 * w + lr) * HD + 8 * q;
            ep_step = 8 * HD;
        }
        l0 += __shfl_xor_sync(0xffffffffu, l0, 1); l1 += __shfl_xor_sync(0xffffffffu, l1, 1);
        l0 += __shfl_xor_sync(0xffffffffu, l0, 2); l1 += __shfl_xor_sync(0xffffffffu, l1, 2);
        l0 = rcp(l0); l1 = rcp(l1);
        wgmma_wait<0>();
        c.release(pend);
        fence_regs(o); fence_regs(pf);
#pragma unroll
        for (int i = 0; i < 32; i++) pf[i] = pack_bf16(o[2 * i] * ((i & 1) ? l1 : l0), o[2 * i + 1] * ((i & 1) ? l1 : l0));
    }
    PROFG(187);
    PROF(3);
    {
        float a1[64], a2[96];
        uint32_t px = 0, py = 0;
        auto mma1 = [&](const Slot& x, int acc) {
#pragma unroll
            for (int k = 0; k < 4; k++) wgmma_ss_n128<0, 1>(a1, x.dl + wg * 512 + lbo(16) + k * 2, x.dl + 1024 + lbo(4096) + (k >> 1) * 512 + (k & 1) * 128, k ? 1 : acc);
        };
        auto mma2 = [&](const Slot& x, const Slot& y, int acc) {
#pragma unroll
            for (int k = 0; k < 4; k++) wgmma_ss_n192<0, 1>(a2, x.dl + wg * 512 + lbo(16) + k * 2, y.dl + lbo(4096) + (k >> 1) * 768 + (k & 1) * 128, k ? 1 : acc);
        };
#pragma unroll 1
        for (int t = 0, more = 1; more; t++) {
            const Slot sx = c.next(), sy = c.next();
            c.wait(sx);
            wgmma_fence();
            mma1(sx, t);
            wgmma_commit();
            asm volatile("ld.shared.u32 %0, [%1];" : "=r"(more) : "r"(bars + CTL_OFF + sx.bo) : "memory");
            more = !__any_sync(0xffffffffu, more);
            wgmma_wait<1>();
            if (t > 0) { c.release(px); c.release(py); }
            px = sx.bo; py = sy.bo;
            c.wait(sy);
            wgmma_fence();
            mma2(sx, sy, t);
            wgmma_commit();
            if (t == 0) {
#pragma unroll
                for (int i = 0; i < 4; i++) stg128(ep_ptr + 32 * i, pf[8 * i], pf[8 * i + 2], pf[8 * i + 4], pf[8 * i + 6]);
            }
            if (t == 1) {
#pragma unroll
                for (int i = 0; i < 4; i++) stg128(ep_ptr + 8 * HD + 32 * i, pf[8 * i + 1], pf[8 * i + 3], pf[8 * i + 5], pf[8 * i + 7]);
                signal(bars, wg, 8, lane);
            }
        }
        const Slot x0 = c.next(), y0 = c.next(), x1 = c.next(), y1 = c.next(), x2 = c.next(), y2 = c.next(), fr = c.next();
        const int cw = __reduce_or_sync(0xffffffffu, wg * 4 + w);
        const int orow = unperm_row(256 * out_p(ca, cb) + 128 * rank + 16 * cw), ocol = 320 * (ca >> 2);
        const uint32_t sa = ((lane & 7) + (lane & 8)) * 128, sx = (lane >> 4) ^ (lane & 7);
        auto send = [&](auto chv, uint32_t box) {
            constexpr int ch = chv.value;
#pragma unroll
            for (int i = 0; i < 4; i++) {
                uint32_t r[4];
#pragma unroll
                for (int e = 0; e < 4; e++) {
                    const int k = 32 * ch + 8 * i + 2 * e;
                    r[e] = (ch < 2) ? pack_bf16(a1[k & 63], a1[(k & 63) + 1]) : pack_bf16(a2[ch < 2 ? 0 : k - 64], a2[ch < 2 ? 1 : k - 63]);
                }
                asm volatile("stmatrix.sync.aligned.m8n8.x4.shared.b16 [%0], {%1, %2, %3, %4};"
                             ::"r"(box + sa + ((sx ^ (2 * i)) << 4)), "r"(r[0]), "r"(r[1]), "r"(r[2]), "r"(r[3]) : "memory");
            }
            asm volatile("fence.proxy.async.shared::cta;" ::: "memory");
            __syncwarp();
            asm volatile(ELECT "cp.reduce.async.bulk.tensor.2d.global.shared::cta.add.bulk_group [%0, {%2, %3}], [%1];\n}\n"
                         ::"l"(&P.outm), "r"(box), "r"(ocol + 64 * ch), "r"(orow) : "memory");
        };
        auto addr = [&](const Slot& t) { return smem + t.bo * (SLOT / 8); };
        c.wait(x0);
        wgmma_fence();
        mma1(x0, 1);
        wgmma_commit();
        wgmma_wait<1>();
        c.release(px); c.release(py);
        c.wait(x1);
        c.wait(x2);
        c.wait(y0);
        mbar_wait(bars + BAR_DEP + 9 * 8, 0);
        wgmma_fence();
        mma1(x1, 1);
        mma1(x2, 1);
        wgmma_commit();
        mma2(x0, y0, 1);
        wgmma_commit();
        mbar_wait(bars + BAR_EMPTY + fr.bo, fr.par ^ 1);
        c.wait(y1);
        wgmma_wait<1>();
        fence_regs(a1);
        send(IntT<0>{}, addr(fr) + cw * 4096);
        wgmma_fence();
        mma2(x1, y1, 1);
        wgmma_commit();
        send(IntT<1>{}, addr(fr) + cw * 4096 + 2048);
        c.wait(y2);
        wgmma_fence();
        mma2(x2, y2, 1);
        wgmma_commit();
        wgmma_wait<0>();
        fence_regs(a2);
        PROFG(188);
        PROF(4);
        send(IntT<2>{}, addr(x0) + cw * 2048);
        send(IntT<3>{}, addr(x1) + cw * 2048);
        send(IntT<4>{}, addr(x2) + cw * 2048);
        PROF(5);
        asm volatile("cp.async.bulk.commit_group;\ncp.async.bulk.wait_group.read 0;" ::: "memory");
    }
    PROF(6);
}

__device__ __forceinline__ void mma_rows(float (&acc)[8][4], uint32_t a0, uint32_t a2, const uint4& w0, const uint4& w1, const uint4& w2, const uint4& w3) {
    const uint32_t r0[4] = {w0.x, w0.y, w0.z, w0.w}, r1[4] = {w1.x, w1.y, w1.z, w1.w};
    const uint32_t r2[4] = {w2.x, w2.y, w2.z, w2.w}, r3[4] = {w3.x, w3.y, w3.z, w3.w};
#pragma unroll
    for (int i = 0; i < 4; i++) {
        mma16816(acc[2 * i][0], acc[2 * i][1], acc[2 * i][2], acc[2 * i][3], a0, 0u, a2, 0u, __byte_perm(r0[i], r1[i], 0x5410), __byte_perm(r2[i], r3[i], 0x5410));
        mma16816(acc[2 * i + 1][0], acc[2 * i + 1][1], acc[2 * i + 1][2], acc[2 * i + 1][3], a0, 0u, a2, 0u, __byte_perm(r0[i], r1[i], 0x7632), __byte_perm(r2[i], r3[i], 0x7632));
    }
}

__device__ __forceinline__ void mod_ffn(const Params& P, uint8_t* sm, int mc  ) {
    const int tid = threadIdx.x - 128, lane = tid & 31, cw = tid >> 5, q = lane & 3, lr = lane >> 2;
    const uint32_t epoch = (tid == 0) ? read_epoch() : 0u;
    uint32_t* xs = reinterpret_cast<uint32_t*>(sm);
    uint32_t* wmax = xs + 8 * 324;
    int* sidx = reinterpret_cast<int*>(wmax + 16);
    const int fg = cw * 4 + mc;
    const uint32_t ring = smem_u32(sm) + 16384 + cw * 24576, rbar = smem_u32(sm) + 12288 + cw * 32;
    auto issue = [&](int u, int st) {
        if (lane == 0 && u < 30) {
            mbar_expect_tx(rbar + st * 8, 8192);
            if (u < 20) {
                tma_load_stream(ring + st * 8192, &P.wg, fg * 64, u * 32, rbar + st * 8);
                tma_load_stream(ring + st * 8192 + 4096, &P.wu, fg * 64, u * 32, rbar + st * 8);
            } else {
                tma_load_stream(ring + st * 8192, &P.wd, (u - 20) * 64, fg * 64, rbar + st * 8);
            }
        }
    };
    if (lane == 0) {
        mbar_init(rbar, 1); mbar_init(rbar + 8, 1); mbar_init(rbar + 16, 1);
        asm volatile("fence.mbarrier_init.release.cluster;" ::: "memory");
    }
    if (tid == 0) flag_wait<100>(F_LN, 256u * (epoch + 1));
    named_sync(1, 256);
    PROF(1);
    if (fg < 27) {
#pragma unroll 1
        for (int u = 0; u < 3; u++) issue(u, u);
    }
    PROF(2);
    uint32_t key[8];
#pragma unroll
    for (int i = 0; i < 8; i++) {
        const int t = tid + 256 * i;
        uint32_t b = __float_as_uint(__ldcg(g_r + t) + 0.f) >> 16;
        b = (b & 0x8000u) ? (~b & 0xffffu) : (b | 0x8000u);
        key[i] = (b << 16) | (uint32_t)(0xffff - t);
    }
#pragma unroll 1
    for (int rnd = 0; rnd < 8; rnd++) {
        uint32_t mx = key[0];
#pragma unroll
        for (int i = 1; i < 8; i++) mx = max(mx, key[i]);
        mx = __reduce_max_sync(0xffffffffu, mx);
        if (lane == 0) wmax[(rnd & 1) * 8 + cw] = mx;
        named_sync(1, 256);
        mx = __reduce_max_sync(0xffffffffu, wmax[(rnd & 1) * 8 + (lane & 7)]);
#pragma unroll
        for (int i = 0; i < 8; i++) if (key[i] == mx) key[i] = 0;
        if (tid == 0) sidx[rnd] = 0xffff - (int)(mx & 0xffffu);
    }
    named_sync(1, 256);
    {
        const uint32_t* src = reinterpret_cast<const uint32_t*>(g_xn + (size_t)perm_row(sidx[cw]) * DM);
#pragma unroll 2
        for (int i = lane; i < 320; i += 32) xs[cw * 324 + i] = __ldcg(src + i);
    }
    named_sync(1, 256);
    PROF(3);
    if (fg < 27) {
        float g[8][4], v[8][4];
        uint32_t hp[8];
#pragma unroll
        for (int i = 0; i < 8; i++)
#pragma unroll
            for (int e = 0; e < 4; e++) { g[i][e] = 0.f; v[i][e] = 0.f; }
        int st = 0, ph = 0;
#pragma unroll 1
        for (int u = 0; u < 60; u++) {
            if (!(u & 1)) mbar_wait(rbar + st * 8, ph);
            uint4 a[8];
#pragma unroll
            for (int r = 0; r < 8; r++) {
                const int row = (u < 40) ? 32 * (r >> 2) + 16 * (u & 1) + 2 * q + (r & 1) + 4 * (r & 2) : 16 * q + 8 * (u & 1) + r;
                asm volatile("ld.shared.v4.b32 {%0, %1, %2, %3}, [%4];" : "=r"(a[r].x), "=r"(a[r].y), "=r"(a[r].z), "=r"(a[r].w)
                             : "r"(ring + st * 8192 + row * 128 + ((lr ^ row) & 7) * 16) : "memory");
            }
            uint32_t f0, f1, f2, f3;
            if (u < 40) { f0 = f2 = xs[lr * 324 + u * 8 + q]; f1 = f3 = xs[lr * 324 + u * 8 + 4 + q]; }
            else if (u & 1) { f0 = hp[4]; f1 = hp[5]; f2 = hp[6]; f3 = hp[7]; }
            else { f0 = hp[0]; f1 = hp[1]; f2 = hp[2]; f3 = hp[3]; }
            mma_rows(g, f0, f1, a[0], a[1], a[2], a[3]);
            mma_rows(v, f2, f3, a[4], a[5], a[6], a[7]);
            if (u & 1) {
                __syncwarp();
                issue((u >> 1) + 3, st);
                if (++st == 3) { st = 0; ph ^= 1; }
                if (u >= 39) {
                    if (u == 39) {
                        float hv[16];
#pragma unroll
                        for (int i = 0; i < 16; i++) {
                            const float gp = round_bf16(g[i & 7][i >> 3]);
                            hv[i] = round_bf16(__fdividef(gp, 1.0f + __expf(fminf(-gp, 80.f)))) * round_bf16(v[i & 7][i >> 3]);
                        }
#pragma unroll
                        for (int i = 0; i < 8; i++) hp[i] = pack_bf16(hv[2 * i], hv[2 * i + 1]);
                    } else {
                        float4* dst = reinterpret_cast<float4*>(g_ypart + (fg * 8 + lr) * DM + ((u - 40) >> 1) * 64 + 16 * q);
#pragma unroll
                        for (int i = 0; i < 4; i++) {
                            const int j = 4 * (i & 1), e = i >> 1;
                            dst[i] = make_float4(g[j][e] + v[j][e], g[j + 1][e] + v[j + 1][e], g[j + 2][e] + v[j + 2][e], g[j + 3][e] + v[j + 3][e]);
                        }
                    }
#pragma unroll
                    for (int i = 0; i < 8; i++) { g[i][0] = 0.f; g[i][1] = 0.f; v[i][0] = 0.f; v[i][1] = 0.f; }
                }
            }
        }
    }
    PROF(5);
    named_sync(1, 256);
    if (tid == 0) {
        flag_add(F_MODP);
        flag_wait<100>(F_MODP, 4u * (epoch + 1));
    }
    named_sync(1, 256);
    PROF(6);
#pragma unroll 1
    for (int i = tid; i < 2 * DM; i += 256) {
        const int c = 2 * mc + (i >= DM), col = i - (i >= DM) * DM, t = sidx[c];
        float y = 0.f;
#pragma unroll 9
        for (int k = 0; k < 27; k++) y += __ldcg(g_ypart + (k * 8 + c) * DM + col);
        const float rs = round_bf16(__fdividef(1.0f, 1.0f + __expf(fminf(-__ldcg(g_r + t), 80.f))));
        const float xn = __bfloat162float(reinterpret_cast<const __nv_bfloat16*>(xs + c * 324)[col]);
        P.out[(size_t)t * DM + col] = __float2bfloat16_rn(__bfloat162float(P.x[(size_t)t * DM + col]) + round_bf16(xn + round_bf16(round_bf16(y) * rs)));
    }
    named_sync(1, 256);
    if (tid == 0) flag_add(F_MOD);
    PROF(7);
}

__global__ void __cluster_dims__(2, 1, 1) __launch_bounds__(384, 1) fused_kernel(const __grid_constant__ Params P) {
    extern __shared__ __align__(1024) uint8_t smem_raw[];
    const uint32_t smem = (smem_u32(smem_raw) + 1023u) & ~1023u;
    uint8_t* smem_gen = smem_raw + (smem - smem_u32(smem_raw));
    const uint32_t bars = smem + NSLOT * SLOT;
    const int wgi = __reduce_or_sync(0xffffffffu, threadIdx.x >> 7);
    const int cl = blockIdx.x >> 1, rank = blockIdx.x & 1, ca = cl & 7, cb = cl >> 3;
    PROFG(30);
    PROF(0);
    if (threadIdx.x >= 64 && threadIdx.x < 64 + 32 * FASTSTART && (threadIdx.x & 31) == 0) {
        const int u = (threadIdx.x >> 5) - 2;
        const uint32_t fa = bars + BAR_FULL + slot_a(u) * 8, fw = bars + BAR_FULL + slot_w(u) * 8;
        mbar_init(fa, 1); mbar_init(fw, 1);
        asm volatile("fence.mbarrier_init.release.cluster;" ::: "memory");
        if (cl < 64) {
            mbar_expect_tx(fa, SLOT);
            mbar_expect_tx(fw, SLOT);
            tma_load(smem + slot_a(u) * SLOT, &P.ckv, u * 128, (2 * ca + rank) * 128, fa);
            tma_load(smem + slot_w(u) * SLOT, &P.wuk, (cb + 8 * kv_round(0)) * 128, u * 128, fw);
            tma_load(smem + slot_w(u) * SLOT + 16384, &P.wuk, (cb + 8 * kv_round(0)) * 128 + 64, u * 128, fw);
            tma_load(smem + slot_a(u) * SLOT + 16384, &P.ckv, u * 128 + 64, (2 * ca + rank) * 128, fa);
        }
    } else if (threadIdx.x == 0) {
#pragma unroll
        for (int i = 0; i < NSLOT; i++) {
            if (i != 0 && i != 4 && (FASTSTART < 2 || (i != 1 && i != 6))) mbar_init(bars + BAR_FULL + i * 8, 1);
            mbar_init(bars + BAR_EMPTY + i * 8, 16);
        }
        mbar_arrive(bars + BAR_FULL + 16);
        asm volatile("mbarrier.arrive.shared::cta.b64 _, [%0], 16;" ::"r"(bars + BAR_EMPTY + 16) : "memory");
        asm volatile("fence.mbarrier_init.release.cluster;" ::: "memory");
        PROF(24);
    } else if (threadIdx.x == 32) {
#pragma unroll
        for (int i = 0; i < 18; i++) mbar_init(bars + BAR_SIG + i * 8, 4);
#pragma unroll
        for (int i = 0; i < 18; i++) mbar_init(bars + BAR_DEP + i * 8, 1);
        asm volatile("fence.mbarrier_init.release.cluster;" ::: "memory");
    }
    __syncthreads();
    PROF(29);
    cluster_arrive();
    if (wgi > 0) {
        asm volatile("setmaxnreg.inc.sync.aligned.u32 232;");
        if (cl >= 64) {
            cluster_wait();
            mod_ffn(P, smem_gen, blockIdx.x - 128);
        } else {
            consumer(P, smem, bars, ca, cb, rank, wgi - 1);
        }
        if (ENDBAR) cluster_arrive();
        PROFG(31);
        PROFDUMP();
    } else {
        asm volatile("setmaxnreg.dec.sync.aligned.u32 40;");
        const int w = __reduce_or_sync(0xffffffffu, threadIdx.x >> 5), lane = threadIdx.x & 31;
        if (threadIdx.x == 32) {
            prefetch_map(&P.wuv); prefetch_map(&P.xn); prefetch_map(&P.wq); prefetch_map(&P.kv); prefetch_map(&P.ctx); prefetch_map(&P.wo); prefetch_map(&P.outm);
        }
        __syncwarp();
        cluster_wait();
        PROF(27);
        if (cl < 64) {
            if (w == 0) {
                producer(P, smem, bars, ca, cb, rank);
            } else if (w < 3 && lane == 0) {
                const int wg = w - 1;
#pragma unroll 1
                for (int i = 0; i < 9; i++) {
                    const int nb = wg * LNSTAG + (LNOFF + 7 - 3) / 8;
                    const int e = (i < nb) ? i + 1 : (i == nb) ? 0 : i;
                    mbar_wait_sleep(bars + BAR_SIG + (wg * 9 + e) * 8, 0);
                    int f;
                    if (e == 0) f = F_LN;
                    else if (e < 5) f = F_KV + cb + 8 * kv_round(e - 1);
                    else { const int rd = e - 5; f = F_CTX + rd * 16 + item_p(ca, rd) * 2 + rank; }
                    flag_add(f);
                }
            } else if (lane == 0) {
                const uint32_t epoch = read_epoch();
                asm volatile("st.shared.u32 [%0], %1;" ::"r"(bars + MISC_OFF), "r"(epoch) : "memory");
#pragma unroll 1
                for (int e = 0; e < 10; e++) {
                    int f;
                    uint32_t n;
                    if (e == 0) { f = F_LN; n = 256; }
                    else if (e < 5) { f = F_KV + cb + 8 * (e - 1); n = 32; }
                    else if (e < 9) { f = F_CTX + (e - 5) * 16 + out_p(ca, cb) * 2 + rank; n = 16; }
                    else { f = F_MOD; n = 4; }
                    flag_wait<200>(f, n * (epoch + 1));
                    fence_proxy_async();
                    mbar_arrive(bars + BAR_DEP + e * 8);
                }
            }
        }
        if (ENDBAR) { __syncwarp(); cluster_arrive(); cluster_wait(); }
        PROFG(31);
        PROFDUMP();
    }
}

typedef CUresult (*EncodeFn)(CUtensorMap*, CUtensorMapDataType, cuuint32_t, void*, const cuuint64_t*, const cuuint64_t*, const cuuint32_t*,
                             const cuuint32_t*, CUtensorMapInterleave, CUtensorMapSwizzle, CUtensorMapL2promotion, CUtensorMapFloatOOBfill);

void make_map(EncodeFn fn, CUtensorMap* m, const void* ptr, uint64_t rows, uint64_t cols, uint32_t box_rows) {
    cuuint64_t dims[2] = {cols, rows};
    cuuint64_t strides[1] = {cols * 2};
    cuuint32_t box[2] = {64, box_rows};
    cuuint32_t es[2] = {1, 1};
    fn(m, CU_TENSOR_MAP_DATA_TYPE_BFLOAT16, 2, const_cast<void*>(ptr), dims, strides, box, es, CU_TENSOR_MAP_INTERLEAVE_NONE,
       CU_TENSOR_MAP_SWIZZLE_128B, CU_TENSOR_MAP_L2_PROMOTION_L2_128B, CU_TENSOR_MAP_FLOAT_OOB_FILL_NONE);
}

}

extern "C" void kernel_launch(void* const* d_in, const int* in_sizes, int n_in, void* d_out, int out_size) {
    (void)in_sizes; (void)n_in; (void)out_size;
    void* fnp = nullptr;
    cudaDriverEntryPointQueryResult qr;
    cudaGetDriverEntryPoint("cuTensorMapEncodeTiled", &fnp, cudaEnableDefault, &qr);
    EncodeFn fn = (EncodeFn)fnp;
    void *xn, *kv, *ctx;
    cudaGetSymbolAddress(&xn, g_xn);
    cudaGetSymbolAddress(&kv, g_kv);
    cudaGetSymbolAddress(&ctx, g_ctx);
    Params P;
    make_map(fn, &P.ckv, d_in[1], SEQ, DC, 128);
    make_map(fn, &P.wq, d_in[2], DM, NH * HD, 64);
    make_map(fn, &P.wuk, d_in[3], DC, NH * HD, 128);
    make_map(fn, &P.wuv, d_in[4], DC, NH * HD, 128);
    make_map(fn, &P.wo, d_in[5], NH * HD, DM, 32);
    make_map(fn, &P.xn, xn, SEQ, DM, 128);
    make_map(fn, &P.kv, kv, NH * 16 * 2 * 128, 128, 128);
    make_map(fn, &P.ctx, ctx, NH * SEQ, HD, 128);
    P.x = (const __nv_bfloat16*)d_in[0];
    P.wr = (const __nv_bfloat16*)d_in[7];
    make_map(fn, &P.wg, d_in[8], DM, FF, 32);
    make_map(fn, &P.wu, d_in[9], DM, FF, 32);
    make_map(fn, &P.wd, d_in[10], FF, DM, 64);
    make_map(fn, &P.outm, d_out, SEQ, DM, 16);
    P.out = (__nv_bfloat16*)d_out;
    cudaFuncSetAttribute(fused_kernel, cudaFuncAttributeMaxDynamicSharedMemorySize, SMEM_BYTES);
    fused_kernel<<<NCTA, 384, SMEM_BYTES>>>(P);
}
```

```cpp
#include <cuda_runtime.h>
#include <cuda_bf16.h>
#include <cuda.h>
#include <stdint.h>

namespace {

constexpr int SEQ = 2048, DM = 640, DC = 512, NH = 32, HD = 128, FF = 1728;
constexpr int NSLOT = 7, SLOT = 32768;
constexpr int NCTA = 132;
#define PINGPONG 1
#define SIGMA 1
#define KVORDER 0x1023
#define KVSPLIT 1
#define LNSTAG 1
#define NPOOL 44
#define LATEST 1
#define LASTRD 7
#define LASTN 2
#define EFMASK 13
#define LNOFF 4
#define LNLEAD 2
#define FASTSTART 1
#define ENDBAR 0
#define OFFLOAD 0
#define SPLITJ 8
constexpr uint32_t DESC_HI = (1024u >> 4) | (1u << 30);
constexpr int SMEM_BYTES = NSLOT * SLOT + 3072;

constexpr int BAR_FULL = 0, BAR_EMPTY = 64, BAR_SIG = 128  , BAR_DEP = 320  , BAR_MAIL = 400  ;
constexpr int MISC_OFF = 512  , MAIL_OFF = 544  , CTL_OFF = 576  ;

constexpr int F_EPOCH = 0, F_LN = 1, F_MOD = 2, F_MODP = 3, F_KV = 4  , F_CTX = 36  , F_POOL = 100  , F_NUM = 116;

__device__ __align__(1024) __nv_bfloat16 g_xn[SEQ * DM];
__device__ __align__(1024) __nv_bfloat16 g_kv[NH * 16 * 2 * 128 * 128];
__device__ __align__(1024) __nv_bfloat16 g_ctx[NH * SEQ * HD];
__device__ __align__(16) float g_r[SEQ];
__device__ __align__(16) float g_ypart[8 * 8 * DM];
__device__ uint32_t g_flags[F_NUM * 8];

struct TrueT { static constexpr bool value = true; };
struct FalseT { static constexpr bool value = false; };

struct Params {
    CUtensorMap ckv, wuk, wuv, xn, wq, kv, ctx, wo, wg, wu, wd, outm;
    const __nv_bfloat16 *x, *wr;
    __nv_bfloat16* out;
};

__device__ __forceinline__ uint32_t smem_u32(const void* p) { return (uint32_t)__cvta_generic_to_shared(p); }
__device__ __forceinline__ void mbar_init(uint32_t bar, uint32_t cnt) {
    asm volatile("mbarrier.init.shared::cta.b64 [%0], %1;" ::"r"(bar), "r"(cnt) : "memory");
}
__device__ __forceinline__ void mbar_expect_tx(uint32_t bar, uint32_t bytes) {
    asm volatile("mbarrier.arrive.expect_tx.shared::cta.b64 _, [%0], %1;" ::"r"(bar), "r"(bytes) : "memory");
}
__device__ __forceinline__ void mbar_arrive(uint32_t bar) {
    asm volatile("mbarrier.arrive.shared::cta.b64 _, [%0];" ::"r"(bar) : "memory");
}
__device__ __forceinline__ uint32_t mapa(uint32_t addr, uint32_t cta) {
    uint32_t r;
    asm("mapa.shared::cluster.u32 %0, %1, %2;" : "=r"(r) : "r"(addr), "r"(cta));
    return r;
}
__device__ __forceinline__ void mbar_wait(uint32_t bar, uint32_t parity) {
    asm volatile(
        "{\n.reg .pred p;\n.reg .b32 c;\n"
        "mov.b32 c, 0;\n"
        "WLOOP:\n"
        "mbarrier.try_wait.parity.shared::cta.b64 p, [%0], %1;\n"
        "@p bra.uni WDONE;\n"
        "add.u32 c, c, 1;\n"
        "setp.lt.u32 p, c, 0x400000;\n"
        "@p bra.uni WLOOP;\n"
        "trap;\n"
        "WDONE:\n}\n" ::"r"(bar), "r"(parity) : "memory");
}
__device__ __forceinline__ void mbar_wait_sleep(uint32_t bar, uint32_t parity) {
    asm volatile(
        "{\n.reg .pred p;\n.reg .b32 c;\n"
        "mov.b32 c, 0;\n"
        "WLOOP:\n"
        "mbarrier.try_wait.parity.shared::cta.b64 p, [%0], %1, 20000;\n"
        "@p bra.uni WDONE;\n"
        "add.u32 c, c, 1;\n"
        "setp.lt.u32 p, c, 0x40000;\n"
        "@p bra.uni WLOOP;\n"
        "trap;\n"
        "WDONE:\n}\n" ::"r"(bar), "r"(parity) : "memory");
}
__device__ __forceinline__ void tma_load(uint32_t dst, const CUtensorMap* m, int c0, int c1, uint32_t bar) {
    asm volatile("cp.async.bulk.tensor.2d.shared::cluster.global.mbarrier::complete_tx::bytes [%0], [%1, {%3, %4}], [%2];"
                 ::"r"(dst), "l"(m), "r"(bar), "r"(c0), "r"(c1) : "memory");
}
#define ELECT "{\n.reg .pred e;\nelect.sync _|e, 0xffffffff;\n@e "
__device__ __forceinline__ void w_expect_tx(uint32_t bar, uint32_t bytes) {
    asm volatile(ELECT "mbarrier.arrive.expect_tx.shared::cta.b64 _, [%0], %1;\n}\n" ::"r"(bar), "r"(bytes) : "memory");
}
__device__ __forceinline__ void w_tma_load(uint32_t dst, const CUtensorMap* m, int c0, int c1, uint32_t bar) {
    asm volatile(ELECT "cp.async.bulk.tensor.2d.shared::cluster.global.mbarrier::complete_tx::bytes [%0], [%1, {%3, %4}], [%2];\n}\n"
                 ::"r"(dst), "l"(m), "r"(bar), "r"(c0), "r"(c1) : "memory");
}
__device__ __forceinline__ void w_tma_load_mc(uint32_t dst, const CUtensorMap* m, int c0, int c1, uint32_t bar) {
    asm volatile(ELECT "cp.async.bulk.tensor.2d.shared::cluster.global.mbarrier::complete_tx::bytes.multicast::cluster [%0], [%1, {%3, %4}], [%2], %5;\n}\n"
                 ::"r"(dst), "l"(m), "r"(bar), "r"(c0), "r"(c1), "h"((uint16_t)3) : "memory");
}
__device__ __forceinline__ void w_tma_prefetch(const CUtensorMap* m, int c0, int c1) {
    asm volatile(ELECT "cp.async.bulk.prefetch.tensor.2d.L2.global [%0, {%1, %2}];\n}\n" ::"l"(m), "r"(c0), "r"(c1) : "memory");
}
__device__ __forceinline__ uint64_t policy_evict_first() {
    uint64_t p;
    asm("createpolicy.fractional.L2::evict_first.b64 %0, 1.0;" : "=l"(p));
    return p;
}
__device__ __forceinline__ void w_tma_load_mc_last(uint32_t dst, const CUtensorMap* m, int c0, int c1, uint32_t bar) {
    asm volatile(ELECT "cp.async.bulk.tensor.2d.shared::cluster.global.mbarrier::complete_tx::bytes.multicast::cluster.L2::cache_hint [%0], [%1, {%3, %4}], [%2], %5, %6;\n}\n"
                 ::"r"(dst), "l"(m), "r"(bar), "r"(c0), "r"(c1), "h"((uint16_t)3), "l"(policy_evict_first()) : "memory");
}
__device__ __forceinline__ void w_tma_load_stream(uint32_t dst, const CUtensorMap* m, int c0, int c1, uint32_t bar) {
    asm volatile(ELECT "cp.async.bulk.tensor.2d.shared::cluster.global.mbarrier::complete_tx::bytes.L2::cache_hint [%0], [%1, {%3, %4}], [%2], %5;\n}\n"
                 ::"r"(dst), "l"(m), "r"(bar), "r"(c0), "r"(c1), "l"(policy_evict_first()) : "memory");
}
__device__ __forceinline__ uint4 ldg_stream(const void* p) {
    uint4 v;
    asm volatile("ld.global.nc.L2::cache_hint.v4.b32 {%0, %1, %2, %3}, [%4], %5;" : "=r"(v.x), "=r"(v.y), "=r"(v.z), "=r"(v.w) : "l"(p), "l"(policy_evict_first()));
    return v;
}
__device__ __forceinline__ void prefetch_map(const CUtensorMap* m) {
    asm volatile("prefetch.tensormap [%0];" ::"l"(m) : "memory");
}
__device__ __forceinline__ void cluster_arrive() { asm volatile("barrier.cluster.arrive.relaxed.aligned;" ::: "memory"); }
__device__ __forceinline__ void cluster_wait() { asm volatile("barrier.cluster.wait.aligned;" ::: "memory"); }
__device__ __forceinline__ void named_sync(int id, int n) { asm volatile("bar.sync %0, %1;" ::"r"(id), "r"(n) : "memory"); }
__device__ __forceinline__ void named_arrive(int id, int n) { asm volatile("bar.arrive %0, %1;" ::"r"(id), "r"(n) : "memory"); }

__device__ __forceinline__ void flag_add(int f) {
    asm volatile("fence.acq_rel.gpu;\nred.relaxed.gpu.global.add.u32 [%0], 1;" ::"l"(g_flags + f * 8) : "memory");
}
template <int SLEEP>
__device__ __forceinline__ void flag_wait(int f, uint32_t target) {
    asm volatile(
        "{\n.reg .pred p;\n.reg .b32 c, v;\n"
        "mov.b32 c, 0;\n"
        "FLOOP:\n"
        "ld.acquire.gpu.global.u32 v, [%0];\n"
        "sub.u32 v, v, %1;\n"
        "setp.ge.s32 p, v, 0;\n"
        "@p bra FDONE;\n"
        "nanosleep.u32 %2;\n"
        "add.u32 c, c, 1;\n"
        "setp.lt.u32 p, c, 0x400000;\n"
        "@p bra FLOOP;\n"
        "trap;\n"
        "FDONE:\n}\n" ::"l"(g_flags + f * 8), "r"(target), "n"(SLEEP) : "memory");
}
__device__ __forceinline__ uint32_t read_epoch() { return atomicAdd(g_flags + F_EPOCH * 8, 1u) / NCTA; }
__device__ __forceinline__ void fence_proxy_async() { asm volatile("fence.proxy.async;" ::: "memory"); }

__device__ __forceinline__ void wgmma_fence() { asm volatile("wgmma.fence.sync.aligned;" ::: "memory"); }
__device__ __forceinline__ void wgmma_commit() { asm volatile("wgmma.commit_group.sync.aligned;" ::: "memory"); }
template <int N>
__device__ __forceinline__ void wgmma_wait() { asm volatile("wgmma.wait_group.sync.aligned %0;" ::"n"(N) : "memory"); }
template <int N>
__device__ __forceinline__ void fence_regs(float (&d)[N]) {
#pragma unroll
    for (int i = 0; i < N; i++) asm volatile("" : "+f"(d[i])::"memory");
}
template <int N>
__device__ __forceinline__ void fence_regs(uint32_t (&d)[N]) {
#pragma unroll
    for (int i = 0; i < N; i++) asm volatile("" : "+r"(d[i])::"memory");
}

template <int TA, int TB>
__device__ __forceinline__ void wgmma_ss_n128(float (&d)[64], uint32_t alo, uint32_t blo, int scale_d) {
    asm volatile("{\n.reg .pred p;\n.reg .b64 da, db;\nsetp.ne.b32 p, %66, 0;\n"
        "mov.b64 da, {%64, %69};\nmov.b64 db, {%65, %69};\n"
        "wgmma.mma_async.sync.aligned.m64n128k16.f32.bf16.bf16 "
        "{%0, %1, %2, %3, %4, %5, %6, %7, %8, %9, %10, %11, %12, %13, %14, %15, %16, %17, %18, %19, %20, %21, %22, %23, %24, %25, %26, %27, %28, %29, %30, %31, %32, %33, %34, %35, %36, %37, %38, %39, %40, %41, %42, %43, %44, %45, %46, %47, %48, %49, %50, %51, %52, %53, %54, %55, %56, %57, %58, %59, %60, %61, %62, %63}, da, db, p, 1, 1, %67, %68;\n}\n"
        :
          "+f"(d[0]), "+f"(d[1]), "+f"(d[2]), "+f"(d[3]), "+f"(d[4]), "+f"(d[5]), "+f"(d[6]), "+f"(d[7]),
          "+f"(d[8]), "+f"(d[9]), "+f"(d[10]), "+f"(d[11]), "+f"(d[12]), "+f"(d[13]), "+f"(d[14]), "+f"(d[15]),
          "+f"(d[16]), "+f"(d[17]), "+f"(d[18]), "+f"(d[19]), "+f"(d[20]), "+f"(d[21]), "+f"(d[22]), "+f"(d[23]),
          "+f"(d[24]), "+f"(d[25]), "+f"(d[26]), "+f"(d[27]), "+f"(d[28]), "+f"(d[29]), "+f"(d[30]), "+f"(d[31]),
          "+f"(d[32]), "+f"(d[33]), "+f"(d[34]), "+f"(d[35]), "+f"(d[36]), "+f"(d[37]), "+f"(d[38]), "+f"(d[39]),
          "+f"(d[40]), "+f"(d[41]), "+f"(d[42]), "+f"(d[43]), "+f"(d[44]), "+f"(d[45]), "+f"(d[46]), "+f"(d[47]),
          "+f"(d[48]), "+f"(d[49]), "+f"(d[50]), "+f"(d[51]), "+f"(d[52]), "+f"(d[53]), "+f"(d[54]), "+f"(d[55]),
          "+f"(d[56]), "+f"(d[57]), "+f"(d[58]), "+f"(d[59]), "+f"(d[60]), "+f"(d[61]), "+f"(d[62]), "+f"(d[63])
        : "r"(alo), "r"(blo), "r"(scale_d), "n"(TA), "n"(TB), "r"(DESC_HI));
}
template <int TA, int TB>
__device__ __forceinline__ void wgmma_ss_n192(float (&d)[96], uint32_t alo, uint32_t blo, int scale_d) {
    asm volatile("{\n.reg .pred p;\n.reg .b64 da, db;\nsetp.ne.b32 p, %98, 0;\n"
        "mov.b64 da, {%96, %101};\nmov.b64 db, {%97, %101};\n"
        "wgmma.mma_async.sync.aligned.m64n192k16.f32.bf16.bf16 "
        "{%0, %1, %2, %3, %4, %5, %6, %7, %8, %9, %10, %11, %12, %13, %14, %15, %16, %17, %18, %19, %20, %21, %22, %23, %24, %25, %26, %27, %28, %29, %30, %31, %32, %33, %34, %35, %36, %37, %38, %39, %40, %41, %42, %43, %44, %45, %46, %47, %48, %49, %50, %51, %52, %53, %54, %55, %56, %57, %58, %59, %60, %61, %62, %63, %64, %65, %66, %67, %68, %69, %70, %71, %72, %73, %74, %75, %76, %77, %78, %79, %80, %81, %82, %83, %84, %85, %86, %87, %88, %89, %90, %91, %92, %93, %94, %95}, da, db, p, 1, 1, %99, %100;\n}\n"
        :
          "+f"(d[0]), "+f"(d[1]), "+f"(d[2]), "+f"(d[3]), "+f"(d[4]), "+f"(d[5]), "+f"(d[6]), "+f"(d[7]),
          "+f"(d[8]), "+f"(d[9]), "+f"(d[10]), "+f"(d[11]), "+f"(d[12]), "+f"(d[13]), "+f"(d[14]), "+f"(d[15]),
          "+f"(d[16]), "+f"(d[17]), "+f"(d[18]), "+f"(d[19]), "+f"(d[20]), "+f"(d[21]), "+f"(d[22]), "+f"(d[23]),
          "+f"(d[24]), "+f"(d[25]), "+f"(d[26]), "+f"(d[27]), "+f"(d[28]), "+f"(d[29]), "+f"(d[30]), "+f"(d[31]),
          "+f"(d[32]), "+f"(d[33]), "+f"(d[34]), "+f"(d[35]), "+f"(d[36]), "+f"(d[37]), "+f"(d[38]), "+f"(d[39]),
          "+f"(d[40]), "+f"(d[41]), "+f"(d[42]), "+f"(d[43]), "+f"(d[44]), "+f"(d[45]), "+f"(d[46]), "+f"(d[47]),
          "+f"(d[48]), "+f"(d[49]), "+f"(d[50]), "+f"(d[51]), "+f"(d[52]), "+f"(d[53]), "+f"(d[54]), "+f"(d[55]),
          "+f"(d[56]), "+f"(d[57]), "+f"(d[58]), "+f"(d[59]), "+f"(d[60]), "+f"(d[61]), "+f"(d[62]), "+f"(d[63]),
          "+f"(d[64]), "+f"(d[65]), "+f"(d[66]), "+f"(d[67]), "+f"(d[68]), "+f"(d[69]), "+f"(d[70]), "+f"(d[71]),
          "+f"(d[72]), "+f"(d[73]), "+f"(d[74]), "+f"(d[75]), "+f"(d[76]), "+f"(d[77]), "+f"(d[78]), "+f"(d[79]),
          "+f"(d[80]), "+f"(d[81]), "+f"(d[82]), "+f"(d[83]), "+f"(d[84]), "+f"(d[85]), "+f"(d[86]), "+f"(d[87]),
          "+f"(d[88]), "+f"(d[89]), "+f"(d[90]), "+f"(d[91]), "+f"(d[92]), "+f"(d[93]), "+f"(d[94]), "+f"(d[95])
        : "r"(alo), "r"(blo), "r"(scale_d), "n"(TA), "n"(TB), "r"(DESC_HI));
}
template <int TA, int TB>
__device__ __forceinline__ void wgmma_ss_n8(float (&d)[4], uint32_t alo, uint32_t blo, int scale_d) {
    asm volatile("{\n.reg .pred p;\n.reg .b64 da, db;\nsetp.ne.b32 p, %6, 0;\n"
        "mov.b64 da, {%4, %9};\nmov.b64 db, {%5, %9};\n"
        "wgmma.mma_async.sync.aligned.m64n8k16.f32.bf16.bf16 "
        "{%0, %1, %2, %3}, da, db, p, 1, 1, %7, %8;\n}\n"
        :
          "+f"(d[0]), "+f"(d[1]), "+f"(d[2]), "+f"(d[3])
        : "r"(alo), "r"(blo), "r"(scale_d), "n"(TA), "n"(TB), "r"(DESC_HI));
}
template <int TB>
__device__ __forceinline__ void wgmma_rs_n128(float (&d)[64], uint32_t a0, uint32_t a1, uint32_t a2, uint32_t a3, uint32_t blo, int scale_d) {
    asm volatile("{\n.reg .pred p;\n.reg .b64 db;\nsetp.ne.b32 p, %69, 0;\n"
        "mov.b64 db, {%68, %71};\n"
        "wgmma.mma_async.sync.aligned.m64n128k16.f32.bf16.bf16 "
        "{%0, %1, %2, %3, %4, %5, %6, %7, %8, %9, %10, %11, %12, %13, %14, %15, %16, %17, %18, %19, %20, %21, %22, %23, %24, %25, %26, %27, %28, %29, %30, %31, %32, %33, %34, %35, %36, %37, %38, %39, %40, %41, %42, %43, %44, %45, %46, %47, %48, %49, %50, %51, %52, %53, %54, %55, %56, %57, %58, %59, %60, %61, %62, %63}, {%64, %65, %66, %67}, db, p, 1, 1, %70;\n}\n"
        :
          "+f"(d[0]), "+f"(d[1]), "+f"(d[2]), "+f"(d[3]), "+f"(d[4]), "+f"(d[5]), "+f"(d[6]), "+f"(d[7]),
          "+f"(d[8]), "+f"(d[9]), "+f"(d[10]), "+f"(d[11]), "+f"(d[12]), "+f"(d[13]), "+f"(d[14]), "+f"(d[15]),
          "+f"(d[16]), "+f"(d[17]), "+f"(d[18]), "+f"(d[19]), "+f"(d[20]), "+f"(d[21]), "+f"(d[22]), "+f"(d[23]),
          "+f"(d[24]), "+f"(d[25]), "+f"(d[26]), "+f"(d[27]), "+f"(d[28]), "+f"(d[29]), "+f"(d[30]), "+f"(d[31]),
          "+f"(d[32]), "+f"(d[33]), "+f"(d[34]), "+f"(d[35]), "+f"(d[36]), "+f"(d[37]), "+f"(d[38]), "+f"(d[39]),
          "+f"(d[40]), "+f"(d[41]), "+f"(d[42]), "+f"(d[43]), "+f"(d[44]), "+f"(d[45]), "+f"(d[46]), "+f"(d[47]),
          "+f"(d[48]), "+f"(d[49]), "+f"(d[50]), "+f"(d[51]), "+f"(d[52]), "+f"(d[53]), "+f"(d[54]), "+f"(d[55]),
          "+f"(d[56]), "+f"(d[57]), "+f"(d[58]), "+f"(d[59]), "+f"(d[60]), "+f"(d[61]), "+f"(d[62]), "+f"(d[63])
        : "r"(a0), "r"(a1), "r"(a2), "r"(a3), "r"(blo), "r"(scale_d), "n"(TB), "r"(DESC_HI));
}
template <int TB>
__device__ __forceinline__ void wgmma_rs_n128_z(float (&d)[64], uint32_t a0, uint32_t a1, uint32_t a2, uint32_t a3, uint32_t blo) {
    asm volatile("{\n.reg .pred p;\n.reg .b64 db;\nsetp.ne.b32 p, %69, 0;\n"
        "mov.b64 db, {%68, %71};\n"
        "wgmma.mma_async.sync.aligned.m64n128k16.f32.bf16.bf16 "
        "{%0, %1, %2, %3, %4, %5, %6, %7, %8, %9, %10, %11, %12, %13, %14, %15, %16, %17, %18, %19, %20, %21, %22, %23, %24, %25, %26, %27, %28, %29, %30, %31, %32, %33, %34, %35, %36, %37, %38, %39, %40, %41, %42, %43, %44, %45, %46, %47, %48, %49, %50, %51, %52, %53, %54, %55, %56, %57, %58, %59, %60, %61, %62, %63}, {%64, %65, %66, %67}, db, p, 1, 1, %70;\n}\n"
        :
          "=f"(d[0]), "=f"(d[1]), "=f"(d[2]), "=f"(d[3]), "=f"(d[4]), "=f"(d[5]), "=f"(d[6]), "=f"(d[7]),
          "=f"(d[8]), "=f"(d[9]), "=f"(d[10]), "=f"(d[11]), "=f"(d[12]), "=f"(d[13]), "=f"(d[14]), "=f"(d[15]),
          "=f"(d[16]), "=f"(d[17]), "=f"(d[18]), "=f"(d[19]), "=f"(d[20]), "=f"(d[21]), "=f"(d[22]), "=f"(d[23]),
          "=f"(d[24]), "=f"(d[25]), "=f"(d[26]), "=f"(d[27]), "=f"(d[28]), "=f"(d[29]), "=f"(d[30]), "=f"(d[31]),
          "=f"(d[32]), "=f"(d[33]), "=f"(d[34]), "=f"(d[35]), "=f"(d[36]), "=f"(d[37]), "=f"(d[38]), "=f"(d[39]),
          "=f"(d[40]), "=f"(d[41]), "=f"(d[42]), "=f"(d[43]), "=f"(d[44]), "=f"(d[45]), "=f"(d[46]), "=f"(d[47]),
          "=f"(d[48]), "=f"(d[49]), "=f"(d[50]), "=f"(d[51]), "=f"(d[52]), "=f"(d[53]), "=f"(d[54]), "=f"(d[55]),
          "=f"(d[56]), "=f"(d[57]), "=f"(d[58]), "=f"(d[59]), "=f"(d[60]), "=f"(d[61]), "=f"(d[62]), "=f"(d[63])
        : "r"(a0), "r"(a1), "r"(a2), "r"(a3), "r"(blo), "n"(0), "n"(TB), "r"(DESC_HI));
}
template <int TA, int TB>
__device__ __forceinline__ void wgmma_ss_n128_z(float (&d)[64], uint32_t alo, uint32_t blo) {
    asm volatile("{\n.reg .pred p;\n.reg .b64 da, db;\nsetp.ne.b32 p, %66, 0;\n"
        "mov.b64 da, {%64, %69};\nmov.b64 db, {%65, %69};\n"
        "wgmma.mma_async.sync.aligned.m64n128k16.f32.bf16.bf16 "
        "{%0, %1, %2, %3, %4, %5, %6, %7, %8, %9, %10, %11, %12, %13, %14, %15, %16, %17, %18, %19, %20, %21, %22, %23, %24, %25, %26, %27, %28, %29, %30, %31, %32, %33, %34, %35, %36, %37, %38, %39, %40, %41, %42, %43, %44, %45, %46, %47, %48, %49, %50, %51, %52, %53, %54, %55, %56, %57, %58, %59, %60, %61, %62, %63}, da, db, p, 1, 1, %67, %68;\n}\n"
        :
          "=f"(d[0]), "=f"(d[1]), "=f"(d[2]), "=f"(d[3]), "=f"(d[4]), "=f"(d[5]), "=f"(d[6]), "=f"(d[7]),
          "=f"(d[8]), "=f"(d[9]), "=f"(d[10]), "=f"(d[11]), "=f"(d[12]), "=f"(d[13]), "=f"(d[14]), "=f"(d[15]),
          "=f"(d[16]), "=f"(d[17]), "=f"(d[18]), "=f"(d[19]), "=f"(d[20]), "=f"(d[21]), "=f"(d[22]), "=f"(d[23]),
          "=f"(d[24]), "=f"(d[25]), "=f"(d[26]), "=f"(d[27]), "=f"(d[28]), "=f"(d[29]), "=f"(d[30]), "=f"(d[31]),
          "=f"(d[32]), "=f"(d[33]), "=f"(d[34]), "=f"(d[35]), "=f"(d[36]), "=f"(d[37]), "=f"(d[38]), "=f"(d[39]),
          "=f"(d[40]), "=f"(d[41]), "=f"(d[42]), "=f"(d[43]), "=f"(d[44]), "=f"(d[45]), "=f"(d[46]), "=f"(d[47]),
          "=f"(d[48]), "=f"(d[49]), "=f"(d[50]), "=f"(d[51]), "=f"(d[52]), "=f"(d[53]), "=f"(d[54]), "=f"(d[55]),
          "=f"(d[56]), "=f"(d[57]), "=f"(d[58]), "=f"(d[59]), "=f"(d[60]), "=f"(d[61]), "=f"(d[62]), "=f"(d[63])
        : "r"(alo), "r"(blo), "n"(0), "n"(TA), "n"(TB), "r"(DESC_HI));
}

__device__ __forceinline__ uint32_t pack_bf16(float lo, float hi) {
    uint32_t r;
    asm("cvt.rn.bf16x2.f32 %0, %1, %2;" : "=r"(r) : "f"(hi), "f"(lo));
    return r;
}
__device__ __forceinline__ uint32_t add_bf16x2(uint32_t a, uint32_t b) {
    uint32_t r;
    asm("add.rn.bf16x2 %0, %1, %2;" : "=r"(r) : "r"(a), "r"(b));
    return r;
}
__device__ __forceinline__ float bf_lo(uint32_t v) { return __uint_as_float(v << 16); }
__device__ __forceinline__ float bf_hi(uint32_t v) { return __uint_as_float(v & 0xffff0000u); }
__device__ __forceinline__ float round_bf16(float v) { return __bfloat162float(__float2bfloat16_rn(v)); }
__device__ __forceinline__ float ex2(float x) {
    float y;
    asm("ex2.approx.ftz.f32 %0, %1;" : "=f"(y) : "f"(x));
    return y;
}
__device__ __forceinline__ float rcp(float x) {
    float y;
    asm("rcp.approx.ftz.f32 %0, %1;" : "=f"(y) : "f"(x));
    return y;
}
__device__ __forceinline__ void stg128(void* p, uint32_t a, uint32_t b, uint32_t c, uint32_t d) {
    asm volatile("st.global.v4.b32 [%0], {%1, %2, %3, %4};" ::"l"(p), "r"(a), "r"(b), "r"(c), "r"(d) : "memory");
}
__device__ __forceinline__ void stg128p(void* p, uint32_t a, uint32_t b, uint32_t c, uint32_t d, uint64_t pol) {
    asm volatile("st.global.L2::cache_hint.v4.b32 [%0], {%1, %2, %3, %4}, %5;" ::"l"(p), "r"(a), "r"(b), "r"(c), "r"(d), "l"(pol) : "memory");
}
__device__ __forceinline__ uint64_t policy_sel(bool first) {
    uint64_t p;
    asm("createpolicy.fractional.L2::evict_normal.b64 %0, 1.0;" : "=l"(p));
    return first ? policy_evict_first() : p;
}
__device__ __forceinline__ int perm_row(int t) { return (t & ~255) | (((0x78 >> (((t >> 6) & 3) * 2)) & 3) << 6) | (t & 63); }
__device__ __forceinline__ int unperm_row(int t) { return (t & ~255) | (((0x9C >> (((t >> 6) & 3) * 2)) & 3) << 6) | (t & 63); }

#define PROF(i)
#define PROFG(i)
#define PROFDUMP()
#define TR(i)
#define BP(r, i)
#define LP(i)

template <int I>
__device__ __forceinline__ void store_chunk(const float (&a)[64], __nv_bfloat16* row0, __nv_bfloat16* row1, float s0, float s1, uint64_t pol) {
    stg128p(row0 + 32 * I, pack_bf16(a[16 * I + 0] * s0, a[16 * I + 1] * s0), pack_bf16(a[16 * I + 4] * s0, a[16 * I + 5] * s0),
           pack_bf16(a[16 * I + 8] * s0, a[16 * I + 9] * s0), pack_bf16(a[16 * I + 12] * s0, a[16 * I + 13] * s0), pol);
    stg128p(row1 + 32 * I, pack_bf16(a[16 * I + 2] * s1, a[16 * I + 3] * s1), pack_bf16(a[16 * I + 6] * s1, a[16 * I + 7] * s1),
           pack_bf16(a[16 * I + 10] * s1, a[16 * I + 11] * s1), pack_bf16(a[16 * I + 14] * s1, a[16 * I + 15] * s1), pol);
}
template <int I>
struct IntT { static constexpr int value = I; };
template <class F>
__device__ __forceinline__ void for4(F f) { f(IntT<0>{}); f(IntT<1>{}); f(IntT<2>{}); f(IntT<3>{}); }

struct Prod {
    uint32_t smem, bars;
    uint32_t bo, par;
    uint32_t dst, fb;
    __device__ __forceinline__ void acquire(uint32_t o, uint32_t parity, uint32_t bytes) {
        mbar_wait(bars + BAR_EMPTY + o, parity);
        fb = bars + BAR_FULL + o;
        dst = smem + o * (SLOT / 8);
        w_expect_tx(fb, bytes);
    }
    __device__ __forceinline__ void next(uint32_t bytes) {
        acquire(bo, par, bytes);
        const bool wrap = bo == (NSLOT - 1) * 8;
        bo = wrap ? 0u : bo + 8;
        par ^= wrap ? 1u : 0u;
    }
};

__device__ __forceinline__ int item_p(int ca, int rd) {
    const int v = (rd & 1) ? (ca + 4) & 7 : ca;
    return (rd & 2) ? 7 - v : v;
}
__device__ __forceinline__ int n_items(int ca, int cb) { return cb == 8 ? 8 : (OFFLOAD && (ca & 3) == 3) ? 3 : 4; }
__device__ __forceinline__ int item_rd(int ca, int cb, int j) { return cb == 8 ? 2 + ca : (OFFLOAD && ca == 7 && j == 2) ? 3 : j; }
__device__ __forceinline__ int out_p(int ca, int cb) { return (cb + 2 * (ca & 3)) & 7; }
__device__ __forceinline__ int kv_round(int i) { return (KVORDER >> (4 * i)) & 3; }
__device__ __forceinline__ int slot_a(int i) { return (0x5310 >> (4 * i)) & 15; }
__device__ __forceinline__ int slot_w(int m) { return (0x264 >> (4 * m)) & 15; }

__device__ __forceinline__ void producer(const Params& P, uint32_t smem, uint32_t bars, int ca, int cb, int rank) {
    Prod pr{smem, bars, 0u, 0u, 0u, 0u};
    {
        int m = 0;
        uint32_t lap = 1;
#pragma unroll 1
        for (int u = 0; u < 32; u++) {
            if (u >= 3) {
                const int v = (u == 3) ? 3 + ca : u + 7;
                if (v < 32 && (u == 3 || (v & 7) == ca)) w_tma_prefetch((v & 4) ? &P.wuv : &P.wuk, (cb + 8 * kv_round(v >> 3)) * 128 + rank * 64, (v & 3) * 128);
                if (u == 24) {
                    w_tma_prefetch(&P.wq, cb * 128 + rank * 64, ca * 64);
                    if (ca < 2) w_tma_prefetch(&P.wq, cb * 128 + rank * 64, (ca + 8) * 64);
                }
            }
            if (u >= FASTSTART) pr.acquire(slot_w(m) * 8, lap ^ (m >> 1), SLOT);
            lap ^= m >> 1;
            m = (m == 2) ? 0 : m + 1;
            TR(1 + u);
            if (u >= FASTSTART) w_tma_load_mc(pr.dst + rank * 16384, (u & 4) ? &P.wuv : &P.wuk, (cb + 8 * kv_round(u >> 3)) * 128 + rank * 64, (u & 3) * 128, pr.fb);
            if (u < 3 && u + 1 >= FASTSTART) {
                pr.acquire(slot_a(u + 1) * 8, 1, SLOT);
                w_tma_load(pr.dst, &P.ckv, u * 128 + 128, (2 * ca + rank) * 128, pr.fb);
                w_tma_load(pr.dst + 16384, &P.ckv, u * 128 + 192, (2 * ca + rank) * 128, pr.fb);
            }
        }
    }
    PROF(1);
    mbar_wait(bars + BAR_DEP, 0);
#pragma unroll 1
    for (int j = 0, pfs = 1; j < n_items(ca, cb); j++) {
        const int rd = item_rd(ca, cb, j), h = 8 * rd + cb, p = item_p(ca, rd);
#pragma unroll 1
        for (int ks = 0; ks < 10; ks++) {
            pr.next(SLOT);
            w_tma_load_mc(pr.dst + 16384 + rank * 8192, &P.wq, h * 128 + rank * 64, ks * 64, pr.fb);
            w_tma_load(pr.dst, &P.xn, ks * 64, 256 * p + 128 * rank, pr.fb);
        }
        PROF(8 + rd * 4);
        mbar_wait(bars + BAR_DEP + (1 + rd) * 8, 0);
        const int last = 4 * p + 3, top = h * 32 + last;
#pragma unroll 1
        for (int i = 0; i <= last; i++) {
            const int t = (i == 0) ? top - 1 : (i == last) ? h * 32 + 1 : (i & 1) ? top - 2 - i : top + 2 - i;
            pr.next(SLOT);
            const bool lastrd = (rd == 0) ? ((LASTRD & 1) && ca >= 8 - LASTN) : (rd == 1) ? ((LASTRD & 2) && (ca & 3) >= 4 - LASTN) : (rd == 2) ? ((LASTRD & 4) && (ca == 3 || (ca < 3 && (t & 31) >= 4 * p))) : (LASTRD & 8) != 0;
            if (lastrd) w_tma_load_mc_last(pr.dst + rank * 16384, &P.kv, rank * 64, t * 128, pr.fb);
            else w_tma_load_mc(pr.dst + rank * 16384, &P.kv, rank * 64, t * 128, pr.fb);
            if (i == 2) {
                const int upto = (j == n_items(ca, cb) - 1) ? 4 : item_rd(ca, cb, j + 1);
#pragma unroll 1
                for (; pfs <= upto; pfs++) {
                    if (pfs < 4) {
                        w_tma_prefetch(&P.wq, (8 * pfs + cb) * 128 + rank * 64, ca * 64);
                        if (ca < 2) w_tma_prefetch(&P.wq, (8 * pfs + cb) * 128 + rank * 64, (ca + 8) * 64);
                    } else {
#pragma unroll 1
                        for (int k = 0; k < 10; k++)
                            w_tma_prefetch(&P.wo, 320 * (ca >> 2) + 64 * (k >= 5 ? k - 5 : k), (cb * 4 + (ca & 3) + (k >= 5 ? 32 : 0)) * 64 + rank * 32);
                    }
                }
            }
        }
        PROF(9 + rd * 4);
    }
    {
        const int n0 = 320 * (ca >> 2), op = out_p(ca, cb);
        uint32_t* pool = g_flags + (F_POOL + op * 2 + (ca >> 2)) * 8;
        uint32_t base, nxt = 0;
        asm volatile("ld.shared.u32 %0, [%1];" : "=r"(base) : "r"(bars + MISC_OFF) : "memory");
        base *= NPOOL + 4;
        auto draw = [&]() {
            if (NPOOL && rank == 0) asm volatile(ELECT "atom.relaxed.gpu.global.add.u32 %0, [%1], 1;\n}\n" : "+r"(nxt) : "l"(pool) : "memory");
        };
        draw();
        int fixed = NPOOL ? -1 : 0;
#pragma unroll 1
        for (int i = 0; fixed < (64 - NPOOL) / 4; i++) {
            int st;
            if (fixed < 0) {
                const uint32_t mb = bars + BAR_MAIL + (i & 7) * 8, md = bars + MAIL_OFF + (i & 7) * 4;
                if (rank == 0) {
                    st = __reduce_add_sync(0xffffffffu, nxt) - base;
                    asm volatile(ELECT "st.async.shared::cluster.mbarrier::complete_tx::bytes.b32 [%0], %1, [%2];\n}\n" ::"r"(mapa(md, 1)), "r"(st), "r"(mapa(mb, 1)) : "memory");
                    if (st < NPOOL) draw();
                } else {
                    w_expect_tx(mb, 4);
                    mbar_wait(mb, (i >> 3) & 1);
                    asm volatile("ld.shared.u32 %0, [%1];" : "=r"(st) : "r"(md) : "memory");
                    st = __reduce_or_sync(0xffffffffu, st);
                }
                if (st >= NPOOL) fixed = 0;
            }
            if (fixed >= 0) { st = NPOOL + (ca & 3) + 4 * fixed; fixed++; }
            const int krow = st * 64 + rank * 32;
            mbar_wait(bars + BAR_EMPTY + pr.bo, pr.par);
            asm volatile("st.shared.u32 [%0], %1;" ::"r"(bars + CTL_OFF + pr.bo), "r"((int)(fixed == (64 - NPOOL) / 4 - 3)) : "memory");
            __syncwarp();
            pr.next(SLOT);
            w_tma_load_mc(pr.dst + 16384 + rank * 8192, &P.wo, n0, krow, pr.fb);
            w_tma_load_mc(pr.dst + 16384 + rank * 8192 + 4096, &P.wo, n0 + 64, krow, pr.fb);
            mbar_wait(bars + BAR_DEP + (5 + (st >> 4)) * 8, 0);
            w_tma_load(pr.dst, &P.ctx, (st & 1) * 64, (st >> 1) * SEQ + 256 * op + 128 * rank, pr.fb);
            pr.next(24576);
#pragma unroll
            for (int c = 0; c < 3; c++) w_tma_load_mc(pr.dst + rank * 12288 + c * 4096, &P.wo, n0 + 128 + 64 * c, krow, pr.fb);
        }
    }
}

struct Slot {
    uint32_t bo, dl, par;
};
struct Cons {
    uint32_t bars, rel;
    uint32_t dl0;
    uint32_t lane;
    Slot cur;
    __device__ __forceinline__ Slot slot(int s, uint32_t par) const { return Slot{(uint32_t)s * 8, dl0 + (uint32_t)s * (SLOT >> 4), par}; }
    __device__ __forceinline__ void wait(const Slot& s) const { mbar_wait(bars + BAR_FULL + s.bo, s.par); }
    __device__ __forceinline__ void release(uint32_t bo) const {
        asm volatile("{\n.reg .pred p;\nsetp.lt.u32 p, %1, 2;\n@p mbarrier.arrive.shared::cluster.b64 _, [%0];\n}\n" ::"r"(rel + bo), "r"(lane) : "memory");
    }
    __device__ __forceinline__ Slot next() {
        const Slot s = cur;
        const bool wrap = s.bo == (NSLOT - 1) * 8;
        cur.bo = wrap ? 0u : s.bo + 8;
        cur.dl = wrap ? dl0 : s.dl + (SLOT >> 4);
        cur.par = s.par ^ (wrap ? 1u : 0u);
        return s;
    }
};
__host__ __device__ constexpr uint32_t lbo(uint32_t bytes) { return (bytes >> 4) << 16; }

__device__ __forceinline__ float div640(float x) {
    const float q = x * (1.0f / DM);
    return fmaf(fmaf(-q, (float)DM, x), 1.0f / DM, q);
}
__device__ __forceinline__ float sqrt_approx(float x) {
    float y;
    asm("sqrt.approx.ftz.f32 %0, %1;" : "=f"(y) : "f"(x));
    return y;
}
struct LayerNorm {
    uint4 xv[5], wv[5];
    float mean, inv, r;
    static __device__ __forceinline__ float half_sum(float v) {
#pragma unroll
        for (int o = 8; o > 0; o >>= 1) v += __shfl_xor_sync(0xffffffffu, v, o);
        return v;
    }
    __device__ __forceinline__ void load(const __nv_bfloat16* x, const __nv_bfloat16* wr, int t, int l) {
#pragma unroll
        for (int i = 0; i < 5; i++) {
            xv[i] = ldg_stream(reinterpret_cast<const uint4*>(x + t * DM) + l + 16 * i);
            wv[i] = __ldg(reinterpret_cast<const uint4*>(wr) + l + 16 * i);
        }
    }
    __device__ __forceinline__ void stat1() {
        float a[4] = {0.f, 0.f, 0.f, 0.f};
#pragma unroll
        for (int i = 0; i < 20; i++) { const uint32_t u = (&xv[i >> 2].x)[i & 3]; a[i & 3] += bf_lo(u) + bf_hi(u); }
        mean = div640(half_sum((a[0] + a[1]) + (a[2] + a[3])));
        r = 0.f;
    }
    template <int H>
    __device__ __forceinline__ void stat2() {
        float a[4] = {r, 0.f, 0.f, 0.f};
#pragma unroll
        for (int i = H ? 12 : 0; i < (H ? 20 : 12); i++) {
            uint32_t u = (&xv[i >> 2].x)[i & 3];
            asm volatile("" : "+r"(u));
            const float d0 = bf_lo(u) - mean, d1 = bf_hi(u) - mean;
            a[i & 3] = fmaf(d0, d0, fmaf(d1, d1, a[i & 3]));
        }
        r = (a[0] + a[1]) + (a[2] + a[3]);
        if (H) {
            inv = rcp(round_bf16(sqrt_approx(round_bf16(round_bf16(div640(half_sum(r))) + 1e-5f))));
            r = 0.f;
        }
    }
    template <int I>
    __device__ __forceinline__ void piece(__nv_bfloat16* out, int t, int l) {
        const uint32_t nmb = pack_bf16(-mean, -mean);
        uint32_t o[4], z[4];
        float a[4];
#pragma unroll
        for (int j = 0; j < 4; j++) {
            const uint32_t u = (&xv[I].x)[j], w = (&wv[I].x)[j];
            const uint32_t d = add_bf16x2(u, nmb);
            o[j] = pack_bf16(bf_lo(d) * inv, bf_hi(d) * inv);
            z[j] = add_bf16x2(u, o[j]);
            a[j] = fmaf(bf_hi(o[j]), bf_hi(w), bf_lo(o[j]) * bf_lo(w));
        }
        r += (a[0] + a[1]) + (a[2] + a[3]);
        stg128(g_xn + perm_row(t) * DM + 8 * (l + 16 * I), o[0], o[1], o[2], o[3]);
        stg128p(out + t * DM + 8 * (l + 16 * I), z[0], z[1], z[2], z[3], policy_sel(EFMASK & 1));
        if (I == 4) {
            r = half_sum(r);
            if (l == 0) g_r[t] = round_bf16(r);
        }
    }
};

constexpr float SM_SCALE = 0.08838834764831845f * 1.4426950408889634f;

template <int J0, int J1>
__device__ __forceinline__ void exp_part(float (&s)[64], float n0, float n1, float& r0, float& r1) {
    float a1 = 0.f, b1 = 0.f;
#pragma unroll
    for (int j = J0; j < J1; j++) {
        s[4 * j + 0] = ex2(fmaf(s[4 * j + 0], SM_SCALE, n0));
        s[4 * j + 1] = ex2(fmaf(s[4 * j + 1], SM_SCALE, n0));
        s[4 * j + 2] = ex2(fmaf(s[4 * j + 2], SM_SCALE, n1));
        s[4 * j + 3] = ex2(fmaf(s[4 * j + 3], SM_SCALE, n1));
        r0 += s[4 * j + 0]; r1 += s[4 * j + 2];
        if (j == J0) { a1 = s[4 * j + 1]; b1 = s[4 * j + 3]; } else { a1 += s[4 * j + 1]; b1 += s[4 * j + 3]; }
    }
    r0 += a1;
    r1 += b1;
}
__device__ __forceinline__ void sched_barrier(float x, float y, uint32_t scratch) {
    asm volatile("{\n.reg .pred p;\nsetp.lt.f32 p, %0, 0f00000000;\n@p st.shared.f32 [%2], %1;\n}\n" ::"f"(x), "f"(y), "r"(scratch) : "memory");
}
__device__ __forceinline__ void pack_tile(const float (&s)[64], uint32_t (&p)[32]) {
#pragma unroll
    for (int i = 0; i < 32; i++) p[i] = pack_bf16(s[2 * i], s[2 * i + 1]);
}
template <bool ZERO>
__device__ __forceinline__ void gemm_rs(float (&d)[64], const uint32_t (&a)[32], uint32_t dl, int acc = 1) {
    const uint32_t b = dl + lbo(16384);
    if (ZERO) wgmma_rs_n128_z<1>(d, a[0], a[1], a[2], a[3], b);
#pragma unroll
    for (int k = ZERO ? 1 : 0; k < 8; k++) wgmma_rs_n128<1>(d, a[4 * k], a[4 * k + 1], a[4 * k + 2], a[4 * k + 3], b + k * 128, k ? 1 : acc);
}
template <int ZERO>
__device__ __forceinline__ void gemm_q(float (&d)[64], uint32_t dl, int role) {
    const uint32_t a = dl + role * 512 + lbo(16), b = dl + 1024 + lbo(8192);
    if (ZERO) wgmma_ss_n128_z<0, 1>(d, a, b);
#pragma unroll
    for (int k = ZERO ? 1 : 0; k < 4; k++) wgmma_ss_n128<0, 1>(d, a + k * 2, b + k * 128, 1);
}
template <bool KT, bool ZERO, int K0, int K1>
__device__ __forceinline__ void gemm_kv(float (&d)[64], uint32_t ckv, uint32_t wt, int wg) {
    if (KT) {
        const uint32_t a = wt + wg * 1024 + lbo(16), b = ckv + lbo(16);
        if (ZERO) wgmma_ss_n128_z<1, 0>(d, a, b);
#pragma unroll
        for (int k = ZERO ? 1 : K0; k < K1; k++) wgmma_ss_n128<1, 0>(d, a + k * 128, b + (k >> 2) * 1024 + (k & 3) * 2, 1);
    } else {
        const uint32_t a = ckv + wg * 512 + lbo(16), b = wt + lbo(16384);
        if (ZERO) wgmma_ss_n128_z<0, 1>(d, a, b);
#pragma unroll
        for (int k = ZERO ? 1 : K0; k < K1; k++) wgmma_ss_n128<0, 1>(d, a + (k >> 2) * 1024 + (k & 3) * 2, b + k * 128, 1);
    }
}
__device__ __forceinline__ void mma16816(float& d0, float& d1, float& d2, float& d3, uint32_t a0, uint32_t a1, uint32_t a2, uint32_t a3, uint32_t b0, uint32_t b1) {
    asm volatile("mma.sync.aligned.m16n8k16.row.col.f32.bf16.bf16.f32 {%0,%1,%2,%3}, {%4,%5,%6,%7}, {%8,%9}, {%0,%1,%2,%3};"
                 : "+f"(d0), "+f"(d1), "+f"(d2), "+f"(d3) : "r"(a0), "r"(a1), "r"(a2), "r"(a3), "r"(b0), "r"(b1));
}
__device__ __forceinline__ uint32_t ld_pair(const __nv_bfloat16* p) {
    const unsigned short* u = reinterpret_cast<const unsigned short*>(p);
    return (uint32_t)__ldcg(u) | ((uint32_t)__ldcg(u + 128) << 16);
}
__device__ __forceinline__ void attention_exact(float (&o)[64], const uint32_t (&qf)[32], float& l0, float& l1, int h, int nblk, int rr, int lane) {
    const int q = lane & 3, lr = lane >> 2;
    float m0 = -INFINITY, m1 = -INFINITY;
    l0 = 0.f; l1 = 0.f;
#pragma unroll
    for (int i = 0; i < 64; i++) o[i] = 0.f;
#pragma unroll 1
    for (int cidx = 0; cidx < nblk * 8; cidx++) {
        const int kc = cidx & 7;
        const __nv_bfloat16* kt = g_kv + (size_t)((h * 16 + (cidx >> 3)) * 2) * 16384;
        float sc[8];
#pragma unroll
        for (int i = 0; i < 8; i++) sc[i] = 0.f;
#pragma unroll
        for (int kk = 0; kk < 8; kk++)
#pragma unroll
            for (int nt = 0; nt < 2; nt++) {
                const __nv_bfloat16* b = kt + (16 * kk + 2 * q) * 128 + 16 * kc + 8 * nt + lr;
                mma16816(sc[4 * nt], sc[4 * nt + 1], sc[4 * nt + 2], sc[4 * nt + 3], qf[4 * kk], qf[4 * kk + 1], qf[4 * kk + 2], qf[4 * kk + 3],
                         ld_pair(b), ld_pair(b + 8 * 128));
            }
        const int lim = rr + ((nblk - 1) - (cidx >> 3)) * 128 - 32 * (kc >> 1) - 4 * (kc & 1);
#pragma unroll
        for (int i = 0; i < 8; i++)
            if (2 * (i >> 2) + (i & 1) > lim + 4 * (i & 2)) sc[i] = -INFINITY;
        float x0 = fmaxf(fmaxf(sc[0], sc[1]), fmaxf(sc[4], sc[5])), x1 = fmaxf(fmaxf(sc[2], sc[3]), fmaxf(sc[6], sc[7]));
        x0 = fmaxf(x0, __shfl_xor_sync(0xffffffffu, x0, 1)); x1 = fmaxf(x1, __shfl_xor_sync(0xffffffffu, x1, 1));
        x0 = fmaxf(x0, __shfl_xor_sync(0xffffffffu, x0, 2)); x1 = fmaxf(x1, __shfl_xor_sync(0xffffffffu, x1, 2));
        x0 = fmaxf(x0, m0); x1 = fmaxf(x1, m1);
        const float a0 = ex2((m0 - x0) * SM_SCALE), a1 = ex2((m1 - x1) * SM_SCALE);
        m0 = x0; m1 = x1;
#pragma unroll
        for (int i = 0; i < 8; i++) sc[i] = ex2((sc[i] - ((i & 2) ? m1 : m0)) * SM_SCALE);
        l0 = l0 * a0 + (sc[0] + sc[1]) + (sc[4] + sc[5]);
        l1 = l1 * a1 + (sc[2] + sc[3]) + (sc[6] + sc[7]);
        const uint32_t p0 = pack_bf16(sc[0], sc[1]), p1 = pack_bf16(sc[2], sc[3]), p2 = pack_bf16(sc[4], sc[5]), p3 = pack_bf16(sc[6], sc[7]);
        const __nv_bfloat16* vb = kt + 16384 + (16 * kc + 2 * q) * 128 + lr;
#pragma unroll
        for (int nt = 0; nt < 16; nt++) {
            o[4 * nt] *= a0; o[4 * nt + 1] *= a0; o[4 * nt + 2] *= a1; o[4 * nt + 3] *= a1;
            mma16816(o[4 * nt], o[4 * nt + 1], o[4 * nt + 2], o[4 * nt + 3], p0, p1, p2, p3, ld_pair(vb + 8 * nt), ld_pair(vb + 8 * nt + 8 * 128));
        }
    }
}

__device__ __forceinline__ void signal(uint32_t bars, int wg, int e, int lane) {
    __syncwarp();
    asm volatile("{\n.reg .pred p;\nsetp.eq.u32 p, %1, 0;\n@p mbarrier.arrive.shared::cta.b64 _, [%0];\n}\n" ::"r"(bars + BAR_SIG + (wg * 9 + e) * 8), "r"(lane) : "memory");
}

__device__ __forceinline__ void consumer(const Params& P, uint32_t smem, uint32_t bars, int ca, int cb, int rank, int wg) {
    const int lane = threadIdx.x & 31, w = (threadIdx.x >> 5) & 3, q = lane & 3, lr = lane >> 2;
    PROF(7);
    cluster_wait();
    Cons c{bars, mapa(bars + BAR_EMPTY, lane & 1), (smem & 0x3FFFF) >> 4, (uint32_t)lane, Slot{0u, (smem & 0x3FFFF) >> 4, 1u}};
    PROFG(180);
    PROF(1);
    float o[64], s[64];
    uint32_t pend;
    __nv_bfloat16* ep_ptr;
    int ep_step;
    {
        const int ln_t = blockIdx.x * 16 + wg * 8 + w * 2 + (lane >> 4);
        const int krow = 64 * wg + 16 * w + lr;
        const int vrow = 64 * wg + 32 * (w >> 1) + 8 * (lr >> 1) + 4 * (w & 1) + (lr & 1);
        ep_step = 2 * 128;
        int m = 0;
        uint32_t lap = 0;
        LayerNorm ln;
        auto step = [&](auto kt, auto kc, float (&d)[64], int hh) {
            const Slot sa = c.slot(slot_a(kc.value), 0), sw = c.slot(slot_w(m), lap ^ (m >> 1));
            lap ^= m >> 1;
            m = (m == 2) ? 0 : m + 1;
            TR(1 + (hh * 8 + (kt.value ? 0 : 4) + kc.value) * 2);
            if (kt.value && hh == 0) c.wait(sa);
            c.wait(sw);
            TR(2 + (hh * 8 + (kt.value ? 0 : 4) + kc.value) * 2);
            wgmma_fence();
            gemm_kv<kt.value, kc.value == 0, 0, KVSPLIT>(d, sa.dl, sw.dl, wg);
            wgmma_commit();
            wgmma_wait<1>();
            if (!(kt.value && kc.value == 0 && hh == 0)) c.release(pend);
            if (!kt.value && kc.value > 0 && hh == 3) c.release(slot_a(kc.value - 1) * 8);
            pend = sw.bo;
            wgmma_fence();
            gemm_kv<kt.value, false, KVSPLIT, 8>(d, sa.dl, sw.dl, wg);
            wgmma_commit();
        };
#pragma unroll 1
        for (int hh = 0; hh < 4; hh++) {
            __nv_bfloat16* base = g_kv + (size_t)(((cb + 8 * kv_round(hh)) * 16 + 2 * ca + rank) * 2) * 16384 + 8 * q;
            auto ln_stage = [&](auto pos) {
                constexpr int j = (pos.value + 8 - LNOFF % 8) % 8;
                if (hh == wg * LNSTAG + (LNOFF + j) / 8) {
                    if (j == 0) ln.stat1();
                    if (j == 1) ln.template stat2<0>();
                    if (j == 2) ln.template stat2<1>();
                    if constexpr (j >= 3) ln.template piece<j - 3>(P.out, ln_t, lane & 15);
                    if (j == 7) signal(bars, wg, 0, lane);
                }
                if (pos.value == (LNOFF - LNLEAD) % 8 && hh == wg * LNSTAG + (LNOFF - LNLEAD) / 8) ln.load(P.x, P.wr, ln_t, lane & 15);
            };
            for4([&](auto kc) {
                step(TrueT{}, kc, s, hh);
                if (hh > 0) {
                    if (kc.value == 0) fence_regs(o);
                    store_chunk<kc.value>(o, ep_ptr, ep_ptr + ep_step, 1.f, 1.f, policy_sel(false));
                    if (kc.value == 3) signal(bars, wg, hh, lane);
                }
                ln_stage(kc);
            });
            for4([&](auto kc) {
                step(FalseT{}, kc, o, hh);
                if (kc.value == 0) fence_regs(s);
                store_chunk<kc.value>(s, base + krow * 128, base + (krow + 8) * 128, 1.f, 1.f, policy_sel(false));
                ln_stage(IntT<kc.value + 4>{});
            });
            PROF(24 + hh);
            if (hh == 1) PROFG(181);
            ep_ptr = base + 16384 + vrow * 128;
        }
    }
    PROFG(182);
    PROF(2);
    uint32_t pf[32];
    {
        uint32_t qf[32];
        float l0 = 0.25f, l1 = 0.25f;
        const int bar_me = 2 + wg, bar_other = 3 - wg;
#pragma unroll 1
        for (int j = 0; j < n_items(ca, cb); j++) {
            const int rd = item_rd(ca, cb, j), h = 8 * rd + cb, p = item_p(ca, rd);
            const int role = wg ^ (j & 1);
            const int nrest = 2 * p + role;
            Slot kfirst;
            const int lim = 64 * (role ^ rank) + 16 * w + lr - 8 * q;
            const uint64_t pol = policy_sel(((EFMASK & 4) && j == 1) || ((EFMASK & 8) && j == 2));
            {
                auto qstep = [&](auto zero, int ks) {
                    const Slot sl = c.next();
                    c.wait(sl);
                    BP(2, 5 + 3 * ks);
                    wgmma_fence();
                    gemm_q<zero.value>(s, sl.dl, role);
                    wgmma_commit();
                    wgmma_wait<1>();
                    c.release(pend);
                    pend = sl.bo;
                };
                qstep(TrueT{}, 0);
                if (j == 0) c.release(slot_a(3) * 8);
                fence_regs(o);
                l0 += __shfl_xor_sync(0xffffffffu, l0, 1); l1 += __shfl_xor_sync(0xffffffffu, l1, 1);
                l0 += __shfl_xor_sync(0xffffffffu, l0, 2); l1 += __shfl_xor_sync(0xffffffffu, l1, 2);
                l0 = rcp(l0); l1 = rcp(l1);
                for4([&](auto i) {
                    constexpr int B = 16 * i.value;
#pragma unroll
                    for (int r = 0; r < 2; r++) {
                        qstep(FalseT{}, 1 + 2 * i.value + r);
                        const float f = r ? l1 : l0;
                        stg128p(ep_ptr + r * ep_step + 2 * B, pack_bf16(o[B + 2 * r] * f, o[B + 2 * r + 1] * f), pack_bf16(o[B + 2 * r + 4] * f, o[B + 2 * r + 5] * f),
                                pack_bf16(o[B + 2 * r + 8] * f, o[B + 2 * r + 9] * f), pack_bf16(o[B + 2 * r + 12] * f, o[B + 2 * r + 13] * f), pol);
#pragma unroll
                        for (int k = 0; k < 8; k++) {
                            float& v = o[B + 4 * (k >> 1) + 2 * r + (k & 1)];
                            v = (2 * B + k > lim + 8 * r) ? -1e30f : 0.f;
                            asm volatile("" : "+f"(v));
                        }
                    }
                });
                signal(bars, wg, 4 + j, lane);
                PROF(11 + rd * 4);
                qstep(FalseT{}, 9);
                if (!role) { const Slot sl = c.next(); c.wait(sl); c.release(sl.bo); }
                kfirst = c.next();
                c.wait(kfirst);
                wgmma_wait<0>();
                BP(2, 34);
                c.release(pend);
                fence_regs(s);
                pack_tile(s, qf);
            }
            PROF(8 + rd * 4);
            fence_regs(qf); fence_regs(o);
            if (PINGPONG && !role) named_sync(bar_me, 256);
            BP(2, 36);
            wgmma_fence();
            gemm_rs<false>(o, qf, kfirst.dl);
            wgmma_commit();
            if (PINGPONG) named_arrive(bar_other, 256);
            if (!role) { const Slot sl = c.next(); c.wait(sl); c.release(sl.bo); }
            wgmma_wait<0>();
            BP(2, 38);
            fence_regs(o);
            c.release(kfirst.bo);
            float n0 = fmaxf(fmaxf(fmaxf(o[0], o[1]), fmaxf(o[4], o[5])), fmaxf(fmaxf(o[8], o[9]), fmaxf(o[12], o[13])));
            float n1 = fmaxf(fmaxf(fmaxf(o[2], o[3]), fmaxf(o[6], o[7])), fmaxf(fmaxf(o[10], o[11]), fmaxf(o[14], o[15])));
            n0 = __shfl_sync(0xffffffffu, n0, lane & 28); n1 = __shfl_sync(0xffffffffu, n1, lane & 28);
            n0 *= -SM_SCALE; n1 *= -SM_SCALE;
            l0 = 0.f; l1 = 0.f;
#pragma unroll
            for (int i = 0; i < 64; i++) s[i] = o[i];
            exp_part<0, 8>(s, n0, n1, l0, l1);
#pragma unroll
            for (int i = 0; i < 16; i++) pf[i] = pack_bf16(s[2 * i], s[2 * i + 1]);
            if (role != rank) {
                exp_part<8, 16>(s, n0, n1, l0, l1);
#pragma unroll
                for (int i = 16; i < 32; i++) pf[i] = pack_bf16(s[2 * i], s[2 * i + 1]);
            } else {
#pragma unroll
                for (int i = 16; i < 32; i++) pf[i] = 0u;
            }
            PROF(9 + rd * 4);
#pragma unroll 1
            for (int it = 0; it < nrest; it++) {
                const Slot sk = c.next(), sv = c.next();
                LP(0);
                c.wait(sk);
                c.wait(sv);
                fence_regs(o); fence_regs(pf);
                LP(1);
                if (PINGPONG) named_sync(bar_me, 256);
                LP(2);
                if (it < 3) BP(2, 42 + 4 * it);
                if (it >= nrest - 2) BP(1, 62 + 4 * (it - nrest + 2));
                wgmma_fence();
                gemm_rs<true>(s, qf, sk.dl);
                wgmma_commit();
                gemm_rs<false>(o, pf, sv.dl, it);
                wgmma_commit();
                if (PINGPONG) named_arrive(bar_other, 256);
                LP(3);
                wgmma_wait<1>();
                LP(4);
                c.release(sk.bo);
                fence_regs(s);
                exp_part<0, SPLITJ>(s, n0, n1, l0, l1);
                sched_barrier(l0, l1, bars + MISC_OFF + 16);
                LP(5);
                wgmma_wait<0>();
                LP(6);
                c.release(sv.bo);
                fence_regs(o); fence_regs(pf);
                exp_part<SPLITJ, 16>(s, n0, n1, l0, l1);
                pack_tile(s, pf);
            }
            PROF(10 + rd * 4);
            PROFG(183 + rd);
            const Slot sv = c.next();
            BP(1, 0);
            c.wait(sv);
            if (nrest == 0) {
#pragma unroll
                for (int i = 0; i < 64; i++) o[i] = 0.f;
            }
            if (__builtin_expect(__any_sync(0xffffffffu, !(l0 < 0x1p60f && l1 < 0x1p60f)), 0)) {
                attention_exact(o, qf, l0, l1, h, nrest + 1, lim, lane);
#pragma unroll
                for (int i = 0; i < 32; i++) pf[i] = 0u;
            }
            fence_regs(o); fence_regs(pf);
            if (PINGPONG && !role) named_sync(bar_me, 256);
            BP(1, 2);
            wgmma_fence();
            gemm_rs<false>(o, pf, sv.dl);
            wgmma_commit();
            pend = sv.bo;
            ep_ptr = g_ctx + (size_t)(h * SEQ + 256 * p + 128 * rank + 64 * role + 16 * w + lr) * HD + 8 * q;
            ep_step = 8 * HD;
        }
        l0 += __shfl_xor_sync(0xffffffffu, l0, 1); l1 += __shfl_xor_sync(0xffffffffu, l1, 1);
        l0 += __shfl_xor_sync(0xffffffffu, l0, 2); l1 += __shfl_xor_sync(0xffffffffu, l1, 2);
        l0 = rcp(l0); l1 = rcp(l1);
        wgmma_wait<0>();
        c.release(pend);
        fence_regs(o); fence_regs(pf);
#pragma unroll
        for (int i = 0; i < 32; i++) pf[i] = pack_bf16(o[2 * i] * ((i & 1) ? l1 : l0), o[2 * i + 1] * ((i & 1) ? l1 : l0));
    }
    PROFG(187);
    PROF(3);
    {
        float a1[64], a2[96];
        uint32_t px = 0, py = 0;
        auto mma1 = [&](const Slot& x, int acc) {
#pragma unroll
            for (int k = 0; k < 4; k++) wgmma_ss_n128<0, 1>(a1, x.dl + wg * 512 + lbo(16) + k * 2, x.dl + 1024 + lbo(4096) + (k >> 1) * 512 + (k & 1) * 128, k ? 1 : acc);
        };
        auto mma2 = [&](const Slot& x, const Slot& y, int acc) {
#pragma unroll
            for (int k = 0; k < 4; k++) wgmma_ss_n192<0, 1>(a2, x.dl + wg * 512 + lbo(16) + k * 2, y.dl + lbo(4096) + (k >> 1) * 768 + (k & 1) * 128, k ? 1 : acc);
        };
#pragma unroll 1
        for (int t = 0, more = 1; more; t++) {
            const Slot sx = c.next(), sy = c.next();
            c.wait(sx);
            wgmma_fence();
            mma1(sx, t);
            wgmma_commit();
            asm volatile("ld.shared.u32 %0, [%1];" : "=r"(more) : "r"(bars + CTL_OFF + sx.bo) : "memory");
            more = !__any_sync(0xffffffffu, more);
            wgmma_wait<1>();
            if (t > 0) { c.release(px); c.release(py); }
            px = sx.bo; py = sy.bo;
            c.wait(sy);
            wgmma_fence();
            mma2(sx, sy, t);
            wgmma_commit();
            if (t == 0) {
#pragma unroll
                for (int i = 0; i < 4; i++) stg128(ep_ptr + 32 * i, pf[8 * i], pf[8 * i + 2], pf[8 * i + 4], pf[8 * i + 6]);
            }
            if (t == 1) {
#pragma unroll
                for (int i = 0; i < 4; i++) stg128(ep_ptr + 8 * HD + 32 * i, pf[8 * i + 1], pf[8 * i + 3], pf[8 * i + 5], pf[8 * i + 7]);
                signal(bars, wg, 4 + n_items(ca, cb), lane);
            }
        }
        const Slot x0 = c.next(), y0 = c.next(), x1 = c.next(), y1 = c.next(), x2 = c.next(), y2 = c.next(), fr = c.next();
        const int cw = __reduce_or_sync(0xffffffffu, wg * 4 + w);
        const int orow = unperm_row(256 * out_p(ca, cb) + 128 * rank + 16 * cw), ocol = 320 * (ca >> 2);
        const uint32_t sa = ((lane & 7) + (lane & 8)) * 128, sx = (lane >> 4) ^ (lane & 7);
        auto send = [&](auto chv, uint32_t box) {
            constexpr int ch = chv.value;
#pragma unroll
            for (int i = 0; i < 4; i++) {
                uint32_t r[4];
#pragma unroll
                for (int e = 0; e < 4; e++) {
                    const int k = 32 * ch + 8 * i + 2 * e;
                    r[e] = (ch < 2) ? pack_bf16(a1[k & 63], a1[(k & 63) + 1]) : pack_bf16(a2[ch < 2 ? 0 : k - 64], a2[ch < 2 ? 1 : k - 63]);
                }
                asm volatile("stmatrix.sync.aligned.m8n8.x4.shared.b16 [%0], {%1, %2, %3, %4};"
                             ::"r"(box + sa + ((sx ^ (2 * i)) << 4)), "r"(r[0]), "r"(r[1]), "r"(r[2]), "r"(r[3]) : "memory");
            }
            asm volatile("fence.proxy.async.shared::cta;" ::: "memory");
            __syncwarp();
            asm volatile(ELECT "cp.reduce.async.bulk.tensor.2d.global.shared::cta.add.bulk_group [%0, {%2, %3}], [%1];\n}\n"
                         ::"l"(&P.outm), "r"(box), "r"(ocol + 64 * ch), "r"(orow) : "memory");
        };
        auto addr = [&](const Slot& t) { return smem + t.bo * (SLOT / 8); };
        c.wait(x0);
        wgmma_fence();
        mma1(x0, 1);
        wgmma_commit();
        wgmma_wait<1>();
        c.release(px); c.release(py);
        c.wait(x1);
        c.wait(x2);
        c.wait(y0);
        mbar_wait(bars + BAR_DEP + 9 * 8, 0);
        wgmma_fence();
        mma1(x1, 1);
        mma1(x2, 1);
        wgmma_commit();
        mma2(x0, y0, 1);
        wgmma_commit();
        mbar_wait(bars + BAR_EMPTY + fr.bo, fr.par ^ 1);
        c.wait(y1);
        wgmma_wait<1>();
        fence_regs(a1);
        send(IntT<0>{}, addr(fr) + cw * 4096);
        wgmma_fence();
        mma2(x1, y1, 1);
        wgmma_commit();
        send(IntT<1>{}, addr(fr) + cw * 4096 + 2048);
        c.wait(y2);
        wgmma_fence();
        mma2(x2, y2, 1);
        wgmma_commit();
        wgmma_wait<0>();
        fence_regs(a2);
        PROFG(188);
        PROF(4);
        send(IntT<2>{}, addr(x0) + cw * 2048);
        send(IntT<3>{}, addr(x1) + cw * 2048);
        send(IntT<4>{}, addr(x2) + cw * 2048);
        PROF(5);
        asm volatile("cp.async.bulk.commit_group;\ncp.async.bulk.wait_group.read 0;" ::: "memory");
    }
    PROF(6);
}

__device__ __forceinline__ void mod_ffn(const Params& P, uint32_t smem, int mc  , int wg) {
    const int tid = threadIdx.x - 128, lane = tid & 31, cw = tid >> 5, q = lane & 3, lr = lane >> 2;
    const uint32_t xs = smem + 6 * SLOT, hs = xs + 10240 + wg * 1024, wmax = xs + 12288, sidx = wmax + 64, rbar = xs + 13312 + wg * 32;
    const uint32_t ring = smem + wg * 3 * SLOT;
    const int f0 = mc + 4 * wg, nunit = ((34 - f0) >> 3) * 8;
    const bool lead = __reduce_or_sync(0xffffffffu, cw & 3) == 0;
    auto lds = [](uint32_t a) { uint32_t v; asm volatile("ld.shared.u32 %0, [%1];" : "=r"(v) : "r"(a) : "memory"); return v; };
    auto sts = [](uint32_t a, uint32_t v) { asm volatile("st.shared.u32 [%0], %1;" ::"r"(a), "r"(v) : "memory"); };
    auto issue = [&](int u, int st) {
        if (lead && u < nunit) {
            const int fc = (f0 + (u & ~7)) * 64, k = u & 7;
            const uint32_t dst = ring + st * SLOT, bar = rbar + st * 8;
            w_expect_tx(bar, k == 7 ? 16384 : SLOT);
            if (k < 5) {
                w_tma_load_stream(dst, &P.wg, fc, k * 128, bar);
                w_tma_load_stream(dst + 16384, &P.wu, fc, k * 128, bar);
            } else {
#pragma unroll 1
                for (int b = 0; b < (k == 7 ? 2 : 4); b++) w_tma_load_stream(dst + b * 8192, &P.wd, (4 * (k - 5) + b) * 64, fc, bar);
            }
        }
    };
    if ((tid & 127) == 0) {
        mbar_init(rbar, 1); mbar_init(rbar + 8, 1); mbar_init(rbar + 16, 1);
        asm volatile("fence.mbarrier_init.release.cluster;" ::: "memory");
    }
    mbar_wait_sleep(smem + NSLOT * SLOT + BAR_DEP, 0);
    named_sync(1, 256);
    PROF(1);
#pragma unroll 1
    for (int u = 0; u < 3; u++) issue(u, u);
    uint32_t key[8];
#pragma unroll
    for (int i = 0; i < 8; i++) {
        const int t = tid + 256 * i;
        uint32_t b = __float_as_uint(__ldcg(g_r + t) + 0.f) >> 16;
        b = (b & 0x8000u) ? (~b & 0xffffu) : (b | 0x8000u);
        key[i] = (b << 16) | (uint32_t)(0xffff - t);
    }
#pragma unroll 1
    for (int rnd = 0; rnd < 8; rnd++) {
        uint32_t mx = key[0];
#pragma unroll
        for (int i = 1; i < 8; i++) mx = max(mx, key[i]);
        sts(wmax + ((rnd & 1) * 8 + cw) * 4, __reduce_max_sync(0xffffffffu, mx));
        named_sync(1, 256);
        mx = __reduce_max_sync(0xffffffffu, lds(wmax + ((rnd & 1) * 8 + (lane & 7)) * 4));
#pragma unroll
        for (int i = 0; i < 8; i++) if (key[i] == mx) key[i] = 0;
        if (cw == rnd) sts(sidx + rnd * 4, 0xffff - (mx & 0xffffu));
    }
    __syncwarp();
    {
        const int t = lds(sidx + cw * 4);
        const uint4* src = reinterpret_cast<const uint4*>(g_xn + perm_row(t) * DM);
#pragma unroll
        for (int i = 0; i < 3; i++) {
            const int ch = lane + 32 * i;
            if (ch < 80) {
                const uint4 v = __ldcg(src + ch);
                asm volatile("st.shared.v4.b32 [%0], {%1, %2, %3, %4};" ::"r"(xs + (ch >> 3) * 1024 + cw * 128 + ((ch ^ cw) & 7) * 16), "r"(v.x), "r"(v.y), "r"(v.z), "r"(v.w) : "memory");
            }
        }
        asm volatile("fence.proxy.async.shared::cta;" ::: "memory");
    }
    named_sync(1, 256);
    PROF(3);
    float y[10][4];
#pragma unroll
    for (int i = 0; i < 10; i++) { y[i][0] = 0.f; y[i][1] = 0.f; y[i][2] = 0.f; y[i][3] = 0.f; }
    int st = 0, ph = 0, u = 0;
    auto begin = [&]() { mbar_wait(rbar + st * 8, ph); wgmma_fence(); return (((ring + st * SLOT) & 0x3FFFF) >> 4) + lbo(16); };
    auto end = [&]() {
        wgmma_commit();
        wgmma_wait<0>();
        named_sync(4 + wg, 128);
        issue(u + 3, st);
        u++;
        ph ^= st == 2;
        st = (st == 2) ? 0 : st + 1;
    };
    const uint32_t dx = ((xs & 0x3FFFF) >> 4) + lbo(16), dh = ((hs & 0x3FFFF) >> 4) + lbo(16);
#pragma unroll 1
    while (u < nunit) {
        float g[4], v[4];
#pragma unroll 1
        for (int kc = 0; kc < 5; kc++) {
            const uint32_t da = begin();
#pragma unroll
            for (int k = 0; k < 8; k++) {
                const uint32_t db = dx + (2 * kc + (k >> 2)) * 64 + (k & 3) * 2;
                wgmma_ss_n8<1, 0>(g, da + k * 128, db, k ? 1 : kc);
                wgmma_ss_n8<1, 0>(v, da + 1024 + k * 128, db, k ? 1 : kc);
            }
            end();
        }
        fence_regs(g); fence_regs(v);
#pragma unroll
        for (int e = 0; e < 4; e++) {
            const float gp = round_bf16(g[e]);
            const float hv = round_bf16(__fdividef(gp, 1.0f + __expf(fminf(-gp, 80.f)))) * round_bf16(v[e]);
            const int tok = 2 * q + (e & 1), ch = 2 * (cw & 3) + (e >> 1);
            asm volatile("st.shared.u16 [%0], %1;" ::"r"(hs + tok * 128 + ((ch ^ tok) * 16) + lr * 2), "h"((unsigned short)pack_bf16(hv, 0.f)) : "memory");
        }
        asm volatile("fence.proxy.async.shared::cta;" ::: "memory");
        named_sync(4 + wg, 128);
#pragma unroll
        for (int k3 = 0; k3 < 3; k3++) {
            const uint32_t da = begin();
#pragma unroll
            for (int b = 0; b < (k3 == 2 ? 2 : 4); b++)
#pragma unroll
                for (int k = 0; k < 4; k++) wgmma_ss_n8<1, 0>(y[4 * k3 + b], da + b * 512 + k * 128, dh + k * 2, 1);
            end();
        }
    }
    PROF(5);
#pragma unroll
    for (int i = 0; i < 10; i++) {
        fence_regs(y[i]);
#pragma unroll
        for (int e = 0; e < 4; e++) g_ypart[((mc * 2 + wg) * 8 + 2 * q + (e & 1)) * DM + 64 * i + 16 * (cw & 3) + lr + 8 * (e >> 1)] = y[i][e];
    }
    named_sync(1, 256);
    if (tid == 0) {
        flag_add(F_MODP);
        flag_wait<100>(F_MODP, 4u * (lds(smem + NSLOT * SLOT + MISC_OFF) + 1));
    }
    named_sync(1, 256);
    PROF(6);
    {
        const int c = 2 * mc + wg, t = lds(sidx + c * 4);
        const float rs = round_bf16(__fdividef(1.0f, 1.0f + __expf(fminf(-__ldcg(g_r + t), 80.f))));
#pragma unroll
        for (int i = 0; i < 5; i++) {
            const int col = (tid & 127) + 128 * i;
            float yy = 0.f;
#pragma unroll
            for (int k = 0; k < 8; k++) yy += __ldcg(g_ypart + (k * 8 + c) * DM + col);
            const uint32_t xw = lds(xs + (col >> 6) * 1024 + c * 128 + (((col >> 3) ^ c) & 7) * 16 + (col & 6) * 2);
            const float xn = (col & 1) ? bf_hi(xw) : bf_lo(xw);
            P.out[t * DM + col] = __float2bfloat16_rn(__bfloat162float(P.x[t * DM + col]) + round_bf16(xn + round_bf16(round_bf16(yy) * rs)));
        }
    }
    named_sync(1, 256);
    if (tid == 0) flag_add(F_MOD);
    PROF(7);
}

__global__ void __cluster_dims__(2, 1, 1) __launch_bounds__(384, 1) fused_kernel(const __grid_constant__ Params P) {
    extern __shared__ __align__(1024) uint8_t smem_raw[];
    const uint32_t smem = (smem_u32(smem_raw) + 1023u) & ~1023u;
    const uint32_t bars = smem + NSLOT * SLOT;
    const int wgi = __reduce_or_sync(0xffffffffu, threadIdx.x >> 7);
    const int cl = blockIdx.x >> 1, rank = blockIdx.x & 1, ca = cl & 7, cb = cl >> 3;
    PROFG(30);
    PROF(0);
    if (threadIdx.x >= 64 && threadIdx.x < 64 + 32 * FASTSTART && (threadIdx.x & 31) == 0) {
        const int u = (threadIdx.x >> 5) - 2;
        const uint32_t fa = bars + BAR_FULL + slot_a(u) * 8, fw = bars + BAR_FULL + slot_w(u) * 8;
        mbar_init(fa, 1); mbar_init(fw, 1);
        asm volatile("fence.mbarrier_init.release.cluster;" ::: "memory");
        if (cl < 64) {
            mbar_expect_tx(fa, SLOT);
            mbar_expect_tx(fw, SLOT);
            tma_load(smem + slot_a(u) * SLOT, &P.ckv, u * 128, (2 * ca + rank) * 128, fa);
            tma_load(smem + slot_w(u) * SLOT, &P.wuk, (cb + 8 * kv_round(0)) * 128, u * 128, fw);
            tma_load(smem + slot_w(u) * SLOT + 16384, &P.wuk, (cb + 8 * kv_round(0)) * 128 + 64, u * 128, fw);
            tma_load(smem + slot_a(u) * SLOT + 16384, &P.ckv, u * 128 + 64, (2 * ca + rank) * 128, fa);
        }
    } else if (threadIdx.x == 0) {
#pragma unroll
        for (int i = 0; i < NSLOT; i++) {
            if (i != 0 && i != 4 && (FASTSTART < 2 || (i != 1 && i != 6))) mbar_init(bars + BAR_FULL + i * 8, 1);
            mbar_init(bars + BAR_EMPTY + i * 8, 16);
        }
        mbar_arrive(bars + BAR_FULL + 16);
        asm volatile("mbarrier.arrive.shared::cta.b64 _, [%0], 16;" ::"r"(bars + BAR_EMPTY + 16) : "memory");
        asm volatile("fence.mbarrier_init.release.cluster;" ::: "memory");
        PROF(24);
    } else if (threadIdx.x == 32) {
#pragma unroll
        for (int i = 0; i < 18; i++) mbar_init(bars + BAR_SIG + i * 8, 4);
#pragma unroll
        for (int i = 0; i < 18; i++) mbar_init(bars + BAR_DEP + i * 8, 1);
        asm volatile("fence.mbarrier_init.release.cluster;" ::: "memory");
    }
    __syncthreads();
    PROF(29);
    cluster_arrive();
    if (wgi > 0) {
        asm volatile("setmaxnreg.inc.sync.aligned.u32 232;");
        if (cl >= 64) {
            cluster_wait();
            mod_ffn(P, smem, blockIdx.x - 128, wgi - 1);
        } else {
            consumer(P, smem, bars, ca, cb, rank, wgi - 1);
        }
        if (ENDBAR) cluster_arrive();
        PROFG(31);
        PROFDUMP();
    } else {
        asm volatile("setmaxnreg.dec.sync.aligned.u32 40;");
        const int w = __reduce_or_sync(0xffffffffu, threadIdx.x >> 5), lane = threadIdx.x & 31;
        if (threadIdx.x == 32) {
            prefetch_map(&P.wuv); prefetch_map(&P.xn); prefetch_map(&P.wq); prefetch_map(&P.kv); prefetch_map(&P.ctx); prefetch_map(&P.wo); prefetch_map(&P.outm);
        }
        __syncwarp();
        cluster_wait();
        PROF(27);
        {
            if (cl >= 64 && w < 3) {
            } else if (w == 0) {
                producer(P, smem, bars, ca, cb, rank);
            } else if (w < 3 && lane == 0) {
                const int wg = w - 1;
#pragma unroll 1
                for (int i = 0; i < 5 + n_items(ca, cb); i++) {
                    const int nb = wg * LNSTAG + (LNOFF + 7 - 3) / 8;
                    const int e = (i < nb) ? i + 1 : (i == nb) ? 0 : i;
                    mbar_wait_sleep(bars + BAR_SIG + (wg * 9 + e) * 8, 0);
                    int f;
                    if (e == 0) f = F_LN;
                    else if (e < 5) f = F_KV + cb + 8 * kv_round(e - 1);
                    else { const int rd = item_rd(ca, cb, e - 5); f = F_CTX + rd * 16 + item_p(ca, rd) * 2 + rank; }
                    flag_add(f);
                }
            } else if (lane == 0) {
                const uint32_t epoch = read_epoch();
                asm volatile("st.shared.u32 [%0], %1;" ::"r"(bars + MISC_OFF), "r"(epoch) : "memory");
#pragma unroll 1
                for (int e = 0; e < (cl < 64 ? 10 : 1); e++) {
                    int f;
                    uint32_t n;
                    if (e == 0) { f = F_LN; n = 256; }
                    else if (e < 5) { f = F_KV + cb + 8 * (e - 1); n = 32; }
                    else if (e < 9) { f = F_CTX + (e - 5) * 16 + out_p(ca, cb) * 2 + rank; n = (OFFLOAD == 2 && e >= 7 && out_p(ca, cb) == 0) ? 0 : 16; }
                    else { f = F_MOD; n = 4; }
                    flag_wait<200>(f, n * (epoch + 1));
                    fence_proxy_async();
                    mbar_arrive(bars + BAR_DEP + e * 8);
                }
            }
        }
        if (ENDBAR) { __syncwarp(); cluster_arrive(); cluster_wait(); }
        PROFG(31);
        PROFDUMP();
    }
}

typedef CUresult (*EncodeFn)(CUtensorMap*, CUtensorMapDataType, cuuint32_t, void*, const cuuint64_t*, const cuuint64_t*, const cuuint32_t*,
                             const cuuint32_t*, CUtensorMapInterleave, CUtensorMapSwizzle, CUtensorMapL2promotion, CUtensorMapFloatOOBfill);

void make_map(EncodeFn fn, CUtensorMap* m, const void* ptr, uint64_t rows, uint64_t cols, uint32_t box_rows) {
    cuuint64_t dims[2] = {cols, rows};
    cuuint64_t strides[1] = {cols * 2};
    cuuint32_t box[2] = {64, box_rows};
    cuuint32_t es[2] = {1, 1};
    fn(m, CU_TENSOR_MAP_DATA_TYPE_BFLOAT16, 2, const_cast<void*>(ptr), dims, strides, box, es, CU_TENSOR_MAP_INTERLEAVE_NONE,
       CU_TENSOR_MAP_SWIZZLE_128B, CU_TENSOR_MAP_L2_PROMOTION_L2_128B, CU_TENSOR_MAP_FLOAT_OOB_FILL_NONE);
}

}

extern "C" void kernel_launch(void* const* d_in, const int* in_sizes, int n_in, void* d_out, int out_size) {
    (void)in_sizes; (void)n_in; (void)out_size;
    void* fnp = nullptr;
    cudaDriverEntryPointQueryResult qr;
    cudaGetDriverEntryPoint("cuTensorMapEncodeTiled", &fnp, cudaEnableDefault, &qr);
    EncodeFn fn = (EncodeFn)fnp;
    void *xn, *kv, *ctx;
    cudaGetSymbolAddress(&xn, g_xn);
    cudaGetSymbolAddress(&kv, g_kv);
    cudaGetSymbolAddress(&ctx, g_ctx);
    Params P;
    make_map(fn, &P.ckv, d_in[1], SEQ, DC, 128);
    make_map(fn, &P.wq, d_in[2], DM, NH * HD, 64);
    make_map(fn, &P.wuk, d_in[3], DC, NH * HD, 128);
    make_map(fn, &P.wuv, d_in[4], DC, NH * HD, 128);
    make_map(fn, &P.wo, d_in[5], NH * HD, DM, 32);
    make_map(fn, &P.xn, xn, SEQ, DM, 128);
    make_map(fn, &P.kv, kv, NH * 16 * 2 * 128, 128, 128);
    make_map(fn, &P.ctx, ctx, NH * SEQ, HD, 128);
    P.x = (const __nv_bfloat16*)d_in[0];
    P.wr = (const __nv_bfloat16*)d_in[7];
    make_map(fn, &P.wg, d_in[8], DM, FF, 128);
    make_map(fn, &P.wu, d_in[9], DM, FF, 128);
    make_map(fn, &P.wd, d_in[10], FF, DM, 64);
    make_map(fn, &P.outm, d_out, SEQ, DM, 16);
    P.out = (__nv_bfloat16*)d_out;
    cudaFuncSetAttribute(fused_kernel, cudaFuncAttributeMaxDynamicSharedMemorySize, SMEM_BYTES);
    fused_kernel<<<NCTA, 384, SMEM_BYTES>>>(P);
}
```

```cpp
#include <cuda_runtime.h>
#include <cuda_bf16.h>
#include <cuda.h>
#include <stdint.h>

namespace {

constexpr int SEQ = 2048, DM = 640, DC = 512, NH = 32, HD = 128, FF = 1728;
constexpr int NSLOT = 7, SLOT = 32768;
constexpr int NCTA = 132;
#define PINGPONG 1
#define SIGMA 1
#define KVORDER 0x1023
#define KVSPLIT 1
#define LNSTAG 1
#define NPOOL 44
#define LASTRD 7
#define LASTN 2
#define EFMASK 13
#define LNOFF 4
#define LNLEAD 2
#define FASTSTART 1
#define OFFLOAD 1
#define SPLITJ 8
constexpr uint32_t DESC_HI = (1024u >> 4) | (1u << 30);
constexpr int SMEM_BYTES = NSLOT * SLOT + 3072;

constexpr int BAR_FULL = 0, BAR_EMPTY = 64, BAR_SIG = 128  , BAR_DEP = 320  , BAR_MAIL = 400  ;
constexpr int MISC_OFF = 512  , MAIL_OFF = 544  , CTL_OFF = 576  ;

constexpr int F_EPOCH = 0, F_LN = 1, F_MODP = 3, F_KV = 4  , F_CTX = 36  , F_POOL = 100  , F_NUM = 116;

__device__ __align__(1024) __nv_bfloat16 g_xn[SEQ * DM];
__device__ __align__(1024) __nv_bfloat16 g_kv[NH * 16 * 2 * 128 * 128];
__device__ __align__(1024) __nv_bfloat16 g_ctx[NH * SEQ * HD];
__device__ __align__(16) float g_r[SEQ];
__device__ __align__(16) float g_ypart[8 * 8 * DM];
__device__ uint32_t g_flags[F_NUM * 8];

struct TrueT { static constexpr bool value = true; };
struct FalseT { static constexpr bool value = false; };

struct Params {
    CUtensorMap ckv, wuk, wuv, xn, wq, kv, ctx, wo, wg, wu, wd, outm;
    const __nv_bfloat16 *x, *wr;
    __nv_bfloat16* out;
};

__device__ __forceinline__ uint32_t smem_u32(const void* p) { return (uint32_t)__cvta_generic_to_shared(p); }
__device__ __forceinline__ void mbar_init(uint32_t bar, uint32_t cnt) {
    asm volatile("mbarrier.init.shared::cta.b64 [%0], %1;" ::"r"(bar), "r"(cnt) : "memory");
}
__device__ __forceinline__ void mbar_expect_tx(uint32_t bar, uint32_t bytes) {
    asm volatile("mbarrier.arrive.expect_tx.shared::cta.b64 _, [%0], %1;" ::"r"(bar), "r"(bytes) : "memory");
}
__device__ __forceinline__ void mbar_arrive(uint32_t bar) {
    asm volatile("mbarrier.arrive.shared::cta.b64 _, [%0];" ::"r"(bar) : "memory");
}
__device__ __forceinline__ uint32_t mapa(uint32_t addr, uint32_t cta) {
    uint32_t r;
    asm("mapa.shared::cluster.u32 %0, %1, %2;" : "=r"(r) : "r"(addr), "r"(cta));
    return r;
}
__device__ __forceinline__ void mbar_wait(uint32_t bar, uint32_t parity) {
    asm volatile(
        "{\n.reg .pred p;\n.reg .b32 c;\n"
        "mov.b32 c, 0;\n"
        "WLOOP:\n"
        "mbarrier.try_wait.parity.shared::cta.b64 p, [%0], %1;\n"
        "@p bra.uni WDONE;\n"
        "add.u32 c, c, 1;\n"
        "setp.lt.u32 p, c, 0x400000;\n"
        "@p bra.uni WLOOP;\n"
        "trap;\n"
        "WDONE:\n}\n" ::"r"(bar), "r"(parity) : "memory");
}
__device__ __forceinline__ void mbar_wait_sleep(uint32_t bar, uint32_t parity) {
    asm volatile(
        "{\n.reg .pred p;\n.reg .b32 c;\n"
        "mov.b32 c, 0;\n"
        "WLOOP:\n"
        "mbarrier.try_wait.parity.shared::cta.b64 p, [%0], %1, 20000;\n"
        "@p bra.uni WDONE;\n"
        "add.u32 c, c, 1;\n"
        "setp.lt.u32 p, c, 0x40000;\n"
        "@p bra.uni WLOOP;\n"
        "trap;\n"
        "WDONE:\n}\n" ::"r"(bar), "r"(parity) : "memory");
}
__device__ __forceinline__ void tma_load(uint32_t dst, const CUtensorMap* m, int c0, int c1, uint32_t bar) {
    asm volatile("cp.async.bulk.tensor.2d.shared::cluster.global.mbarrier::complete_tx::bytes [%0], [%1, {%3, %4}], [%2];"
                 ::"r"(dst), "l"(m), "r"(bar), "r"(c0), "r"(c1) : "memory");
}
#define ELECT "{\n.reg .pred e;\nelect.sync _|e, 0xffffffff;\n@e "
__device__ __forceinline__ void w_expect_tx(uint32_t bar, uint32_t bytes) {
    asm volatile(ELECT "mbarrier.arrive.expect_tx.shared::cta.b64 _, [%0], %1;\n}\n" ::"r"(bar), "r"(bytes) : "memory");
}
__device__ __forceinline__ void w_tma_load(uint32_t dst, const CUtensorMap* m, int c0, int c1, uint32_t bar) {
    asm volatile(ELECT "cp.async.bulk.tensor.2d.shared::cluster.global.mbarrier::complete_tx::bytes [%0], [%1, {%3, %4}], [%2];\n}\n"
                 ::"r"(dst), "l"(m), "r"(bar), "r"(c0), "r"(c1) : "memory");
}
__device__ __forceinline__ void w_tma_load_mc(uint32_t dst, const CUtensorMap* m, int c0, int c1, uint32_t bar) {
    asm volatile(ELECT "cp.async.bulk.tensor.2d.shared::cluster.global.mbarrier::complete_tx::bytes.multicast::cluster [%0], [%1, {%3, %4}], [%2], %5;\n}\n"
                 ::"r"(dst), "l"(m), "r"(bar), "r"(c0), "r"(c1), "h"((uint16_t)3) : "memory");
}
__device__ __forceinline__ void w_tma_prefetch(const CUtensorMap* m, int c0, int c1) {
    asm volatile(ELECT "cp.async.bulk.prefetch.tensor.2d.L2.global [%0, {%1, %2}];\n}\n" ::"l"(m), "r"(c0), "r"(c1) : "memory");
}
__device__ __forceinline__ uint64_t policy_evict_first() {
    uint64_t p;
    asm("createpolicy.fractional.L2::evict_first.b64 %0, 1.0;" : "=l"(p));
    return p;
}
__device__ __forceinline__ void w_tma_load_mc_last(uint32_t dst, const CUtensorMap* m, int c0, int c1, uint32_t bar) {
    asm volatile(ELECT "cp.async.bulk.tensor.2d.shared::cluster.global.mbarrier::complete_tx::bytes.multicast::cluster.L2::cache_hint [%0], [%1, {%3, %4}], [%2], %5, %6;\n}\n"
                 ::"r"(dst), "l"(m), "r"(bar), "r"(c0), "r"(c1), "h"((uint16_t)3), "l"(policy_evict_first()) : "memory");
}
__device__ __forceinline__ void w_tma_load_stream(uint32_t dst, const CUtensorMap* m, int c0, int c1, uint32_t bar) {
    asm volatile(ELECT "cp.async.bulk.tensor.2d.shared::cluster.global.mbarrier::complete_tx::bytes.L2::cache_hint [%0], [%1, {%3, %4}], [%2], %5;\n}\n"
                 ::"r"(dst), "l"(m), "r"(bar), "r"(c0), "r"(c1), "l"(policy_evict_first()) : "memory");
}
__device__ __forceinline__ uint4 ldg_stream(const void* p) {
    uint4 v;
    asm volatile("ld.global.nc.L2::cache_hint.v4.b32 {%0, %1, %2, %3}, [%4], %5;" : "=r"(v.x), "=r"(v.y), "=r"(v.z), "=r"(v.w) : "l"(p), "l"(policy_evict_first()));
    return v;
}
__device__ __forceinline__ void prefetch_map(const CUtensorMap* m) {
    asm volatile("prefetch.tensormap [%0];" ::"l"(m) : "memory");
}
__device__ __forceinline__ void cluster_arrive() { asm volatile("barrier.cluster.arrive.relaxed.aligned;" ::: "memory"); }
__device__ __forceinline__ void cluster_wait() { asm volatile("barrier.cluster.wait.aligned;" ::: "memory"); }
__device__ __forceinline__ void named_sync(int id, int n) { asm volatile("bar.sync %0, %1;" ::"r"(id), "r"(n) : "memory"); }
__device__ __forceinline__ void named_arrive(int id, int n) { asm volatile("bar.arrive %0, %1;" ::"r"(id), "r"(n) : "memory"); }

__device__ __forceinline__ void flag_add(int f) {
    asm volatile("fence.acq_rel.gpu;\nred.relaxed.gpu.global.add.u32 [%0], 1;" ::"l"(g_flags + f * 8) : "memory");
}
template <int SLEEP>
__device__ __forceinline__ void flag_wait(int f, uint32_t target) {
    asm volatile(
        "{\n.reg .pred p;\n.reg .b32 c, v;\n"
        "mov.b32 c, 0;\n"
        "FLOOP:\n"
        "ld.acquire.gpu.global.u32 v, [%0];\n"
        "sub.u32 v, v, %1;\n"
        "setp.ge.s32 p, v, 0;\n"
        "@p bra FDONE;\n"
        "nanosleep.u32 %2;\n"
        "add.u32 c, c, 1;\n"
        "setp.lt.u32 p, c, 0x400000;\n"
        "@p bra FLOOP;\n"
        "trap;\n"
        "FDONE:\n}\n" ::"l"(g_flags + f * 8), "r"(target), "n"(SLEEP) : "memory");
}
__device__ __forceinline__ uint32_t read_epoch() { return atomicAdd(g_flags + F_EPOCH * 8, 1u) / NCTA; }
__device__ __forceinline__ void fence_proxy_async() { asm volatile("fence.proxy.async;" ::: "memory"); }

__device__ __forceinline__ void wgmma_fence() { asm volatile("wgmma.fence.sync.aligned;" ::: "memory"); }
__device__ __forceinline__ void wgmma_commit() { asm volatile("wgmma.commit_group.sync.aligned;" ::: "memory"); }
template <int N>
__device__ __forceinline__ void wgmma_wait() { asm volatile("wgmma.wait_group.sync.aligned %0;" ::"n"(N) : "memory"); }
template <int N>
__device__ __forceinline__ void fence_regs(float (&d)[N]) {
#pragma unroll
    for (int i = 0; i < N; i++) asm volatile("" : "+f"(d[i])::"memory");
}
template <int N>
__device__ __forceinline__ void fence_regs(uint32_t (&d)[N]) {
#pragma unroll
    for (int i = 0; i < N; i++) asm volatile("" : "+r"(d[i])::"memory");
}

template <int TA, int TB>
__device__ __forceinline__ void wgmma_ss_n128(float (&d)[64], uint32_t alo, uint32_t blo, int scale_d) {
    asm volatile("{\n.reg .pred p;\n.reg .b64 da, db;\nsetp.ne.b32 p, %66, 0;\n"
        "mov.b64 da, {%64, %69};\nmov.b64 db, {%65, %69};\n"
        "wgmma.mma_async.sync.aligned.m64n128k16.f32.bf16.bf16 "
        "{%0, %1, %2, %3, %4, %5, %6, %7, %8, %9, %10, %11, %12, %13, %14, %15, %16, %17, %18, %19, %20, %21, %22, %23, %24, %25, %26, %27, %28, %29, %30, %31, %32, %33, %34, %35, %36, %37, %38, %39, %40, %41, %42, %43, %44, %45, %46, %47, %48, %49, %50, %51, %52, %53, %54, %55, %56, %57, %58, %59, %60, %61, %62, %63}, da, db, p, 1, 1, %67, %68;\n}\n"
        :
          "+f"(d[0]), "+f"(d[1]), "+f"(d[2]), "+f"(d[3]), "+f"(d[4]), "+f"(d[5]), "+f"(d[6]), "+f"(d[7]),
          "+f"(d[8]), "+f"(d[9]), "+f"(d[10]), "+f"(d[11]), "+f"(d[12]), "+f"(d[13]), "+f"(d[14]), "+f"(d[15]),
          "+f"(d[16]), "+f"(d[17]), "+f"(d[18]), "+f"(d[19]), "+f"(d[20]), "+f"(d[21]), "+f"(d[22]), "+f"(d[23]),
          "+f"(d[24]), "+f"(d[25]), "+f"(d[26]), "+f"(d[27]), "+f"(d[28]), "+f"(d[29]), "+f"(d[30]), "+f"(d[31]),
          "+f"(d[32]), "+f"(d[33]), "+f"(d[34]), "+f"(d[35]), "+f"(d[36]), "+f"(d[37]), "+f"(d[38]), "+f"(d[39]),
          "+f"(d[40]), "+f"(d[41]), "+f"(d[42]), "+f"(d[43]), "+f"(d[44]), "+f"(d[45]), "+f"(d[46]), "+f"(d[47]),
          "+f"(d[48]), "+f"(d[49]), "+f"(d[50]), "+f"(d[51]), "+f"(d[52]), "+f"(d[53]), "+f"(d[54]), "+f"(d[55]),
          "+f"(d[56]), "+f"(d[57]), "+f"(d[58]), "+f"(d[59]), "+f"(d[60]), "+f"(d[61]), "+f"(d[62]), "+f"(d[63])
        : "r"(alo), "r"(blo), "r"(scale_d), "n"(TA), "n"(TB), "r"(DESC_HI));
}
template <int TA, int TB>
__device__ __forceinline__ void wgmma_ss_n192(float (&d)[96], uint32_t alo, uint32_t blo, int scale_d) {
    asm volatile("{\n.reg .pred p;\n.reg .b64 da, db;\nsetp.ne.b32 p, %98, 0;\n"
        "mov.b64 da, {%96, %101};\nmov.b64 db, {%97, %101};\n"
        "wgmma.mma_async.sync.aligned.m64n192k16.f32.bf16.bf16 "
        "{%0, %1, %2, %3, %4, %5, %6, %7, %8, %9, %10, %11, %12, %13, %14, %15, %16, %17, %18, %19, %20, %21, %22, %23, %24, %25, %26, %27, %28, %29, %30, %31, %32, %33, %34, %35, %36, %37, %38, %39, %40, %41, %42, %43, %44, %45, %46, %47, %48, %49, %50, %51, %52, %53, %54, %55, %56, %57, %58, %59, %60, %61, %62, %63, %64, %65, %66, %67, %68, %69, %70, %71, %72, %73, %74, %75, %76, %77, %78, %79, %80, %81, %82, %83, %84, %85, %86, %87, %88, %89, %90, %91, %92, %93, %94, %95}, da, db, p, 1, 1, %99, %100;\n}\n"
        :
          "+f"(d[0]), "+f"(d[1]), "+f"(d[2]), "+f"(d[3]), "+f"(d[4]), "+f"(d[5]), "+f"(d[6]), "+f"(d[7]),
          "+f"(d[8]), "+f"(d[9]), "+f"(d[10]), "+f"(d[11]), "+f"(d[12]), "+f"(d[13]), "+f"(d[14]), "+f"(d[15]),
          "+f"(d[16]), "+f"(d[17]), "+f"(d[18]), "+f"(d[19]), "+f"(d[20]), "+f"(d[21]), "+f"(d[22]), "+f"(d[23]),
          "+f"(d[24]), "+f"(d[25]), "+f"(d[26]), "+f"(d[27]), "+f"(d[28]), "+f"(d[29]), "+f"(d[30]), "+f"(d[31]),
          "+f"(d[32]), "+f"(d[33]), "+f"(d[34]), "+f"(d[35]), "+f"(d[36]), "+f"(d[37]), "+f"(d[38]), "+f"(d[39]),
          "+f"(d[40]), "+f"(d[41]), "+f"(d[42]), "+f"(d[43]), "+f"(d[44]), "+f"(d[45]), "+f"(d[46]), "+f"(d[47]),
          "+f"(d[48]), "+f"(d[49]), "+f"(d[50]), "+f"(d[51]), "+f"(d[52]), "+f"(d[53]), "+f"(d[54]), "+f"(d[55]),
          "+f"(d[56]), "+f"(d[57]), "+f"(d[58]), "+f"(d[59]), "+f"(d[60]), "+f"(d[61]), "+f"(d[62]), "+f"(d[63]),
          "+f"(d[64]), "+f"(d[65]), "+f"(d[66]), "+f"(d[67]), "+f"(d[68]), "+f"(d[69]), "+f"(d[70]), "+f"(d[71]),
          "+f"(d[72]), "+f"(d[73]), "+f"(d[74]), "+f"(d[75]), "+f"(d[76]), "+f"(d[77]), "+f"(d[78]), "+f"(d[79]),
          "+f"(d[80]), "+f"(d[81]), "+f"(d[82]), "+f"(d[83]), "+f"(d[84]), "+f"(d[85]), "+f"(d[86]), "+f"(d[87]),
          "+f"(d[88]), "+f"(d[89]), "+f"(d[90]), "+f"(d[91]), "+f"(d[92]), "+f"(d[93]), "+f"(d[94]), "+f"(d[95])
        : "r"(alo), "r"(blo), "r"(scale_d), "n"(TA), "n"(TB), "r"(DESC_HI));
}
template <int TA, int TB>
__device__ __forceinline__ void wgmma_ss_n8(float (&d)[4], uint32_t alo, uint32_t blo, int scale_d) {
    asm volatile("{\n.reg .pred p;\n.reg .b64 da, db;\nsetp.ne.b32 p, %6, 0;\n"
        "mov.b64 da, {%4, %9};\nmov.b64 db, {%5, %9};\n"
        "wgmma.mma_async.sync.aligned.m64n8k16.f32.bf16.bf16 "
        "{%0, %1, %2, %3}, da, db, p, 1, 1, %7, %8;\n}\n"
        :
          "+f"(d[0]), "+f"(d[1]), "+f"(d[2]), "+f"(d[3])
        : "r"(alo), "r"(blo), "r"(scale_d), "n"(TA), "n"(TB), "r"(DESC_HI));
}
template <int TB>
__device__ __forceinline__ void wgmma_rs_n128(float (&d)[64], uint32_t a0, uint32_t a1, uint32_t a2, uint32_t a3, uint32_t blo, int scale_d) {
    asm volatile("{\n.reg .pred p;\n.reg .b64 db;\nsetp.ne.b32 p, %69, 0;\n"
        "mov.b64 db, {%68, %71};\n"
        "wgmma.mma_async.sync.aligned.m64n128k16.f32.bf16.bf16 "
        "{%0, %1, %2, %3, %4, %5, %6, %7, %8, %9, %10, %11, %12, %13, %14, %15, %16, %17, %18, %19, %20, %21, %22, %23, %24, %25, %26, %27, %28, %29, %30, %31, %32, %33, %34, %35, %36, %37, %38, %39, %40, %41, %42, %43, %44, %45, %46, %47, %48, %49, %50, %51, %52, %53, %54, %55, %56, %57, %58, %59, %60, %61, %62, %63}, {%64, %65, %66, %67}, db, p, 1, 1, %70;\n}\n"
        :
          "+f"(d[0]), "+f"(d[1]), "+f"(d[2]), "+f"(d[3]), "+f"(d[4]), "+f"(d[5]), "+f"(d[6]), "+f"(d[7]),
          "+f"(d[8]), "+f"(d[9]), "+f"(d[10]), "+f"(d[11]), "+f"(d[12]), "+f"(d[13]), "+f"(d[14]), "+f"(d[15]),
          "+f"(d[16]), "+f"(d[17]), "+f"(d[18]), "+f"(d[19]), "+f"(d[20]), "+f"(d[21]), "+f"(d[22]), "+f"(d[23]),
          "+f"(d[24]), "+f"(d[25]), "+f"(d[26]), "+f"(d[27]), "+f"(d[28]), "+f"(d[29]), "+f"(d[30]), "+f"(d[31]),
          "+f"(d[32]), "+f"(d[33]), "+f"(d[34]), "+f"(d[35]), "+f"(d[36]), "+f"(d[37]), "+f"(d[38]), "+f"(d[39]),
          "+f"(d[40]), "+f"(d[41]), "+f"(d[42]), "+f"(d[43]), "+f"(d[44]), "+f"(d[45]), "+f"(d[46]), "+f"(d[47]),
          "+f"(d[48]), "+f"(d[49]), "+f"(d[50]), "+f"(d[51]), "+f"(d[52]), "+f"(d[53]), "+f"(d[54]), "+f"(d[55]),
          "+f"(d[56]), "+f"(d[57]), "+f"(d[58]), "+f"(d[59]), "+f"(d[60]), "+f"(d[61]), "+f"(d[62]), "+f"(d[63])
        : "r"(a0), "r"(a1), "r"(a2), "r"(a3), "r"(blo), "r"(scale_d), "n"(TB), "r"(DESC_HI));
}
template <int TB>
__device__ __forceinline__ void wgmma_rs_n128_z(float (&d)[64], uint32_t a0, uint32_t a1, uint32_t a2, uint32_t a3, uint32_t blo) {
    asm volatile("{\n.reg .pred p;\n.reg .b64 db;\nsetp.ne.b32 p, %69, 0;\n"
        "mov.b64 db, {%68, %71};\n"
        "wgmma.mma_async.sync.aligned.m64n128k16.f32.bf16.bf16 "
        "{%0, %1, %2, %3, %4, %5, %6, %7, %8, %9, %10, %11, %12, %13, %14, %15, %16, %17, %18, %19, %20, %21, %22, %23, %24, %25, %26, %27, %28, %29, %30, %31, %32, %33, %34, %35, %36, %37, %38, %39, %40, %41, %42, %43, %44, %45, %46, %47, %48, %49, %50, %51, %52, %53, %54, %55, %56, %57, %58, %59, %60, %61, %62, %63}, {%64, %65, %66, %67}, db, p, 1, 1, %70;\n}\n"
        :
          "=f"(d[0]), "=f"(d[1]), "=f"(d[2]), "=f"(d[3]), "=f"(d[4]), "=f"(d[5]), "=f"(d[6]), "=f"(d[7]),
          "=f"(d[8]), "=f"(d[9]), "=f"(d[10]), "=f"(d[11]), "=f"(d[12]), "=f"(d[13]), "=f"(d[14]), "=f"(d[15]),
          "=f"(d[16]), "=f"(d[17]), "=f"(d[18]), "=f"(d[19]), "=f"(d[20]), "=f"(d[21]), "=f"(d[22]), "=f"(d[23]),
          "=f"(d[24]), "=f"(d[25]), "=f"(d[26]), "=f"(d[27]), "=f"(d[28]), "=f"(d[29]), "=f"(d[30]), "=f"(d[31]),
          "=f"(d[32]), "=f"(d[33]), "=f"(d[34]), "=f"(d[35]), "=f"(d[36]), "=f"(d[37]), "=f"(d[38]), "=f"(d[39]),
          "=f"(d[40]), "=f"(d[41]), "=f"(d[42]), "=f"(d[43]), "=f"(d[44]), "=f"(d[45]), "=f"(d[46]), "=f"(d[47]),
          "=f"(d[48]), "=f"(d[49]), "=f"(d[50]), "=f"(d[51]), "=f"(d[52]), "=f"(d[53]), "=f"(d[54]), "=f"(d[55]),
          "=f"(d[56]), "=f"(d[57]), "=f"(d[58]), "=f"(d[59]), "=f"(d[60]), "=f"(d[61]), "=f"(d[62]), "=f"(d[63])
        : "r"(a0), "r"(a1), "r"(a2), "r"(a3), "r"(blo), "n"(0), "n"(TB), "r"(DESC_HI));
}
template <int TA, int TB>
__device__ __forceinline__ void wgmma_ss_n128_z(float (&d)[64], uint32_t alo, uint32_t blo) {
    asm volatile("{\n.reg .pred p;\n.reg .b64 da, db;\nsetp.ne.b32 p, %66, 0;\n"
        "mov.b64 da, {%64, %69};\nmov.b64 db, {%65, %69};\n"
        "wgmma.mma_async.sync.aligned.m64n128k16.f32.bf16.bf16 "
        "{%0, %1, %2, %3, %4, %5, %6, %7, %8, %9, %10, %11, %12, %13, %14, %15, %16, %17, %18, %19, %20, %21, %22, %23, %24, %25, %26, %27, %28, %29, %30, %31, %32, %33, %34, %35, %36, %37, %38, %39, %40, %41, %42, %43, %44, %45, %46, %47, %48, %49, %50, %51, %52, %53, %54, %55, %56, %57, %58, %59, %60, %61, %62, %63}, da, db, p, 1, 1, %67, %68;\n}\n"
        :
          "=f"(d[0]), "=f"(d[1]), "=f"(d[2]), "=f"(d[3]), "=f"(d[4]), "=f"(d[5]), "=f"(d[6]), "=f"(d[7]),
          "=f"(d[8]), "=f"(d[9]), "=f"(d[10]), "=f"(d[11]), "=f"(d[12]), "=f"(d[13]), "=f"(d[14]), "=f"(d[15]),
          "=f"(d[16]), "=f"(d[17]), "=f"(d[18]), "=f"(d[19]), "=f"(d[20]), "=f"(d[21]), "=f"(d[22]), "=f"(d[23]),
          "=f"(d[24]), "=f"(d[25]), "=f"(d[26]), "=f"(d[27]), "=f"(d[28]), "=f"(d[29]), "=f"(d[30]), "=f"(d[31]),
          "=f"(d[32]), "=f"(d[33]), "=f"(d[34]), "=f"(d[35]), "=f"(d[36]), "=f"(d[37]), "=f"(d[38]), "=f"(d[39]),
          "=f"(d[40]), "=f"(d[41]), "=f"(d[42]), "=f"(d[43]), "=f"(d[44]), "=f"(d[45]), "=f"(d[46]), "=f"(d[47]),
          "=f"(d[48]), "=f"(d[49]), "=f"(d[50]), "=f"(d[51]), "=f"(d[52]), "=f"(d[53]), "=f"(d[54]), "=f"(d[55]),
          "=f"(d[56]), "=f"(d[57]), "=f"(d[58]), "=f"(d[59]), "=f"(d[60]), "=f"(d[61]), "=f"(d[62]), "=f"(d[63])
        : "r"(alo), "r"(blo), "n"(0), "n"(TA), "n"(TB), "r"(DESC_HI));
}

__device__ __forceinline__ uint32_t pack_bf16(float lo, float hi) {
    uint32_t r;
    asm("cvt.rn.bf16x2.f32 %0, %1, %2;" : "=r"(r) : "f"(hi), "f"(lo));
    return r;
}
__device__ __forceinline__ uint32_t add_bf16x2(uint32_t a, uint32_t b) {
    uint32_t r;
    asm("add.rn.bf16x2 %0, %1, %2;" : "=r"(r) : "r"(a), "r"(b));
    return r;
}
__device__ __forceinline__ float bf_lo(uint32_t v) { return __uint_as_float(v << 16); }
__device__ __forceinline__ float bf_hi(uint32_t v) { return __uint_as_float(v & 0xffff0000u); }
__device__ __forceinline__ float round_bf16(float v) { return __bfloat162float(__float2bfloat16_rn(v)); }
__device__ __forceinline__ float ex2(float x) {
    float y;
    asm("ex2.approx.ftz.f32 %0, %1;" : "=f"(y) : "f"(x));
    return y;
}
__device__ __forceinline__ float rcp(float x) {
    float y;
    asm("rcp.approx.ftz.f32 %0, %1;" : "=f"(y) : "f"(x));
    return y;
}
__device__ __forceinline__ void stg128(void* p, uint32_t a, uint32_t b, uint32_t c, uint32_t d) {
    asm volatile("st.global.v4.b32 [%0], {%1, %2, %3, %4};" ::"l"(p), "r"(a), "r"(b), "r"(c), "r"(d) : "memory");
}
__device__ __forceinline__ void stg128p(void* p, uint32_t a, uint32_t b, uint32_t c, uint32_t d, uint64_t pol) {
    asm volatile("st.global.L2::cache_hint.v4.b32 [%0], {%1, %2, %3, %4}, %5;" ::"l"(p), "r"(a), "r"(b), "r"(c), "r"(d), "l"(pol) : "memory");
}
__device__ __forceinline__ uint64_t policy_sel(bool first) {
    uint64_t p;
    asm("createpolicy.fractional.L2::evict_normal.b64 %0, 1.0;" : "=l"(p));
    return first ? policy_evict_first() : p;
}
__device__ __forceinline__ int perm_row(int t) { return (t & ~255) | (((0x78 >> (((t >> 6) & 3) * 2)) & 3) << 6) | (t & 63); }
__device__ __forceinline__ int unperm_row(int t) { return (t & ~255) | (((0x9C >> (((t >> 6) & 3) * 2)) & 3) << 6) | (t & 63); }

#define PROF(i)
#define PROFG(i)
#define PROFDUMP()
#define TR(i)
#define BP(r, i)
#define LP(i)

template <int I>
__device__ __forceinline__ void store_chunk(const float (&a)[64], __nv_bfloat16* row0, __nv_bfloat16* row1, float s0, float s1, uint64_t pol) {
    stg128p(row0 + 32 * I, pack_bf16(a[16 * I + 0] * s0, a[16 * I + 1] * s0), pack_bf16(a[16 * I + 4] * s0, a[16 * I + 5] * s0),
           pack_bf16(a[16 * I + 8] * s0, a[16 * I + 9] * s0), pack_bf16(a[16 * I + 12] * s0, a[16 * I + 13] * s0), pol);
    stg128p(row1 + 32 * I, pack_bf16(a[16 * I + 2] * s1, a[16 * I + 3] * s1), pack_bf16(a[16 * I + 6] * s1, a[16 * I + 7] * s1),
           pack_bf16(a[16 * I + 10] * s1, a[16 * I + 11] * s1), pack_bf16(a[16 * I + 14] * s1, a[16 * I + 15] * s1), pol);
}
template <int I>
struct IntT { static constexpr int value = I; };
template <class F>
__device__ __forceinline__ void for4(F f) { f(IntT<0>{}); f(IntT<1>{}); f(IntT<2>{}); f(IntT<3>{}); }

struct Prod {
    uint32_t smem, bars;
    uint32_t bo, par;
    uint32_t dst, fb;
    __device__ __forceinline__ void acquire(uint32_t o, uint32_t parity, uint32_t bytes) {
        mbar_wait(bars + BAR_EMPTY + o, parity);
        fb = bars + BAR_FULL + o;
        dst = smem + o * (SLOT / 8);
        w_expect_tx(fb, bytes);
    }
    __device__ __forceinline__ void next(uint32_t bytes) {
        acquire(bo, par, bytes);
        const bool wrap = bo == (NSLOT - 1) * 8;
        bo = wrap ? 0u : bo + 8;
        par ^= wrap ? 1u : 0u;
    }
};

__device__ __forceinline__ int item_p(int ca, int rd) {
    const int v = (rd & 1) ? (ca + 4) & 7 : ca;
    return (rd & 2) ? 7 - v : v;
}
__device__ __forceinline__ int n_items(int ca, int cb) { return cb == 8 ? (OFFLOAD ? 8 : 0) : (OFFLOAD && (ca & 3) == 3) ? 3 : 4; }
__device__ __forceinline__ int item_rd(int ca, int cb, int j) { return cb == 8 ? 2 + ca : (OFFLOAD && ca == 7 && j == 2) ? 3 : j; }
__device__ __forceinline__ int item_h(int cb, int rd, int j) { return 8 * rd + (cb == 8 ? j : cb); }
__device__ __forceinline__ int item_q(int ca, int cb, int rd) { return cb == 8 ? 0 : item_p(ca, rd); }
__device__ __forceinline__ int out_p(int ca, int cb) { return (cb + 2 * (ca & 3)) & 7; }
__device__ __forceinline__ int kv_round(int i) { return (KVORDER >> (4 * i)) & 3; }
__device__ __forceinline__ int slot_a(int i) { return (0x5310 >> (4 * i)) & 15; }
__device__ __forceinline__ int slot_w(int m) { return (0x264 >> (4 * m)) & 15; }

__device__ __forceinline__ void producer(const Params& P, uint32_t smem, uint32_t bars, int ca, int cb, int rank) {
    Prod pr{smem, bars, 0u, cb == 8 ? 1u : 0u, 0u, 0u};
    if (cb < 8) {
        int m = 0;
        uint32_t lap = 1;
#pragma unroll 1
        for (int u = 0; u < 32; u++) {
            if (u >= 3) {
                const int v = (u == 3) ? 3 + ca : u + 7;
                if (v < 32 && (u == 3 || (v & 7) == ca)) w_tma_prefetch((v & 4) ? &P.wuv : &P.wuk, (cb + 8 * kv_round(v >> 3)) * 128 + rank * 64, (v & 3) * 128);
                if (u == 24) {
                    w_tma_prefetch(&P.wq, cb * 128 + rank * 64, ca * 64);
                    if (ca < 2) w_tma_prefetch(&P.wq, cb * 128 + rank * 64, (ca + 8) * 64);
                }
            }
            if (u >= FASTSTART) pr.acquire(slot_w(m) * 8, lap ^ (m >> 1), SLOT);
            lap ^= m >> 1;
            m = (m == 2) ? 0 : m + 1;
            TR(1 + u);
            if (u >= FASTSTART) w_tma_load_mc(pr.dst + rank * 16384, (u & 4) ? &P.wuv : &P.wuk, (cb + 8 * kv_round(u >> 3)) * 128 + rank * 64, (u & 3) * 128, pr.fb);
            if (u < 3 && u + 1 >= FASTSTART) {
                pr.acquire(slot_a(u + 1) * 8, 1, SLOT);
                w_tma_load(pr.dst, &P.ckv, u * 128 + 128, (2 * ca + rank) * 128, pr.fb);
                w_tma_load(pr.dst + 16384, &P.ckv, u * 128 + 192, (2 * ca + rank) * 128, pr.fb);
            }
        }
    }
    PROF(1);
    mbar_wait_sleep(bars + BAR_DEP, 0);
#pragma unroll 1
    for (int j = 0, pfs = 1; j < n_items(ca, cb); j++) {
        const int rd = item_rd(ca, cb, j), h = item_h(cb, rd, j), p = item_q(ca, cb, rd);
#pragma unroll 1
        for (int ks = 0; ks < 10; ks++) {
            pr.next(SLOT);
            w_tma_load_mc(pr.dst + 16384 + rank * 8192, &P.wq, h * 128 + rank * 64, ks * 64, pr.fb);
            w_tma_load(pr.dst, &P.xn, ks * 64, 256 * p + 128 * rank, pr.fb);
            if (cb == 8 && j < 7) w_tma_prefetch(&P.wq, (h + 1) * 128 + rank * 64, ks * 64);
        }
        PROF(8 + rd * 4);
        mbar_wait(bars + BAR_DEP + (1 + (cb == 8 ? j : rd)) * 8, 0);
        const int last = 4 * p + 3, top = h * 32 + last;
#pragma unroll 1
        for (int i = 0; i <= last; i++) {
            const int t = (i == 0) ? top - 1 : (i == last) ? h * 32 + 1 : (i & 1) ? top - 2 - i : top + 2 - i;
            pr.next(SLOT);
            const bool lastrd = (cb == 8) ? false : (rd == 0) ? ((LASTRD & 1) && ca >= 8 - LASTN) : (rd == 1) ? ((LASTRD & 2) && (ca & 3) >= 4 - LASTN) : (rd == 2) ? ((LASTRD & 4) && (ca == 3 || (ca < 3 && (t & 31) >= 4 * p))) : (LASTRD & 8) != 0;
            if (lastrd) w_tma_load_mc_last(pr.dst + rank * 16384, &P.kv, rank * 64, t * 128, pr.fb);
            else w_tma_load_mc(pr.dst + rank * 16384, &P.kv, rank * 64, t * 128, pr.fb);
            if (i == 2 && cb < 8) {
                const int upto = (j == n_items(ca, cb) - 1) ? 4 : item_rd(ca, cb, j + 1);
#pragma unroll 1
                for (; pfs <= upto; pfs++) {
                    if (pfs < 4) {
                        w_tma_prefetch(&P.wq, (8 * pfs + cb) * 128 + rank * 64, ca * 64);
                        if (ca < 2) w_tma_prefetch(&P.wq, (8 * pfs + cb) * 128 + rank * 64, (ca + 8) * 64);
                    } else {
#pragma unroll 1
                        for (int k = 0; k < 10; k++)
                            w_tma_prefetch(&P.wo, 320 * (ca >> 2) + 64 * (k >= 5 ? k - 5 : k), (cb * 4 + (ca & 3) + (k >= 5 ? 32 : 0)) * 64 + rank * 32);
                    }
                }
            }
        }
        PROF(9 + rd * 4);
    }
    if (cb < 8) {
        const int n0 = 320 * (ca >> 2), op = out_p(ca, cb);
        uint32_t* pool = g_flags + (F_POOL + op * 2 + (ca >> 2)) * 8;
        uint32_t base, nxt = 0;
        asm volatile("ld.shared.u32 %0, [%1];" : "=r"(base) : "r"(bars + MISC_OFF) : "memory");
        base *= NPOOL + 4;
        auto draw = [&]() {
            if (NPOOL && rank == 0) asm volatile(ELECT "atom.relaxed.gpu.global.add.u32 %0, [%1], 1;\n}\n" : "+r"(nxt) : "l"(pool) : "memory");
        };
        draw();
        int fixed = NPOOL ? -1 : 0;
#pragma unroll 1
        for (int i = 0; fixed < (64 - NPOOL) / 4; i++) {
            int st;
            if (fixed < 0) {
                const uint32_t mb = bars + BAR_MAIL + (i & 7) * 8, md = bars + MAIL_OFF + (i & 7) * 4;
                if (rank == 0) {
                    st = __reduce_add_sync(0xffffffffu, nxt) - base;
                    asm volatile(ELECT "st.async.shared::cluster.mbarrier::complete_tx::bytes.b32 [%0], %1, [%2];\n}\n" ::"r"(mapa(md, 1)), "r"(st), "r"(mapa(mb, 1)) : "memory");
                    if (st < NPOOL) draw();
                } else {
                    w_expect_tx(mb, 4);
                    mbar_wait(mb, (i >> 3) & 1);
                    asm volatile("ld.shared.u32 %0, [%1];" : "=r"(st) : "r"(md) : "memory");
                    st = __reduce_or_sync(0xffffffffu, st);
                }
                if (st >= NPOOL) fixed = 0;
            }
            if (fixed >= 0) { st = NPOOL + (ca & 3) + 4 * fixed; fixed++; }
            const int krow = st * 64 + rank * 32;
            mbar_wait(bars + BAR_EMPTY + pr.bo, pr.par);
            asm volatile("st.shared.u32 [%0], %1;" ::"r"(bars + CTL_OFF + pr.bo), "r"((int)(fixed == (64 - NPOOL) / 4 - 3)) : "memory");
            __syncwarp();
            pr.next(SLOT);
            w_tma_load_mc(pr.dst + 16384 + rank * 8192, &P.wo, n0, krow, pr.fb);
            w_tma_load_mc(pr.dst + 16384 + rank * 8192 + 4096, &P.wo, n0 + 64, krow, pr.fb);
            mbar_wait(bars + BAR_DEP + (5 + (st >> 4)) * 8, 0);
            w_tma_load(pr.dst, &P.ctx, (st & 1) * 64, (st >> 1) * SEQ + 256 * op + 128 * rank, pr.fb);
            pr.next(24576);
#pragma unroll
            for (int c = 0; c < 3; c++) w_tma_load_mc(pr.dst + rank * 12288 + c * 4096, &P.wo, n0 + 128 + 64 * c, krow, pr.fb);
        }
    }
}

struct Slot {
    uint32_t bo, dl, par;
};
struct Cons {
    uint32_t bars, rel;
    uint32_t dl0;
    uint32_t lane;
    Slot cur;
    __device__ __forceinline__ Slot slot(int s, uint32_t par) const { return Slot{(uint32_t)s * 8, dl0 + (uint32_t)s * (SLOT >> 4), par}; }
    __device__ __forceinline__ void wait(const Slot& s) const { mbar_wait(bars + BAR_FULL + s.bo, s.par); }
    __device__ __forceinline__ void release(uint32_t bo) const {
        asm volatile("{\n.reg .pred p;\nsetp.lt.u32 p, %1, 2;\n@p mbarrier.arrive.shared::cluster.b64 _, [%0];\n}\n" ::"r"(rel + bo), "r"(lane) : "memory");
    }
    __device__ __forceinline__ Slot next() {
        const Slot s = cur;
        const bool wrap = s.bo == (NSLOT - 1) * 8;
        cur.bo = wrap ? 0u : s.bo + 8;
        cur.dl = wrap ? dl0 : s.dl + (SLOT >> 4);
        cur.par = s.par ^ (wrap ? 1u : 0u);
        return s;
    }
};
__host__ __device__ constexpr uint32_t lbo(uint32_t bytes) { return (bytes >> 4) << 16; }

__device__ __forceinline__ float div640(float x) {
    const float q = x * (1.0f / DM);
    return fmaf(fmaf(-q, (float)DM, x), 1.0f / DM, q);
}
__device__ __forceinline__ float sqrt_approx(float x) {
    float y;
    asm("sqrt.approx.ftz.f32 %0, %1;" : "=f"(y) : "f"(x));
    return y;
}
struct LayerNorm {
    uint4 xv[5], wv[5];
    float mean, inv, r;
    static __device__ __forceinline__ float half_sum(float v) {
#pragma unroll
        for (int o = 8; o > 0; o >>= 1) v += __shfl_xor_sync(0xffffffffu, v, o);
        return v;
    }
    __device__ __forceinline__ void load(const __nv_bfloat16* x, const __nv_bfloat16* wr, int t, int l) {
#pragma unroll
        for (int i = 0; i < 5; i++) {
            xv[i] = ldg_stream(reinterpret_cast<const uint4*>(x + t * DM) + l + 16 * i);
            wv[i] = __ldg(reinterpret_cast<const uint4*>(wr) + l + 16 * i);
        }
    }
    __device__ __forceinline__ void stat1() {
        float a[4] = {0.f, 0.f, 0.f, 0.f};
#pragma unroll
        for (int i = 0; i < 20; i++) { const uint32_t u = (&xv[i >> 2].x)[i & 3]; a[i & 3] += bf_lo(u) + bf_hi(u); }
        mean = div640(half_sum((a[0] + a[1]) + (a[2] + a[3])));
        r = 0.f;
    }
    template <int H>
    __device__ __forceinline__ void stat2() {
        float a[4] = {r, 0.f, 0.f, 0.f};
#pragma unroll
        for (int i = H ? 12 : 0; i < (H ? 20 : 12); i++) {
            uint32_t u = (&xv[i >> 2].x)[i & 3];
            asm volatile("" : "+r"(u));
            const float d0 = bf_lo(u) - mean, d1 = bf_hi(u) - mean;
            a[i & 3] = fmaf(d0, d0, fmaf(d1, d1, a[i & 3]));
        }
        r = (a[0] + a[1]) + (a[2] + a[3]);
        if (H) {
            inv = rcp(round_bf16(sqrt_approx(round_bf16(round_bf16(div640(half_sum(r))) + 1e-5f))));
            r = 0.f;
        }
    }
    template <int I>
    __device__ __forceinline__ void piece(__nv_bfloat16* out, int t, int l) {
        const uint32_t nmb = pack_bf16(-mean, -mean);
        uint32_t o[4], z[4];
        float a[4];
#pragma unroll
        for (int j = 0; j < 4; j++) {
            const uint32_t u = (&xv[I].x)[j], w = (&wv[I].x)[j];
            const uint32_t d = add_bf16x2(u, nmb);
            o[j] = pack_bf16(bf_lo(d) * inv, bf_hi(d) * inv);
            z[j] = add_bf16x2(u, o[j]);
            a[j] = fmaf(bf_hi(o[j]), bf_hi(w), bf_lo(o[j]) * bf_lo(w));
        }
        r += (a[0] + a[1]) + (a[2] + a[3]);
        stg128(g_xn + perm_row(t) * DM + 8 * (l + 16 * I), o[0], o[1], o[2], o[3]);
        stg128p(out + t * DM + 8 * (l + 16 * I), z[0], z[1], z[2], z[3], policy_sel(EFMASK & 1));
        if (I == 4) {
            r = half_sum(r);
            if (l == 0) g_r[t] = round_bf16(r);
        }
    }
};

constexpr float SM_SCALE = 0.08838834764831845f * 1.4426950408889634f;

template <int J0, int J1>
__device__ __forceinline__ void exp_part(float (&s)[64], float n0, float n1, float& r0, float& r1) {
    float a1 = 0.f, b1 = 0.f;
#pragma unroll
    for (int j = J0; j < J1; j++) {
        s[4 * j + 0] = ex2(fmaf(s[4 * j + 0], SM_SCALE, n0));
        s[4 * j + 1] = ex2(fmaf(s[4 * j + 1], SM_SCALE, n0));
        s[4 * j + 2] = ex2(fmaf(s[4 * j + 2], SM_SCALE, n1));
        s[4 * j + 3] = ex2(fmaf(s[4 * j + 3], SM_SCALE, n1));
        r0 += s[4 * j + 0]; r1 += s[4 * j + 2];
        if (j == J0) { a1 = s[4 * j + 1]; b1 = s[4 * j + 3]; } else { a1 += s[4 * j + 1]; b1 += s[4 * j + 3]; }
    }
    r0 += a1;
    r1 += b1;
}
__device__ __forceinline__ void sched_barrier(float x, float y, uint32_t scratch) {
    asm volatile("{\n.reg .pred p;\nsetp.lt.f32 p, %0, 0f00000000;\n@p st.shared.f32 [%2], %1;\n}\n" ::"f"(x), "f"(y), "r"(scratch) : "memory");
}
__device__ __forceinline__ void pack_tile(const float (&s)[64], uint32_t (&p)[32]) {
#pragma unroll
    for (int i = 0; i < 32; i++) p[i] = pack_bf16(s[2 * i], s[2 * i + 1]);
}
template <bool ZERO>
__device__ __forceinline__ void gemm_rs(float (&d)[64], const uint32_t (&a)[32], uint32_t dl, int acc = 1) {
    const uint32_t b = dl + lbo(16384);
    if (ZERO) wgmma_rs_n128_z<1>(d, a[0], a[1], a[2], a[3], b);
#pragma unroll
    for (int k = ZERO ? 1 : 0; k < 8; k++) wgmma_rs_n128<1>(d, a[4 * k], a[4 * k + 1], a[4 * k + 2], a[4 * k + 3], b + k * 128, k ? 1 : acc);
}
template <int ZERO>
__device__ __forceinline__ void gemm_q(float (&d)[64], uint32_t dl, int role) {
    const uint32_t a = dl + role * 512 + lbo(16), b = dl + 1024 + lbo(8192);
    if (ZERO) wgmma_ss_n128_z<0, 1>(d, a, b);
#pragma unroll
    for (int k = ZERO ? 1 : 0; k < 4; k++) wgmma_ss_n128<0, 1>(d, a + k * 2, b + k * 128, 1);
}
template <bool KT, bool ZERO, int K0, int K1>
__device__ __forceinline__ void gemm_kv(float (&d)[64], uint32_t ckv, uint32_t wt, int wg) {
    if (KT) {
        const uint32_t a = wt + wg * 1024 + lbo(16), b = ckv + lbo(16);
        if (ZERO) wgmma_ss_n128_z<1, 0>(d, a, b);
#pragma unroll
        for (int k = ZERO ? 1 : K0; k < K1; k++) wgmma_ss_n128<1, 0>(d, a + k * 128, b + (k >> 2) * 1024 + (k & 3) * 2, 1);
    } else {
        const uint32_t a = ckv + wg * 512 + lbo(16), b = wt + lbo(16384);
        if (ZERO) wgmma_ss_n128_z<0, 1>(d, a, b);
#pragma unroll
        for (int k = ZERO ? 1 : K0; k < K1; k++) wgmma_ss_n128<0, 1>(d, a + (k >> 2) * 1024 + (k & 3) * 2, b + k * 128, 1);
    }
}
__device__ __forceinline__ void mma16816(float& d0, float& d1, float& d2, float& d3, uint32_t a0, uint32_t a1, uint32_t a2, uint32_t a3, uint32_t b0, uint32_t b1) {
    asm volatile("mma.sync.aligned.m16n8k16.row.col.f32.bf16.bf16.f32 {%0,%1,%2,%3}, {%4,%5,%6,%7}, {%8,%9}, {%0,%1,%2,%3};"
                 : "+f"(d0), "+f"(d1), "+f"(d2), "+f"(d3) : "r"(a0), "r"(a1), "r"(a2), "r"(a3), "r"(b0), "r"(b1));
}
__device__ __forceinline__ uint32_t ld_pair(const __nv_bfloat16* p) {
    const unsigned short* u = reinterpret_cast<const unsigned short*>(p);
    return (uint32_t)__ldcg(u) | ((uint32_t)__ldcg(u + 128) << 16);
}
__device__ __forceinline__ void attention_exact(float (&o)[64], const uint32_t (&qf)[32], float& l0, float& l1, int h, int nblk, int rr, int lane) {
    const int q = lane & 3, lr = lane >> 2;
    float m0 = -INFINITY, m1 = -INFINITY;
    l0 = 0.f; l1 = 0.f;
#pragma unroll
    for (int i = 0; i < 64; i++) o[i] = 0.f;
#pragma unroll 1
    for (int cidx = 0; cidx < nblk * 8; cidx++) {
        const int kc = cidx & 7;
        const __nv_bfloat16* kt = g_kv + (size_t)((h * 16 + (cidx >> 3)) * 2) * 16384;
        float sc[8];
#pragma unroll
        for (int i = 0; i < 8; i++) sc[i] = 0.f;
#pragma unroll
        for (int kk = 0; kk < 8; kk++)
#pragma unroll
            for (int nt = 0; nt < 2; nt++) {
                const __nv_bfloat16* b = kt + (16 * kk + 2 * q) * 128 + 16 * kc + 8 * nt + lr;
                mma16816(sc[4 * nt], sc[4 * nt + 1], sc[4 * nt + 2], sc[4 * nt + 3], qf[4 * kk], qf[4 * kk + 1], qf[4 * kk + 2], qf[4 * kk + 3],
                         ld_pair(b), ld_pair(b + 8 * 128));
            }
        const int lim = rr + ((nblk - 1) - (cidx >> 3)) * 128 - 32 * (kc >> 1) - 4 * (kc & 1);
#pragma unroll
        for (int i = 0; i < 8; i++)
            if (2 * (i >> 2) + (i & 1) > lim + 4 * (i & 2)) sc[i] = -INFINITY;
        float x0 = fmaxf(fmaxf(sc[0], sc[1]), fmaxf(sc[4], sc[5])), x1 = fmaxf(fmaxf(sc[2], sc[3]), fmaxf(sc[6], sc[7]));
        x0 = fmaxf(x0, __shfl_xor_sync(0xffffffffu, x0, 1)); x1 = fmaxf(x1, __shfl_xor_sync(0xffffffffu, x1, 1));
        x0 = fmaxf(x0, __shfl_xor_sync(0xffffffffu, x0, 2)); x1 = fmaxf(x1, __shfl_xor_sync(0xffffffffu, x1, 2));
        x0 = fmaxf(x0, m0); x1 = fmaxf(x1, m1);
        const float a0 = ex2((m0 - x0) * SM_SCALE), a1 = ex2((m1 - x1) * SM_SCALE);
        m0 = x0; m1 = x1;
#pragma unroll
        for (int i = 0; i < 8; i++) sc[i] = ex2((sc[i] - ((i & 2) ? m1 : m0)) * SM_SCALE);
        l0 = l0 * a0 + (sc[0] + sc[1]) + (sc[4] + sc[5]);
        l1 = l1 * a1 + (sc[2] + sc[3]) + (sc[6] + sc[7]);
        const uint32_t p0 = pack_bf16(sc[0], sc[1]), p1 = pack_bf16(sc[2], sc[3]), p2 = pack_bf16(sc[4], sc[5]), p3 = pack_bf16(sc[6], sc[7]);
        const __nv_bfloat16* vb = kt + 16384 + (16 * kc + 2 * q) * 128 + lr;
#pragma unroll
        for (int nt = 0; nt < 16; nt++) {
            o[4 * nt] *= a0; o[4 * nt + 1] *= a0; o[4 * nt + 2] *= a1; o[4 * nt + 3] *= a1;
            mma16816(o[4 * nt], o[4 * nt + 1], o[4 * nt + 2], o[4 * nt + 3], p0, p1, p2, p3, ld_pair(vb + 8 * nt), ld_pair(vb + 8 * nt + 8 * 128));
        }
    }
}

__device__ __forceinline__ void signal(uint32_t bars, int wg, int e, int lane) {
    __syncwarp();
    asm volatile("{\n.reg .pred p;\nsetp.eq.u32 p, %1, 0;\n@p mbarrier.arrive.shared::cta.b64 _, [%0];\n}\n" ::"r"(bars + BAR_SIG + (wg * 9 + e) * 8), "r"(lane) : "memory");
}

__device__ __forceinline__ void mod_ffn(const Params& P, uint32_t smem, int mc, int wg);

__device__ __forceinline__ void consumer(const Params& P, uint32_t smem, uint32_t bars, int ca, int cb, int rank, int wg) {
    const int lane = threadIdx.x & 31, w = (threadIdx.x >> 5) & 3, q = lane & 3, lr = lane >> 2;
    PROF(7);
    cluster_wait();
    Cons c{bars, mapa(bars + BAR_EMPTY, lane & 1), (smem & 0x3FFFF) >> 4, (uint32_t)lane, Slot{0u, (smem & 0x3FFFF) >> 4, cb == 8 ? 0u : 1u}};
    PROFG(180);
    PROF(1);
    float o[64], s[64];
    uint32_t pend;
    __nv_bfloat16* ep_ptr;
    int ep_step;
    if (cb == 8) {
        pend = 0;
        ep_ptr = g_ctx + (size_t)(item_h(cb, 2 + ca, 0) * SEQ + 128 * rank + 64 * wg + 16 * w + lr) * HD + 8 * q;
        ep_step = 8 * HD;
    } else {
        const int ln_t = blockIdx.x * 16 + wg * 8 + w * 2 + (lane >> 4);
        const int krow = 64 * wg + 16 * w + lr;
        const int vrow = 64 * wg + 32 * (w >> 1) + 8 * (lr >> 1) + 4 * (w & 1) + (lr & 1);
        ep_step = 2 * 128;
        int m = 0;
        uint32_t lap = 0;
        LayerNorm ln;
        auto step = [&](auto kt, auto kc, float (&d)[64], int hh) {
            const Slot sa = c.slot(slot_a(kc.value), 0), sw = c.slot(slot_w(m), lap ^ (m >> 1));
            lap ^= m >> 1;
            m = (m == 2) ? 0 : m + 1;
            TR(1 + (hh * 8 + (kt.value ? 0 : 4) + kc.value) * 2);
            if (kt.value && hh == 0) c.wait(sa);
            c.wait(sw);
            TR(2 + (hh * 8 + (kt.value ? 0 : 4) + kc.value) * 2);
            wgmma_fence();
            gemm_kv<kt.value, kc.value == 0, 0, KVSPLIT>(d, sa.dl, sw.dl, wg);
            wgmma_commit();
            wgmma_wait<1>();
            if (!(kt.value && kc.value == 0 && hh == 0)) c.release(pend);
            if (!kt.value && kc.value > 0 && hh == 3) c.release(slot_a(kc.value - 1) * 8);
            pend = sw.bo;
            wgmma_fence();
            gemm_kv<kt.value, false, KVSPLIT, 8>(d, sa.dl, sw.dl, wg);
            wgmma_commit();
        };
#pragma unroll 1
        for (int hh = 0; hh < 4; hh++) {
            __nv_bfloat16* base = g_kv + (size_t)(((cb + 8 * kv_round(hh)) * 16 + 2 * ca + rank) * 2) * 16384 + 8 * q;
            auto ln_stage = [&](auto pos) {
                constexpr int j = (pos.value + 8 - LNOFF % 8) % 8;
                if (hh == wg * LNSTAG + (LNOFF + j) / 8) {
                    if (j == 0) ln.stat1();
                    if (j == 1) ln.template stat2<0>();
                    if (j == 2) ln.template stat2<1>();
                    if constexpr (j >= 3) ln.template piece<j - 3>(P.out, ln_t, lane & 15);
                    if (j == 7) signal(bars, wg, 0, lane);
                }
                if (pos.value == (LNOFF - LNLEAD) % 8 && hh == wg * LNSTAG + (LNOFF - LNLEAD) / 8) ln.load(P.x, P.wr, ln_t, lane & 15);
            };
            for4([&](auto kc) {
                step(TrueT{}, kc, s, hh);
                if (hh > 0) {
                    if (kc.value == 0) fence_regs(o);
                    store_chunk<kc.value>(o, ep_ptr, ep_ptr + ep_step, 1.f, 1.f, policy_sel(false));
                    if (kc.value == 3) signal(bars, wg, hh, lane);
                }
                ln_stage(kc);
            });
            for4([&](auto kc) {
                step(FalseT{}, kc, o, hh);
                if (kc.value == 0) fence_regs(s);
                store_chunk<kc.value>(s, base + krow * 128, base + (krow + 8) * 128, 1.f, 1.f, policy_sel(false));
                ln_stage(IntT<kc.value + 4>{});
            });
            PROF(24 + hh);
            if (hh == 1) PROFG(181);
            ep_ptr = base + 16384 + vrow * 128;
        }
    }
    PROFG(182);
    PROF(2);
    uint32_t pf[32];
    {
        uint32_t qf[32];
        float l0 = 0.25f, l1 = 0.25f;
        const int bar_me = 2 + wg, bar_other = 3 - wg;
#pragma unroll 1
        for (int j = 0; j < n_items(ca, cb); j++) {
            const int rd = item_rd(ca, cb, j), h = item_h(cb, rd, j), p = item_q(ca, cb, rd);
            const int role = wg ^ (j & 1);
            const int nrest = 2 * p + role;
            Slot kfirst;
            const int lim = 64 * (role ^ rank) + 16 * w + lr - 8 * q;
            const uint64_t pol = policy_sel(((EFMASK & 4) && j == 1) || ((EFMASK & 8) && j == 2));
            {
                auto qstep = [&](auto zero, int ks) {
                    const Slot sl = c.next();
                    c.wait(sl);
                    BP(2, 5 + 3 * ks);
                    wgmma_fence();
                    gemm_q<zero.value>(s, sl.dl, role);
                    wgmma_commit();
                    wgmma_wait<1>();
                    if (!zero.value || j > 0 || cb < 8) c.release(pend);
                    pend = sl.bo;
                };
                qstep(TrueT{}, 0);
                if (j == 0 && cb < 8) c.release(slot_a(3) * 8);
                fence_regs(o);
                l0 += __shfl_xor_sync(0xffffffffu, l0, 1); l1 += __shfl_xor_sync(0xffffffffu, l1, 1);
                l0 += __shfl_xor_sync(0xffffffffu, l0, 2); l1 += __shfl_xor_sync(0xffffffffu, l1, 2);
                l0 = rcp(l0); l1 = rcp(l1);
                for4([&](auto i) {
                    constexpr int B = 16 * i.value;
#pragma unroll
                    for (int r = 0; r < 2; r++) {
                        qstep(FalseT{}, 1 + 2 * i.value + r);
                        const float f = r ? l1 : l0;
                        stg128p(ep_ptr + r * ep_step + 2 * B, pack_bf16(o[B + 2 * r] * f, o[B + 2 * r + 1] * f), pack_bf16(o[B + 2 * r + 4] * f, o[B + 2 * r + 5] * f),
                                pack_bf16(o[B + 2 * r + 8] * f, o[B + 2 * r + 9] * f), pack_bf16(o[B + 2 * r + 12] * f, o[B + 2 * r + 13] * f), pol);
#pragma unroll
                        for (int k = 0; k < 8; k++) {
                            float& v = o[B + 4 * (k >> 1) + 2 * r + (k & 1)];
                            v = (2 * B + k > lim + 8 * r) ? -1e30f : 0.f;
                            asm volatile("" : "+f"(v));
                        }
                    }
                });
                signal(bars, wg, (cb == 8 ? 0 : 4) + j, lane);
                PROF(11 + rd * 4);
                qstep(FalseT{}, 9);
                if (!role) { const Slot sl = c.next(); c.wait(sl); c.release(sl.bo); }
                kfirst = c.next();
                c.wait(kfirst);
                wgmma_wait<0>();
                BP(2, 34);
                c.release(pend);
                fence_regs(s);
                pack_tile(s, qf);
            }
            PROF(8 + rd * 4);
            fence_regs(qf); fence_regs(o);
            if (PINGPONG && !role) named_sync(bar_me, 256);
            BP(2, 36);
            wgmma_fence();
            gemm_rs<false>(o, qf, kfirst.dl);
            wgmma_commit();
            if (PINGPONG) named_arrive(bar_other, 256);
            if (!role) { const Slot sl = c.next(); c.wait(sl); c.release(sl.bo); }
            wgmma_wait<0>();
            BP(2, 38);
            fence_regs(o);
            c.release(kfirst.bo);
            float n0 = fmaxf(fmaxf(fmaxf(o[0], o[1]), fmaxf(o[4], o[5])), fmaxf(fmaxf(o[8], o[9]), fmaxf(o[12], o[13])));
            float n1 = fmaxf(fmaxf(fmaxf(o[2], o[3]), fmaxf(o[6], o[7])), fmaxf(fmaxf(o[10], o[11]), fmaxf(o[14], o[15])));
            n0 = __shfl_sync(0xffffffffu, n0, lane & 28); n1 = __shfl_sync(0xffffffffu, n1, lane & 28);
            n0 *= -SM_SCALE; n1 *= -SM_SCALE;
            l0 = 0.f; l1 = 0.f;
#pragma unroll
            for (int i = 0; i < 64; i++) s[i] = o[i];
            exp_part<0, 8>(s, n0, n1, l0, l1);
#pragma unroll
            for (int i = 0; i < 16; i++) pf[i] = pack_bf16(s[2 * i], s[2 * i + 1]);
            if (role != rank) {
                exp_part<8, 16>(s, n0, n1, l0, l1);
#pragma unroll
                for (int i = 16; i < 32; i++) pf[i] = pack_bf16(s[2 * i], s[2 * i + 1]);
            } else {
#pragma unroll
                for (int i = 16; i < 32; i++) pf[i] = 0u;
            }
            PROF(9 + rd * 4);
#pragma unroll 1
            for (int it = 0; it < nrest; it++) {
                const Slot sk = c.next(), sv = c.next();
                LP(0);
                c.wait(sk);
                c.wait(sv);
                fence_regs(o); fence_regs(pf);
                LP(1);
                if (PINGPONG) named_sync(bar_me, 256);
                LP(2);
                if (it < 3) BP(2, 42 + 4 * it);
                if (it >= nrest - 2) BP(1, 62 + 4 * (it - nrest + 2));
                wgmma_fence();
                gemm_rs<true>(s, qf, sk.dl);
                wgmma_commit();
                gemm_rs<false>(o, pf, sv.dl, it);
                wgmma_commit();
                if (PINGPONG) named_arrive(bar_other, 256);
                LP(3);
                wgmma_wait<1>();
                LP(4);
                c.release(sk.bo);
                fence_regs(s);
                exp_part<0, SPLITJ>(s, n0, n1, l0, l1);
                sched_barrier(l0, l1, bars + MISC_OFF + 16);
                LP(5);
                wgmma_wait<0>();
                LP(6);
                c.release(sv.bo);
                fence_regs(o); fence_regs(pf);
                exp_part<SPLITJ, 16>(s, n0, n1, l0, l1);
                pack_tile(s, pf);
            }
            PROF(10 + rd * 4);
            PROFG(183 + rd);
            const Slot sv = c.next();
            BP(1, 0);
            c.wait(sv);
            if (nrest == 0) {
#pragma unroll
                for (int i = 0; i < 64; i++) o[i] = 0.f;
            }
            if (__builtin_expect(__any_sync(0xffffffffu, !(l0 < 0x1p60f && l1 < 0x1p60f)), 0)) {
                attention_exact(o, qf, l0, l1, h, nrest + 1, lim, lane);
#pragma unroll
                for (int i = 0; i < 32; i++) pf[i] = 0u;
            }
            fence_regs(o); fence_regs(pf);
            if (PINGPONG && !role) named_sync(bar_me, 256);
            BP(1, 2);
            wgmma_fence();
            gemm_rs<false>(o, pf, sv.dl);
            wgmma_commit();
            pend = sv.bo;
            ep_ptr = g_ctx + (size_t)(h * SEQ + 256 * p + 128 * rank + 64 * role + 16 * w + lr) * HD + 8 * q;
            ep_step = 8 * HD;
        }
        l0 += __shfl_xor_sync(0xffffffffu, l0, 1); l1 += __shfl_xor_sync(0xffffffffu, l1, 1);
        l0 += __shfl_xor_sync(0xffffffffu, l0, 2); l1 += __shfl_xor_sync(0xffffffffu, l1, 2);
        l0 = rcp(l0); l1 = rcp(l1);
        wgmma_wait<0>();
        c.release(pend);
        fence_regs(o); fence_regs(pf);
#pragma unroll
        for (int i = 0; i < 32; i++) pf[i] = pack_bf16(o[2 * i] * ((i & 1) ? l1 : l0), o[2 * i + 1] * ((i & 1) ? l1 : l0));
    }
    PROFG(187);
    PROF(3);
    if (cb == 8) {
#pragma unroll
        for (int i = 0; i < 8; i++) stg128(ep_ptr + (i & 1) * 8 * HD + 32 * (i >> 1), pf[4 * (i & 6) + (i & 1)], pf[4 * (i & 6) + (i & 1) + 2], pf[4 * (i & 6) + (i & 1) + 4], pf[4 * (i & 6) + (i & 1) + 6]);
        signal(bars, wg, 8, lane);
        cluster_arrive();
        named_sync(1, 256);
        mod_ffn(P, smem, 2 * ca + rank, wg);
    } else
    {
        float a1[64], a2[96];
        uint32_t px = 0, py = 0;
        auto mma1 = [&](const Slot& x, int acc) {
#pragma unroll
            for (int k = 0; k < 4; k++) wgmma_ss_n128<0, 1>(a1, x.dl + wg * 512 + lbo(16) + k * 2, x.dl + 1024 + lbo(4096) + (k >> 1) * 512 + (k & 1) * 128, k ? 1 : acc);
        };
        auto mma2 = [&](const Slot& x, const Slot& y, int acc) {
#pragma unroll
            for (int k = 0; k < 4; k++) wgmma_ss_n192<0, 1>(a2, x.dl + wg * 512 + lbo(16) + k * 2, y.dl + lbo(4096) + (k >> 1) * 768 + (k & 1) * 128, k ? 1 : acc);
        };
#pragma unroll 1
        for (int t = 0, more = 1; more; t++) {
            const Slot sx = c.next(), sy = c.next();
            c.wait(sx);
            wgmma_fence();
            mma1(sx, t);
            wgmma_commit();
            asm volatile("ld.shared.u32 %0, [%1];" : "=r"(more) : "r"(bars + CTL_OFF + sx.bo) : "memory");
            more = !__any_sync(0xffffffffu, more);
            wgmma_wait<1>();
            if (t > 0) { c.release(px); c.release(py); }
            px = sx.bo; py = sy.bo;
            c.wait(sy);
            wgmma_fence();
            mma2(sx, sy, t);
            wgmma_commit();
            if (t == 0) {
#pragma unroll
                for (int i = 0; i < 4; i++) stg128(ep_ptr + 32 * i, pf[8 * i], pf[8 * i + 2], pf[8 * i + 4], pf[8 * i + 6]);
            }
            if (t == 1) {
#pragma unroll
                for (int i = 0; i < 4; i++) stg128(ep_ptr + 8 * HD + 32 * i, pf[8 * i + 1], pf[8 * i + 3], pf[8 * i + 5], pf[8 * i + 7]);
                signal(bars, wg, 4 + n_items(ca, cb), lane);
            }
        }
        const Slot x0 = c.next(), y0 = c.next(), x1 = c.next(), y1 = c.next(), x2 = c.next(), y2 = c.next(), fr = c.next();
        const int cw = __reduce_or_sync(0xffffffffu, wg * 4 + w);
        const int orow = unperm_row(256 * out_p(ca, cb) + 128 * rank + 16 * cw), ocol = 320 * (ca >> 2);
        const uint32_t sa = ((lane & 7) + (lane & 8)) * 128, sx = (lane >> 4) ^ (lane & 7);
        auto send = [&](auto chv, uint32_t box) {
            constexpr int ch = chv.value;
#pragma unroll
            for (int i = 0; i < 4; i++) {
                uint32_t r[4];
#pragma unroll
                for (int e = 0; e < 4; e++) {
                    const int k = 32 * ch + 8 * i + 2 * e;
                    r[e] = (ch < 2) ? pack_bf16(a1[k & 63], a1[(k & 63) + 1]) : pack_bf16(a2[ch < 2 ? 0 : k - 64], a2[ch < 2 ? 1 : k - 63]);
                }
                asm volatile("stmatrix.sync.aligned.m8n8.x4.shared.b16 [%0], {%1, %2, %3, %4};"
                             ::"r"(box + sa + ((sx ^ (2 * i)) << 4)), "r"(r[0]), "r"(r[1]), "r"(r[2]), "r"(r[3]) : "memory");
            }
            asm volatile("fence.proxy.async.shared::cta;" ::: "memory");
            __syncwarp();
            asm volatile(ELECT "cp.reduce.async.bulk.tensor.2d.global.shared::cta.add.bulk_group [%0, {%2, %3}], [%1];\n}\n"
                         ::"l"(&P.outm), "r"(box), "r"(ocol + 64 * ch), "r"(orow) : "memory");
        };
        auto addr = [&](const Slot& t) { return smem + t.bo * (SLOT / 8); };
        c.wait(x0);
        wgmma_fence();
        mma1(x0, 1);
        wgmma_commit();
        wgmma_wait<1>();
        c.release(px); c.release(py);
        c.wait(x1);
        c.wait(x2);
        c.wait(y0);
        mbar_wait(bars + BAR_DEP, 0);
        wgmma_fence();
        mma1(x1, 1);
        mma1(x2, 1);
        wgmma_commit();
        mma2(x0, y0, 1);
        wgmma_commit();
        mbar_wait(bars + BAR_EMPTY + fr.bo, fr.par ^ 1);
        c.wait(y1);
        wgmma_wait<1>();
        fence_regs(a1);
        send(IntT<0>{}, addr(fr) + cw * 4096);
        wgmma_fence();
        mma2(x1, y1, 1);
        wgmma_commit();
        send(IntT<1>{}, addr(fr) + cw * 4096 + 2048);
        c.wait(y2);
        wgmma_fence();
        mma2(x2, y2, 1);
        wgmma_commit();
        wgmma_wait<0>();
        fence_regs(a2);
        PROFG(188);
        PROF(4);
        send(IntT<2>{}, addr(x0) + cw * 2048);
        send(IntT<3>{}, addr(x1) + cw * 2048);
        send(IntT<4>{}, addr(x2) + cw * 2048);
        PROF(5);
        asm volatile("cp.async.bulk.commit_group;\ncp.async.bulk.wait_group.read 0;" ::: "memory");
    }
    PROF(6);
}

__device__ __forceinline__ void mod_ffn(const Params& P, uint32_t smem, int mc  , int wg) {
    const int tid = threadIdx.x - 128, lane = tid & 31, cw = tid >> 5, q = lane & 3, lr = lane >> 2;
    const uint32_t xs = smem + 6 * SLOT, hs = xs + 10240 + wg * 1024, wmax = xs + 12288, sidx = wmax + 64, rbar = xs + 13312 + wg * 32;
    const uint32_t ring = smem + wg * 3 * SLOT;
    const int f0 = mc + 4 * wg, nunit = ((34 - f0) >> 3) * 8;
    const bool lead = __reduce_or_sync(0xffffffffu, cw & 3) == 0;
    auto lds = [](uint32_t a) { uint32_t v; asm volatile("ld.shared.u32 %0, [%1];" : "=r"(v) : "r"(a) : "memory"); return v; };
    auto sts = [](uint32_t a, uint32_t v) { asm volatile("st.shared.u32 [%0], %1;" ::"r"(a), "r"(v) : "memory"); };
    auto issue = [&](int u, int st) {
        if (lead && u < nunit) {
            const int fc = (f0 + (u & ~7)) * 64, k = u & 7;
            const uint32_t dst = ring + st * SLOT, bar = rbar + st * 8;
            w_expect_tx(bar, k == 7 ? 16384 : SLOT);
            if (k < 5) {
                w_tma_load_stream(dst, &P.wg, fc, k * 128, bar);
                w_tma_load_stream(dst + 16384, &P.wu, fc, k * 128, bar);
            } else {
#pragma unroll 1
                for (int b = 0; b < (k == 7 ? 2 : 4); b++) w_tma_load_stream(dst + b * 8192, &P.wd, (4 * (k - 5) + b) * 64, fc, bar);
            }
        }
    };
    if ((tid & 127) == 0) {
        mbar_init(rbar, 1); mbar_init(rbar + 8, 1); mbar_init(rbar + 16, 1);
        asm volatile("fence.mbarrier_init.release.cluster;" ::: "memory");
    }
    mbar_wait(smem + NSLOT * SLOT + BAR_DEP, 0);
    asm volatile("fence.proxy.async.shared::cta;" ::: "memory");
    named_sync(1, 256);
    PROF(1);
#pragma unroll 1
    for (int u = 0; u < 3; u++) issue(u, u);
    uint32_t key[8];
#pragma unroll
    for (int i = 0; i < 8; i++) {
        const int t = tid + 256 * i;
        uint32_t b = __float_as_uint(__ldcg(g_r + t) + 0.f) >> 16;
        b = (b & 0x8000u) ? (~b & 0xffffu) : (b | 0x8000u);
        key[i] = (b << 16) | (uint32_t)(0xffff - t);
    }
#pragma unroll 1
    for (int rnd = 0; rnd < 8; rnd++) {
        uint32_t mx = key[0];
#pragma unroll
        for (int i = 1; i < 8; i++) mx = max(mx, key[i]);
        sts(wmax + ((rnd & 1) * 8 + cw) * 4, __reduce_max_sync(0xffffffffu, mx));
        named_sync(1, 256);
        mx = __reduce_max_sync(0xffffffffu, lds(wmax + ((rnd & 1) * 8 + (lane & 7)) * 4));
#pragma unroll
        for (int i = 0; i < 8; i++) if (key[i] == mx) key[i] = 0;
        if (cw == rnd) sts(sidx + rnd * 4, 0xffff - (mx & 0xffffu));
    }
    __syncwarp();
    {
        const int t = lds(sidx + cw * 4);
        const uint4* src = reinterpret_cast<const uint4*>(g_xn + perm_row(t) * DM);
#pragma unroll
        for (int i = 0; i < 3; i++) {
            const int ch = lane + 32 * i;
            if (ch < 80) {
                const uint4 v = __ldcg(src + ch);
                asm volatile("st.shared.v4.b32 [%0], {%1, %2, %3, %4};" ::"r"(xs + (ch >> 3) * 1024 + cw * 128 + ((ch ^ cw) & 7) * 16), "r"(v.x), "r"(v.y), "r"(v.z), "r"(v.w) : "memory");
            }
        }
        asm volatile("fence.proxy.async.shared::cta;" ::: "memory");
    }
    named_sync(1, 256);
    PROF(3);
    float y[10][4];
#pragma unroll
    for (int i = 0; i < 10; i++) { y[i][0] = 0.f; y[i][1] = 0.f; y[i][2] = 0.f; y[i][3] = 0.f; }
    int st = 0, ph = 0, u = 0;
    auto begin = [&]() { mbar_wait(rbar + st * 8, ph); wgmma_fence(); return (((ring + st * SLOT) & 0x3FFFF) >> 4) + lbo(16); };
    auto end = [&]() {
        wgmma_commit();
        wgmma_wait<0>();
        named_sync(4 + wg, 128);
        issue(u + 3, st);
        u++;
        ph ^= st == 2;
        st = (st == 2) ? 0 : st + 1;
    };
    const uint32_t dx = ((xs & 0x3FFFF) >> 4) + lbo(16), dh = ((hs & 0x3FFFF) >> 4) + lbo(16);
#pragma unroll 1
    while (u < nunit) {
        float g[4], v[4];
#pragma unroll 1
        for (int kc = 0; kc < 5; kc++) {
            const uint32_t da = begin();
#pragma unroll
            for (int k = 0; k < 8; k++) {
                const uint32_t db = dx + (2 * kc + (k >> 2)) * 64 + (k & 3) * 2;
                wgmma_ss_n8<1, 0>(g, da + k * 128, db, k ? 1 : kc);
                wgmma_ss_n8<1, 0>(v, da + 1024 + k * 128, db, k ? 1 : kc);
            }
            end();
        }
        fence_regs(g); fence_regs(v);
#pragma unroll
        for (int e = 0; e < 4; e++) {
            const float gp = round_bf16(g[e]);
            const float hv = round_bf16(__fdividef(gp, 1.0f + __expf(fminf(-gp, 80.f)))) * round_bf16(v[e]);
            const int tok = 2 * q + (e & 1), ch = 2 * (cw & 3) + (e >> 1);
            asm volatile("st.shared.u16 [%0], %1;" ::"r"(hs + tok * 128 + ((ch ^ tok) * 16) + lr * 2), "h"((unsigned short)pack_bf16(hv, 0.f)) : "memory");
        }
        asm volatile("fence.proxy.async.shared::cta;" ::: "memory");
        named_sync(4 + wg, 128);
#pragma unroll
        for (int k3 = 0; k3 < 3; k3++) {
            const uint32_t da = begin();
#pragma unroll
            for (int b = 0; b < (k3 == 2 ? 2 : 4); b++)
#pragma unroll
                for (int k = 0; k < 4; k++) wgmma_ss_n8<1, 0>(y[4 * k3 + b], da + b * 512 + k * 128, dh + k * 2, 1);
            end();
        }
    }
    PROF(5);
#pragma unroll
    for (int i = 0; i < 10; i++) {
        fence_regs(y[i]);
#pragma unroll
        for (int e = 0; e < 4; e++) g_ypart[((mc * 2 + wg) * 8 + 2 * q + (e & 1)) * DM + 64 * i + 16 * (cw & 3) + lr + 8 * (e >> 1)] = y[i][e];
    }
    named_sync(1, 256);
    if (tid == 0) {
        flag_add(F_MODP);
        flag_wait<100>(F_MODP, 4u * (lds(smem + NSLOT * SLOT + MISC_OFF) + 1));
    }
    named_sync(1, 256);
    PROF(6);
    {
        const int c = 2 * mc + wg, t = lds(sidx + c * 4);
        const float rs = round_bf16(__fdividef(1.0f, 1.0f + __expf(fminf(-__ldcg(g_r + t), 80.f))));
#pragma unroll
        for (int i = 0; i < 3; i++) {
            const int c2 = (tid & 127) + 128 * i;
            if (c2 < DM / 2) {
                float y0 = 0.f, y1 = 0.f;
#pragma unroll
                for (int k = 0; k < 8; k++) {
                    const float2 v = __ldcg(reinterpret_cast<const float2*>(g_ypart + (k * 8 + c) * DM) + c2);
                    y0 += v.x; y1 += v.y;
                }
                asm volatile("red.relaxed.gpu.global.add.noftz.bf16x2 [%0], %1;" ::"l"(P.out + t * DM + 2 * c2), "r"(pack_bf16(round_bf16(y0) * rs, round_bf16(y1) * rs)) : "memory");
            }
        }
    }
    PROF(7);
}

__global__ void __cluster_dims__(2, 1, 1) __launch_bounds__(384, 1) fused_kernel(const __grid_constant__ Params P) {
    extern __shared__ __align__(1024) uint8_t smem_raw[];
    const uint32_t smem = (smem_u32(smem_raw) + 1023u) & ~1023u;
    const uint32_t bars = smem + NSLOT * SLOT;
    const int wgi = __reduce_or_sync(0xffffffffu, threadIdx.x >> 7);
    const int cl = blockIdx.x >> 1, rank = blockIdx.x & 1, ca = cl & 7, cb = cl >> 3;
    PROFG(30);
    PROF(0);
    if (threadIdx.x >= 64 && threadIdx.x < 64 + 32 * FASTSTART && (threadIdx.x & 31) == 0) {
        const int u = (threadIdx.x >> 5) - 2;
        const uint32_t fa = bars + BAR_FULL + slot_a(u) * 8, fw = bars + BAR_FULL + slot_w(u) * 8;
        mbar_init(fa, 1); mbar_init(fw, 1);
        asm volatile("fence.mbarrier_init.release.cluster;" ::: "memory");
        if (cl < 64) {
            mbar_expect_tx(fa, SLOT);
            mbar_expect_tx(fw, SLOT);
            tma_load(smem + slot_a(u) * SLOT, &P.ckv, u * 128, (2 * ca + rank) * 128, fa);
            tma_load(smem + slot_w(u) * SLOT, &P.wuk, (cb + 8 * kv_round(0)) * 128, u * 128, fw);
            tma_load(smem + slot_w(u) * SLOT + 16384, &P.wuk, (cb + 8 * kv_round(0)) * 128 + 64, u * 128, fw);
            tma_load(smem + slot_a(u) * SLOT + 16384, &P.ckv, u * 128 + 64, (2 * ca + rank) * 128, fa);
        }
    } else if (threadIdx.x == 0) {
#pragma unroll
        for (int i = 0; i < NSLOT; i++) {
            if (i != 0 && i != 4 && (FASTSTART < 2 || (i != 1 && i != 6))) mbar_init(bars + BAR_FULL + i * 8, 1);
            mbar_init(bars + BAR_EMPTY + i * 8, 16);
        }
        if (cb < 8) {
            mbar_arrive(bars + BAR_FULL + 16);
            asm volatile("mbarrier.arrive.shared::cta.b64 _, [%0], 16;" ::"r"(bars + BAR_EMPTY + 16) : "memory");
        }
        asm volatile("fence.mbarrier_init.release.cluster;" ::: "memory");
        PROF(24);
    } else if (threadIdx.x == 32) {
#pragma unroll
        for (int i = 0; i < 18; i++) mbar_init(bars + BAR_SIG + i * 8, 4);
#pragma unroll
        for (int i = 0; i < 18; i++) mbar_init(bars + BAR_DEP + i * 8, 1);
        asm volatile("fence.mbarrier_init.release.cluster;" ::: "memory");
    }
    __syncthreads();
    PROF(29);
    cluster_arrive();
    if (wgi > 0) {
        asm volatile("setmaxnreg.inc.sync.aligned.u32 232;");
        consumer(P, smem, bars, ca, cb, rank, wgi - 1);
        PROFG(31);
        PROFDUMP();
    } else {
        asm volatile("setmaxnreg.dec.sync.aligned.u32 40;");
        const int w = __reduce_or_sync(0xffffffffu, threadIdx.x >> 5), lane = threadIdx.x & 31;
        if (threadIdx.x == 32) {
            prefetch_map(&P.wuv); prefetch_map(&P.xn); prefetch_map(&P.wq); prefetch_map(&P.kv); prefetch_map(&P.ctx); prefetch_map(&P.wo); prefetch_map(&P.outm);
        }
        __syncwarp();
        cluster_wait();
        PROF(27);
        {
            if (w == 0) {
                producer(P, smem, bars, ca, cb, rank);
            } else if (w < 3 && lane == 0) {
                const int wg = w - 1;
#pragma unroll 1
                for (int i = (cb == 8); i < (cb == 8 ? 9 : 5 + n_items(ca, cb)); i++) {
                    const int nb = wg * LNSTAG + (LNOFF + 7 - 4) / 8;
                    const int e = (cb == 8) ? i : (i < nb) ? i + 1 : (i == nb) ? 0 : i;
                    mbar_wait_sleep(bars + BAR_SIG + (wg * 9 + e) * 8, 0);
                    int f;
                    if (cb == 8) f = F_CTX + (2 + ca) * 16 + rank;
                    else if (e == 0) f = F_LN;
                    else if (e < 5) f = F_KV + cb + 8 * kv_round(e - 1);
                    else { const int rd = item_rd(ca, cb, e - 5); f = F_CTX + rd * 16 + item_p(ca, rd) * 2 + rank; }
                    flag_add(f);
                }
            } else if (lane == 0) {
                const uint32_t epoch = read_epoch();
                asm volatile("st.shared.u32 [%0], %1;" ::"r"(bars + MISC_OFF), "r"(epoch) : "memory");
#pragma unroll 1
                for (int e = 0; e < 9; e++) {
                    int f;
                    uint32_t n;
                    if (e == 0) { f = F_LN; n = 256; }
                    else if (cb == 8) { f = F_KV + item_h(cb, 2 + ca, e - 1); n = 32; }
                    else if (e < 5) { f = F_KV + cb + 8 * (e - 1); n = 32; }
                    else { f = F_CTX + (e - 5) * 16 + out_p(ca, cb) * 2 + rank; n = 16; }
                    flag_wait<200>(f, n * (epoch + 1));
                    fence_proxy_async();
                    mbar_arrive(bars + BAR_DEP + e * 8);
                }
            }
        }
        if (cb == 8) { __syncwarp(); cluster_arrive(); cluster_wait(); }
        PROFG(31);
        PROFDUMP();
    }
}

typedef CUresult (*EncodeFn)(CUtensorMap*, CUtensorMapDataType, cuuint32_t, void*, const cuuint64_t*, const cuuint64_t*, const cuuint32_t*,
                             const cuuint32_t*, CUtensorMapInterleave, CUtensorMapSwizzle, CUtensorMapL2promotion, CUtensorMapFloatOOBfill);

void make_map(EncodeFn fn, CUtensorMap* m, const void* ptr, uint64_t rows, uint64_t cols, uint32_t box_rows) {
    cuuint64_t dims[2] = {cols, rows};
    cuuint64_t strides[1] = {cols * 2};
    cuuint32_t box[2] = {64, box_rows};
    cuuint32_t es[2] = {1, 1};
    fn(m, CU_TENSOR_MAP_DATA_TYPE_BFLOAT16, 2, const_cast<void*>(ptr), dims, strides, box, es, CU_TENSOR_MAP_INTERLEAVE_NONE,
       CU_TENSOR_MAP_SWIZZLE_128B, CU_TENSOR_MAP_L2_PROMOTION_L2_128B, CU_TENSOR_MAP_FLOAT_OOB_FILL_NONE);
}

}

extern "C" void kernel_launch(void* const* d_in, const int* in_sizes, int n_in, void* d_out, int out_size) {
    (void)in_sizes; (void)n_in; (void)out_size;
    void* fnp = nullptr;
    cudaDriverEntryPointQueryResult qr;
    cudaGetDriverEntryPoint("cuTensorMapEncodeTiled", &fnp, cudaEnableDefault, &qr);
    EncodeFn fn = (EncodeFn)fnp;
    void *xn, *kv, *ctx;
    cudaGetSymbolAddress(&xn, g_xn);
    cudaGetSymbolAddress(&kv, g_kv);
    cudaGetSymbolAddress(&ctx, g_ctx);
    Params P;
    make_map(fn, &P.ckv, d_in[1], SEQ, DC, 128);
    make_map(fn, &P.wq, d_in[2], DM, NH * HD, 64);
    make_map(fn, &P.wuk, d_in[3], DC, NH * HD, 128);
    make_map(fn, &P.wuv, d_in[4], DC, NH * HD, 128);
    make_map(fn, &P.wo, d_in[5], NH * HD, DM, 32);
    make_map(fn, &P.xn, xn, SEQ, DM, 128);
    make_map(fn, &P.kv, kv, NH * 16 * 2 * 128, 128, 128);
    make_map(fn, &P.ctx, ctx, NH * SEQ, HD, 128);
    P.x = (const __nv_bfloat16*)d_in[0];
    P.wr = (const __nv_bfloat16*)d_in[7];
    make_map(fn, &P.wg, d_in[8], DM, FF, 128);
    make_map(fn, &P.wu, d_in[9], DM, FF, 128);
    make_map(fn, &P.wd, d_in[10], FF, DM, 64);
    make_map(fn, &P.outm, d_out, SEQ, DM, 16);
    P.out = (__nv_bfloat16*)d_out;
    cudaFuncSetAttribute(fused_kernel, cudaFuncAttributeMaxDynamicSharedMemorySize, SMEM_BYTES);
    fused_kernel<<<NCTA, 384, SMEM_BYTES>>>(P);
}
```

```cpp
#include <cuda_runtime.h>
#include <cuda_bf16.h>
#include <cuda.h>
#include <stdint.h>

namespace {

constexpr int SEQ = 2048, DM = 640, DC = 512, NH = 32, HD = 128, FF = 1728;
constexpr int NSLOT = 7, SLOT = 32768;
constexpr int NCTA = 132;
#define PINGPONG 1
#define SIGMA 1
#define KVORDER 0x1023
#define KVSPLIT 1
#define LNSTAG 1
#define LASTRD 7
#define LASTN 2
#define EFMASK 13
#define LNOFF 4
#define LNLEAD 2
#define FASTSTART 1
#define OFFLOAD 1
#define SPLITJ 8
constexpr uint32_t DESC_HI = (1024u >> 4) | (1u << 30);
constexpr int SMEM_BYTES = NSLOT * SLOT + 3072;

constexpr int BAR_FULL = 0, BAR_EMPTY = 64, BAR_SIG = 128  , BAR_DEP = 320  , BAR_MAIL = 400  ;
constexpr int MISC_OFF = 512  , MAIL_OFF = 544  , CTL_OFF = 576  ;

constexpr int F_EPOCH = 0, F_LN = 1, F_MODP = 3, F_KV = 4  , F_CTX = 36  , F_POOL = 100  , F_NUM = 116;

__device__ __align__(1024) __nv_bfloat16 g_xn[SEQ * DM];
__device__ __align__(1024) __nv_bfloat16 g_kv[NH * 16 * 2 * 128 * 128];
__device__ __align__(1024) __nv_bfloat16 g_ctx[NH * SEQ * HD];
__device__ __align__(16) float g_r[SEQ];
__device__ __align__(16) float g_ypart[8 * 8 * DM];
__device__ uint32_t g_flags[F_NUM * 8];

struct TrueT { static constexpr bool value = true; };
struct FalseT { static constexpr bool value = false; };

struct Params {
    CUtensorMap ckv, wuk, wuv, xn, wq, kv, ctx, wo, wg, wu, wd, outm;
    const __nv_bfloat16 *x, *wr;
    __nv_bfloat16* out;
};

__device__ __forceinline__ uint32_t smem_u32(const void* p) { return (uint32_t)__cvta_generic_to_shared(p); }
__device__ __forceinline__ void mbar_init(uint32_t bar, uint32_t cnt) {
    asm volatile("mbarrier.init.shared::cta.b64 [%0], %1;" ::"r"(bar), "r"(cnt) : "memory");
}
__device__ __forceinline__ void mbar_expect_tx(uint32_t bar, uint32_t bytes) {
    asm volatile("mbarrier.arrive.expect_tx.shared::cta.b64 _, [%0], %1;" ::"r"(bar), "r"(bytes) : "memory");
}
__device__ __forceinline__ void mbar_arrive(uint32_t bar) {
    asm volatile("mbarrier.arrive.shared::cta.b64 _, [%0];" ::"r"(bar) : "memory");
}
__device__ __forceinline__ uint32_t mapa(uint32_t addr, uint32_t cta) {
    uint32_t r;
    asm("mapa.shared::cluster.u32 %0, %1, %2;" : "=r"(r) : "r"(addr), "r"(cta));
    return r;
}
__device__ __forceinline__ void mbar_wait(uint32_t bar, uint32_t parity) {
    asm volatile(
        "{\n.reg .pred p;\n.reg .b32 c;\n"
        "mov.b32 c, 0;\n"
        "WLOOP:\n"
        "mbarrier.try_wait.parity.shared::cta.b64 p, [%0], %1;\n"
        "@p bra.uni WDONE;\n"
        "add.u32 c, c, 1;\n"
        "setp.lt.u32 p, c, 0x400000;\n"
        "@p bra.uni WLOOP;\n"
        "trap;\n"
        "WDONE:\n}\n" ::"r"(bar), "r"(parity) : "memory");
}
__device__ __forceinline__ void mbar_wait_sleep(uint32_t bar, uint32_t parity) {
    asm volatile(
        "{\n.reg .pred p;\n.reg .b32 c;\n"
        "mov.b32 c, 0;\n"
        "WLOOP:\n"
        "mbarrier.try_wait.parity.shared::cta.b64 p, [%0], %1, 20000;\n"
        "@p bra.uni WDONE;\n"
        "add.u32 c, c, 1;\n"
        "setp.lt.u32 p, c, 0x40000;\n"
        "@p bra.uni WLOOP;\n"
        "trap;\n"
        "WDONE:\n}\n" ::"r"(bar), "r"(parity) : "memory");
}
__device__ __forceinline__ void tma_load(uint32_t dst, const CUtensorMap* m, int c0, int c1, uint32_t bar) {
    asm volatile("cp.async.bulk.tensor.2d.shared::cluster.global.mbarrier::complete_tx::bytes [%0], [%1, {%3, %4}], [%2];"
                 ::"r"(dst), "l"(m), "r"(bar), "r"(c0), "r"(c1) : "memory");
}
#define ELECT "{\n.reg .pred e;\nelect.sync _|e, 0xffffffff;\n@e "
__device__ __forceinline__ void w_expect_tx(uint32_t bar, uint32_t bytes) {
    asm volatile(ELECT "mbarrier.arrive.expect_tx.shared::cta.b64 _, [%0], %1;\n}\n" ::"r"(bar), "r"(bytes) : "memory");
}
__device__ __forceinline__ void w_tma_load(uint32_t dst, const CUtensorMap* m, int c0, int c1, uint32_t bar) {
    asm volatile(ELECT "cp.async.bulk.tensor.2d.shared::cluster.global.mbarrier::complete_tx::bytes [%0], [%1, {%3, %4}], [%2];\n}\n"
                 ::"r"(dst), "l"(m), "r"(bar), "r"(c0), "r"(c1) : "memory");
}
__device__ __forceinline__ void w_tma_load_mc(uint32_t dst, const CUtensorMap* m, int c0, int c1, uint32_t bar) {
    asm volatile(ELECT "cp.async.bulk.tensor.2d.shared::cluster.global.mbarrier::complete_tx::bytes.multicast::cluster [%0], [%1, {%3, %4}], [%2], %5;\n}\n"
                 ::"r"(dst), "l"(m), "r"(bar), "r"(c0), "r"(c1), "h"((uint16_t)3) : "memory");
}
__device__ __forceinline__ void w_tma_prefetch(const CUtensorMap* m, int c0, int c1) {
    asm volatile(ELECT "cp.async.bulk.prefetch.tensor.2d.L2.global [%0, {%1, %2}];\n}\n" ::"l"(m), "r"(c0), "r"(c1) : "memory");
}
__device__ __forceinline__ uint64_t policy_evict_first() {
    uint64_t p;
    asm("createpolicy.fractional.L2::evict_first.b64 %0, 1.0;" : "=l"(p));
    return p;
}
__device__ __forceinline__ void w_tma_load_mc_last(uint32_t dst, const CUtensorMap* m, int c0, int c1, uint32_t bar) {
    asm volatile(ELECT "cp.async.bulk.tensor.2d.shared::cluster.global.mbarrier::complete_tx::bytes.multicast::cluster.L2::cache_hint [%0], [%1, {%3, %4}], [%2], %5, %6;\n}\n"
                 ::"r"(dst), "l"(m), "r"(bar), "r"(c0), "r"(c1), "h"((uint16_t)3), "l"(policy_evict_first()) : "memory");
}
__device__ __forceinline__ void w_tma_load_stream(uint32_t dst, const CUtensorMap* m, int c0, int c1, uint32_t bar) {
    asm volatile(ELECT "cp.async.bulk.tensor.2d.shared::cluster.global.mbarrier::complete_tx::bytes.L2::cache_hint [%0], [%1, {%3, %4}], [%2], %5;\n}\n"
                 ::"r"(dst), "l"(m), "r"(bar), "r"(c0), "r"(c1), "l"(policy_evict_first()) : "memory");
}
__device__ __forceinline__ uint4 ldg_stream(const void* p) {
    uint4 v;
    asm volatile("ld.global.nc.L2::cache_hint.v4.b32 {%0, %1, %2, %3}, [%4], %5;" : "=r"(v.x), "=r"(v.y), "=r"(v.z), "=r"(v.w) : "l"(p), "l"(policy_evict_first()));
    return v;
}
__device__ __forceinline__ void prefetch_map(const CUtensorMap* m) {
    asm volatile("prefetch.tensormap [%0];" ::"l"(m) : "memory");
}
__device__ __forceinline__ void cluster_arrive() { asm volatile("barrier.cluster.arrive.relaxed.aligned;" ::: "memory"); }
__device__ __forceinline__ void cluster_wait() { asm volatile("barrier.cluster.wait.aligned;" ::: "memory"); }
__device__ __forceinline__ void named_sync(int id, int n) { asm volatile("bar.sync %0, %1;" ::"r"(id), "r"(n) : "memory"); }
__device__ __forceinline__ void named_arrive(int id, int n) { asm volatile("bar.arrive %0, %1;" ::"r"(id), "r"(n) : "memory"); }

__device__ __forceinline__ void flag_add(int f) {
    asm volatile("fence.acq_rel.gpu;\nred.relaxed.gpu.global.add.u32 [%0], 1;" ::"l"(g_flags + f * 8) : "memory");
}
template <int SLEEP>
__device__ __forceinline__ void flag_wait(int f, uint32_t target) {
    asm volatile(
        "{\n.reg .pred p;\n.reg .b32 c, v;\n"
        "mov.b32 c, 0;\n"
        "FLOOP:\n"
        "ld.acquire.gpu.global.u32 v, [%0];\n"
        "sub.u32 v, v, %1;\n"
        "setp.ge.s32 p, v, 0;\n"
        "@p bra FDONE;\n"
        "nanosleep.u32 %2;\n"
        "add.u32 c, c, 1;\n"
        "setp.lt.u32 p, c, 0x400000;\n"
        "@p bra FLOOP;\n"
        "trap;\n"
        "FDONE:\n}\n" ::"l"(g_flags + f * 8), "r"(target), "n"(SLEEP) : "memory");
}
__device__ __forceinline__ uint32_t read_epoch() { return atomicAdd(g_flags + F_EPOCH * 8, 1u) / NCTA; }
__device__ __forceinline__ void fence_proxy_async() { asm volatile("fence.proxy.async;" ::: "memory"); }

__device__ __forceinline__ void wgmma_fence() { asm volatile("wgmma.fence.sync.aligned;" ::: "memory"); }
__device__ __forceinline__ void wgmma_commit() { asm volatile("wgmma.commit_group.sync.aligned;" ::: "memory"); }
template <int N>
__device__ __forceinline__ void wgmma_wait() { asm volatile("wgmma.wait_group.sync.aligned %0;" ::"n"(N) : "memory"); }
template <int N>
__device__ __forceinline__ void fence_regs(float (&d)[N]) {
#pragma unroll
    for (int i = 0; i < N; i++) asm volatile("" : "+f"(d[i])::"memory");
}
template <int N>
__device__ __forceinline__ void fence_regs(uint32_t (&d)[N]) {
#pragma unroll
    for (int i = 0; i < N; i++) asm volatile("" : "+r"(d[i])::"memory");
}

template <int TA, int TB>
__device__ __forceinline__ void wgmma_ss_n128(float (&d)[64], uint32_t alo, uint32_t blo, int scale_d) {
    asm volatile("{\n.reg .pred p;\n.reg .b64 da, db;\nsetp.ne.b32 p, %66, 0;\n"
        "mov.b64 da, {%64, %69};\nmov.b64 db, {%65, %69};\n"
        "wgmma.mma_async.sync.aligned.m64n128k16.f32.bf16.bf16 "
        "{%0, %1, %2, %3, %4, %5, %6, %7, %8, %9, %10, %11, %12, %13, %14, %15, %16, %17, %18, %19, %20, %21, %22, %23, %24, %25, %26, %27, %28, %29, %30, %31, %32, %33, %34, %35, %36, %37, %38, %39, %40, %41, %42, %43, %44, %45, %46, %47, %48, %49, %50, %51, %52, %53, %54, %55, %56, %57, %58, %59, %60, %61, %62, %63}, da, db, p, 1, 1, %67, %68;\n}\n"
        :
          "+f"(d[0]), "+f"(d[1]), "+f"(d[2]), "+f"(d[3]), "+f"(d[4]), "+f"(d[5]), "+f"(d[6]), "+f"(d[7]),
          "+f"(d[8]), "+f"(d[9]), "+f"(d[10]), "+f"(d[11]), "+f"(d[12]), "+f"(d[13]), "+f"(d[14]), "+f"(d[15]),
          "+f"(d[16]), "+f"(d[17]), "+f"(d[18]), "+f"(d[19]), "+f"(d[20]), "+f"(d[21]), "+f"(d[22]), "+f"(d[23]),
          "+f"(d[24]), "+f"(d[25]), "+f"(d[26]), "+f"(d[27]), "+f"(d[28]), "+f"(d[29]), "+f"(d[30]), "+f"(d[31]),
          "+f"(d[32]), "+f"(d[33]), "+f"(d[34]), "+f"(d[35]), "+f"(d[36]), "+f"(d[37]), "+f"(d[38]), "+f"(d[39]),
          "+f"(d[40]), "+f"(d[41]), "+f"(d[42]), "+f"(d[43]), "+f"(d[44]), "+f"(d[45]), "+f"(d[46]), "+f"(d[47]),
          "+f"(d[48]), "+f"(d[49]), "+f"(d[50]), "+f"(d[51]), "+f"(d[52]), "+f"(d[53]), "+f"(d[54]), "+f"(d[55]),
          "+f"(d[56]), "+f"(d[57]), "+f"(d[58]), "+f"(d[59]), "+f"(d[60]), "+f"(d[61]), "+f"(d[62]), "+f"(d[63])
        : "r"(alo), "r"(blo), "r"(scale_d), "n"(TA), "n"(TB), "r"(DESC_HI));
}
template <int TA, int TB>
__device__ __forceinline__ void wgmma_ss_n192(float (&d)[96], uint32_t alo, uint32_t blo, int scale_d) {
    asm volatile("{\n.reg .pred p;\n.reg .b64 da, db;\nsetp.ne.b32 p, %98, 0;\n"
        "mov.b64 da, {%96, %101};\nmov.b64 db, {%97, %101};\n"
        "wgmma.mma_async.sync.aligned.m64n192k16.f32.bf16.bf16 "
        "{%0, %1, %2, %3, %4, %5, %6, %7, %8, %9, %10, %11, %12, %13, %14, %15, %16, %17, %18, %19, %20, %21, %22, %23, %24, %25, %26, %27, %28, %29, %30, %31, %32, %33, %34, %35, %36, %37, %38, %39, %40, %41, %42, %43, %44, %45, %46, %47, %48, %49, %50, %51, %52, %53, %54, %55, %56, %57, %58, %59, %60, %61, %62, %63, %64, %65, %66, %67, %68, %69, %70, %71, %72, %73, %74, %75, %76, %77, %78, %79, %80, %81, %82, %83, %84, %85, %86, %87, %88, %89, %90, %91, %92, %93, %94, %95}, da, db, p, 1, 1, %99, %100;\n}\n"
        :
          "+f"(d[0]), "+f"(d[1]), "+f"(d[2]), "+f"(d[3]), "+f"(d[4]), "+f"(d[5]), "+f"(d[6]), "+f"(d[7]),
          "+f"(d[8]), "+f"(d[9]), "+f"(d[10]), "+f"(d[11]), "+f"(d[12]), "+f"(d[13]), "+f"(d[14]), "+f"(d[15]),
          "+f"(d[16]), "+f"(d[17]), "+f"(d[18]), "+f"(d[19]), "+f"(d[20]), "+f"(d[21]), "+f"(d[22]), "+f"(d[23]),
          "+f"(d[24]), "+f"(d[25]), "+f"(d[26]), "+f"(d[27]), "+f"(d[28]), "+f"(d[29]), "+f"(d[30]), "+f"(d[31]),
          "+f"(d[32]), "+f"(d[33]), "+f"(d[34]), "+f"(d[35]), "+f"(d[36]), "+f"(d[37]), "+f"(d[38]), "+f"(d[39]),
          "+f"(d[40]), "+f"(d[41]), "+f"(d[42]), "+f"(d[43]), "+f"(d[44]), "+f"(d[45]), "+f"(d[46]), "+f"(d[47]),
          "+f"(d[48]), "+f"(d[49]), "+f"(d[50]), "+f"(d[51]), "+f"(d[52]), "+f"(d[53]), "+f"(d[54]), "+f"(d[55]),
          "+f"(d[56]), "+f"(d[57]), "+f"(d[58]), "+f"(d[59]), "+f"(d[60]), "+f"(d[61]), "+f"(d[62]), "+f"(d[63]),
          "+f"(d[64]), "+f"(d[65]), "+f"(d[66]), "+f"(d[67]), "+f"(d[68]), "+f"(d[69]), "+f"(d[70]), "+f"(d[71]),
          "+f"(d[72]), "+f"(d[73]), "+f"(d[74]), "+f"(d[75]), "+f"(d[76]), "+f"(d[77]), "+f"(d[78]), "+f"(d[79]),
          "+f"(d[80]), "+f"(d[81]), "+f"(d[82]), "+f"(d[83]), "+f"(d[84]), "+f"(d[85]), "+f"(d[86]), "+f"(d[87]),
          "+f"(d[88]), "+f"(d[89]), "+f"(d[90]), "+f"(d[91]), "+f"(d[92]), "+f"(d[93]), "+f"(d[94]), "+f"(d[95])
        : "r"(alo), "r"(blo), "r"(scale_d), "n"(TA), "n"(TB), "r"(DESC_HI));
}
template <int TA, int TB>
__device__ __forceinline__ void wgmma_ss_n8(float (&d)[4], uint32_t alo, uint32_t blo, int scale_d) {
    asm volatile("{\n.reg .pred p;\n.reg .b64 da, db;\nsetp.ne.b32 p, %6, 0;\n"
        "mov.b64 da, {%4, %9};\nmov.b64 db, {%5, %9};\n"
        "wgmma.mma_async.sync.aligned.m64n8k16.f32.bf16.bf16 "
        "{%0, %1, %2, %3}, da, db, p, 1, 1, %7, %8;\n}\n"
        :
          "+f"(d[0]), "+f"(d[1]), "+f"(d[2]), "+f"(d[3])
        : "r"(alo), "r"(blo), "r"(scale_d), "n"(TA), "n"(TB), "r"(DESC_HI));
}
template <int TB>
__device__ __forceinline__ void wgmma_rs_n128(float (&d)[64], uint32_t a0, uint32_t a1, uint32_t a2, uint32_t a3, uint32_t blo, int scale_d) {
    asm volatile("{\n.reg .pred p;\n.reg .b64 db;\nsetp.ne.b32 p, %69, 0;\n"
        "mov.b64 db, {%68, %71};\n"
        "wgmma.mma_async.sync.aligned.m64n128k16.f32.bf16.bf16 "
        "{%0, %1, %2, %3, %4, %5, %6, %7, %8, %9, %10, %11, %12, %13, %14, %15, %16, %17, %18, %19, %20, %21, %22, %23, %24, %25, %26, %27, %28, %29, %30, %31, %32, %33, %34, %35, %36, %37, %38, %39, %40, %41, %42, %43, %44, %45, %46, %47, %48, %49, %50, %51, %52, %53, %54, %55, %56, %57, %58, %59, %60, %61, %62, %63}, {%64, %65, %66, %67}, db, p, 1, 1, %70;\n}\n"
        :
          "+f"(d[0]), "+f"(d[1]), "+f"(d[2]), "+f"(d[3]), "+f"(d[4]), "+f"(d[5]), "+f"(d[6]), "+f"(d[7]),
          "+f"(d[8]), "+f"(d[9]), "+f"(d[10]), "+f"(d[11]), "+f"(d[12]), "+f"(d[13]), "+f"(d[14]), "+f"(d[15]),
          "+f"(d[16]), "+f"(d[17]), "+f"(d[18]), "+f"(d[19]), "+f"(d[20]), "+f"(d[21]), "+f"(d[22]), "+f"(d[23]),
          "+f"(d[24]), "+f"(d[25]), "+f"(d[26]), "+f"(d[27]), "+f"(d[28]), "+f"(d[29]), "+f"(d[30]), "+f"(d[31]),
          "+f"(d[32]), "+f"(d[33]), "+f"(d[34]), "+f"(d[35]), "+f"(d[36]), "+f"(d[37]), "+f"(d[38]), "+f"(d[39]),
          "+f"(d[40]), "+f"(d[41]), "+f"(d[42]), "+f"(d[43]), "+f"(d[44]), "+f"(d[45]), "+f"(d[46]), "+f"(d[47]),
          "+f"(d[48]), "+f"(d[49]), "+f"(d[50]), "+f"(d[51]), "+f"(d[52]), "+f"(d[53]), "+f"(d[54]), "+f"(d[55]),
          "+f"(d[56]), "+f"(d[57]), "+f"(d[58]), "+f"(d[59]), "+f"(d[60]), "+f"(d[61]), "+f"(d[62]), "+f"(d[63])
        : "r"(a0), "r"(a1), "r"(a2), "r"(a3), "r"(blo), "r"(scale_d), "n"(TB), "r"(DESC_HI));
}
template <int TB>
__device__ __forceinline__ void wgmma_rs_n128_z(float (&d)[64], uint32_t a0, uint32_t a1, uint32_t a2, uint32_t a3, uint32_t blo) {
    asm volatile("{\n.reg .pred p;\n.reg .b64 db;\nsetp.ne.b32 p, %69, 0;\n"
        "mov.b64 db, {%68, %71};\n"
        "wgmma.mma_async.sync.aligned.m64n128k16.f32.bf16.bf16 "
        "{%0, %1, %2, %3, %4, %5, %6, %7, %8, %9, %10, %11, %12, %13, %14, %15, %16, %17, %18, %19, %20, %21, %22, %23, %24, %25, %26, %27, %28, %29, %30, %31, %32, %33, %34, %35, %36, %37, %38, %39, %40, %41, %42, %43, %44, %45, %46, %47, %48, %49, %50, %51, %52, %53, %54, %55, %56, %57, %58, %59, %60, %61, %62, %63}, {%64, %65, %66, %67}, db, p, 1, 1, %70;\n}\n"
        :
          "=f"(d[0]), "=f"(d[1]), "=f"(d[2]), "=f"(d[3]), "=f"(d[4]), "=f"(d[5]), "=f"(d[6]), "=f"(d[7]),
          "=f"(d[8]), "=f"(d[9]), "=f"(d[10]), "=f"(d[11]), "=f"(d[12]), "=f"(d[13]), "=f"(d[14]), "=f"(d[15]),
          "=f"(d[16]), "=f"(d[17]), "=f"(d[18]), "=f"(d[19]), "=f"(d[20]), "=f"(d[21]), "=f"(d[22]), "=f"(d[23]),
          "=f"(d[24]), "=f"(d[25]), "=f"(d[26]), "=f"(d[27]), "=f"(d[28]), "=f"(d[29]), "=f"(d[30]), "=f"(d[31]),
          "=f"(d[32]), "=f"(d[33]), "=f"(d[34]), "=f"(d[35]), "=f"(d[36]), "=f"(d[37]), "=f"(d[38]), "=f"(d[39]),
          "=f"(d[40]), "=f"(d[41]), "=f"(d[42]), "=f"(d[43]), "=f"(d[44]), "=f"(d[45]), "=f"(d[46]), "=f"(d[47]),
          "=f"(d[48]), "=f"(d[49]), "=f"(d[50]), "=f"(d[51]), "=f"(d[52]), "=f"(d[53]), "=f"(d[54]), "=f"(d[55]),
          "=f"(d[56]), "=f"(d[57]), "=f"(d[58]), "=f"(d[59]), "=f"(d[60]), "=f"(d[61]), "=f"(d[62]), "=f"(d[63])
        : "r"(a0), "r"(a1), "r"(a2), "r"(a3), "r"(blo), "n"(0), "n"(TB), "r"(DESC_HI));
}
template <int TA, int TB>
__device__ __forceinline__ void wgmma_ss_n128_z(float (&d)[64], uint32_t alo, uint32_t blo) {
    asm volatile("{\n.reg .pred p;\n.reg .b64 da, db;\nsetp.ne.b32 p, %66, 0;\n"
        "mov.b64 da, {%64, %69};\nmov.b64 db, {%65, %69};\n"
        "wgmma.mma_async.sync.aligned.m64n128k16.f32.bf16.bf16 "
        "{%0, %1, %2, %3, %4, %5, %6, %7, %8, %9, %10, %11, %12, %13, %14, %15, %16, %17, %18, %19, %20, %21, %22, %23, %24, %25, %26, %27, %28, %29, %30, %31, %32, %33, %34, %35, %36, %37, %38, %39, %40, %41, %42, %43, %44, %45, %46, %47, %48, %49, %50, %51, %52, %53, %54, %55, %56, %57, %58, %59, %60, %61, %62, %63}, da, db, p, 1, 1, %67, %68;\n}\n"
        :
          "=f"(d[0]), "=f"(d[1]), "=f"(d[2]), "=f"(d[3]), "=f"(d[4]), "=f"(d[5]), "=f"(d[6]), "=f"(d[7]),
          "=f"(d[8]), "=f"(d[9]), "=f"(d[10]), "=f"(d[11]), "=f"(d[12]), "=f"(d[13]), "=f"(d[14]), "=f"(d[15]),
          "=f"(d[16]), "=f"(d[17]), "=f"(d[18]), "=f"(d[19]), "=f"(d[20]), "=f"(d[21]), "=f"(d[22]), "=f"(d[23]),
          "=f"(d[24]), "=f"(d[25]), "=f"(d[26]), "=f"(d[27]), "=f"(d[28]), "=f"(d[29]), "=f"(d[30]), "=f"(d[31]),
          "=f"(d[32]), "=f"(d[33]), "=f"(d[34]), "=f"(d[35]), "=f"(d[36]), "=f"(d[37]), "=f"(d[38]), "=f"(d[39]),
          "=f"(d[40]), "=f"(d[41]), "=f"(d[42]), "=f"(d[43]), "=f"(d[44]), "=f"(d[45]), "=f"(d[46]), "=f"(d[47]),
          "=f"(d[48]), "=f"(d[49]), "=f"(d[50]), "=f"(d[51]), "=f"(d[52]), "=f"(d[53]), "=f"(d[54]), "=f"(d[55]),
          "=f"(d[56]), "=f"(d[57]), "=f"(d[58]), "=f"(d[59]), "=f"(d[60]), "=f"(d[61]), "=f"(d[62]), "=f"(d[63])
        : "r"(alo), "r"(blo), "n"(0), "n"(TA), "n"(TB), "r"(DESC_HI));
}

__device__ __forceinline__ uint32_t pack_bf16(float lo, float hi) {
    uint32_t r;
    asm("cvt.rn.bf16x2.f32 %0, %1, %2;" : "=r"(r) : "f"(hi), "f"(lo));
    return r;
}
__device__ __forceinline__ uint32_t add_bf16x2(uint32_t a, uint32_t b) {
    uint32_t r;
    asm("add.rn.bf16x2 %0, %1, %2;" : "=r"(r) : "r"(a), "r"(b));
    return r;
}
__device__ __forceinline__ float bf_lo(uint32_t v) { return __uint_as_float(v << 16); }
__device__ __forceinline__ float bf_hi(uint32_t v) { return __uint_as_float(v & 0xffff0000u); }
__device__ __forceinline__ float round_bf16(float v) { return __bfloat162float(__float2bfloat16_rn(v)); }
__device__ __forceinline__ float ex2(float x) {
    float y;
    asm("ex2.approx.ftz.f32 %0, %1;" : "=f"(y) : "f"(x));
    return y;
}
__device__ __forceinline__ float rcp(float x) {
    float y;
    asm("rcp.approx.ftz.f32 %0, %1;" : "=f"(y) : "f"(x));
    return y;
}
__device__ __forceinline__ void stg128(void* p, uint32_t a, uint32_t b, uint32_t c, uint32_t d) {
    asm volatile("st.global.v4.b32 [%0], {%1, %2, %3, %4};" ::"l"(p), "r"(a), "r"(b), "r"(c), "r"(d) : "memory");
}
__device__ __forceinline__ void stg128p(void* p, uint32_t a, uint32_t b, uint32_t c, uint32_t d, uint64_t pol) {
    asm volatile("st.global.L2::cache_hint.v4.b32 [%0], {%1, %2, %3, %4}, %5;" ::"l"(p), "r"(a), "r"(b), "r"(c), "r"(d), "l"(pol) : "memory");
}
__device__ __forceinline__ uint64_t policy_sel(bool first) {
    uint64_t p;
    asm("createpolicy.fractional.L2::evict_normal.b64 %0, 1.0;" : "=l"(p));
    return first ? policy_evict_first() : p;
}
__device__ __forceinline__ int perm_row(int t) { return (t & ~255) | (((0x78 >> (((t >> 6) & 3) * 2)) & 3) << 6) | (t & 63); }
__device__ __forceinline__ int unperm_row(int t) { return (t & ~255) | (((0x9C >> (((t >> 6) & 3) * 2)) & 3) << 6) | (t & 63); }

#define PROF(i)
#define PROFG(i)
#define PROFDUMP()
#define TR(i)
#define BP(r, i)
#define LP(i)

template <int I>
__device__ __forceinline__ void store_chunk(const float (&a)[64], __nv_bfloat16* row0, __nv_bfloat16* row1, float s0, float s1, uint64_t pol) {
    stg128p(row0 + 32 * I, pack_bf16(a[16 * I + 0] * s0, a[16 * I + 1] * s0), pack_bf16(a[16 * I + 4] * s0, a[16 * I + 5] * s0),
           pack_bf16(a[16 * I + 8] * s0, a[16 * I + 9] * s0), pack_bf16(a[16 * I + 12] * s0, a[16 * I + 13] * s0), pol);
    stg128p(row1 + 32 * I, pack_bf16(a[16 * I + 2] * s1, a[16 * I + 3] * s1), pack_bf16(a[16 * I + 6] * s1, a[16 * I + 7] * s1),
           pack_bf16(a[16 * I + 10] * s1, a[16 * I + 11] * s1), pack_bf16(a[16 * I + 14] * s1, a[16 * I + 15] * s1), pol);
}
template <int I>
struct IntT { static constexpr int value = I; };
template <class F>
__device__ __forceinline__ void for4(F f) { f(IntT<0>{}); f(IntT<1>{}); f(IntT<2>{}); f(IntT<3>{}); }

struct Prod {
    uint32_t smem, bars;
    uint32_t bo, par;
    uint32_t dst, fb;
    __device__ __forceinline__ void acquire(uint32_t o, uint32_t parity, uint32_t bytes) {
        mbar_wait(bars + BAR_EMPTY + o, parity);
        fb = bars + BAR_FULL + o;
        dst = smem + o * (SLOT / 8);
        w_expect_tx(fb, bytes);
    }
    __device__ __forceinline__ void next(uint32_t bytes) {
        acquire(bo, par, bytes);
        const bool wrap = bo == (NSLOT - 1) * 8;
        bo = wrap ? 0u : bo + 8;
        par ^= wrap ? 1u : 0u;
    }
};

__device__ __forceinline__ int item_p(int ca, int rd) {
    const int v = (rd & 1) ? (ca + 4) & 7 : ca;
    return (rd & 2) ? 7 - v : v;
}
__device__ __forceinline__ int n_items(int ca, int cb) { return cb == 8 ? (OFFLOAD ? 8 : 0) : (OFFLOAD && (ca & 3) == 3) ? 3 : 4; }
__device__ __forceinline__ int item_rd(int ca, int cb, int j) { return cb == 8 ? 2 + ca : (OFFLOAD && ca == 7 && j == 2) ? 3 : j; }
__device__ __forceinline__ int item_h(int cb, int rd, int j) { return 8 * rd + (cb == 8 ? j : cb); }
__device__ __forceinline__ int item_q(int ca, int cb, int rd) { return cb == 8 ? 0 : item_p(ca, rd); }
__device__ __forceinline__ int out_p(int ca, int cb) { return (cb + 2 * (ca & 3)) & 7; }
__device__ __forceinline__ int kv_round(int i) { return (KVORDER >> (4 * i)) & 3; }
__device__ __forceinline__ int slot_a(int i) { return (0x5310 >> (4 * i)) & 15; }
__device__ __forceinline__ int slot_w(int m) { return (0x264 >> (4 * m)) & 15; }

__device__ __forceinline__ void producer(const Params& P, uint32_t smem, uint32_t bars, int ca, int cb, int rank) {
    Prod pr{smem, bars, 0u, cb == 8 ? 1u : 0u, 0u, 0u};
    if (cb < 8) {
        int m = 0;
        uint32_t lap = 1;
#pragma unroll 1
        for (int u = 0; u < 32; u++) {
            if (u >= 3) {
                const int v = (u == 3) ? 3 + ca : u + 7;
                if (v < 32 && (u == 3 || (v & 7) == ca)) w_tma_prefetch((v & 4) ? &P.wuv : &P.wuk, (cb + 8 * kv_round(v >> 3)) * 128 + rank * 64, (v & 3) * 128);
                if (u == 24) {
                    w_tma_prefetch(&P.wq, cb * 128 + rank * 64, ca * 64);
                    if (ca < 2) w_tma_prefetch(&P.wq, cb * 128 + rank * 64, (ca + 8) * 64);
                }
            }
            if (u >= FASTSTART) pr.acquire(slot_w(m) * 8, lap ^ (m >> 1), SLOT);
            lap ^= m >> 1;
            m = (m == 2) ? 0 : m + 1;
            TR(1 + u);
            if (u >= FASTSTART) w_tma_load_mc(pr.dst + rank * 16384, (u & 4) ? &P.wuv : &P.wuk, (cb + 8 * kv_round(u >> 3)) * 128 + rank * 64, (u & 3) * 128, pr.fb);
            if (u < 3 && u + 1 >= FASTSTART) {
                pr.acquire(slot_a(u + 1) * 8, 1, SLOT);
                w_tma_load(pr.dst, &P.ckv, u * 128 + 128, (2 * ca + rank) * 128, pr.fb);
                w_tma_load(pr.dst + 16384, &P.ckv, u * 128 + 192, (2 * ca + rank) * 128, pr.fb);
            }
        }
    }
    PROF(1);
    mbar_wait_sleep(bars + BAR_DEP, 0);
#pragma unroll 1
    for (int j = 0, pfs = 1; j < n_items(ca, cb); j++) {
        const int rd = item_rd(ca, cb, j), h = item_h(cb, rd, j), p = item_q(ca, cb, rd);
#pragma unroll 1
        for (int ks = 0; ks < 10; ks++) {
            pr.next(SLOT);
            w_tma_load_mc(pr.dst + 16384 + rank * 8192, &P.wq, h * 128 + rank * 64, ks * 64, pr.fb);
            w_tma_load(pr.dst, &P.xn, ks * 64, 256 * p + 128 * rank, pr.fb);
            if (cb == 8 && j < 7) w_tma_prefetch(&P.wq, (h + 1) * 128 + rank * 64, ks * 64);
        }
        PROF(8 + rd * 4);
        mbar_wait(bars + BAR_DEP + (1 + (cb == 8 ? j : rd)) * 8, 0);
        const int last = 4 * p + 3, top = h * 32 + last;
#pragma unroll 1
        for (int i = 0; i <= last; i++) {
            const int t = (i == 0) ? top - 1 : (i == last) ? h * 32 + 1 : (i & 1) ? top - 2 - i : top + 2 - i;
            pr.next(SLOT);
            const bool lastrd = (cb == 8) ? false : (rd == 0) ? ((LASTRD & 1) && ca >= 8 - LASTN) : (rd == 1) ? ((LASTRD & 2) && (ca & 3) >= 4 - LASTN) : (rd == 2) ? ((LASTRD & 4) && (ca == 3 || (ca < 3 && (t & 31) >= 4 * p))) : (LASTRD & 8) != 0;
            if (lastrd) w_tma_load_mc_last(pr.dst + rank * 16384, &P.kv, rank * 64, t * 128, pr.fb);
            else w_tma_load_mc(pr.dst + rank * 16384, &P.kv, rank * 64, t * 128, pr.fb);
            if (i == 2 && cb < 8) {
                const int upto = (j == n_items(ca, cb) - 1) ? 4 : item_rd(ca, cb, j + 1);
#pragma unroll 1
                for (; pfs <= upto; pfs++) {
                    if (pfs < 4) {
                        w_tma_prefetch(&P.wq, (8 * pfs + cb) * 128 + rank * 64, ca * 64);
                        if (ca < 2) w_tma_prefetch(&P.wq, (8 * pfs + cb) * 128 + rank * 64, (ca + 8) * 64);
                    } else {
#pragma unroll 1
                        for (int k = 0; k < 10; k++)
                            w_tma_prefetch(&P.wo, 320 * (ca >> 2) + 64 * (k >= 5 ? k - 5 : k), (cb * 4 + (ca & 3) + (k >= 5 ? 32 : 0)) * 64 + rank * 32);
                    }
                }
            }
        }
        PROF(9 + rd * 4);
    }
    if (cb < 8) {
        const int n0 = 320 * (ca >> 2), op = out_p(ca, cb);
        uint32_t* pool = g_flags + (F_POOL + op * 2 + (ca >> 2)) * 8;
        uint32_t base, nxt = 0;
        asm volatile("ld.shared.u32 %0, [%1];" : "=r"(base) : "r"(bars + MISC_OFF) : "memory");
        base = base * 44 - 8;
        auto draw = [&]() {
            if (rank == 0) asm volatile(ELECT "atom.relaxed.gpu.global.add.u32 %0, [%1], 1;\n}\n" : "+r"(nxt) : "l"(pool) : "memory");
        };
        int fixed = -1;
#pragma unroll 1
        for (int i = -2; fixed < 4; i++) {
            int st = (ca & 3) + 4 * (i + 2);
            if (i == -1) draw();
            if (i >= 0 && fixed < 0) {
                const uint32_t mb = bars + BAR_MAIL + (i & 7) * 8, md = bars + MAIL_OFF + (i & 7) * 4;
                if (rank == 0) {
                    st = __reduce_add_sync(0xffffffffu, nxt) - base;
                    asm volatile(ELECT "st.async.shared::cluster.mbarrier::complete_tx::bytes.b32 [%0], %1, [%2];\n}\n" ::"r"(mapa(md, 1)), "r"(st), "r"(mapa(mb, 1)) : "memory");
                    if (st < 48) draw();
                } else {
                    w_expect_tx(mb, 4);
                    mbar_wait(mb, (i >> 3) & 1);
                    asm volatile("ld.shared.u32 %0, [%1];" : "=r"(st) : "r"(md) : "memory");
                    st = __reduce_or_sync(0xffffffffu, st);
                }
                if (st >= 48) fixed = 0;
            }
            if (fixed >= 0) { st = 48 + (ca & 3) + 4 * fixed; fixed++; }
            const int krow = st * 64 + rank * 32;
            mbar_wait(bars + BAR_EMPTY + pr.bo, pr.par);
            asm volatile("st.shared.u32 [%0], %1;" ::"r"(bars + CTL_OFF + pr.bo), "r"((int)(fixed == 1)) : "memory");
            __syncwarp();
            pr.next(SLOT);
            w_tma_load_mc(pr.dst + 16384 + rank * 8192, &P.wo, n0, krow, pr.fb);
            w_tma_load_mc(pr.dst + 16384 + rank * 8192 + 4096, &P.wo, n0 + 64, krow, pr.fb);
            mbar_wait(bars + BAR_DEP + (5 + (st >> 4)) * 8, 0);
            w_tma_load(pr.dst, &P.ctx, (st & 1) * 64, (st >> 1) * SEQ + 256 * op + 128 * rank, pr.fb);
            pr.next(24576);
#pragma unroll
            for (int c = 0; c < 3; c++) w_tma_load_mc(pr.dst + rank * 12288 + c * 4096, &P.wo, n0 + 128 + 64 * c, krow, pr.fb);
        }
    }
}

struct Slot {
    uint32_t bo, dl, par;
};
struct Cons {
    uint32_t bars, rel;
    uint32_t dl0;
    uint32_t lane;
    Slot cur;
    __device__ __forceinline__ Slot slot(int s, uint32_t par) const { return Slot{(uint32_t)s * 8, dl0 + (uint32_t)s * (SLOT >> 4), par}; }
    __device__ __forceinline__ void wait(const Slot& s) const { mbar_wait(bars + BAR_FULL + s.bo, s.par); }
    __device__ __forceinline__ void release(uint32_t bo) const {
        asm volatile("{\n.reg .pred p;\nsetp.lt.u32 p, %1, 2;\n@p mbarrier.arrive.shared::cluster.b64 _, [%0];\n}\n" ::"r"(rel + bo), "r"(lane) : "memory");
    }
    __device__ __forceinline__ Slot next() {
        const Slot s = cur;
        const bool wrap = s.bo == (NSLOT - 1) * 8;
        cur.bo = wrap ? 0u : s.bo + 8;
        cur.dl = wrap ? dl0 : s.dl + (SLOT >> 4);
        cur.par = s.par ^ (wrap ? 1u : 0u);
        return s;
    }
};
__host__ __device__ constexpr uint32_t lbo(uint32_t bytes) { return (bytes >> 4) << 16; }

__device__ __forceinline__ float div640(float x) {
    const float q = x * (1.0f / DM);
    return fmaf(fmaf(-q, (float)DM, x), 1.0f / DM, q);
}
__device__ __forceinline__ float sqrt_approx(float x) {
    float y;
    asm("sqrt.approx.ftz.f32 %0, %1;" : "=f"(y) : "f"(x));
    return y;
}
struct LayerNorm {
    uint4 xv[5], wv[5];
    float mean, inv, r;
    static __device__ __forceinline__ float half_sum(float v) {
#pragma unroll
        for (int o = 8; o > 0; o >>= 1) v += __shfl_xor_sync(0xffffffffu, v, o);
        return v;
    }
    __device__ __forceinline__ void load(const __nv_bfloat16* x, const __nv_bfloat16* wr, int t, int l) {
#pragma unroll
        for (int i = 0; i < 5; i++) {
            xv[i] = ldg_stream(reinterpret_cast<const uint4*>(x + t * DM) + l + 16 * i);
            wv[i] = __ldg(reinterpret_cast<const uint4*>(wr) + l + 16 * i);
        }
    }
    __device__ __forceinline__ void stat1() {
        float a[4] = {0.f, 0.f, 0.f, 0.f};
#pragma unroll
        for (int i = 0; i < 20; i++) { const uint32_t u = (&xv[i >> 2].x)[i & 3]; a[i & 3] += bf_lo(u) + bf_hi(u); }
        mean = div640(half_sum((a[0] + a[1]) + (a[2] + a[3])));
        r = 0.f;
    }
    template <int H>
    __device__ __forceinline__ void stat2() {
        float a[4] = {r, 0.f, 0.f, 0.f};
#pragma unroll
        for (int i = H ? 12 : 0; i < (H ? 20 : 12); i++) {
            uint32_t u = (&xv[i >> 2].x)[i & 3];
            asm volatile("" : "+r"(u));
            const float d0 = bf_lo(u) - mean, d1 = bf_hi(u) - mean;
            a[i & 3] = fmaf(d0, d0, fmaf(d1, d1, a[i & 3]));
        }
        r = (a[0] + a[1]) + (a[2] + a[3]);
        if (H) {
            inv = rcp(round_bf16(sqrt_approx(round_bf16(round_bf16(div640(half_sum(r))) + 1e-5f))));
            r = 0.f;
        }
    }
    template <int I>
    __device__ __forceinline__ void piece(__nv_bfloat16* out, int t, int l) {
        const uint32_t nmb = pack_bf16(-mean, -mean);
        uint32_t o[4], z[4];
        float a[4];
#pragma unroll
        for (int j = 0; j < 4; j++) {
            const uint32_t u = (&xv[I].x)[j], w = (&wv[I].x)[j];
            const uint32_t d = add_bf16x2(u, nmb);
            o[j] = pack_bf16(bf_lo(d) * inv, bf_hi(d) * inv);
            z[j] = add_bf16x2(u, o[j]);
            a[j] = fmaf(bf_hi(o[j]), bf_hi(w), bf_lo(o[j]) * bf_lo(w));
        }
        r += (a[0] + a[1]) + (a[2] + a[3]);
        stg128(g_xn + perm_row(t) * DM + 8 * (l + 16 * I), o[0], o[1], o[2], o[3]);
        stg128p(out + t * DM + 8 * (l + 16 * I), z[0], z[1], z[2], z[3], policy_sel(EFMASK & 1));
        if (I == 4) {
            r = half_sum(r);
            if (l == 0) g_r[t] = round_bf16(r);
        }
    }
};

constexpr float SM_SCALE = 0.08838834764831845f * 1.4426950408889634f;

template <int J0, int J1>
__device__ __forceinline__ void exp_part(float (&s)[64], float n0, float n1, float& r0, float& r1) {
    float a1 = 0.f, b1 = 0.f;
#pragma unroll
    for (int j = J0; j < J1; j++) {
        s[4 * j + 0] = ex2(fmaf(s[4 * j + 0], SM_SCALE, n0));
        s[4 * j + 1] = ex2(fmaf(s[4 * j + 1], SM_SCALE, n0));
        s[4 * j + 2] = ex2(fmaf(s[4 * j + 2], SM_SCALE, n1));
        s[4 * j + 3] = ex2(fmaf(s[4 * j + 3], SM_SCALE, n1));
        r0 += s[4 * j + 0]; r1 += s[4 * j + 2];
        if (j == J0) { a1 = s[4 * j + 1]; b1 = s[4 * j + 3]; } else { a1 += s[4 * j + 1]; b1 += s[4 * j + 3]; }
    }
    r0 += a1;
    r1 += b1;
}
__device__ __forceinline__ void sched_barrier(float x, float y, uint32_t scratch) {
    asm volatile("{\n.reg .pred p;\nsetp.lt.f32 p, %0, 0f00000000;\n@p st.shared.f32 [%2], %1;\n}\n" ::"f"(x), "f"(y), "r"(scratch) : "memory");
}
__device__ __forceinline__ void pack_tile(const float (&s)[64], uint32_t (&p)[32]) {
#pragma unroll
    for (int i = 0; i < 32; i++) p[i] = pack_bf16(s[2 * i], s[2 * i + 1]);
}
template <bool ZERO>
__device__ __forceinline__ void gemm_rs(float (&d)[64], const uint32_t (&a)[32], uint32_t dl, int acc = 1) {
    const uint32_t b = dl + lbo(16384);
    if (ZERO) wgmma_rs_n128_z<1>(d, a[0], a[1], a[2], a[3], b);
#pragma unroll
    for (int k = ZERO ? 1 : 0; k < 8; k++) wgmma_rs_n128<1>(d, a[4 * k], a[4 * k + 1], a[4 * k + 2], a[4 * k + 3], b + k * 128, k ? 1 : acc);
}
template <int ZERO>
__device__ __forceinline__ void gemm_q(float (&d)[64], uint32_t dl, int role) {
    const uint32_t a = dl + role * 512 + lbo(16), b = dl + 1024 + lbo(8192);
    if (ZERO) wgmma_ss_n128_z<0, 1>(d, a, b);
#pragma unroll
    for (int k = ZERO ? 1 : 0; k < 4; k++) wgmma_ss_n128<0, 1>(d, a + k * 2, b + k * 128, 1);
}
template <bool KT, bool ZERO, int K0, int K1>
__device__ __forceinline__ void gemm_kv(float (&d)[64], uint32_t ckv, uint32_t wt, int wg) {
    if (KT) {
        const uint32_t a = wt + wg * 1024 + lbo(16), b = ckv + lbo(16);
        if (ZERO) wgmma_ss_n128_z<1, 0>(d, a, b);
#pragma unroll
        for (int k = ZERO ? 1 : K0; k < K1; k++) wgmma_ss_n128<1, 0>(d, a + k * 128, b + (k >> 2) * 1024 + (k & 3) * 2, 1);
    } else {
        const uint32_t a = ckv + wg * 512 + lbo(16), b = wt + lbo(16384);
        if (ZERO) wgmma_ss_n128_z<0, 1>(d, a, b);
#pragma unroll
        for (int k = ZERO ? 1 : K0; k < K1; k++) wgmma_ss_n128<0, 1>(d, a + (k >> 2) * 1024 + (k & 3) * 2, b + k * 128, 1);
    }
}
__device__ __forceinline__ void mma16816(float& d0, float& d1, float& d2, float& d3, uint32_t a0, uint32_t a1, uint32_t a2, uint32_t a3, uint32_t b0, uint32_t b1) {
    asm volatile("mma.sync.aligned.m16n8k16.row.col.f32.bf16.bf16.f32 {%0,%1,%2,%3}, {%4,%5,%6,%7}, {%8,%9}, {%0,%1,%2,%3};"
                 : "+f"(d0), "+f"(d1), "+f"(d2), "+f"(d3) : "r"(a0), "r"(a1), "r"(a2), "r"(a3), "r"(b0), "r"(b1));
}
__device__ __forceinline__ uint32_t ld_pair(const __nv_bfloat16* p) {
    const unsigned short* u = reinterpret_cast<const unsigned short*>(p);
    return (uint32_t)__ldcg(u) | ((uint32_t)__ldcg(u + 128) << 16);
}
__device__ __forceinline__ void attention_exact(float (&o)[64], const uint32_t (&qf)[32], float& l0, float& l1, int h, int nblk, int rr, int lane) {
    const int q = lane & 3, lr = lane >> 2;
    float m0 = -INFINITY, m1 = -INFINITY;
    l0 = 0.f; l1 = 0.f;
#pragma unroll
    for (int i = 0; i < 64; i++) o[i] = 0.f;
#pragma unroll 1
    for (int cidx = 0; cidx < nblk * 8; cidx++) {
        const int kc = cidx & 7;
        const __nv_bfloat16* kt = g_kv + (size_t)((h * 16 + (cidx >> 3)) * 2) * 16384;
        float sc[8];
#pragma unroll
        for (int i = 0; i < 8; i++) sc[i] = 0.f;
#pragma unroll
        for (int kk = 0; kk < 8; kk++)
#pragma unroll
            for (int nt = 0; nt < 2; nt++) {
                const __nv_bfloat16* b = kt + (16 * kk + 2 * q) * 128 + 16 * kc + 8 * nt + lr;
                mma16816(sc[4 * nt], sc[4 * nt + 1], sc[4 * nt + 2], sc[4 * nt + 3], qf[4 * kk], qf[4 * kk + 1], qf[4 * kk + 2], qf[4 * kk + 3],
                         ld_pair(b), ld_pair(b + 8 * 128));
            }
        const int lim = rr + ((nblk - 1) - (cidx >> 3)) * 128 - 32 * (kc >> 1) - 4 * (kc & 1);
#pragma unroll
        for (int i = 0; i < 8; i++)
            if (2 * (i >> 2) + (i & 1) > lim + 4 * (i & 2)) sc[i] = -INFINITY;
        float x0 = fmaxf(fmaxf(sc[0], sc[1]), fmaxf(sc[4], sc[5])), x1 = fmaxf(fmaxf(sc[2], sc[3]), fmaxf(sc[6], sc[7]));
        x0 = fmaxf(x0, __shfl_xor_sync(0xffffffffu, x0, 1)); x1 = fmaxf(x1, __shfl_xor_sync(0xffffffffu, x1, 1));
        x0 = fmaxf(x0, __shfl_xor_sync(0xffffffffu, x0, 2)); x1 = fmaxf(x1, __shfl_xor_sync(0xffffffffu, x1, 2));
        x0 = fmaxf(x0, m0); x1 = fmaxf(x1, m1);
        const float a0 = ex2((m0 - x0) * SM_SCALE), a1 = ex2((m1 - x1) * SM_SCALE);
        m0 = x0; m1 = x1;
#pragma unroll
        for (int i = 0; i < 8; i++) sc[i] = ex2((sc[i] - ((i & 2) ? m1 : m0)) * SM_SCALE);
        l0 = l0 * a0 + (sc[0] + sc[1]) + (sc[4] + sc[5]);
        l1 = l1 * a1 + (sc[2] + sc[3]) + (sc[6] + sc[7]);
        const uint32_t p0 = pack_bf16(sc[0], sc[1]), p1 = pack_bf16(sc[2], sc[3]), p2 = pack_bf16(sc[4], sc[5]), p3 = pack_bf16(sc[6], sc[7]);
        const __nv_bfloat16* vb = kt + 16384 + (16 * kc + 2 * q) * 128 + lr;
#pragma unroll
        for (int nt = 0; nt < 16; nt++) {
            o[4 * nt] *= a0; o[4 * nt + 1] *= a0; o[4 * nt + 2] *= a1; o[4 * nt + 3] *= a1;
            mma16816(o[4 * nt], o[4 * nt + 1], o[4 * nt + 2], o[4 * nt + 3], p0, p1, p2, p3, ld_pair(vb + 8 * nt), ld_pair(vb + 8 * nt + 8 * 128));
        }
    }
}

__device__ __forceinline__ void signal(uint32_t bars, int wg, int e, int lane) {
    __syncwarp();
    asm volatile("{\n.reg .pred p;\nsetp.eq.u32 p, %1, 0;\n@p mbarrier.arrive.shared::cta.b64 _, [%0];\n}\n" ::"r"(bars + BAR_SIG + (wg * 9 + e) * 8), "r"(lane) : "memory");
}

__device__ __forceinline__ void mod_ffn(const Params& P, uint32_t smem, int mc, int wg);

__device__ __forceinline__ void consumer(const Params& P, uint32_t smem, uint32_t bars, int ca, int cb, int rank, int wg) {
    const int lane = threadIdx.x & 31, w = (threadIdx.x >> 5) & 3, q = lane & 3, lr = lane >> 2;
    PROF(7);
    cluster_wait();
    Cons c{bars, mapa(bars + BAR_EMPTY, lane & 1), (smem & 0x3FFFF) >> 4, (uint32_t)lane, Slot{0u, (smem & 0x3FFFF) >> 4, cb == 8 ? 0u : 1u}};
    PROFG(180);
    PROF(1);
    float o[64], s[64];
    uint32_t pend;
    __nv_bfloat16* ep_ptr;
    int ep_step;
    if (cb == 8) {
        pend = 0;
        ep_ptr = g_ctx + (size_t)(item_h(cb, 2 + ca, 0) * SEQ + 128 * rank + 64 * wg + 16 * w + lr) * HD + 8 * q;
        ep_step = 8 * HD;
    } else {
        const int ln_t = blockIdx.x * 16 + wg * 8 + w * 2 + (lane >> 4);
        const int krow = 64 * wg + 16 * w + lr;
        const int vrow = 64 * wg + 32 * (w >> 1) + 8 * (lr >> 1) + 4 * (w & 1) + (lr & 1);
        ep_step = 2 * 128;
        int m = 0;
        uint32_t lap = 0;
        LayerNorm ln;
        auto step = [&](auto kt, auto kc, float (&d)[64], int hh) {
            const Slot sa = c.slot(slot_a(kc.value), 0), sw = c.slot(slot_w(m), lap ^ (m >> 1));
            lap ^= m >> 1;
            m = (m == 2) ? 0 : m + 1;
            TR(1 + (hh * 8 + (kt.value ? 0 : 4) + kc.value) * 2);
            if (kt.value && hh == 0) c.wait(sa);
            c.wait(sw);
            TR(2 + (hh * 8 + (kt.value ? 0 : 4) + kc.value) * 2);
            wgmma_fence();
            gemm_kv<kt.value, kc.value == 0, 0, KVSPLIT>(d, sa.dl, sw.dl, wg);
            wgmma_commit();
            wgmma_wait<1>();
            if (!(kt.value && kc.value == 0 && hh == 0)) c.release(pend);
            if (!kt.value && kc.value > 0 && hh == 3) c.release(slot_a(kc.value - 1) * 8);
            pend = sw.bo;
            wgmma_fence();
            gemm_kv<kt.value, false, KVSPLIT, 8>(d, sa.dl, sw.dl, wg);
            wgmma_commit();
        };
#pragma unroll 1
        for (int hh = 0; hh < 4; hh++) {
            __nv_bfloat16* base = g_kv + (size_t)(((cb + 8 * kv_round(hh)) * 16 + 2 * ca + rank) * 2) * 16384 + 8 * q;
            auto ln_stage = [&](auto pos) {
                constexpr int j = (pos.value + 8 - LNOFF % 8) % 8;
                if (hh == wg * LNSTAG + (LNOFF + j) / 8) {
                    if (j == 0) ln.stat1();
                    if (j == 1) ln.template stat2<0>();
                    if (j == 2) ln.template stat2<1>();
                    if constexpr (j >= 3) ln.template piece<j - 3>(P.out, ln_t, lane & 15);
                    if (j == 7) signal(bars, wg, 0, lane);
                }
                if (pos.value == (LNOFF - LNLEAD) % 8 && hh == wg * LNSTAG + (LNOFF - LNLEAD) / 8) ln.load(P.x, P.wr, ln_t, lane & 15);
            };
            for4([&](auto kc) {
                step(TrueT{}, kc, s, hh);
                if (hh > 0) {
                    if (kc.value == 0) fence_regs(o);
                    store_chunk<kc.value>(o, ep_ptr, ep_ptr + ep_step, 1.f, 1.f, policy_sel(false));
                    if (kc.value == 3) signal(bars, wg, hh, lane);
                }
                ln_stage(kc);
            });
            for4([&](auto kc) {
                step(FalseT{}, kc, o, hh);
                if (kc.value == 0) fence_regs(s);
                store_chunk<kc.value>(s, base + krow * 128, base + (krow + 8) * 128, 1.f, 1.f, policy_sel(false));
                ln_stage(IntT<kc.value + 4>{});
            });
            PROF(24 + hh);
            if (hh == 1) PROFG(181);
            ep_ptr = base + 16384 + vrow * 128;
        }
    }
    PROFG(182);
    PROF(2);
    uint32_t pf[32];
    {
        uint32_t qf[32];
        float l0 = 0.25f, l1 = 0.25f;
        const int bar_me = 2 + wg, bar_other = 3 - wg;
#pragma unroll 1
        for (int j = 0; j < n_items(ca, cb); j++) {
            const int rd = item_rd(ca, cb, j), h = item_h(cb, rd, j), p = item_q(ca, cb, rd);
            const int role = wg ^ (j & 1);
            const int nrest = 2 * p + role;
            Slot kfirst;
            const int lim = 64 * (role ^ rank) + 16 * w + lr - 8 * q;
            const uint64_t pol = policy_sel(((EFMASK & 4) && j == 1) || ((EFMASK & 8) && j == 2));
            {
                auto qstep = [&](auto zero, int ks) {
                    const Slot sl = c.next();
                    c.wait(sl);
                    BP(2, 5 + 3 * ks);
                    wgmma_fence();
                    gemm_q<zero.value>(s, sl.dl, role);
                    wgmma_commit();
                    wgmma_wait<1>();
                    if (!zero.value || j > 0 || cb < 8) c.release(pend);
                    pend = sl.bo;
                };
                qstep(TrueT{}, 0);
                if (j == 0 && cb < 8) c.release(slot_a(3) * 8);
                fence_regs(o);
                l0 += __shfl_xor_sync(0xffffffffu, l0, 1); l1 += __shfl_xor_sync(0xffffffffu, l1, 1);
                l0 += __shfl_xor_sync(0xffffffffu, l0, 2); l1 += __shfl_xor_sync(0xffffffffu, l1, 2);
                l0 = rcp(l0); l1 = rcp(l1);
                for4([&](auto i) {
                    constexpr int B = 16 * i.value;
#pragma unroll
                    for (int r = 0; r < 2; r++) {
                        qstep(FalseT{}, 1 + 2 * i.value + r);
                        const float f = r ? l1 : l0;
                        stg128p(ep_ptr + r * ep_step + 2 * B, pack_bf16(o[B + 2 * r] * f, o[B + 2 * r + 1] * f), pack_bf16(o[B + 2 * r + 4] * f, o[B + 2 * r + 5] * f),
                                pack_bf16(o[B + 2 * r + 8] * f, o[B + 2 * r + 9] * f), pack_bf16(o[B + 2 * r + 12] * f, o[B + 2 * r + 13] * f), pol);
#pragma unroll
                        for (int k = 0; k < 8; k++) {
                            float& v = o[B + 4 * (k >> 1) + 2 * r + (k & 1)];
                            v = (2 * B + k > lim + 8 * r) ? -1e30f : 0.f;
                            asm volatile("" : "+f"(v));
                        }
                    }
                });
                signal(bars, wg, (cb == 8 ? 0 : 4) + j, lane);
                PROF(11 + rd * 4);
                qstep(FalseT{}, 9);
                if (!role) { const Slot sl = c.next(); c.wait(sl); c.release(sl.bo); }
                kfirst = c.next();
                c.wait(kfirst);
                wgmma_wait<0>();
                BP(2, 34);
                c.release(pend);
                fence_regs(s);
                pack_tile(s, qf);
            }
            PROF(8 + rd * 4);
            if (cb == 8) PROF(40 + 3 * j);
            fence_regs(qf); fence_regs(o);
            if (PINGPONG && !role) named_sync(bar_me, 256);
            BP(2, 36);
            wgmma_fence();
            gemm_rs<false>(o, qf, kfirst.dl);
            wgmma_commit();
            if (PINGPONG) named_arrive(bar_other, 256);
            if (!role) { const Slot sl = c.next(); c.wait(sl); c.release(sl.bo); }
            wgmma_wait<0>();
            BP(2, 38);
            fence_regs(o);
            c.release(kfirst.bo);
            float n0 = fmaxf(fmaxf(fmaxf(o[0], o[1]), fmaxf(o[4], o[5])), fmaxf(fmaxf(o[8], o[9]), fmaxf(o[12], o[13])));
            float n1 = fmaxf(fmaxf(fmaxf(o[2], o[3]), fmaxf(o[6], o[7])), fmaxf(fmaxf(o[10], o[11]), fmaxf(o[14], o[15])));
            n0 = __shfl_sync(0xffffffffu, n0, lane & 28); n1 = __shfl_sync(0xffffffffu, n1, lane & 28);
            n0 *= -SM_SCALE; n1 *= -SM_SCALE;
            l0 = 0.f; l1 = 0.f;
#pragma unroll
            for (int i = 0; i < 64; i++) s[i] = o[i];
            exp_part<0, 8>(s, n0, n1, l0, l1);
#pragma unroll
            for (int i = 0; i < 16; i++) pf[i] = pack_bf16(s[2 * i], s[2 * i + 1]);
            if (role != rank) {
                exp_part<8, 16>(s, n0, n1, l0, l1);
#pragma unroll
                for (int i = 16; i < 32; i++) pf[i] = pack_bf16(s[2 * i], s[2 * i + 1]);
            } else {
#pragma unroll
                for (int i = 16; i < 32; i++) pf[i] = 0u;
            }
            PROF(9 + rd * 4);
            if (cb == 8) PROF(41 + 3 * j);
#pragma unroll 1
            for (int it = 0; it < nrest; it++) {
                const Slot sk = c.next(), sv = c.next();
                LP(0);
                c.wait(sk);
                c.wait(sv);
                fence_regs(o); fence_regs(pf);
                LP(1);
                if (PINGPONG) named_sync(bar_me, 256);
                LP(2);
                if (it < 3) BP(2, 42 + 4 * it);
                if (it >= nrest - 2) BP(1, 62 + 4 * (it - nrest + 2));
                wgmma_fence();
                gemm_rs<true>(s, qf, sk.dl);
                wgmma_commit();
                gemm_rs<false>(o, pf, sv.dl, it);
                wgmma_commit();
                if (PINGPONG) named_arrive(bar_other, 256);
                LP(3);
                wgmma_wait<1>();
                LP(4);
                c.release(sk.bo);
                fence_regs(s);
                exp_part<0, SPLITJ>(s, n0, n1, l0, l1);
                sched_barrier(l0, l1, bars + MISC_OFF + 16);
                LP(5);
                wgmma_wait<0>();
                LP(6);
                c.release(sv.bo);
                fence_regs(o); fence_regs(pf);
                exp_part<SPLITJ, 16>(s, n0, n1, l0, l1);
                pack_tile(s, pf);
            }
            PROF(10 + rd * 4);
            if (cb == 8) PROF(42 + 3 * j);
            PROFG(183 + rd);
            const Slot sv = c.next();
            BP(1, 0);
            c.wait(sv);
            if (nrest == 0) {
#pragma unroll
                for (int i = 0; i < 64; i++) o[i] = 0.f;
            }
            if (__builtin_expect(__any_sync(0xffffffffu, !(l0 < 0x1p60f && l1 < 0x1p60f)), 0)) {
                attention_exact(o, qf, l0, l1, h, nrest + 1, lim, lane);
#pragma unroll
                for (int i = 0; i < 32; i++) pf[i] = 0u;
            }
            fence_regs(o); fence_regs(pf);
            if (PINGPONG && !role) named_sync(bar_me, 256);
            BP(1, 2);
            wgmma_fence();
            gemm_rs<false>(o, pf, sv.dl);
            wgmma_commit();
            pend = sv.bo;
            ep_ptr = g_ctx + (size_t)(h * SEQ + 256 * p + 128 * rank + 64 * role + 16 * w + lr) * HD + 8 * q;
            ep_step = 8 * HD;
        }
        l0 += __shfl_xor_sync(0xffffffffu, l0, 1); l1 += __shfl_xor_sync(0xffffffffu, l1, 1);
        l0 += __shfl_xor_sync(0xffffffffu, l0, 2); l1 += __shfl_xor_sync(0xffffffffu, l1, 2);
        l0 = rcp(l0); l1 = rcp(l1);
        wgmma_wait<0>();
        c.release(pend);
        fence_regs(o); fence_regs(pf);
#pragma unroll
        for (int i = 0; i < 32; i++) pf[i] = pack_bf16(o[2 * i] * ((i & 1) ? l1 : l0), o[2 * i + 1] * ((i & 1) ? l1 : l0));
    }
    PROFG(187);
    PROF(3);
    if (cb == 8) {
#pragma unroll
        for (int i = 0; i < 8; i++) stg128(ep_ptr + (i & 1) * 8 * HD + 32 * (i >> 1), pf[4 * (i & 6) + (i & 1)], pf[4 * (i & 6) + (i & 1) + 2], pf[4 * (i & 6) + (i & 1) + 4], pf[4 * (i & 6) + (i & 1) + 6]);
        signal(bars, wg, 8, lane);
        cluster_arrive();
        named_sync(1, 256);
        mod_ffn(P, smem, 2 * ca + rank, wg);
    } else
    {
        float a1[64], a2[96];
        uint32_t px = 0, py = 0;
        auto mma1 = [&](const Slot& x, int acc) {
#pragma unroll
            for (int k = 0; k < 4; k++) wgmma_ss_n128<0, 1>(a1, x.dl + wg * 512 + lbo(16) + k * 2, x.dl + 1024 + lbo(4096) + (k >> 1) * 512 + (k & 1) * 128, k ? 1 : acc);
        };
        auto mma2 = [&](const Slot& x, const Slot& y, int acc) {
#pragma unroll
            for (int k = 0; k < 4; k++) wgmma_ss_n192<0, 1>(a2, x.dl + wg * 512 + lbo(16) + k * 2, y.dl + lbo(4096) + (k >> 1) * 768 + (k & 1) * 128, k ? 1 : acc);
        };
#pragma unroll 1
        for (int t = 0, more = 1; more; t++) {
            const Slot sx = c.next(), sy = c.next();
            c.wait(sx);
            wgmma_fence();
            mma1(sx, t);
            wgmma_commit();
            asm volatile("ld.shared.u32 %0, [%1];" : "=r"(more) : "r"(bars + CTL_OFF + sx.bo) : "memory");
            more = !__any_sync(0xffffffffu, more);
            wgmma_wait<1>();
            if (t > 0) { c.release(px); c.release(py); }
            px = sx.bo; py = sy.bo;
            c.wait(sy);
            wgmma_fence();
            mma2(sx, sy, t);
            wgmma_commit();
            if (t == 0) {
#pragma unroll
                for (int i = 0; i < 4; i++) stg128(ep_ptr + 32 * i, pf[8 * i], pf[8 * i + 2], pf[8 * i + 4], pf[8 * i + 6]);
            }
            if (t == 1) {
#pragma unroll
                for (int i = 0; i < 4; i++) stg128(ep_ptr + 8 * HD + 32 * i, pf[8 * i + 1], pf[8 * i + 3], pf[8 * i + 5], pf[8 * i + 7]);
                signal(bars, wg, 4 + n_items(ca, cb), lane);
            }
        }
        const Slot x0 = c.next(), y0 = c.next(), x1 = c.next(), y1 = c.next(), x2 = c.next(), y2 = c.next(), fr = c.next();
        const int cw = __reduce_or_sync(0xffffffffu, wg * 4 + w);
        const int orow = unperm_row(256 * out_p(ca, cb) + 128 * rank + 16 * cw), ocol = 320 * (ca >> 2);
        const uint32_t sa = ((lane & 7) + (lane & 8)) * 128, sx = (lane >> 4) ^ (lane & 7);
        auto send = [&](auto chv, uint32_t box) {
            constexpr int ch = chv.value;
#pragma unroll
            for (int i = 0; i < 4; i++) {
                uint32_t r[4];
#pragma unroll
                for (int e = 0; e < 4; e++) {
                    const int k = 32 * ch + 8 * i + 2 * e;
                    r[e] = (ch < 2) ? pack_bf16(a1[k & 63], a1[(k & 63) + 1]) : pack_bf16(a2[ch < 2 ? 0 : k - 64], a2[ch < 2 ? 1 : k - 63]);
                }
                asm volatile("stmatrix.sync.aligned.m8n8.x4.shared.b16 [%0], {%1, %2, %3, %4};"
                             ::"r"(box + sa + ((sx ^ (2 * i)) << 4)), "r"(r[0]), "r"(r[1]), "r"(r[2]), "r"(r[3]) : "memory");
            }
            asm volatile("fence.proxy.async.shared::cta;" ::: "memory");
            __syncwarp();
            asm volatile(ELECT "cp.reduce.async.bulk.tensor.2d.global.shared::cta.add.bulk_group [%0, {%2, %3}], [%1];\n}\n"
                         ::"l"(&P.outm), "r"(box), "r"(ocol + 64 * ch), "r"(orow) : "memory");
        };
        auto addr = [&](const Slot& t) { return smem + t.bo * (SLOT / 8); };
        c.wait(x0);
        wgmma_fence();
        mma1(x0, 1);
        wgmma_commit();
        wgmma_wait<1>();
        c.release(px); c.release(py);
        c.wait(x1);
        c.wait(x2);
        c.wait(y0);
        mbar_wait(bars + BAR_DEP, 0);
        wgmma_fence();
        mma1(x1, 1);
        mma1(x2, 1);
        wgmma_commit();
        mma2(x0, y0, 1);
        wgmma_commit();
        mbar_wait(bars + BAR_EMPTY + fr.bo, fr.par ^ 1);
        c.wait(y1);
        wgmma_wait<1>();
        fence_regs(a1);
        send(IntT<0>{}, addr(fr) + cw * 4096);
        wgmma_fence();
        mma2(x1, y1, 1);
        wgmma_commit();
        send(IntT<1>{}, addr(fr) + cw * 4096 + 2048);
        c.wait(y2);
        wgmma_fence();
        mma2(x2, y2, 1);
        wgmma_commit();
        wgmma_wait<0>();
        fence_regs(a2);
        PROFG(188);
        PROF(4);
        send(IntT<2>{}, addr(x0) + cw * 2048);
        send(IntT<3>{}, addr(x1) + cw * 2048);
        send(IntT<4>{}, addr(x2) + cw * 2048);
        PROF(5);
        asm volatile("cp.async.bulk.commit_group;\ncp.async.bulk.wait_group.read 0;" ::: "memory");
    }
    PROF(6);
}

__device__ __forceinline__ void mod_ffn(const Params& P, uint32_t smem, int mc  , int wg) {
    const int tid = threadIdx.x - 128, lane = tid & 31, cw = tid >> 5, q = lane & 3, lr = lane >> 2;
    const uint32_t xs = smem + 6 * SLOT, hs = xs + 10240 + wg * 1024, wmax = xs + 12288, sidx = wmax + 64, rbar = xs + 13312 + wg * 32;
    const uint32_t ring = smem + wg * 3 * SLOT;
    const int f0 = mc + 4 * wg, nunit = ((34 - f0) >> 3) * 8;
    const bool lead = __reduce_or_sync(0xffffffffu, cw & 3) == 0;
    auto lds = [](uint32_t a) { uint32_t v; asm volatile("ld.shared.u32 %0, [%1];" : "=r"(v) : "r"(a) : "memory"); return v; };
    auto sts = [](uint32_t a, uint32_t v) { asm volatile("st.shared.u32 [%0], %1;" ::"r"(a), "r"(v) : "memory"); };
    auto issue = [&](int u, int st) {
        if (lead && u < nunit) {
            const int fc = (f0 + (u & ~7)) * 64, k = u & 7;
            const uint32_t dst = ring + st * SLOT, bar = rbar + st * 8;
            w_expect_tx(bar, k == 7 ? 16384 : SLOT);
            if (k < 5) {
                w_tma_load_stream(dst, &P.wg, fc, k * 128, bar);
                w_tma_load_stream(dst + 16384, &P.wu, fc, k * 128, bar);
            } else {
#pragma unroll 1
                for (int b = 0; b < (k == 7 ? 2 : 4); b++) w_tma_load_stream(dst + b * 8192, &P.wd, (4 * (k - 5) + b) * 64, fc, bar);
            }
        }
    };
    if ((tid & 127) == 0) {
        mbar_init(rbar, 1); mbar_init(rbar + 8, 1); mbar_init(rbar + 16, 1);
        asm volatile("fence.mbarrier_init.release.cluster;" ::: "memory");
    }
    mbar_wait(smem + NSLOT * SLOT + BAR_DEP, 0);
    asm volatile("fence.proxy.async.shared::cta;" ::: "memory");
    named_sync(1, 256);
    PROF(1);
#pragma unroll 1
    for (int u = 0; u < 3; u++) issue(u, u);
    uint32_t key[8];
#pragma unroll
    for (int i = 0; i < 8; i++) {
        const int t = tid + 256 * i;
        uint32_t b = __float_as_uint(__ldcg(g_r + t) + 0.f) >> 16;
        b = (b & 0x8000u) ? (~b & 0xffffu) : (b | 0x8000u);
        key[i] = (b << 16) | (uint32_t)(0xffff - t);
    }
#pragma unroll 1
    for (int rnd = 0; rnd < 8; rnd++) {
        uint32_t mx = key[0];
#pragma unroll
        for (int i = 1; i < 8; i++) mx = max(mx, key[i]);
        sts(wmax + ((rnd & 1) * 8 + cw) * 4, __reduce_max_sync(0xffffffffu, mx));
        named_sync(1, 256);
        mx = __reduce_max_sync(0xffffffffu, lds(wmax + ((rnd & 1) * 8 + (lane & 7)) * 4));
#pragma unroll
        for (int i = 0; i < 8; i++) if (key[i] == mx) key[i] = 0;
        if (cw == rnd) sts(sidx + rnd * 4, 0xffff - (mx & 0xffffu));
    }
    __syncwarp();
    {
        const int t = lds(sidx + cw * 4);
        const uint4* src = reinterpret_cast<const uint4*>(g_xn + perm_row(t) * DM);
#pragma unroll
        for (int i = 0; i < 3; i++) {
            const int ch = lane + 32 * i;
            if (ch < 80) {
                const uint4 v = __ldcg(src + ch);
                asm volatile("st.shared.v4.b32 [%0], {%1, %2, %3, %4};" ::"r"(xs + (ch >> 3) * 1024 + cw * 128 + ((ch ^ cw) & 7) * 16), "r"(v.x), "r"(v.y), "r"(v.z), "r"(v.w) : "memory");
            }
        }
        asm volatile("fence.proxy.async.shared::cta;" ::: "memory");
    }
    named_sync(1, 256);
    PROF(3);
    float y[10][4];
#pragma unroll
    for (int i = 0; i < 10; i++) { y[i][0] = 0.f; y[i][1] = 0.f; y[i][2] = 0.f; y[i][3] = 0.f; }
    int st = 0, ph = 0, u = 0;
    auto begin = [&]() { mbar_wait(rbar + st * 8, ph); wgmma_fence(); return (((ring + st * SLOT) & 0x3FFFF) >> 4) + lbo(16); };
    auto end = [&]() {
        wgmma_commit();
        wgmma_wait<0>();
        named_sync(4 + wg, 128);
        issue(u + 3, st);
        u++;
        ph ^= st == 2;
        st = (st == 2) ? 0 : st + 1;
    };
    const uint32_t dx = ((xs & 0x3FFFF) >> 4) + lbo(16), dh = ((hs & 0x3FFFF) >> 4) + lbo(16);
#pragma unroll 1
    while (u < nunit) {
        float g[4], v[4];
#pragma unroll 1
        for (int kc = 0; kc < 5; kc++) {
            const uint32_t da = begin();
#pragma unroll
            for (int k = 0; k < 8; k++) {
                const uint32_t db = dx + (2 * kc + (k >> 2)) * 64 + (k & 3) * 2;
                wgmma_ss_n8<1, 0>(g, da + k * 128, db, k ? 1 : kc);
                wgmma_ss_n8<1, 0>(v, da + 1024 + k * 128, db, k ? 1 : kc);
            }
            end();
        }
        fence_regs(g); fence_regs(v);
#pragma unroll
        for (int e = 0; e < 4; e++) {
            const float gp = round_bf16(g[e]);
            const float hv = round_bf16(__fdividef(gp, 1.0f + __expf(fminf(-gp, 80.f)))) * round_bf16(v[e]);
            const int tok = 2 * q + (e & 1), ch = 2 * (cw & 3) + (e >> 1);
            asm volatile("st.shared.u16 [%0], %1;" ::"r"(hs + tok * 128 + ((ch ^ tok) * 16) + lr * 2), "h"((unsigned short)pack_bf16(hv, 0.f)) : "memory");
        }
        asm volatile("fence.proxy.async.shared::cta;" ::: "memory");
        named_sync(4 + wg, 128);
#pragma unroll
        for (int k3 = 0; k3 < 3; k3++) {
            const uint32_t da = begin();
#pragma unroll
            for (int b = 0; b < (k3 == 2 ? 2 : 4); b++)
#pragma unroll
                for (int k = 0; k < 4; k++) wgmma_ss_n8<1, 0>(y[4 * k3 + b], da + b * 512 + k * 128, dh + k * 2, 1);
            end();
        }
    }
    PROF(5);
#pragma unroll
    for (int i = 0; i < 10; i++) {
        fence_regs(y[i]);
#pragma unroll
        for (int e = 0; e < 4; e++) g_ypart[((mc * 2 + wg) * 8 + 2 * q + (e & 1)) * DM + 64 * i + 16 * (cw & 3) + lr + 8 * (e >> 1)] = y[i][e];
    }
    named_sync(1, 256);
    if (tid == 0) {
        flag_add(F_MODP);
        flag_wait<100>(F_MODP, 4u * (lds(smem + NSLOT * SLOT + MISC_OFF) + 1));
    }
    named_sync(1, 256);
    PROF(6);
    {
        const int c = 2 * mc + wg, t = lds(sidx + c * 4);
        const float rs = round_bf16(__fdividef(1.0f, 1.0f + __expf(fminf(-__ldcg(g_r + t), 80.f))));
#pragma unroll
        for (int i = 0; i < 3; i++) {
            const int c2 = (tid & 127) + 128 * i;
            if (c2 < DM / 2) {
                float y0 = 0.f, y1 = 0.f;
#pragma unroll
                for (int k = 0; k < 8; k++) {
                    const float2 v = __ldcg(reinterpret_cast<const float2*>(g_ypart + (k * 8 + c) * DM) + c2);
                    y0 += v.x; y1 += v.y;
                }
                asm volatile("red.relaxed.gpu.global.add.noftz.bf16x2 [%0], %1;" ::"l"(P.out + t * DM + 2 * c2), "r"(pack_bf16(round_bf16(y0) * rs, round_bf16(y1) * rs)) : "memory");
            }
        }
    }
    PROF(7);
}

__global__ void __cluster_dims__(2, 1, 1) __launch_bounds__(384, 1) fused_kernel(const __grid_constant__ Params P) {
    extern __shared__ __align__(1024) uint8_t smem_raw[];
    const uint32_t smem = (smem_u32(smem_raw) + 1023u) & ~1023u;
    const uint32_t bars = smem + NSLOT * SLOT;
    const int wgi = __reduce_or_sync(0xffffffffu, threadIdx.x >> 7);
    const int cl = blockIdx.x >> 1, rank = blockIdx.x & 1, ca = cl & 7, cb = cl >> 3;
    PROFG(30);
    PROF(0);
    if (threadIdx.x >= 64 && threadIdx.x < 64 + 32 * FASTSTART && (threadIdx.x & 31) == 0) {
        const int u = (threadIdx.x >> 5) - 2;
        const uint32_t fa = bars + BAR_FULL + slot_a(u) * 8, fw = bars + BAR_FULL + slot_w(u) * 8;
        mbar_init(fa, 1); mbar_init(fw, 1);
        asm volatile("fence.mbarrier_init.release.cluster;" ::: "memory");
        if (cl < 64) {
            mbar_expect_tx(fa, SLOT);
            mbar_expect_tx(fw, SLOT);
            tma_load(smem + slot_a(u) * SLOT, &P.ckv, u * 128, (2 * ca + rank) * 128, fa);
            tma_load(smem + slot_w(u) * SLOT, &P.wuk, (cb + 8 * kv_round(0)) * 128, u * 128, fw);
            tma_load(smem + slot_w(u) * SLOT + 16384, &P.wuk, (cb + 8 * kv_round(0)) * 128 + 64, u * 128, fw);
            tma_load(smem + slot_a(u) * SLOT + 16384, &P.ckv, u * 128 + 64, (2 * ca + rank) * 128, fa);
        }
    } else if (threadIdx.x == 0) {
#pragma unroll
        for (int i = 0; i < NSLOT; i++) {
            if (i != 0 && i != 4 && (FASTSTART < 2 || (i != 1 && i != 6))) mbar_init(bars + BAR_FULL + i * 8, 1);
            mbar_init(bars + BAR_EMPTY + i * 8, 16);
        }
        if (cb < 8) {
            mbar_arrive(bars + BAR_FULL + 16);
            asm volatile("mbarrier.arrive.shared::cta.b64 _, [%0], 16;" ::"r"(bars + BAR_EMPTY + 16) : "memory");
        }
        asm volatile("fence.mbarrier_init.release.cluster;" ::: "memory");
        PROF(24);
    } else if (threadIdx.x == 32) {
#pragma unroll
        for (int i = 0; i < 18; i++) mbar_init(bars + BAR_SIG + i * 8, 4);
#pragma unroll
        for (int i = 0; i < 18; i++) mbar_init(bars + BAR_DEP + i * 8, 1);
        asm volatile("fence.mbarrier_init.release.cluster;" ::: "memory");
    }
    __syncthreads();
    PROF(29);
    cluster_arrive();
    if (wgi > 0) {
        asm volatile("setmaxnreg.inc.sync.aligned.u32 232;");
        consumer(P, smem, bars, ca, cb, rank, wgi - 1);
        PROFG(31);
        PROFDUMP();
    } else {
        asm volatile("setmaxnreg.dec.sync.aligned.u32 40;");
        const int w = __reduce_or_sync(0xffffffffu, threadIdx.x >> 5), lane = threadIdx.x & 31;
        if (threadIdx.x == 32) {
            prefetch_map(&P.wuv); prefetch_map(&P.xn); prefetch_map(&P.wq); prefetch_map(&P.kv); prefetch_map(&P.ctx); prefetch_map(&P.wo); prefetch_map(&P.outm);
        }
        __syncwarp();
        cluster_wait();
        PROF(27);
        {
            if (w == 0) {
                producer(P, smem, bars, ca, cb, rank);
            } else if (w < 3 && lane == 0) {
                const int wg = w - 1;
#pragma unroll 1
                for (int i = (cb == 8); i < (cb == 8 ? 9 : 5 + n_items(ca, cb)); i++) {
                    const int nb = wg * LNSTAG + (LNOFF + 7 - 4) / 8;
                    const int e = (cb == 8) ? i : (i < nb) ? i + 1 : (i == nb) ? 0 : i;
                    mbar_wait_sleep(bars + BAR_SIG + (wg * 9 + e) * 8, 0);
                    int f;
                    if (cb == 8) f = F_CTX + (2 + ca) * 16 + rank;
                    else if (e == 0) f = F_LN;
                    else if (e < 5) f = F_KV + cb + 8 * kv_round(e - 1);
                    else { const int rd = item_rd(ca, cb, e - 5); f = F_CTX + rd * 16 + item_p(ca, rd) * 2 + rank; }
                    flag_add(f);
                }
            } else if (lane == 0) {
                const uint32_t epoch = read_epoch();
                asm volatile("st.shared.u32 [%0], %1;" ::"r"(bars + MISC_OFF), "r"(epoch) : "memory");
#pragma unroll 1
                for (int e = 0; e < 9; e++) {
                    int f;
                    uint32_t n;
                    if (e == 0) { f = F_LN; n = 256; }
                    else if (cb == 8) { f = F_KV + item_h(cb, 2 + ca, e - 1); n = 32; }
                    else if (e < 5) { f = F_KV + cb + 8 * (e - 1); n = 32; }
                    else { f = F_CTX + (e - 5) * 16 + out_p(ca, cb) * 2 + rank; n = 16; }
                    flag_wait<200>(f, n * (epoch + 1));
                    fence_proxy_async();
                    mbar_arrive(bars + BAR_DEP + e * 8);
                }
            }
        }
        if (cb == 8) { __syncwarp(); cluster_arrive(); cluster_wait(); }
        PROFG(31);
        PROFDUMP();
    }
}

typedef CUresult (*EncodeFn)(CUtensorMap*, CUtensorMapDataType, cuuint32_t, void*, const cuuint64_t*, const cuuint64_t*, const cuuint32_t*,
                             const cuuint32_t*, CUtensorMapInterleave, CUtensorMapSwizzle, CUtensorMapL2promotion, CUtensorMapFloatOOBfill);

void make_map(EncodeFn fn, CUtensorMap* m, const void* ptr, uint64_t rows, uint64_t cols, uint32_t box_rows) {
    cuuint64_t dims[2] = {cols, rows};
    cuuint64_t strides[1] = {cols * 2};
    cuuint32_t box[2] = {64, box_rows};
    cuuint32_t es[2] = {1, 1};
    fn(m, CU_TENSOR_MAP_DATA_TYPE_BFLOAT16, 2, const_cast<void*>(ptr), dims, strides, box, es, CU_TENSOR_MAP_INTERLEAVE_NONE,
       CU_TENSOR_MAP_SWIZZLE_128B, CU_TENSOR_MAP_L2_PROMOTION_L2_128B, CU_TENSOR_MAP_FLOAT_OOB_FILL_NONE);
}

}

extern "C" void kernel_launch(void* const* d_in, const int* in_sizes, int n_in, void* d_out, int out_size) {
    (void)in_sizes; (void)n_in; (void)out_size;
    void* fnp = nullptr;
    cudaDriverEntryPointQueryResult qr;
    cudaGetDriverEntryPoint("cuTensorMapEncodeTiled", &fnp, cudaEnableDefault, &qr);
    EncodeFn fn = (EncodeFn)fnp;
    void *xn, *kv, *ctx;
    cudaGetSymbolAddress(&xn, g_xn);
    cudaGetSymbolAddress(&kv, g_kv);
    cudaGetSymbolAddress(&ctx, g_ctx);
    Params P;
    make_map(fn, &P.ckv, d_in[1], SEQ, DC, 128);
    make_map(fn, &P.wq, d_in[2], DM, NH * HD, 64);
    make_map(fn, &P.wuk, d_in[3], DC, NH * HD, 128);
    make_map(fn, &P.wuv, d_in[4], DC, NH * HD, 128);
    make_map(fn, &P.wo, d_in[5], NH * HD, DM, 32);
    make_map(fn, &P.xn, xn, SEQ, DM, 128);
    make_map(fn, &P.kv, kv, NH * 16 * 2 * 128, 128, 128);
    make_map(fn, &P.ctx, ctx, NH * SEQ, HD, 128);
    P.x = (const __nv_bfloat16*)d_in[0];
    P.wr = (const __nv_bfloat16*)d_in[7];
    make_map(fn, &P.wg, d_in[8], DM, FF, 128);
    make_map(fn, &P.wu, d_in[9], DM, FF, 128);
    make_map(fn, &P.wd, d_in[10], FF, DM, 64);
    make_map(fn, &P.outm, d_out, SEQ, DM, 16);
    P.out = (__nv_bfloat16*)d_out;
    cudaFuncSetAttribute(fused_kernel, cudaFuncAttributeMaxDynamicSharedMemorySize, SMEM_BYTES);
    fused_kernel<<<NCTA, 384, SMEM_BYTES>>>(P);
}
```

```cpp
#include <cuda_runtime.h>
#include <cuda_bf16.h>
#include <cuda.h>
#include <stdint.h>

namespace {

constexpr int SEQ = 2048, DM = 640, DC = 512, NH = 32, HD = 128, FF = 1728;
constexpr int NSLOT = 7, SLOT = 32768;
constexpr int NCTA = 132;
constexpr int KVSPLIT = 1;
constexpr int LNOFF = 4, LNLEAD = 2;
constexpr int SPLITJ = 8;
constexpr uint32_t DESC_HI = (1024u >> 4) | (1u << 30);
constexpr int SMEM_BYTES = NSLOT * SLOT + 3072;

constexpr int BAR_FULL = 0, BAR_EMPTY = 64, BAR_SIG = 128  , BAR_DEP = 320  , BAR_MAIL = 400  ;
constexpr int MISC_OFF = 512  , MAIL_OFF = 544  , CTL_OFF = 576  ;

constexpr int F_EPOCH = 0, F_LN = 1, F_MODP = 3, F_KV = 4  , F_CTX = 36  , F_POOL = 100  , F_NUM = 116;

__device__ __align__(1024) __nv_bfloat16 g_xn[SEQ * DM];
__device__ __align__(1024) __nv_bfloat16 g_kv[NH * 16 * 2 * 128 * 128];
__device__ __align__(1024) __nv_bfloat16 g_ctx[NH * SEQ * HD];
__device__ __align__(16) float g_r[SEQ];
__device__ __align__(16) float g_ypart[8 * 8 * DM];
__device__ uint32_t g_flags[F_NUM * 8];

struct TrueT { static constexpr bool value = true; };
struct FalseT { static constexpr bool value = false; };

struct Params {
    CUtensorMap ckv, wuk, wuv, xn, wq, kv, ctx, wo, wg, wu, wd, outm;
    const __nv_bfloat16 *x, *wr;
    __nv_bfloat16* out;
};

__device__ __forceinline__ uint32_t smem_u32(const void* p) { return (uint32_t)__cvta_generic_to_shared(p); }
__device__ __forceinline__ void mbar_init(uint32_t bar, uint32_t cnt) {
    asm volatile("mbarrier.init.shared::cta.b64 [%0], %1;" ::"r"(bar), "r"(cnt) : "memory");
}
__device__ __forceinline__ void mbar_expect_tx(uint32_t bar, uint32_t bytes) {
    asm volatile("mbarrier.arrive.expect_tx.shared::cta.b64 _, [%0], %1;" ::"r"(bar), "r"(bytes) : "memory");
}
__device__ __forceinline__ void mbar_arrive(uint32_t bar) {
    asm volatile("mbarrier.arrive.shared::cta.b64 _, [%0];" ::"r"(bar) : "memory");
}
__device__ __forceinline__ uint32_t mapa(uint32_t addr, uint32_t cta) {
    uint32_t r;
    asm("mapa.shared::cluster.u32 %0, %1, %2;" : "=r"(r) : "r"(addr), "r"(cta));
    return r;
}
__device__ __forceinline__ void mbar_wait(uint32_t bar, uint32_t parity) {
    asm volatile(
        "{\n.reg .pred p;\n.reg .b32 c;\n"
        "mov.b32 c, 0;\n"
        "WLOOP:\n"
        "mbarrier.try_wait.parity.shared::cta.b64 p, [%0], %1;\n"
        "@p bra.uni WDONE;\n"
        "add.u32 c, c, 1;\n"
        "setp.lt.u32 p, c, 0x400000;\n"
        "@p bra.uni WLOOP;\n"
        "trap;\n"
        "WDONE:\n}\n" ::"r"(bar), "r"(parity) : "memory");
}
__device__ __forceinline__ void mbar_wait_sleep(uint32_t bar, uint32_t parity) {
    asm volatile(
        "{\n.reg .pred p;\n.reg .b32 c;\n"
        "mov.b32 c, 0;\n"
        "WLOOP:\n"
        "mbarrier.try_wait.parity.shared::cta.b64 p, [%0], %1, 20000;\n"
        "@p bra.uni WDONE;\n"
        "add.u32 c, c, 1;\n"
        "setp.lt.u32 p, c, 0x40000;\n"
        "@p bra.uni WLOOP;\n"
        "trap;\n"
        "WDONE:\n}\n" ::"r"(bar), "r"(parity) : "memory");
}
__device__ __forceinline__ void tma_load(uint32_t dst, const CUtensorMap* m, int c0, int c1, uint32_t bar) {
    asm volatile("cp.async.bulk.tensor.2d.shared::cluster.global.mbarrier::complete_tx::bytes [%0], [%1, {%3, %4}], [%2];"
                 ::"r"(dst), "l"(m), "r"(bar), "r"(c0), "r"(c1) : "memory");
}
#define ELECT "{\n.reg .pred e;\nelect.sync _|e, 0xffffffff;\n@e "
__device__ __forceinline__ void w_expect_tx(uint32_t bar, uint32_t bytes) {
    asm volatile(ELECT "mbarrier.arrive.expect_tx.shared::cta.b64 _, [%0], %1;\n}\n" ::"r"(bar), "r"(bytes) : "memory");
}
__device__ __forceinline__ void w_tma_load(uint32_t dst, const CUtensorMap* m, int c0, int c1, uint32_t bar) {
    asm volatile(ELECT "cp.async.bulk.tensor.2d.shared::cluster.global.mbarrier::complete_tx::bytes [%0], [%1, {%3, %4}], [%2];\n}\n"
                 ::"r"(dst), "l"(m), "r"(bar), "r"(c0), "r"(c1) : "memory");
}
__device__ __forceinline__ void w_tma_load_mc(uint32_t dst, const CUtensorMap* m, int c0, int c1, uint32_t bar) {
    asm volatile(ELECT "cp.async.bulk.tensor.2d.shared::cluster.global.mbarrier::complete_tx::bytes.multicast::cluster [%0], [%1, {%3, %4}], [%2], %5;\n}\n"
                 ::"r"(dst), "l"(m), "r"(bar), "r"(c0), "r"(c1), "h"((uint16_t)3) : "memory");
}
__device__ __forceinline__ void w_tma_prefetch(const CUtensorMap* m, int c0, int c1) {
    asm volatile(ELECT "cp.async.bulk.prefetch.tensor.2d.L2.global [%0, {%1, %2}];\n}\n" ::"l"(m), "r"(c0), "r"(c1) : "memory");
}
__device__ __forceinline__ uint64_t policy_evict_first() {
    uint64_t p;
    asm("createpolicy.fractional.L2::evict_first.b64 %0, 1.0;" : "=l"(p));
    return p;
}
__device__ __forceinline__ void w_tma_load_mc_last(uint32_t dst, const CUtensorMap* m, int c0, int c1, uint32_t bar) {
    asm volatile(ELECT "cp.async.bulk.tensor.2d.shared::cluster.global.mbarrier::complete_tx::bytes.multicast::cluster.L2::cache_hint [%0], [%1, {%3, %4}], [%2], %5, %6;\n}\n"
                 ::"r"(dst), "l"(m), "r"(bar), "r"(c0), "r"(c1), "h"((uint16_t)3), "l"(policy_evict_first()) : "memory");
}
__device__ __forceinline__ void w_tma_load_stream(uint32_t dst, const CUtensorMap* m, int c0, int c1, uint32_t bar) {
    asm volatile(ELECT "cp.async.bulk.tensor.2d.shared::cluster.global.mbarrier::complete_tx::bytes.L2::cache_hint [%0], [%1, {%3, %4}], [%2], %5;\n}\n"
                 ::"r"(dst), "l"(m), "r"(bar), "r"(c0), "r"(c1), "l"(policy_evict_first()) : "memory");
}
__device__ __forceinline__ uint4 ldg_stream(const void* p) {
    uint4 v;
    asm volatile("ld.global.nc.L2::cache_hint.v4.b32 {%0, %1, %2, %3}, [%4], %5;" : "=r"(v.x), "=r"(v.y), "=r"(v.z), "=r"(v.w) : "l"(p), "l"(policy_evict_first()));
    return v;
}
__device__ __forceinline__ void prefetch_map(const CUtensorMap* m) {
    asm volatile("prefetch.tensormap [%0];" ::"l"(m) : "memory");
}
__device__ __forceinline__ void cluster_arrive() { asm volatile("barrier.cluster.arrive.relaxed.aligned;" ::: "memory"); }
__device__ __forceinline__ void cluster_wait() { asm volatile("barrier.cluster.wait.aligned;" ::: "memory"); }
__device__ __forceinline__ void named_sync(int id, int n) { asm volatile("bar.sync %0, %1;" ::"r"(id), "r"(n) : "memory"); }
__device__ __forceinline__ void named_arrive(int id, int n) { asm volatile("bar.arrive %0, %1;" ::"r"(id), "r"(n) : "memory"); }

__device__ __forceinline__ void flag_add(int f) {
    asm volatile("fence.acq_rel.gpu;\nred.relaxed.gpu.global.add.u32 [%0], 1;" ::"l"(g_flags + f * 8) : "memory");
}
template <int SLEEP>
__device__ __forceinline__ void flag_wait(int f, uint32_t target) {
    asm volatile(
        "{\n.reg .pred p;\n.reg .b32 c, v;\n"
        "mov.b32 c, 0;\n"
        "FLOOP:\n"
        "ld.acquire.gpu.global.u32 v, [%0];\n"
        "sub.u32 v, v, %1;\n"
        "setp.ge.s32 p, v, 0;\n"
        "@p bra FDONE;\n"
        "nanosleep.u32 %2;\n"
        "add.u32 c, c, 1;\n"
        "setp.lt.u32 p, c, 0x400000;\n"
        "@p bra FLOOP;\n"
        "trap;\n"
        "FDONE:\n}\n" ::"l"(g_flags + f * 8), "r"(target), "n"(SLEEP) : "memory");
}
__device__ __forceinline__ uint32_t read_epoch() { return atomicAdd(g_flags + F_EPOCH * 8, 1u) / NCTA; }
__device__ __forceinline__ void fence_proxy_async() { asm volatile("fence.proxy.async;" ::: "memory"); }

__device__ __forceinline__ void wgmma_fence() { asm volatile("wgmma.fence.sync.aligned;" ::: "memory"); }
__device__ __forceinline__ void wgmma_commit() { asm volatile("wgmma.commit_group.sync.aligned;" ::: "memory"); }
template <int N>
__device__ __forceinline__ void wgmma_wait() { asm volatile("wgmma.wait_group.sync.aligned %0;" ::"n"(N) : "memory"); }
template <int N>
__device__ __forceinline__ void fence_regs(float (&d)[N]) {
#pragma unroll
    for (int i = 0; i < N; i++) asm volatile("" : "+f"(d[i])::"memory");
}
template <int N>
__device__ __forceinline__ void fence_regs(uint32_t (&d)[N]) {
#pragma unroll
    for (int i = 0; i < N; i++) asm volatile("" : "+r"(d[i])::"memory");
}

template <int TA, int TB>
__device__ __forceinline__ void wgmma_ss_n128(float (&d)[64], uint32_t alo, uint32_t blo, int scale_d) {
    asm volatile("{\n.reg .pred p;\n.reg .b64 da, db;\nsetp.ne.b32 p, %66, 0;\n"
        "mov.b64 da, {%64, %69};\nmov.b64 db, {%65, %69};\n"
        "wgmma.mma_async.sync.aligned.m64n128k16.f32.bf16.bf16 "
        "{%0, %1, %2, %3, %4, %5, %6, %7, %8, %9, %10, %11, %12, %13, %14, %15, %16, %17, %18, %19, %20, %21, %22, %23, %24, %25, %26, %27, %28, %29, %30, %31, %32, %33, %34, %35, %36, %37, %38, %39, %40, %41, %42, %43, %44, %45, %46, %47, %48, %49, %50, %51, %52, %53, %54, %55, %56, %57, %58, %59, %60, %61, %62, %63}, da, db, p, 1, 1, %67, %68;\n}\n"
        :
          "+f"(d[0]), "+f"(d[1]), "+f"(d[2]), "+f"(d[3]), "+f"(d[4]), "+f"(d[5]), "+f"(d[6]), "+f"(d[7]),
          "+f"(d[8]), "+f"(d[9]), "+f"(d[10]), "+f"(d[11]), "+f"(d[12]), "+f"(d[13]), "+f"(d[14]), "+f"(d[15]),
          "+f"(d[16]), "+f"(d[17]), "+f"(d[18]), "+f"(d[19]), "+f"(d[20]), "+f"(d[21]), "+f"(d[22]), "+f"(d[23]),
          "+f"(d[24]), "+f"(d[25]), "+f"(d[26]), "+f"(d[27]), "+f"(d[28]), "+f"(d[29]), "+f"(d[30]), "+f"(d[31]),
          "+f"(d[32]), "+f"(d[33]), "+f"(d[34]), "+f"(d[35]), "+f"(d[36]), "+f"(d[37]), "+f"(d[38]), "+f"(d[39]),
          "+f"(d[40]), "+f"(d[41]), "+f"(d[42]), "+f"(d[43]), "+f"(d[44]), "+f"(d[45]), "+f"(d[46]), "+f"(d[47]),
          "+f"(d[48]), "+f"(d[49]), "+f"(d[50]), "+f"(d[51]), "+f"(d[52]), "+f"(d[53]), "+f"(d[54]), "+f"(d[55]),
          "+f"(d[56]), "+f"(d[57]), "+f"(d[58]), "+f"(d[59]), "+f"(d[60]), "+f"(d[61]), "+f"(d[62]), "+f"(d[63])
        : "r"(alo), "r"(blo), "r"(scale_d), "n"(TA), "n"(TB), "r"(DESC_HI));
}
template <int TA, int TB>
__device__ __forceinline__ void wgmma_ss_n192(float (&d)[96], uint32_t alo, uint32_t blo, int scale_d) {
    asm volatile("{\n.reg .pred p;\n.reg .b64 da, db;\nsetp.ne.b32 p, %98, 0;\n"
        "mov.b64 da, {%96, %101};\nmov.b64 db, {%97, %101};\n"
        "wgmma.mma_async.sync.aligned.m64n192k16.f32.bf16.bf16 "
        "{%0, %1, %2, %3, %4, %5, %6, %7, %8, %9, %10, %11, %12, %13, %14, %15, %16, %17, %18, %19, %20, %21, %22, %23, %24, %25, %26, %27, %28, %29, %30, %31, %32, %33, %34, %35, %36, %37, %38, %39, %40, %41, %42, %43, %44, %45, %46, %47, %48, %49, %50, %51, %52, %53, %54, %55, %56, %57, %58, %59, %60, %61, %62, %63, %64, %65, %66, %67, %68, %69, %70, %71, %72, %73, %74, %75, %76, %77, %78, %79, %80, %81, %82, %83, %84, %85, %86, %87, %88, %89, %90, %91, %92, %93, %94, %95}, da, db, p, 1, 1, %99, %100;\n}\n"
        :
          "+f"(d[0]), "+f"(d[1]), "+f"(d[2]), "+f"(d[3]), "+f"(d[4]), "+f"(d[5]), "+f"(d[6]), "+f"(d[7]),
          "+f"(d[8]), "+f"(d[9]), "+f"(d[10]), "+f"(d[11]), "+f"(d[12]), "+f"(d[13]), "+f"(d[14]), "+f"(d[15]),
          "+f"(d[16]), "+f"(d[17]), "+f"(d[18]), "+f"(d[19]), "+f"(d[20]), "+f"(d[21]), "+f"(d[22]), "+f"(d[23]),
          "+f"(d[24]), "+f"(d[25]), "+f"(d[26]), "+f"(d[27]), "+f"(d[28]), "+f"(d[29]), "+f"(d[30]), "+f"(d[31]),
          "+f"(d[32]), "+f"(d[33]), "+f"(d[34]), "+f"(d[35]), "+f"(d[36]), "+f"(d[37]), "+f"(d[38]), "+f"(d[39]),
          "+f"(d[40]), "+f"(d[41]), "+f"(d[42]), "+f"(d[43]), "+f"(d[44]), "+f"(d[45]), "+f"(d[46]), "+f"(d[47]),
          "+f"(d[48]), "+f"(d[49]), "+f"(d[50]), "+f"(d[51]), "+f"(d[52]), "+f"(d[53]), "+f"(d[54]), "+f"(d[55]),
          "+f"(d[56]), "+f"(d[57]), "+f"(d[58]), "+f"(d[59]), "+f"(d[60]), "+f"(d[61]), "+f"(d[62]), "+f"(d[63]),
          "+f"(d[64]), "+f"(d[65]), "+f"(d[66]), "+f"(d[67]), "+f"(d[68]), "+f"(d[69]), "+f"(d[70]), "+f"(d[71]),
          "+f"(d[72]), "+f"(d[73]), "+f"(d[74]), "+f"(d[75]), "+f"(d[76]), "+f"(d[77]), "+f"(d[78]), "+f"(d[79]),
          "+f"(d[80]), "+f"(d[81]), "+f"(d[82]), "+f"(d[83]), "+f"(d[84]), "+f"(d[85]), "+f"(d[86]), "+f"(d[87]),
          "+f"(d[88]), "+f"(d[89]), "+f"(d[90]), "+f"(d[91]), "+f"(d[92]), "+f"(d[93]), "+f"(d[94]), "+f"(d[95])
        : "r"(alo), "r"(blo), "r"(scale_d), "n"(TA), "n"(TB), "r"(DESC_HI));
}
template <int TA, int TB>
__device__ __forceinline__ void wgmma_ss_n8(float (&d)[4], uint32_t alo, uint32_t blo, int scale_d) {
    asm volatile("{\n.reg .pred p;\n.reg .b64 da, db;\nsetp.ne.b32 p, %6, 0;\n"
        "mov.b64 da, {%4, %9};\nmov.b64 db, {%5, %9};\n"
        "wgmma.mma_async.sync.aligned.m64n8k16.f32.bf16.bf16 "
        "{%0, %1, %2, %3}, da, db, p, 1, 1, %7, %8;\n}\n"
        :
          "+f"(d[0]), "+f"(d[1]), "+f"(d[2]), "+f"(d[3])
        : "r"(alo), "r"(blo), "r"(scale_d), "n"(TA), "n"(TB), "r"(DESC_HI));
}
template <int TB>
__device__ __forceinline__ void wgmma_rs_n64(float (&d)[64], uint32_t a0, uint32_t a1, uint32_t a2, uint32_t a3, uint32_t blo, int scale_d) {
    asm volatile("{\n.reg .pred p;\n.reg .b64 db;\nsetp.ne.b32 p, %37, 0;\n"
        "mov.b64 db, {%36, %39};\n"
        "wgmma.mma_async.sync.aligned.m64n64k16.f32.bf16.bf16 "
        "{%0, %1, %2, %3, %4, %5, %6, %7, %8, %9, %10, %11, %12, %13, %14, %15, %16, %17, %18, %19, %20, %21, %22, %23, %24, %25, %26, %27, %28, %29, %30, %31}, {%32, %33, %34, %35}, db, p, 1, 1, %38;\n}\n"
        :
          "+f"(d[0]), "+f"(d[1]), "+f"(d[2]), "+f"(d[3]), "+f"(d[4]), "+f"(d[5]), "+f"(d[6]), "+f"(d[7]),
          "+f"(d[8]), "+f"(d[9]), "+f"(d[10]), "+f"(d[11]), "+f"(d[12]), "+f"(d[13]), "+f"(d[14]), "+f"(d[15]),
          "+f"(d[16]), "+f"(d[17]), "+f"(d[18]), "+f"(d[19]), "+f"(d[20]), "+f"(d[21]), "+f"(d[22]), "+f"(d[23]),
          "+f"(d[24]), "+f"(d[25]), "+f"(d[26]), "+f"(d[27]), "+f"(d[28]), "+f"(d[29]), "+f"(d[30]), "+f"(d[31])
        : "r"(a0), "r"(a1), "r"(a2), "r"(a3), "r"(blo), "r"(scale_d), "n"(TB), "r"(DESC_HI));
}
template <int TB>
__device__ __forceinline__ void wgmma_rs_n128(float (&d)[64], uint32_t a0, uint32_t a1, uint32_t a2, uint32_t a3, uint32_t blo, int scale_d) {
    asm volatile("{\n.reg .pred p;\n.reg .b64 db;\nsetp.ne.b32 p, %69, 0;\n"
        "mov.b64 db, {%68, %71};\n"
        "wgmma.mma_async.sync.aligned.m64n128k16.f32.bf16.bf16 "
        "{%0, %1, %2, %3, %4, %5, %6, %7, %8, %9, %10, %11, %12, %13, %14, %15, %16, %17, %18, %19, %20, %21, %22, %23, %24, %25, %26, %27, %28, %29, %30, %31, %32, %33, %34, %35, %36, %37, %38, %39, %40, %41, %42, %43, %44, %45, %46, %47, %48, %49, %50, %51, %52, %53, %54, %55, %56, %57, %58, %59, %60, %61, %62, %63}, {%64, %65, %66, %67}, db, p, 1, 1, %70;\n}\n"
        :
          "+f"(d[0]), "+f"(d[1]), "+f"(d[2]), "+f"(d[3]), "+f"(d[4]), "+f"(d[5]), "+f"(d[6]), "+f"(d[7]),
          "+f"(d[8]), "+f"(d[9]), "+f"(d[10]), "+f"(d[11]), "+f"(d[12]), "+f"(d[13]), "+f"(d[14]), "+f"(d[15]),
          "+f"(d[16]), "+f"(d[17]), "+f"(d[18]), "+f"(d[19]), "+f"(d[20]), "+f"(d[21]), "+f"(d[22]), "+f"(d[23]),
          "+f"(d[24]), "+f"(d[25]), "+f"(d[26]), "+f"(d[27]), "+f"(d[28]), "+f"(d[29]), "+f"(d[30]), "+f"(d[31]),
          "+f"(d[32]), "+f"(d[33]), "+f"(d[34]), "+f"(d[35]), "+f"(d[36]), "+f"(d[37]), "+f"(d[38]), "+f"(d[39]),
          "+f"(d[40]), "+f"(d[41]), "+f"(d[42]), "+f"(d[43]), "+f"(d[44]), "+f"(d[45]), "+f"(d[46]), "+f"(d[47]),
          "+f"(d[48]), "+f"(d[49]), "+f"(d[50]), "+f"(d[51]), "+f"(d[52]), "+f"(d[53]), "+f"(d[54]), "+f"(d[55]),
          "+f"(d[56]), "+f"(d[57]), "+f"(d[58]), "+f"(d[59]), "+f"(d[60]), "+f"(d[61]), "+f"(d[62]), "+f"(d[63])
        : "r"(a0), "r"(a1), "r"(a2), "r"(a3), "r"(blo), "r"(scale_d), "n"(TB), "r"(DESC_HI));
}
template <int TB>
__device__ __forceinline__ void wgmma_rs_n128_z(float (&d)[64], uint32_t a0, uint32_t a1, uint32_t a2, uint32_t a3, uint32_t blo) {
    asm volatile("{\n.reg .pred p;\n.reg .b64 db;\nsetp.ne.b32 p, %69, 0;\n"
        "mov.b64 db, {%68, %71};\n"
        "wgmma.mma_async.sync.aligned.m64n128k16.f32.bf16.bf16 "
        "{%0, %1, %2, %3, %4, %5, %6, %7, %8, %9, %10, %11, %12, %13, %14, %15, %16, %17, %18, %19, %20, %21, %22, %23, %24, %25, %26, %27, %28, %29, %30, %31, %32, %33, %34, %35, %36, %37, %38, %39, %40, %41, %42, %43, %44, %45, %46, %47, %48, %49, %50, %51, %52, %53, %54, %55, %56, %57, %58, %59, %60, %61, %62, %63}, {%64, %65, %66, %67}, db, p, 1, 1, %70;\n}\n"
        :
          "=f"(d[0]), "=f"(d[1]), "=f"(d[2]), "=f"(d[3]), "=f"(d[4]), "=f"(d[5]), "=f"(d[6]), "=f"(d[7]),
          "=f"(d[8]), "=f"(d[9]), "=f"(d[10]), "=f"(d[11]), "=f"(d[12]), "=f"(d[13]), "=f"(d[14]), "=f"(d[15]),
          "=f"(d[16]), "=f"(d[17]), "=f"(d[18]), "=f"(d[19]), "=f"(d[20]), "=f"(d[21]), "=f"(d[22]), "=f"(d[23]),
          "=f"(d[24]), "=f"(d[25]), "=f"(d[26]), "=f"(d[27]), "=f"(d[28]), "=f"(d[29]), "=f"(d[30]), "=f"(d[31]),
          "=f"(d[32]), "=f"(d[33]), "=f"(d[34]), "=f"(d[35]), "=f"(d[36]), "=f"(d[37]), "=f"(d[38]), "=f"(d[39]),
          "=f"(d[40]), "=f"(d[41]), "=f"(d[42]), "=f"(d[43]), "=f"(d[44]), "=f"(d[45]), "=f"(d[46]), "=f"(d[47]),
          "=f"(d[48]), "=f"(d[49]), "=f"(d[50]), "=f"(d[51]), "=f"(d[52]), "=f"(d[53]), "=f"(d[54]), "=f"(d[55]),
          "=f"(d[56]), "=f"(d[57]), "=f"(d[58]), "=f"(d[59]), "=f"(d[60]), "=f"(d[61]), "=f"(d[62]), "=f"(d[63])
        : "r"(a0), "r"(a1), "r"(a2), "r"(a3), "r"(blo), "n"(0), "n"(TB), "r"(DESC_HI));
}
template <int TA, int TB>
__device__ __forceinline__ void wgmma_ss_n128_z(float (&d)[64], uint32_t alo, uint32_t blo) {
    asm volatile("{\n.reg .pred p;\n.reg .b64 da, db;\nsetp.ne.b32 p, %66, 0;\n"
        "mov.b64 da, {%64, %69};\nmov.b64 db, {%65, %69};\n"
        "wgmma.mma_async.sync.aligned.m64n128k16.f32.bf16.bf16 "
        "{%0, %1, %2, %3, %4, %5, %6, %7, %8, %9, %10, %11, %12, %13, %14, %15, %16, %17, %18, %19, %20, %21, %22, %23, %24, %25, %26, %27, %28, %29, %30, %31, %32, %33, %34, %35, %36, %37, %38, %39, %40, %41, %42, %43, %44, %45, %46, %47, %48, %49, %50, %51, %52, %53, %54, %55, %56, %57, %58, %59, %60, %61, %62, %63}, da, db, p, 1, 1, %67, %68;\n}\n"
        :
          "=f"(d[0]), "=f"(d[1]), "=f"(d[2]), "=f"(d[3]), "=f"(d[4]), "=f"(d[5]), "=f"(d[6]), "=f"(d[7]),
          "=f"(d[8]), "=f"(d[9]), "=f"(d[10]), "=f"(d[11]), "=f"(d[12]), "=f"(d[13]), "=f"(d[14]), "=f"(d[15]),
          "=f"(d[16]), "=f"(d[17]), "=f"(d[18]), "=f"(d[19]), "=f"(d[20]), "=f"(d[21]), "=f"(d[22]), "=f"(d[23]),
          "=f"(d[24]), "=f"(d[25]), "=f"(d[26]), "=f"(d[27]), "=f"(d[28]), "=f"(d[29]), "=f"(d[30]), "=f"(d[31]),
          "=f"(d[32]), "=f"(d[33]), "=f"(d[34]), "=f"(d[35]), "=f"(d[36]), "=f"(d[37]), "=f"(d[38]), "=f"(d[39]),
          "=f"(d[40]), "=f"(d[41]), "=f"(d[42]), "=f"(d[43]), "=f"(d[44]), "=f"(d[45]), "=f"(d[46]), "=f"(d[47]),
          "=f"(d[48]), "=f"(d[49]), "=f"(d[50]), "=f"(d[51]), "=f"(d[52]), "=f"(d[53]), "=f"(d[54]), "=f"(d[55]),
          "=f"(d[56]), "=f"(d[57]), "=f"(d[58]), "=f"(d[59]), "=f"(d[60]), "=f"(d[61]), "=f"(d[62]), "=f"(d[63])
        : "r"(alo), "r"(blo), "n"(0), "n"(TA), "n"(TB), "r"(DESC_HI));
}

__device__ __forceinline__ uint32_t pack_bf16(float lo, float hi) {
    uint32_t r;
    asm("cvt.rn.bf16x2.f32 %0, %1, %2;" : "=r"(r) : "f"(hi), "f"(lo));
    return r;
}
__device__ __forceinline__ uint32_t add_bf16x2(uint32_t a, uint32_t b) {
    uint32_t r;
    asm("add.rn.bf16x2 %0, %1, %2;" : "=r"(r) : "r"(a), "r"(b));
    return r;
}
__device__ __forceinline__ float bf_lo(uint32_t v) { return __uint_as_float(v << 16); }
__device__ __forceinline__ float bf_hi(uint32_t v) { return __uint_as_float(v & 0xffff0000u); }
__device__ __forceinline__ float round_bf16(float v) { return __bfloat162float(__float2bfloat16_rn(v)); }
__device__ __forceinline__ float ex2(float x) {
    float y;
    asm("ex2.approx.ftz.f32 %0, %1;" : "=f"(y) : "f"(x));
    return y;
}
__device__ __forceinline__ float rcp(float x) {
    float y;
    asm("rcp.approx.ftz.f32 %0, %1;" : "=f"(y) : "f"(x));
    return y;
}
__device__ __forceinline__ void stg128(void* p, uint32_t a, uint32_t b, uint32_t c, uint32_t d) {
    asm volatile("st.global.v4.b32 [%0], {%1, %2, %3, %4};" ::"l"(p), "r"(a), "r"(b), "r"(c), "r"(d) : "memory");
}
__device__ __forceinline__ void stg128p(void* p, uint32_t a, uint32_t b, uint32_t c, uint32_t d, uint64_t pol) {
    asm volatile("st.global.L2::cache_hint.v4.b32 [%0], {%1, %2, %3, %4}, %5;" ::"l"(p), "r"(a), "r"(b), "r"(c), "r"(d), "l"(pol) : "memory");
}
__device__ __forceinline__ uint64_t policy_sel(bool first) {
    uint64_t p;
    asm("createpolicy.fractional.L2::evict_normal.b64 %0, 1.0;" : "=l"(p));
    return first ? policy_evict_first() : p;
}
__device__ __forceinline__ int perm_row(int t) { return (t & ~255) | (((0x78 >> (((t >> 6) & 3) * 2)) & 3) << 6) | (t & 63); }
__device__ __forceinline__ int unperm_row(int t) { return (t & ~255) | (((0x9C >> (((t >> 6) & 3) * 2)) & 3) << 6) | (t & 63); }

#define PROF(i)
#define PROFG(i)
#define PROFDUMP()
#define TR(i)
#define BP(r, i)
#define LP(i)

template <int I>
__device__ __forceinline__ void store_chunk(const float (&a)[64], __nv_bfloat16* row0, __nv_bfloat16* row1, float s0, float s1) {
    stg128(row0 + 32 * I, pack_bf16(a[16 * I + 0] * s0, a[16 * I + 1] * s0), pack_bf16(a[16 * I + 4] * s0, a[16 * I + 5] * s0),
           pack_bf16(a[16 * I + 8] * s0, a[16 * I + 9] * s0), pack_bf16(a[16 * I + 12] * s0, a[16 * I + 13] * s0));
    stg128(row1 + 32 * I, pack_bf16(a[16 * I + 2] * s1, a[16 * I + 3] * s1), pack_bf16(a[16 * I + 6] * s1, a[16 * I + 7] * s1),
           pack_bf16(a[16 * I + 10] * s1, a[16 * I + 11] * s1), pack_bf16(a[16 * I + 14] * s1, a[16 * I + 15] * s1));
}
template <int I>
struct IntT { static constexpr int value = I; };
template <class F>
__device__ __forceinline__ void for4(F f) { f(IntT<0>{}); f(IntT<1>{}); f(IntT<2>{}); f(IntT<3>{}); }

struct Prod {
    uint32_t smem, bars;
    uint32_t bo, par;
    uint32_t dst, fb;
    __device__ __forceinline__ void acquire(uint32_t o, uint32_t parity, uint32_t bytes) {
        mbar_wait(bars + BAR_EMPTY + o, parity);
        fb = bars + BAR_FULL + o;
        dst = smem + o * (SLOT / 8);
        w_expect_tx(fb, bytes);
    }
    __device__ __forceinline__ void next(uint32_t bytes) {
        acquire(bo, par, bytes);
        const bool wrap = bo == (NSLOT - 1) * 8;
        bo = wrap ? 0u : bo + 8;
        par ^= wrap ? 1u : 0u;
    }
};

__device__ __forceinline__ int item_p(int ca, int rd) {
    const int v = (rd & 1) ? (ca + 4) & 7 : ca;
    return (rd & 2) ? 7 - v : v;
}
__device__ __forceinline__ int n_items(int ca, int cb) { return cb == 8 ? 8 : ((ca & 3) == 3) ? 3 : 4; }
__device__ __forceinline__ int item_rd(int ca, int cb, int j) { return cb == 8 ? 2 + ca : (ca == 7 && j == 2) ? 3 : j; }
__device__ __forceinline__ int item_h(int cb, int rd, int j) { return 8 * rd + (cb == 8 ? j : cb); }
__device__ __forceinline__ int item_q(int ca, int cb, int rd) { return cb == 8 ? 0 : item_p(ca, rd); }
__device__ __forceinline__ int out_p(int ca, int cb) { return (cb + 2 * (ca & 3)) & 7; }
__device__ __forceinline__ int kv_round(int i) { return (0x1023 >> (4 * i)) & 3; }
__device__ __forceinline__ int slot_a(int i) { return (0x5310 >> (4 * i)) & 15; }
__device__ __forceinline__ int slot_w(int m) { return (0x264 >> (4 * m)) & 15; }

__device__ __forceinline__ void producer(const Params& P, uint32_t smem, uint32_t bars, int ca, int cb, int rank) {
    Prod pr{smem, bars, 0u, cb == 8 ? 1u : 0u, 0u, 0u};
    if (cb < 8) {
        int m = 0;
        uint32_t lap = 1;
#pragma unroll 1
        for (int u = 0; u < 32; u++) {
            if (u >= 3) {
                const int v = (u == 3) ? 3 + ca : u + 7;
                if (v < 32 && (u == 3 || (v & 7) == ca)) w_tma_prefetch((v & 4) ? &P.wuv : &P.wuk, (cb + 8 * kv_round(v >> 3)) * 128 + rank * 64, (v & 3) * 128);
                if (u == 24) {
                    w_tma_prefetch(&P.wq, cb * 128 + rank * 64, ca * 64);
                    if (ca < 2) w_tma_prefetch(&P.wq, cb * 128 + rank * 64, (ca + 8) * 64);
                }
            }
            if (u > 0) pr.acquire(slot_w(m) * 8, lap ^ (m >> 1), SLOT);
            lap ^= m >> 1;
            m = (m == 2) ? 0 : m + 1;
            TR(1 + u);
            if (u > 0) w_tma_load_mc(pr.dst + rank * 16384, (u & 4) ? &P.wuv : &P.wuk, (cb + 8 * kv_round(u >> 3)) * 128 + rank * 64, (u & 3) * 128, pr.fb);
            if (u < 3) {
                pr.acquire(slot_a(u + 1) * 8, 1, SLOT);
                w_tma_load(pr.dst, &P.ckv, u * 128 + 128, (2 * ca + rank) * 128, pr.fb);
                w_tma_load(pr.dst + 16384, &P.ckv, u * 128 + 192, (2 * ca + rank) * 128, pr.fb);
            }
        }
    }
    PROF(1);
    mbar_wait_sleep(bars + BAR_DEP, 0);
#pragma unroll 1
    for (int j = 0, pfs = 1; j < n_items(ca, cb); j++) {
        const int rd = item_rd(ca, cb, j), h = item_h(cb, rd, j), p = item_q(ca, cb, rd);
#pragma unroll 1
        for (int ks = 0; ks < 10; ks++) {
            pr.next(SLOT);
            w_tma_load_mc(pr.dst + 16384 + rank * 8192, &P.wq, h * 128 + rank * 64, ks * 64, pr.fb);
            w_tma_load(pr.dst, &P.xn, ks * 64, 256 * p + 128 * rank, pr.fb);
            if (cb == 8 && j < 7) w_tma_prefetch(&P.wq, (h + 1) * 128 + rank * 64, ks * 64);
        }
        PROF(8 + rd * 4);
        mbar_wait(bars + BAR_DEP + (1 + (cb == 8 ? j : rd)) * 8, 0);
        const int last = 4 * p + 3, top = h * 32 + last;
#pragma unroll 1
        for (int i = 0; i <= last; i++) {
            const int t = (i == 0) ? top - 1 : (i == last) ? h * 32 + 1 : (i & 1) ? top - 2 - i : top + 2 - i;
            pr.next(SLOT);
            const bool lastrd = (cb == 8 || rd == 3) ? false : (rd == 0) ? ca >= 6 : (rd == 1) ? (ca & 3) >= 2 : (ca == 3 || (ca < 3 && (t & 31) >= 4 * p));
            if (lastrd) w_tma_load_mc_last(pr.dst + rank * 16384, &P.kv, rank * 64, t * 128, pr.fb);
            else w_tma_load_mc(pr.dst + rank * 16384, &P.kv, rank * 64, t * 128, pr.fb);
            if (i == 2 && cb < 8) {
                const int upto = (j == n_items(ca, cb) - 1) ? 4 : item_rd(ca, cb, j + 1);
#pragma unroll 1
                for (; pfs <= upto; pfs++) {
                    if (pfs < 4) {
                        w_tma_prefetch(&P.wq, (8 * pfs + cb) * 128 + rank * 64, ca * 64);
                        if (ca < 2) w_tma_prefetch(&P.wq, (8 * pfs + cb) * 128 + rank * 64, (ca + 8) * 64);
                    } else {
#pragma unroll 1
                        for (int k = 0; k < 10; k++)
                            w_tma_prefetch(&P.wo, 320 * (ca >> 2) + 64 * (k >= 5 ? k - 5 : k), (cb * 4 + (ca & 3) + (k >= 5 ? 32 : 0)) * 64 + rank * 32);
                    }
                }
            }
        }
        PROF(9 + rd * 4);
    }
    if (cb < 8) {
        const int n0 = 320 * (ca >> 2), op = out_p(ca, cb);
        uint32_t* pool = g_flags + (F_POOL + op * 2 + (ca >> 2)) * 8;
        uint32_t nxt = 0;
        auto draw = [&]() {
            if (rank == 0) asm volatile(ELECT "atom.relaxed.gpu.global.add.u32 %0, [%1], 1;\n}\n" : "+r"(nxt) : "l"(pool) : "memory");
        };
        int fixed = -1;
#pragma unroll 1
        for (int i = -2; fixed < 4; i++) {
            int st = (ca & 3) + 4 * (i + 2);
            if (i == -1) draw();
            if (i >= 0 && fixed < 0) {
                const uint32_t mb = bars + BAR_MAIL + (i & 7) * 8, md = bars + MAIL_OFF + (i & 7) * 4;
                if (rank == 0) {
                    st = __reduce_add_sync(0xffffffffu, nxt);
                    asm volatile(ELECT "st.async.shared::cluster.mbarrier::complete_tx::bytes.b32 [%0], %1, [%2];\n}\n" ::"r"(mapa(md, 1)), "r"(st), "r"(mapa(mb, 1)) : "memory");
                    if (st < 48) draw();
                } else {
                    w_expect_tx(mb, 4);
                    mbar_wait(mb, (i >> 3) & 1);
                    asm volatile("ld.shared.u32 %0, [%1];" : "=r"(st) : "r"(md) : "memory");
                    st = __reduce_or_sync(0xffffffffu, st);
                }
                if (st >= 48) fixed = 0;
            }
            if (fixed >= 0) { st = 48 + (ca & 3) + 4 * fixed; fixed++; }
            const int krow = st * 64 + rank * 32;
            mbar_wait(bars + BAR_EMPTY + pr.bo, pr.par);
            asm volatile("st.shared.u32 [%0], %1;" ::"r"(bars + CTL_OFF + pr.bo), "r"((int)(fixed == 1)) : "memory");
            __syncwarp();
            pr.next(SLOT);
            w_tma_load_mc(pr.dst + 16384 + rank * 8192, &P.wo, n0, krow, pr.fb);
            w_tma_load_mc(pr.dst + 16384 + rank * 8192 + 4096, &P.wo, n0 + 64, krow, pr.fb);
            mbar_wait(bars + BAR_DEP + (5 + (st >> 4)) * 8, 0);
            w_tma_load(pr.dst, &P.ctx, (st & 1) * 64, (st >> 1) * SEQ + 256 * op + 128 * rank, pr.fb);
            pr.next(24576);
#pragma unroll
            for (int c = 0; c < 3; c++) w_tma_load_mc(pr.dst + rank * 12288 + c * 4096, &P.wo, n0 + 128 + 64 * c, krow, pr.fb);
        }
    }
}

struct Slot {
    uint32_t bo, dl, par;
};
struct Cons {
    uint32_t bars, rel;
    uint32_t dl0;
    uint32_t lane;
    Slot cur;
    __device__ __forceinline__ Slot slot(int s, uint32_t par) const { return Slot{(uint32_t)s * 8, dl0 + (uint32_t)s * (SLOT >> 4), par}; }
    __device__ __forceinline__ void wait(const Slot& s) const { mbar_wait(bars + BAR_FULL + s.bo, s.par); }
    __device__ __forceinline__ void release(uint32_t bo) const {
        asm volatile("{\n.reg .pred p;\nsetp.lt.u32 p, %1, 2;\n@p mbarrier.arrive.shared::cluster.b64 _, [%0];\n}\n" ::"r"(rel + bo), "r"(lane) : "memory");
    }
    __device__ __forceinline__ Slot next() {
        const Slot s = cur;
        const bool wrap = s.bo == (NSLOT - 1) * 8;
        cur.bo = wrap ? 0u : s.bo + 8;
        cur.dl = wrap ? dl0 : s.dl + (SLOT >> 4);
        cur.par = s.par ^ (wrap ? 1u : 0u);
        return s;
    }
};
__host__ __device__ constexpr uint32_t lbo(uint32_t bytes) { return (bytes >> 4) << 16; }

__device__ __forceinline__ float div640(float x) {
    const float q = x * (1.0f / DM);
    return fmaf(fmaf(-q, (float)DM, x), 1.0f / DM, q);
}
__device__ __forceinline__ float sqrt_approx(float x) {
    float y;
    asm("sqrt.approx.ftz.f32 %0, %1;" : "=f"(y) : "f"(x));
    return y;
}
struct LayerNorm {
    uint4 xv[5], wv[5];
    float mean, inv, r;
    static __device__ __forceinline__ float half_sum(float v) {
#pragma unroll
        for (int o = 8; o > 0; o >>= 1) v += __shfl_xor_sync(0xffffffffu, v, o);
        return v;
    }
    __device__ __forceinline__ void load(const __nv_bfloat16* x, const __nv_bfloat16* wr, int t, int l) {
#pragma unroll
        for (int i = 0; i < 5; i++) {
            xv[i] = ldg_stream(reinterpret_cast<const uint4*>(x + t * DM) + l + 16 * i);
            wv[i] = __ldg(reinterpret_cast<const uint4*>(wr) + l + 16 * i);
        }
    }
    __device__ __forceinline__ void stat1() {
        float a[4] = {0.f, 0.f, 0.f, 0.f};
#pragma unroll
        for (int i = 0; i < 20; i++) { const uint32_t u = (&xv[i >> 2].x)[i & 3]; a[i & 3] += bf_lo(u) + bf_hi(u); }
        mean = div640(half_sum((a[0] + a[1]) + (a[2] + a[3])));
        r = 0.f;
    }
    template <int H>
    __device__ __forceinline__ void stat2() {
        float a[4] = {r, 0.f, 0.f, 0.f};
#pragma unroll
        for (int i = H ? 12 : 0; i < (H ? 20 : 12); i++) {
            uint32_t u = (&xv[i >> 2].x)[i & 3];
            asm volatile("" : "+r"(u));
            const float d0 = bf_lo(u) - mean, d1 = bf_hi(u) - mean;
            a[i & 3] = fmaf(d0, d0, fmaf(d1, d1, a[i & 3]));
        }
        r = (a[0] + a[1]) + (a[2] + a[3]);
        if (H) {
            inv = rcp(round_bf16(sqrt_approx(round_bf16(round_bf16(div640(half_sum(r))) + 1e-5f))));
            r = 0.f;
        }
    }
    template <int I>
    __device__ __forceinline__ void piece(__nv_bfloat16* out, int t, int l) {
        const uint32_t nmb = pack_bf16(-mean, -mean);
        uint32_t o[4], z[4];
        float a[4];
#pragma unroll
        for (int j = 0; j < 4; j++) {
            const uint32_t u = (&xv[I].x)[j], w = (&wv[I].x)[j];
            const uint32_t d = add_bf16x2(u, nmb);
            o[j] = pack_bf16(bf_lo(d) * inv, bf_hi(d) * inv);
            z[j] = add_bf16x2(u, o[j]);
            a[j] = fmaf(bf_hi(o[j]), bf_hi(w), bf_lo(o[j]) * bf_lo(w));
        }
        r += (a[0] + a[1]) + (a[2] + a[3]);
        stg128(g_xn + perm_row(t) * DM + 8 * (l + 16 * I), o[0], o[1], o[2], o[3]);
        stg128p(out + t * DM + 8 * (l + 16 * I), z[0], z[1], z[2], z[3], policy_evict_first());
        if (I == 4) {
            r = half_sum(r);
            if (l == 0) g_r[t] = round_bf16(r);
        }
    }
};

constexpr float SM_SCALE = 0.08838834764831845f * 1.4426950408889634f;

template <int J0, int J1>
__device__ __forceinline__ void exp_part(float (&s)[64], float n0, float n1, float& r0, float& r1) {
    float a1 = 0.f, b1 = 0.f;
#pragma unroll
    for (int j = J0; j < J1; j++) {
        s[4 * j + 0] = ex2(fmaf(s[4 * j + 0], SM_SCALE, n0));
        s[4 * j + 1] = ex2(fmaf(s[4 * j + 1], SM_SCALE, n0));
        s[4 * j + 2] = ex2(fmaf(s[4 * j + 2], SM_SCALE, n1));
        s[4 * j + 3] = ex2(fmaf(s[4 * j + 3], SM_SCALE, n1));
        r0 += s[4 * j + 0]; r1 += s[4 * j + 2];
        if (j == J0) { a1 = s[4 * j + 1]; b1 = s[4 * j + 3]; } else { a1 += s[4 * j + 1]; b1 += s[4 * j + 3]; }
    }
    r0 += a1;
    r1 += b1;
}
__device__ __forceinline__ void sched_barrier(float x, float y, uint32_t scratch) {
    asm volatile("{\n.reg .pred p;\nsetp.lt.f32 p, %0, 0f00000000;\n@p st.shared.f32 [%2], %1;\n}\n" ::"f"(x), "f"(y), "r"(scratch) : "memory");
}
__device__ __forceinline__ void pack_tile(const float (&s)[64], uint32_t (&p)[32]) {
#pragma unroll
    for (int i = 0; i < 32; i++) p[i] = pack_bf16(s[2 * i], s[2 * i + 1]);
}
template <bool ZERO>
__device__ __forceinline__ void gemm_rs(float (&d)[64], const uint32_t (&a)[32], uint32_t dl, int acc = 1) {
    const uint32_t b = dl + lbo(16384);
    if (ZERO) wgmma_rs_n128_z<1>(d, a[0], a[1], a[2], a[3], b);
#pragma unroll
    for (int k = ZERO ? 1 : 0; k < 8; k++) wgmma_rs_n128<1>(d, a[4 * k], a[4 * k + 1], a[4 * k + 2], a[4 * k + 3], b + k * 128, k ? 1 : acc);
}
__device__ __forceinline__ void gemm_pv(float (&d)[64], const uint32_t (&a)[32], uint32_t dl, int acc, int full) {
    const uint32_t b = dl + lbo(16384);
    wgmma_rs_n128<1>(d, a[0], a[1], a[2], a[3], b, acc);
    wgmma_commit();
    if (full) {
        wgmma_fence();
#pragma unroll
        for (int k = 4; k < 8; k++) wgmma_rs_n128<1>(d, a[4 * k], a[4 * k + 1], a[4 * k + 2], a[4 * k + 3], b + k * 128, 1);
        wgmma_commit();
    }
    wgmma_fence();
#pragma unroll
    for (int k = 1; k < 4; k++) wgmma_rs_n128<1>(d, a[4 * k], a[4 * k + 1], a[4 * k + 2], a[4 * k + 3], b + k * 128, 1);
}
template <int ZERO>
__device__ __forceinline__ void gemm_q(float (&d)[64], uint32_t dl, int role) {
    const uint32_t a = dl + role * 512 + lbo(16), b = dl + 1024 + lbo(8192);
    if (ZERO) wgmma_ss_n128_z<0, 1>(d, a, b);
#pragma unroll
    for (int k = ZERO ? 1 : 0; k < 4; k++) wgmma_ss_n128<0, 1>(d, a + k * 2, b + k * 128, 1);
}
template <bool KT, bool ZERO, int K0, int K1>
__device__ __forceinline__ void gemm_kv(float (&d)[64], uint32_t ckv, uint32_t wt, int wg) {
    if (KT) {
        const uint32_t a = wt + wg * 1024 + lbo(16), b = ckv + lbo(16);
        if (ZERO) wgmma_ss_n128_z<1, 0>(d, a, b);
#pragma unroll
        for (int k = ZERO ? 1 : K0; k < K1; k++) wgmma_ss_n128<1, 0>(d, a + k * 128, b + (k >> 2) * 1024 + (k & 3) * 2, 1);
    } else {
        const uint32_t a = ckv + wg * 512 + lbo(16), b = wt + lbo(16384);
        if (ZERO) wgmma_ss_n128_z<0, 1>(d, a, b);
#pragma unroll
        for (int k = ZERO ? 1 : K0; k < K1; k++) wgmma_ss_n128<0, 1>(d, a + (k >> 2) * 1024 + (k & 3) * 2, b + k * 128, 1);
    }
}
__device__ __forceinline__ void mma16816(float& d0, float& d1, float& d2, float& d3, uint32_t a0, uint32_t a1, uint32_t a2, uint32_t a3, uint32_t b0, uint32_t b1) {
    asm volatile("mma.sync.aligned.m16n8k16.row.col.f32.bf16.bf16.f32 {%0,%1,%2,%3}, {%4,%5,%6,%7}, {%8,%9}, {%0,%1,%2,%3};"
                 : "+f"(d0), "+f"(d1), "+f"(d2), "+f"(d3) : "r"(a0), "r"(a1), "r"(a2), "r"(a3), "r"(b0), "r"(b1));
}
__device__ __forceinline__ uint32_t ld_pair(const __nv_bfloat16* p) {
    const unsigned short* u = reinterpret_cast<const unsigned short*>(p);
    return (uint32_t)__ldcg(u) | ((uint32_t)__ldcg(u + 128) << 16);
}
__device__ __forceinline__ void attention_exact(float (&o)[64], const uint32_t (&qf)[32], float& l0, float& l1, int h, int nblk, int rr, int lane) {
    const int q = lane & 3, lr = lane >> 2;
    float m0 = -INFINITY, m1 = -INFINITY;
    l0 = 0.f; l1 = 0.f;
#pragma unroll
    for (int i = 0; i < 64; i++) o[i] = 0.f;
#pragma unroll 1
    for (int cidx = 0; cidx < nblk * 8; cidx++) {
        const int kc = cidx & 7;
        const __nv_bfloat16* kt = g_kv + (size_t)((h * 16 + (cidx >> 3)) * 2) * 16384;
        float sc[8];
#pragma unroll
        for (int i = 0; i < 8; i++) sc[i] = 0.f;
#pragma unroll
        for (int kk = 0; kk < 8; kk++)
#pragma unroll
            for (int nt = 0; nt < 2; nt++) {
                const __nv_bfloat16* b = kt + (16 * kk + 2 * q) * 128 + 16 * kc + 8 * nt + lr;
                mma16816(sc[4 * nt], sc[4 * nt + 1], sc[4 * nt + 2], sc[4 * nt + 3], qf[4 * kk], qf[4 * kk + 1], qf[4 * kk + 2], qf[4 * kk + 3],
                         ld_pair(b), ld_pair(b + 8 * 128));
            }
        const int lim = rr + ((nblk - 1) - (cidx >> 3)) * 128 - 32 * (kc >> 1) - 4 * (kc & 1);
#pragma unroll
        for (int i = 0; i < 8; i++)
            if (2 * (i >> 2) + (i & 1) > lim + 4 * (i & 2)) sc[i] = -INFINITY;
        float x0 = fmaxf(fmaxf(sc[0], sc[1]), fmaxf(sc[4], sc[5])), x1 = fmaxf(fmaxf(sc[2], sc[3]), fmaxf(sc[6], sc[7]));
        x0 = fmaxf(x0, __shfl_xor_sync(0xffffffffu, x0, 1)); x1 = fmaxf(x1, __shfl_xor_sync(0xffffffffu, x1, 1));
        x0 = fmaxf(x0, __shfl_xor_sync(0xffffffffu, x0, 2)); x1 = fmaxf(x1, __shfl_xor_sync(0xffffffffu, x1, 2));
        x0 = fmaxf(x0, m0); x1 = fmaxf(x1, m1);
        const float a0 = ex2((m0 - x0) * SM_SCALE), a1 = ex2((m1 - x1) * SM_SCALE);
        m0 = x0; m1 = x1;
#pragma unroll
        for (int i = 0; i < 8; i++) sc[i] = ex2((sc[i] - ((i & 2) ? m1 : m0)) * SM_SCALE);
        l0 = l0 * a0 + (sc[0] + sc[1]) + (sc[4] + sc[5]);
        l1 = l1 * a1 + (sc[2] + sc[3]) + (sc[6] + sc[7]);
        const uint32_t p0 = pack_bf16(sc[0], sc[1]), p1 = pack_bf16(sc[2], sc[3]), p2 = pack_bf16(sc[4], sc[5]), p3 = pack_bf16(sc[6], sc[7]);
        const __nv_bfloat16* vb = kt + 16384 + (16 * kc + 2 * q) * 128 + lr;
#pragma unroll
        for (int nt = 0; nt < 16; nt++) {
            o[4 * nt] *= a0; o[4 * nt + 1] *= a0; o[4 * nt + 2] *= a1; o[4 * nt + 3] *= a1;
            mma16816(o[4 * nt], o[4 * nt + 1], o[4 * nt + 2], o[4 * nt + 3], p0, p1, p2, p3, ld_pair(vb + 8 * nt), ld_pair(vb + 8 * nt + 8 * 128));
        }
    }
}

__device__ __forceinline__ void signal(uint32_t bars, int wg, int e, int lane) {
    __syncwarp();
    asm volatile("{\n.reg .pred p;\nsetp.eq.u32 p, %1, 0;\n@p mbarrier.arrive.shared::cta.b64 _, [%0];\n}\n" ::"r"(bars + BAR_SIG + (wg * 9 + e) * 8), "r"(lane) : "memory");
}

__device__ __forceinline__ void mod_ffn(const Params& P, uint32_t smem, int mc, int wg);

__device__ __forceinline__ void consumer(const Params& P, uint32_t smem, uint32_t bars, int ca, int cb, int rank, int wg) {
    const int lane = threadIdx.x & 31, w = (threadIdx.x >> 5) & 3, q = lane & 3, lr = lane >> 2;
    PROF(7);
    cluster_wait();
    Cons c{bars, mapa(bars + BAR_EMPTY, lane & 1), (smem & 0x3FFFF) >> 4, (uint32_t)lane, Slot{0u, (smem & 0x3FFFF) >> 4, cb == 8 ? 0u : 1u}};
    PROFG(180);
    PROF(1);
    float o[64], s[64];
    uint32_t pend;
    __nv_bfloat16* ep_ptr;
    int ep_step;
    if (cb == 8) {
        pend = 0;
        ep_ptr = g_ctx + (size_t)(item_h(cb, 2 + ca, 0) * SEQ + 128 * rank + 64 * wg + 16 * w + lr) * HD + 8 * q;
        ep_step = 8 * HD;
    } else {
        const int ln_t = blockIdx.x * 16 + wg * 8 + w * 2 + (lane >> 4);
        const int krow = 64 * wg + 16 * w + lr;
        const int vrow = 64 * wg + 32 * (w >> 1) + 8 * (lr >> 1) + 4 * (w & 1) + (lr & 1);
        ep_step = 2 * 128;
        int m = 0;
        uint32_t lap = 0;
        LayerNorm ln;
        auto step = [&](auto kt, auto kc, float (&d)[64], int hh) {
            const Slot sa = c.slot(slot_a(kc.value), 0), sw = c.slot(slot_w(m), lap ^ (m >> 1));
            lap ^= m >> 1;
            m = (m == 2) ? 0 : m + 1;
            TR(1 + (hh * 8 + (kt.value ? 0 : 4) + kc.value) * 2);
            if (kt.value && hh == 0) c.wait(sa);
            c.wait(sw);
            TR(2 + (hh * 8 + (kt.value ? 0 : 4) + kc.value) * 2);
            wgmma_fence();
            gemm_kv<kt.value, kc.value == 0, 0, KVSPLIT>(d, sa.dl, sw.dl, wg);
            wgmma_commit();
            wgmma_wait<1>();
            if (!(kt.value && kc.value == 0 && hh == 0)) c.release(pend);
            if (!kt.value && kc.value > 0 && hh == 3) c.release(slot_a(kc.value - 1) * 8);
            pend = sw.bo;
            wgmma_fence();
            gemm_kv<kt.value, false, KVSPLIT, 8>(d, sa.dl, sw.dl, wg);
            wgmma_commit();
        };
#pragma unroll 1
        for (int hh = 0; hh < 4; hh++) {
            __nv_bfloat16* base = g_kv + (size_t)(((cb + 8 * kv_round(hh)) * 16 + 2 * ca + rank) * 2) * 16384 + 8 * q;
            auto ln_stage = [&](auto pos) {
                constexpr int j = (pos.value + 8 - LNOFF % 8) % 8;
                if (hh == wg + (LNOFF + j) / 8) {
                    if (j == 0) ln.stat1();
                    if (j == 1) ln.template stat2<0>();
                    if (j == 2) ln.template stat2<1>();
                    if constexpr (j >= 3) ln.template piece<j - 3>(P.out, ln_t, lane & 15);
                    if (j == 7) signal(bars, wg, 0, lane);
                }
                if (pos.value == (LNOFF - LNLEAD) % 8 && hh == wg + (LNOFF - LNLEAD) / 8) ln.load(P.x, P.wr, ln_t, lane & 15);
            };
            for4([&](auto kc) {
                step(TrueT{}, kc, s, hh);
                if (hh > 0) {
                    if (kc.value == 0) fence_regs(o);
                    store_chunk<kc.value>(o, ep_ptr, ep_ptr + ep_step, 1.f, 1.f);
                    if (kc.value == 3) signal(bars, wg, hh, lane);
                }
                ln_stage(kc);
            });
            for4([&](auto kc) {
                step(FalseT{}, kc, o, hh);
                if (kc.value == 0) fence_regs(s);
                store_chunk<kc.value>(s, base + krow * 128, base + (krow + 8) * 128, 1.f, 1.f);
                ln_stage(IntT<kc.value + 4>{});
            });
            PROF(24 + hh);
            if (hh == 1) PROFG(181);
            ep_ptr = base + 16384 + vrow * 128;
        }
    }
    PROFG(182);
    PROF(2);
    uint32_t pf[32];
    {
        uint32_t qf[32];
        float l0 = 0.25f, l1 = 0.25f;
        const int bar_me = 2 + wg, bar_other = 3 - wg;
#pragma unroll 1
        for (int j = 0; j < n_items(ca, cb); j++) {
            const int rd = item_rd(ca, cb, j), h = item_h(cb, rd, j), p = item_q(ca, cb, rd);
            const int role = wg ^ (j & 1);
            const int nrest = 2 * p + role;
            Slot kfirst;
            const int lim = 64 * (role ^ rank) + 16 * w + lr - 8 * q;
            const uint64_t pol = policy_sel(j == 1 || j == 2);
            {
                auto qstep = [&](auto zero, int ks) {
                    const Slot sl = c.next();
                    c.wait(sl);
                    BP(2, 5 + 3 * ks);
                    wgmma_fence();
                    gemm_q<zero.value>(s, sl.dl, role);
                    wgmma_commit();
                    wgmma_wait<1>();
                    if (!zero.value || j > 0 || cb < 8) c.release(pend);
                    pend = sl.bo;
                };
                qstep(TrueT{}, 0);
                if (j == 0 && cb < 8) c.release(slot_a(3) * 8);
                fence_regs(o);
                l0 += __shfl_xor_sync(0xffffffffu, l0, 1); l1 += __shfl_xor_sync(0xffffffffu, l1, 1);
                l0 += __shfl_xor_sync(0xffffffffu, l0, 2); l1 += __shfl_xor_sync(0xffffffffu, l1, 2);
                l0 = rcp(l0); l1 = rcp(l1);
                for4([&](auto i) {
                    constexpr int B = 16 * i.value;
#pragma unroll
                    for (int r = 0; r < 2; r++) {
                        if (1 + 2 * i.value + r == 7 && !(role | rank)) named_sync(bar_me, 256);
                        qstep(FalseT{}, 1 + 2 * i.value + r);
                        const float f = r ? l1 : l0;
                        stg128p(ep_ptr + r * ep_step + 2 * B, pack_bf16(o[B + 2 * r] * f, o[B + 2 * r + 1] * f), pack_bf16(o[B + 2 * r + 4] * f, o[B + 2 * r + 5] * f),
                                pack_bf16(o[B + 2 * r + 8] * f, o[B + 2 * r + 9] * f), pack_bf16(o[B + 2 * r + 12] * f, o[B + 2 * r + 13] * f), pol);
#pragma unroll
                        for (int k = 0; k < 8; k++) {
                            float& v = o[B + 4 * (k >> 1) + 2 * r + (k & 1)];
                            v = (2 * B + k > lim + 8 * r) ? -1e30f : 0.f;
                            asm volatile("" : "+f"(v));
                        }
                    }
                });
                signal(bars, wg, (cb == 8 ? 0 : 4) + j, lane);
                PROF(11 + rd * 4);
                qstep(FalseT{}, 9);
                if (!role) { const Slot sl = c.next(); c.wait(sl); c.release(sl.bo); }
                kfirst = c.next();
                c.wait(kfirst);
                wgmma_wait<0>();
                BP(2, 34);
                c.release(pend);
                fence_regs(s);
                pack_tile(s, qf);
            }
            Slot vskip = c.cur;
            if (!role) vskip = c.next();
            PROF(8 + rd * 4);
            if (cb == 8) PROF(40 + 3 * j);
            fence_regs(qf); fence_regs(o);
            if (!role && rank) named_sync(bar_me, 256);
            BP(2, 36);
            auto first_qk = [&](auto half) {
                wgmma_fence();
#pragma unroll
                for (int k = 0; k < 8; k++) {
                    if (half.value) wgmma_rs_n64<1>(o, qf[4 * k], qf[4 * k + 1], qf[4 * k + 2], qf[4 * k + 3], kfirst.dl + lbo(16384) + k * 128, 1);
                    else wgmma_rs_n128<1>(o, qf[4 * k], qf[4 * k + 1], qf[4 * k + 2], qf[4 * k + 3], kfirst.dl + lbo(16384) + k * 128, 1);
                }
                wgmma_commit();
                named_arrive(bar_other, 256);
                if (!role) { c.wait(vskip); c.release(vskip.bo); }
                wgmma_wait<0>();
            };
            if (role == rank) first_qk(TrueT{});
            else first_qk(FalseT{});
            BP(2, 38);
            fence_regs(o);
            c.release(kfirst.bo);
            float n0 = fmaxf(fmaxf(fmaxf(o[0], o[1]), fmaxf(o[4], o[5])), fmaxf(fmaxf(o[8], o[9]), fmaxf(o[12], o[13])));
            float n1 = fmaxf(fmaxf(fmaxf(o[2], o[3]), fmaxf(o[6], o[7])), fmaxf(fmaxf(o[10], o[11]), fmaxf(o[14], o[15])));
            n0 = __shfl_sync(0xffffffffu, n0, lane & 28); n1 = __shfl_sync(0xffffffffu, n1, lane & 28);
            n0 *= -SM_SCALE; n1 *= -SM_SCALE;
            l0 = 0.f; l1 = 0.f;
#pragma unroll
            for (int i = 0; i < 64; i++) s[i] = o[i];
            exp_part<0, 8>(s, n0, n1, l0, l1);
#pragma unroll
            for (int i = 0; i < 16; i++) pf[i] = pack_bf16(s[2 * i], s[2 * i + 1]);
            if (role != rank) {
                exp_part<8, 16>(s, n0, n1, l0, l1);
#pragma unroll
                for (int i = 16; i < 32; i++) pf[i] = pack_bf16(s[2 * i], s[2 * i + 1]);
            } else {
#pragma unroll
                for (int i = 16; i < 32; i++) pf[i] = 0u;
            }
            PROF(9 + rd * 4);
            if (cb == 8) PROF(41 + 3 * j);
#pragma unroll 1
            for (int it = 0; it < nrest; it++) {
                const Slot sk = c.next(), sv = c.next();
                LP(0);
                c.wait(sk);
                c.wait(sv);
                fence_regs(o); fence_regs(pf);
                LP(1);
                named_sync(bar_me, 256);
                LP(2);
                if (it < 3) BP(2, 42 + 4 * it);
                if (it >= nrest - 2) BP(1, 62 + 4 * (it - nrest + 2));
                wgmma_fence();
                gemm_rs<true>(s, qf, sk.dl);
                wgmma_commit();
                gemm_pv(o, pf, sv.dl, it, it | (role ^ rank));
                wgmma_commit();
                named_arrive(bar_other, 256);
                LP(3);
                wgmma_wait<2>();
                LP(4);
                c.release(sk.bo);
                fence_regs(s);
                exp_part<0, SPLITJ>(s, n0, n1, l0, l1);
                sched_barrier(l0, l1, bars + MISC_OFF + 16);
                LP(5);
                wgmma_wait<0>();
                LP(6);
                c.release(sv.bo);
                fence_regs(o); fence_regs(pf);
                exp_part<SPLITJ, 16>(s, n0, n1, l0, l1);
                pack_tile(s, pf);
            }
            PROF(10 + rd * 4);
            if (cb == 8) PROF(42 + 3 * j);
            PROFG(183 + rd);
            const Slot sv = c.next();
            BP(1, 0);
            c.wait(sv);
            if (nrest == 0) {
#pragma unroll
                for (int i = 0; i < 64; i++) o[i] = 0.f;
            }
            if (__builtin_expect(__any_sync(0xffffffffu, !(l0 < 0x1p60f && l1 < 0x1p60f)), 0)) {
                attention_exact(o, qf, l0, l1, h, nrest + 1, lim, lane);
#pragma unroll
                for (int i = 0; i < 32; i++) pf[i] = 0u;
            }
            fence_regs(o); fence_regs(pf);
            if (!role) named_sync(bar_me, 256);
            BP(1, 2);
            wgmma_fence();
            gemm_rs<false>(o, pf, sv.dl);
            wgmma_commit();
            pend = sv.bo;
            ep_ptr = g_ctx + (size_t)(h * SEQ + 256 * p + 128 * rank + 64 * role + 16 * w + lr) * HD + 8 * q;
            ep_step = 8 * HD;
        }
        l0 += __shfl_xor_sync(0xffffffffu, l0, 1); l1 += __shfl_xor_sync(0xffffffffu, l1, 1);
        l0 += __shfl_xor_sync(0xffffffffu, l0, 2); l1 += __shfl_xor_sync(0xffffffffu, l1, 2);
        l0 = rcp(l0); l1 = rcp(l1);
        wgmma_wait<0>();
        c.release(pend);
        fence_regs(o); fence_regs(pf);
#pragma unroll
        for (int i = 0; i < 32; i++) pf[i] = pack_bf16(o[2 * i] * ((i & 1) ? l1 : l0), o[2 * i + 1] * ((i & 1) ? l1 : l0));
    }
    PROFG(187);
    PROF(3);
    if (cb == 8) {
#pragma unroll
        for (int i = 0; i < 8; i++) stg128(ep_ptr + (i & 1) * 8 * HD + 32 * (i >> 1), pf[4 * (i & 6) + (i & 1)], pf[4 * (i & 6) + (i & 1) + 2], pf[4 * (i & 6) + (i & 1) + 4], pf[4 * (i & 6) + (i & 1) + 6]);
        signal(bars, wg, 8, lane);
        cluster_arrive();
        named_sync(1, 256);
        mod_ffn(P, smem, 2 * ca + rank, wg);
    } else
    {
        float a1[64], a2[96];
        uint32_t px = 0, py = 0;
        auto mma1 = [&](const Slot& x, int acc) {
#pragma unroll
            for (int k = 0; k < 4; k++) wgmma_ss_n128<0, 1>(a1, x.dl + wg * 512 + lbo(16) + k * 2, x.dl + 1024 + lbo(4096) + (k >> 1) * 512 + (k & 1) * 128, k ? 1 : acc);
        };
        auto mma2 = [&](const Slot& x, const Slot& y, int acc) {
#pragma unroll
            for (int k = 0; k < 4; k++) wgmma_ss_n192<0, 1>(a2, x.dl + wg * 512 + lbo(16) + k * 2, y.dl + lbo(4096) + (k >> 1) * 768 + (k & 1) * 128, k ? 1 : acc);
        };
#pragma unroll 1
        for (int t = 0, more = 1; more; t++) {
            const Slot sx = c.next(), sy = c.next();
            c.wait(sx);
            wgmma_fence();
            mma1(sx, t);
            wgmma_commit();
            asm volatile("ld.shared.u32 %0, [%1];" : "=r"(more) : "r"(bars + CTL_OFF + sx.bo) : "memory");
            more = !__any_sync(0xffffffffu, more);
            wgmma_wait<1>();
            if (t > 0) { c.release(px); c.release(py); }
            px = sx.bo; py = sy.bo;
            c.wait(sy);
            wgmma_fence();
            mma2(sx, sy, t);
            wgmma_commit();
            if (t == 0) {
#pragma unroll
                for (int i = 0; i < 4; i++) stg128(ep_ptr + 32 * i, pf[8 * i], pf[8 * i + 2], pf[8 * i + 4], pf[8 * i + 6]);
            }
            if (t == 1) {
#pragma unroll
                for (int i = 0; i < 4; i++) stg128(ep_ptr + 8 * HD + 32 * i, pf[8 * i + 1], pf[8 * i + 3], pf[8 * i + 5], pf[8 * i + 7]);
                signal(bars, wg, 4 + n_items(ca, cb), lane);
            }
        }
        const Slot x0 = c.next(), y0 = c.next(), x1 = c.next(), y1 = c.next(), x2 = c.next(), y2 = c.next(), fr = c.next();
        const int cw = __reduce_or_sync(0xffffffffu, wg * 4 + w);
        const int orow = unperm_row(256 * out_p(ca, cb) + 128 * rank + 16 * cw), ocol = 320 * (ca >> 2);
        const uint32_t sa = ((lane & 7) + (lane & 8)) * 128, sx = (lane >> 4) ^ (lane & 7);
        auto send = [&](auto chv, uint32_t box) {
            constexpr int ch = chv.value;
#pragma unroll
            for (int i = 0; i < 4; i++) {
                uint32_t r[4];
#pragma unroll
                for (int e = 0; e < 4; e++) {
                    const int k = 32 * ch + 8 * i + 2 * e;
                    r[e] = (ch < 2) ? pack_bf16(a1[k & 63], a1[(k & 63) + 1]) : pack_bf16(a2[ch < 2 ? 0 : k - 64], a2[ch < 2 ? 1 : k - 63]);
                }
                asm volatile("stmatrix.sync.aligned.m8n8.x4.shared.b16 [%0], {%1, %2, %3, %4};"
                             ::"r"(box + sa + ((sx ^ (2 * i)) << 4)), "r"(r[0]), "r"(r[1]), "r"(r[2]), "r"(r[3]) : "memory");
            }
            asm volatile("fence.proxy.async.shared::cta;" ::: "memory");
            __syncwarp();
            asm volatile(ELECT "cp.reduce.async.bulk.tensor.2d.global.shared::cta.add.bulk_group [%0, {%2, %3}], [%1];\n}\n"
                         ::"l"(&P.outm), "r"(box), "r"(ocol + 64 * ch), "r"(orow) : "memory");
        };
        auto addr = [&](const Slot& t) { return smem + t.bo * (SLOT / 8); };
        c.wait(x0);
        wgmma_fence();
        mma1(x0, 1);
        wgmma_commit();
        wgmma_wait<1>();
        c.release(px); c.release(py);
        c.wait(x1);
        c.wait(x2);
        c.wait(y0);
        mbar_wait(bars + BAR_DEP, 0);
        wgmma_fence();
        mma1(x1, 1);
        mma1(x2, 1);
        wgmma_commit();
        mma2(x0, y0, 1);
        wgmma_commit();
        mbar_wait(bars + BAR_EMPTY + fr.bo, fr.par ^ 1);
        c.wait(y1);
        wgmma_wait<1>();
        fence_regs(a1);
        send(IntT<0>{}, addr(fr) + cw * 4096);
        wgmma_fence();
        mma2(x1, y1, 1);
        wgmma_commit();
        send(IntT<1>{}, addr(fr) + cw * 4096 + 2048);
        c.wait(y2);
        wgmma_fence();
        mma2(x2, y2, 1);
        wgmma_commit();
        wgmma_wait<0>();
        fence_regs(a2);
        PROFG(188);
        PROF(4);
        send(IntT<2>{}, addr(x0) + cw * 2048);
        send(IntT<3>{}, addr(x1) + cw * 2048);
        send(IntT<4>{}, addr(x2) + cw * 2048);
        PROF(5);
        asm volatile("cp.async.bulk.commit_group;\ncp.async.bulk.wait_group.read 0;" ::: "memory");
    }
    PROF(6);
}

__device__ __forceinline__ void mod_ffn(const Params& P, uint32_t smem, int mc  , int wg) {
    const int tid = threadIdx.x - 128, lane = tid & 31, cw = tid >> 5, q = lane & 3, lr = lane >> 2;
    const uint32_t xs = smem + 6 * SLOT, hs = xs + 10240 + wg * 1024, wmax = xs + 12288, sidx = wmax + 64, rbar = xs + 13312 + wg * 32;
    const uint32_t ring = smem + wg * 3 * SLOT;
    const int f0 = mc + 4 * wg, nunit = ((34 - f0) >> 3) * 8;
    const bool lead = __reduce_or_sync(0xffffffffu, cw & 3) == 0;
    auto lds = [](uint32_t a) { uint32_t v; asm volatile("ld.shared.u32 %0, [%1];" : "=r"(v) : "r"(a) : "memory"); return v; };
    auto sts = [](uint32_t a, uint32_t v) { asm volatile("st.shared.u32 [%0], %1;" ::"r"(a), "r"(v) : "memory"); };
    auto issue = [&](int u, int st) {
        if (lead && u < nunit) {
            const int fc = (f0 + (u & ~7)) * 64, k = u & 7;
            const uint32_t dst = ring + st * SLOT, bar = rbar + st * 8;
            w_expect_tx(bar, k == 7 ? 16384 : SLOT);
            if (k < 5) {
                w_tma_load_stream(dst, &P.wg, fc, k * 128, bar);
                w_tma_load_stream(dst + 16384, &P.wu, fc, k * 128, bar);
            } else {
#pragma unroll 1
                for (int b = 0; b < (k == 7 ? 2 : 4); b++) w_tma_load_stream(dst + b * 8192, &P.wd, (4 * (k - 5) + b) * 64, fc, bar);
            }
        }
    };
    if ((tid & 127) == 0) {
        mbar_init(rbar, 1); mbar_init(rbar + 8, 1); mbar_init(rbar + 16, 1);
        asm volatile("fence.mbarrier_init.release.cluster;" ::: "memory");
    }
    mbar_wait(smem + NSLOT * SLOT + BAR_DEP, 0);
    asm volatile("fence.proxy.async.shared::cta;" ::: "memory");
    named_sync(1, 256);
    PROF(1);
#pragma unroll 1
    for (int u = 0; u < 3; u++) issue(u, u);
    uint32_t key[8];
#pragma unroll
    for (int i = 0; i < 8; i++) {
        const int t = tid + 256 * i;
        uint32_t b = __float_as_uint(__ldcg(g_r + t) + 0.f) >> 16;
        b = (b & 0x8000u) ? (~b & 0xffffu) : (b | 0x8000u);
        key[i] = (b << 16) | (uint32_t)(0xffff - t);
    }
#pragma unroll 1
    for (int rnd = 0; rnd < 8; rnd++) {
        uint32_t mx = key[0];
#pragma unroll
        for (int i = 1; i < 8; i++) mx = max(mx, key[i]);
        sts(wmax + ((rnd & 1) * 8 + cw) * 4, __reduce_max_sync(0xffffffffu, mx));
        named_sync(1, 256);
        mx = __reduce_max_sync(0xffffffffu, lds(wmax + ((rnd & 1) * 8 + (lane & 7)) * 4));
#pragma unroll
        for (int i = 0; i < 8; i++) if (key[i] == mx) key[i] = 0;
        if (cw == rnd) sts(sidx + rnd * 4, 0xffff - (mx & 0xffffu));
    }
    __syncwarp();
    {
        const int t = lds(sidx + cw * 4);
        const uint4* src = reinterpret_cast<const uint4*>(g_xn + perm_row(t) * DM);
#pragma unroll
        for (int i = 0; i < 3; i++) {
            const int ch = lane + 32 * i;
            if (ch < 80) {
                const uint4 v = __ldcg(src + ch);
                asm volatile("st.shared.v4.b32 [%0], {%1, %2, %3, %4};" ::"r"(xs + (ch >> 3) * 1024 + cw * 128 + ((ch ^ cw) & 7) * 16), "r"(v.x), "r"(v.y), "r"(v.z), "r"(v.w) : "memory");
            }
        }
        asm volatile("fence.proxy.async.shared::cta;" ::: "memory");
    }
    named_sync(1, 256);
    PROF(3);
    float y[10][4];
#pragma unroll
    for (int i = 0; i < 10; i++) { y[i][0] = 0.f; y[i][1] = 0.f; y[i][2] = 0.f; y[i][3] = 0.f; }
    int st = 0, ph = 0, u = 0;
    auto begin = [&]() { mbar_wait(rbar + st * 8, ph); wgmma_fence(); return (((ring + st * SLOT) & 0x3FFFF) >> 4) + lbo(16); };
    auto end = [&]() {
        wgmma_commit();
        wgmma_wait<0>();
        named_sync(4 + wg, 128);
        issue(u + 3, st);
        u++;
        ph ^= st == 2;
        st = (st == 2) ? 0 : st + 1;
    };
    const uint32_t dx = ((xs & 0x3FFFF) >> 4) + lbo(16), dh = ((hs & 0x3FFFF) >> 4) + lbo(16);
#pragma unroll 1
    while (u < nunit) {
        float g[4], v[4];
#pragma unroll 1
        for (int kc = 0; kc < 5; kc++) {
            const uint32_t da = begin();
#pragma unroll
            for (int k = 0; k < 8; k++) {
                const uint32_t db = dx + (2 * kc + (k >> 2)) * 64 + (k & 3) * 2;
                wgmma_ss_n8<1, 0>(g, da + k * 128, db, k ? 1 : kc);
                wgmma_ss_n8<1, 0>(v, da + 1024 + k * 128, db, k ? 1 : kc);
            }
            end();
        }
        fence_regs(g); fence_regs(v);
#pragma unroll
        for (int e = 0; e < 4; e++) {
            const float gp = round_bf16(g[e]);
            const float hv = round_bf16(__fdividef(gp, 1.0f + __expf(fminf(-gp, 80.f)))) * round_bf16(v[e]);
            const int tok = 2 * q + (e & 1), ch = 2 * (cw & 3) + (e >> 1);
            asm volatile("st.shared.u16 [%0], %1;" ::"r"(hs + tok * 128 + ((ch ^ tok) * 16) + lr * 2), "h"((unsigned short)pack_bf16(hv, 0.f)) : "memory");
        }
        asm volatile("fence.proxy.async.shared::cta;" ::: "memory");
        named_sync(4 + wg, 128);
#pragma unroll
        for (int k3 = 0; k3 < 3; k3++) {
            const uint32_t da = begin();
#pragma unroll
            for (int b = 0; b < (k3 == 2 ? 2 : 4); b++)
#pragma unroll
                for (int k = 0; k < 4; k++) wgmma_ss_n8<1, 0>(y[4 * k3 + b], da + b * 512 + k * 128, dh + k * 2, 1);
            end();
        }
    }
    PROF(5);
#pragma unroll
    for (int i = 0; i < 10; i++) {
        fence_regs(y[i]);
#pragma unroll
        for (int e = 0; e < 4; e++) g_ypart[((mc * 2 + wg) * 8 + 2 * q + (e & 1)) * DM + 64 * i + 16 * (cw & 3) + lr + 8 * (e >> 1)] = y[i][e];
    }
    named_sync(1, 256);
    if (tid == 0) {
        flag_add(F_MODP);
        flag_wait<100>(F_MODP, 4u * (lds(smem + NSLOT * SLOT + MISC_OFF) + 1));
    }
    named_sync(1, 256);
    PROF(6);
    {
        const int c = 2 * mc + wg, t = lds(sidx + c * 4);
        const float rs = round_bf16(__fdividef(1.0f, 1.0f + __expf(fminf(-__ldcg(g_r + t), 80.f))));
#pragma unroll
        for (int i = 0; i < 3; i++) {
            const int c2 = (tid & 127) + 128 * i;
            if (c2 < DM / 2) {
                float y0 = 0.f, y1 = 0.f;
#pragma unroll
                for (int k = 0; k < 8; k++) {
                    const float2 v = __ldcg(reinterpret_cast<const float2*>(g_ypart + (k * 8 + c) * DM) + c2);
                    y0 += v.x; y1 += v.y;
                }
                asm volatile("red.relaxed.gpu.global.add.noftz.bf16x2 [%0], %1;" ::"l"(P.out + t * DM + 2 * c2), "r"(pack_bf16(round_bf16(y0) * rs, round_bf16(y1) * rs)) : "memory");
            }
        }
    }
    PROF(7);
}

__global__ void __cluster_dims__(2, 1, 1) __launch_bounds__(384, 1) fused_kernel(const __grid_constant__ Params P) {
    extern __shared__ __align__(1024) uint8_t smem_raw[];
    const uint32_t smem = (smem_u32(smem_raw) + 1023u) & ~1023u;
    const uint32_t bars = smem + NSLOT * SLOT;
    const int wgi = __reduce_or_sync(0xffffffffu, threadIdx.x >> 7);
    const int cl = blockIdx.x >> 1, rank = blockIdx.x & 1, ca = cl & 7, cb = cl >> 3;
    PROFG(30);
    PROF(0);
    if (threadIdx.x == 64) {
        const uint32_t fa = bars + BAR_FULL + slot_a(0) * 8, fw = bars + BAR_FULL + slot_w(0) * 8;
        mbar_init(fa, 1); mbar_init(fw, 1);
        asm volatile("fence.mbarrier_init.release.cluster;" ::: "memory");
        if (cb < 8) {
            mbar_expect_tx(fa, SLOT);
            mbar_expect_tx(fw, SLOT);
            tma_load(smem + slot_a(0) * SLOT, &P.ckv, 0, (2 * ca + rank) * 128, fa);
            tma_load(smem + slot_w(0) * SLOT, &P.wuk, (cb + 8 * kv_round(0)) * 128, 0, fw);
            tma_load(smem + slot_w(0) * SLOT + 16384, &P.wuk, (cb + 8 * kv_round(0)) * 128 + 64, 0, fw);
            tma_load(smem + slot_a(0) * SLOT + 16384, &P.ckv, 64, (2 * ca + rank) * 128, fa);
        }
    } else if (threadIdx.x == 0) {
#pragma unroll
        for (int i = 0; i < NSLOT; i++) {
            if (i != slot_a(0) && i != slot_w(0)) mbar_init(bars + BAR_FULL + i * 8, 1);
            mbar_init(bars + BAR_EMPTY + i * 8, 16);
        }
        if (cb < 8) {
            mbar_arrive(bars + BAR_FULL + 16);
            asm volatile("mbarrier.arrive.shared::cta.b64 _, [%0], 16;" ::"r"(bars + BAR_EMPTY + 16) : "memory");
        }
        asm volatile("fence.mbarrier_init.release.cluster;" ::: "memory");
        PROF(24);
    } else if (threadIdx.x == 32) {
#pragma unroll
        for (int i = 0; i < 18; i++) mbar_init(bars + BAR_SIG + i * 8, 4);
#pragma unroll
        for (int i = 0; i < 18; i++) mbar_init(bars + BAR_DEP + i * 8, 1);
        asm volatile("fence.mbarrier_init.release.cluster;" ::: "memory");
    }
    __syncthreads();
    PROF(29);
    cluster_arrive();
    if (wgi > 0) {
        asm volatile("setmaxnreg.inc.sync.aligned.u32 232;");
        consumer(P, smem, bars, ca, cb, rank, wgi - 1);
        PROFG(31);
        PROFDUMP();
    } else {
        asm volatile("setmaxnreg.dec.sync.aligned.u32 40;");
        const int w = __reduce_or_sync(0xffffffffu, threadIdx.x >> 5), lane = threadIdx.x & 31;
        if (threadIdx.x == 32) {
            prefetch_map(&P.wuv); prefetch_map(&P.xn); prefetch_map(&P.wq); prefetch_map(&P.kv); prefetch_map(&P.ctx); prefetch_map(&P.wo); prefetch_map(&P.outm);
        }
        __syncwarp();
        cluster_wait();
        PROF(27);
        {
            if (w == 0) {
                producer(P, smem, bars, ca, cb, rank);
            } else if (w < 3 && lane == 0) {
                const int wg = w - 1;
#pragma unroll 1
                for (int i = (cb == 8); i < (cb == 8 ? 9 : 5 + n_items(ca, cb)); i++) {
                    const int nb = wg + (LNOFF + 7 - 4) / 8;
                    const int e = (cb == 8) ? i : (i < nb) ? i + 1 : (i == nb) ? 0 : i;
                    mbar_wait_sleep(bars + BAR_SIG + (wg * 9 + e) * 8, 0);
                    int f;
                    if (cb == 8) f = F_CTX + (2 + ca) * 16 + rank;
                    else if (e == 0) {
                        f = F_LN;
                        if ((ca & 3) == 0 && rank == 0 && wg == 0) g_flags[(F_POOL + out_p(ca, cb) * 2 + (ca >> 2)) * 8] = 8;
                    }
                    else if (e < 5) f = F_KV + cb + 8 * kv_round(e - 1);
                    else { const int rd = item_rd(ca, cb, e - 5); f = F_CTX + rd * 16 + item_p(ca, rd) * 2 + rank; }
                    flag_add(f);
                }
            } else if (lane == 0) {
                const uint32_t epoch = read_epoch();
                asm volatile("st.shared.u32 [%0], %1;" ::"r"(bars + MISC_OFF), "r"(epoch) : "memory");
#pragma unroll 1
                for (int e = 0; e < 9; e++) {
                    int f;
                    uint32_t n;
                    if (e == 0) { f = F_LN; n = 256; }
                    else if (cb == 8) { f = F_KV + item_h(cb, 2 + ca, e - 1); n = 32; }
                    else if (e < 5) { f = F_KV + cb + 8 * (e - 1); n = 32; }
                    else { f = F_CTX + (e - 5) * 16 + out_p(ca, cb) * 2 + rank; n = 16; }
                    flag_wait<200>(f, n * (epoch + 1));
                    fence_proxy_async();
                    mbar_arrive(bars + BAR_DEP + e * 8);
                }
            }
        }
        if (cb == 8) { __syncwarp(); cluster_arrive(); cluster_wait(); }
        PROFG(31);
        PROFDUMP();
    }
}

typedef CUresult (*EncodeFn)(CUtensorMap*, CUtensorMapDataType, cuuint32_t, void*, const cuuint64_t*, const cuuint64_t*, const cuuint32_t*,
                             const cuuint32_t*, CUtensorMapInterleave, CUtensorMapSwizzle, CUtensorMapL2promotion, CUtensorMapFloatOOBfill);

void make_map(EncodeFn fn, CUtensorMap* m, const void* ptr, uint64_t rows, uint64_t cols, uint32_t box_rows) {
    cuuint64_t dims[2] = {cols, rows};
    cuuint64_t strides[1] = {cols * 2};
    cuuint32_t box[2] = {64, box_rows};
    cuuint32_t es[2] = {1, 1};
    fn(m, CU_TENSOR_MAP_DATA_TYPE_BFLOAT16, 2, const_cast<void*>(ptr), dims, strides, box, es, CU_TENSOR_MAP_INTERLEAVE_NONE,
       CU_TENSOR_MAP_SWIZZLE_128B, CU_TENSOR_MAP_L2_PROMOTION_L2_128B, CU_TENSOR_MAP_FLOAT_OOB_FILL_NONE);
}

}

extern "C" void kernel_launch(void* const* d_in, const int* in_sizes, int n_in, void* d_out, int out_size) {
    (void)in_sizes; (void)n_in; (void)out_size;
    void* fnp = nullptr;
    cudaDriverEntryPointQueryResult qr;
    cudaGetDriverEntryPoint("cuTensorMapEncodeTiled", &fnp, cudaEnableDefault, &qr);
    EncodeFn fn = (EncodeFn)fnp;
    void *xn, *kv, *ctx;
    cudaGetSymbolAddress(&xn, g_xn);
    cudaGetSymbolAddress(&kv, g_kv);
    cudaGetSymbolAddress(&ctx, g_ctx);
    Params P;
    make_map(fn, &P.ckv, d_in[1], SEQ, DC, 128);
    make_map(fn, &P.wq, d_in[2], DM, NH * HD, 64);
    make_map(fn, &P.wuk, d_in[3], DC, NH * HD, 128);
    make_map(fn, &P.wuv, d_in[4], DC, NH * HD, 128);
    make_map(fn, &P.wo, d_in[5], NH * HD, DM, 32);
    make_map(fn, &P.xn, xn, SEQ, DM, 128);
    make_map(fn, &P.kv, kv, NH * 16 * 2 * 128, 128, 128);
    make_map(fn, &P.ctx, ctx, NH * SEQ, HD, 128);
    P.x = (const __nv_bfloat16*)d_in[0];
    P.wr = (const __nv_bfloat16*)d_in[7];
    make_map(fn, &P.wg, d_in[8], DM, FF, 128);
    make_map(fn, &P.wu, d_in[9], DM, FF, 128);
    make_map(fn, &P.wd, d_in[10], FF, DM, 64);
    make_map(fn, &P.outm, d_out, SEQ, DM, 16);
    P.out = (__nv_bfloat16*)d_out;
    cudaFuncSetAttribute(fused_kernel, cudaFuncAttributeMaxDynamicSharedMemorySize, SMEM_BYTES);
    fused_kernel<<<NCTA, 384, SMEM_BYTES>>>(P);
}
```

```cpp
#include <cuda_runtime.h>
#include <cuda_bf16.h>
#include <cuda.h>
#include <stdint.h>

namespace {

constexpr int SEQ = 2048, DM = 640, DC = 512, NH = 32, HD = 128, FF = 1728;
constexpr int NSLOT = 7, SLOT = 32768;
constexpr int NCTA = 132;
#define PEEK 1
constexpr int KVSPLIT = 1;
constexpr int LNOFF = 4, LNLEAD = 2;
constexpr int SPLITJ = 8;
constexpr uint32_t DESC_HI = (1024u >> 4) | (1u << 30);
constexpr int SMEM_BYTES = NSLOT * SLOT + 3072;

constexpr int BAR_FULL = 0, BAR_EMPTY = 64, BAR_SIG = 128  , BAR_DEP = 320  , BAR_MAIL = 400  ;
constexpr int MISC_OFF = 512  , MAIL_OFF = 544  , CTL_OFF = 576  ;

constexpr int F_EPOCH = 0, F_LN = 1, F_MODP = 3, F_KV = 4  , F_CTX = 36  , F_POOL = 100  , F_NUM = 116;

__device__ __align__(1024) __nv_bfloat16 g_xn[SEQ * DM];
__device__ __align__(1024) __nv_bfloat16 g_kv[NH * 16 * 2 * 128 * 128];
__device__ __align__(1024) __nv_bfloat16 g_ctx[NH * SEQ * HD];
__device__ __align__(16) float g_r[SEQ];
__device__ __align__(16) float g_ypart[8 * 8 * DM];
__device__ uint32_t g_flags[F_NUM * 8];

struct TrueT { static constexpr bool value = true; };
struct FalseT { static constexpr bool value = false; };

struct Params {
    CUtensorMap ckv, wuk, wuv, xn, wq, kv, ctx, wo, wg, wu, wd, outm;
    const __nv_bfloat16 *x, *wr;
    __nv_bfloat16* out;
};

__device__ __forceinline__ uint32_t smem_u32(const void* p) { return (uint32_t)__cvta_generic_to_shared(p); }
__device__ __forceinline__ void mbar_init(uint32_t bar, uint32_t cnt) {
    asm volatile("mbarrier.init.shared::cta.b64 [%0], %1;" ::"r"(bar), "r"(cnt) : "memory");
}
__device__ __forceinline__ void mbar_expect_tx(uint32_t bar, uint32_t bytes) {
    asm volatile("mbarrier.arrive.expect_tx.shared::cta.b64 _, [%0], %1;" ::"r"(bar), "r"(bytes) : "memory");
}
__device__ __forceinline__ void mbar_arrive(uint32_t bar) {
    asm volatile("mbarrier.arrive.shared::cta.b64 _, [%0];" ::"r"(bar) : "memory");
}
__device__ __forceinline__ uint32_t mapa(uint32_t addr, uint32_t cta) {
    uint32_t r;
    asm("mapa.shared::cluster.u32 %0, %1, %2;" : "=r"(r) : "r"(addr), "r"(cta));
    return r;
}
__device__ __forceinline__ void mbar_wait(uint32_t bar, uint32_t parity) {
    asm volatile(
        "{\n.reg .pred p;\n.reg .b32 c;\n"
        "mov.b32 c, 0;\n"
        "WLOOP:\n"
        "mbarrier.try_wait.parity.shared::cta.b64 p, [%0], %1;\n"
        "@p bra.uni WDONE;\n"
        "add.u32 c, c, 1;\n"
        "setp.lt.u32 p, c, 0x400000;\n"
        "@p bra.uni WLOOP;\n"
        "trap;\n"
        "WDONE:\n}\n" ::"r"(bar), "r"(parity) : "memory");
}
__device__ __forceinline__ uint32_t mbar_peek(uint32_t bar, uint32_t parity) {
    uint32_t ok;
    asm volatile("{\n.reg .pred p;\nmbarrier.test_wait.parity.shared::cta.b64 p, [%1], %2;\nselp.b32 %0, 1, 0, p;\n}\n" : "=r"(ok) : "r"(bar), "r"(parity) : "memory");
    return ok;
}
__device__ __forceinline__ void mbar_wait_unless(uint32_t ok, uint32_t bar, uint32_t parity) {
    asm volatile(
        "{\n.reg .pred p;\n.reg .b32 c;\n"
        "setp.ne.b32 p, %2, 0;\n"
        "@p bra.uni WDONE;\n"
        "mov.b32 c, 0;\n"
        "WLOOP:\n"
        "mbarrier.try_wait.parity.shared::cta.b64 p, [%0], %1;\n"
        "@p bra.uni WDONE;\n"
        "add.u32 c, c, 1;\n"
        "setp.lt.u32 p, c, 0x400000;\n"
        "@p bra.uni WLOOP;\n"
        "trap;\n"
        "WDONE:\n}\n" ::"r"(bar), "r"(parity), "r"(ok) : "memory");
}
__device__ __forceinline__ void mbar_wait_sleep(uint32_t bar, uint32_t parity) {
    asm volatile(
        "{\n.reg .pred p;\n.reg .b32 c;\n"
        "mov.b32 c, 0;\n"
        "WLOOP:\n"
        "mbarrier.try_wait.parity.shared::cta.b64 p, [%0], %1, 20000;\n"
        "@p bra.uni WDONE;\n"
        "add.u32 c, c, 1;\n"
        "setp.lt.u32 p, c, 0x40000;\n"
        "@p bra.uni WLOOP;\n"
        "trap;\n"
        "WDONE:\n}\n" ::"r"(bar), "r"(parity) : "memory");
}
__device__ __forceinline__ void tma_load(uint32_t dst, const CUtensorMap* m, int c0, int c1, uint32_t bar) {
    asm volatile("cp.async.bulk.tensor.2d.shared::cluster.global.mbarrier::complete_tx::bytes [%0], [%1, {%3, %4}], [%2];"
                 ::"r"(dst), "l"(m), "r"(bar), "r"(c0), "r"(c1) : "memory");
}
#define ELECT "{\n.reg .pred e;\nelect.sync _|e, 0xffffffff;\n@e "
__device__ __forceinline__ void w_expect_tx(uint32_t bar, uint32_t bytes) {
    asm volatile(ELECT "mbarrier.arrive.expect_tx.shared::cta.b64 _, [%0], %1;\n}\n" ::"r"(bar), "r"(bytes) : "memory");
}
__device__ __forceinline__ void w_tma_load(uint32_t dst, const CUtensorMap* m, int c0, int c1, uint32_t bar) {
    asm volatile(ELECT "cp.async.bulk.tensor.2d.shared::cluster.global.mbarrier::complete_tx::bytes [%0], [%1, {%3, %4}], [%2];\n}\n"
                 ::"r"(dst), "l"(m), "r"(bar), "r"(c0), "r"(c1) : "memory");
}
__device__ __forceinline__ void w_tma_load_mc(uint32_t dst, const CUtensorMap* m, int c0, int c1, uint32_t bar) {
    asm volatile(ELECT "cp.async.bulk.tensor.2d.shared::cluster.global.mbarrier::complete_tx::bytes.multicast::cluster [%0], [%1, {%3, %4}], [%2], %5;\n}\n"
                 ::"r"(dst), "l"(m), "r"(bar), "r"(c0), "r"(c1), "h"((uint16_t)3) : "memory");
}
__device__ __forceinline__ void w_tma_prefetch(const CUtensorMap* m, int c0, int c1) {
    asm volatile(ELECT "cp.async.bulk.prefetch.tensor.2d.L2.global [%0, {%1, %2}];\n}\n" ::"l"(m), "r"(c0), "r"(c1) : "memory");
}
__device__ __forceinline__ uint64_t policy_evict_first() {
    uint64_t p;
    asm("createpolicy.fractional.L2::evict_first.b64 %0, 1.0;" : "=l"(p));
    return p;
}
__device__ __forceinline__ void w_tma_load_mc_last(uint32_t dst, const CUtensorMap* m, int c0, int c1, uint32_t bar) {
    asm volatile(ELECT "cp.async.bulk.tensor.2d.shared::cluster.global.mbarrier::complete_tx::bytes.multicast::cluster.L2::cache_hint [%0], [%1, {%3, %4}], [%2], %5, %6;\n}\n"
                 ::"r"(dst), "l"(m), "r"(bar), "r"(c0), "r"(c1), "h"((uint16_t)3), "l"(policy_evict_first()) : "memory");
}
__device__ __forceinline__ void w_tma_load_stream(uint32_t dst, const CUtensorMap* m, int c0, int c1, uint32_t bar) {
    asm volatile(ELECT "cp.async.bulk.tensor.2d.shared::cluster.global.mbarrier::complete_tx::bytes.L2::cache_hint [%0], [%1, {%3, %4}], [%2], %5;\n}\n"
                 ::"r"(dst), "l"(m), "r"(bar), "r"(c0), "r"(c1), "l"(policy_evict_first()) : "memory");
}
__device__ __forceinline__ uint4 ldg_stream(const void* p) {
    uint4 v;
    asm volatile("ld.global.nc.L2::cache_hint.v4.b32 {%0, %1, %2, %3}, [%4], %5;" : "=r"(v.x), "=r"(v.y), "=r"(v.z), "=r"(v.w) : "l"(p), "l"(policy_evict_first()));
    return v;
}
__device__ __forceinline__ void prefetch_map(const CUtensorMap* m) {
    asm volatile("prefetch.tensormap [%0];" ::"l"(m) : "memory");
}
__device__ __forceinline__ void cluster_arrive() { asm volatile("barrier.cluster.arrive.relaxed.aligned;" ::: "memory"); }
__device__ __forceinline__ void cluster_wait() { asm volatile("barrier.cluster.wait.aligned;" ::: "memory"); }
__device__ __forceinline__ void named_sync(int id, int n) { asm volatile("bar.sync %0, %1;" ::"r"(id), "r"(n) : "memory"); }
__device__ __forceinline__ void named_arrive(int id, int n) { asm volatile("bar.arrive %0, %1;" ::"r"(id), "r"(n) : "memory"); }

__device__ __forceinline__ void flag_add(int f) {
    asm volatile("fence.acq_rel.gpu;\nred.relaxed.gpu.global.add.u32 [%0], 1;" ::"l"(g_flags + f * 8) : "memory");
}
template <int SLEEP>
__device__ __forceinline__ void flag_wait(int f, uint32_t target) {
    asm volatile(
        "{\n.reg .pred p;\n.reg .b32 c, v;\n"
        "mov.b32 c, 0;\n"
        "FLOOP:\n"
        "ld.acquire.gpu.global.u32 v, [%0];\n"
        "sub.u32 v, v, %1;\n"
        "setp.ge.s32 p, v, 0;\n"
        "@p bra FDONE;\n"
        "nanosleep.u32 %2;\n"
        "add.u32 c, c, 1;\n"
        "setp.lt.u32 p, c, 0x400000;\n"
        "@p bra FLOOP;\n"
        "trap;\n"
        "FDONE:\n}\n" ::"l"(g_flags + f * 8), "r"(target), "n"(SLEEP) : "memory");
}
__device__ __forceinline__ uint32_t read_epoch() { return atomicAdd(g_flags + F_EPOCH * 8, 1u) / NCTA; }
__device__ __forceinline__ void fence_proxy_async() { asm volatile("fence.proxy.async;" ::: "memory"); }

__device__ __forceinline__ void wgmma_fence() { asm volatile("wgmma.fence.sync.aligned;" ::: "memory"); }
__device__ __forceinline__ void wgmma_commit() { asm volatile("wgmma.commit_group.sync.aligned;" ::: "memory"); }
template <int N>
__device__ __forceinline__ void wgmma_wait() { asm volatile("wgmma.wait_group.sync.aligned %0;" ::"n"(N) : "memory"); }
template <int N>
__device__ __forceinline__ void fence_regs(float (&d)[N]) {
#pragma unroll
    for (int i = 0; i < N; i++) asm volatile("" : "+f"(d[i])::"memory");
}
template <int N>
__device__ __forceinline__ void fence_regs(uint32_t (&d)[N]) {
#pragma unroll
    for (int i = 0; i < N; i++) asm volatile("" : "+r"(d[i])::"memory");
}

template <int TA, int TB>
__device__ __forceinline__ void wgmma_ss_n128(float (&d)[64], uint32_t alo, uint32_t blo, int scale_d) {
    asm volatile("{\n.reg .pred p;\n.reg .b64 da, db;\nsetp.ne.b32 p, %66, 0;\n"
        "mov.b64 da, {%64, %69};\nmov.b64 db, {%65, %69};\n"
        "wgmma.mma_async.sync.aligned.m64n128k16.f32.bf16.bf16 "
        "{%0, %1, %2, %3, %4, %5, %6, %7, %8, %9, %10, %11, %12, %13, %14, %15, %16, %17, %18, %19, %20, %21, %22, %23, %24, %25, %26, %27, %28, %29, %30, %31, %32, %33, %34, %35, %36, %37, %38, %39, %40, %41, %42, %43, %44, %45, %46, %47, %48, %49, %50, %51, %52, %53, %54, %55, %56, %57, %58, %59, %60, %61, %62, %63}, da, db, p, 1, 1, %67, %68;\n}\n"
        :
          "+f"(d[0]), "+f"(d[1]), "+f"(d[2]), "+f"(d[3]), "+f"(d[4]), "+f"(d[5]), "+f"(d[6]), "+f"(d[7]),
          "+f"(d[8]), "+f"(d[9]), "+f"(d[10]), "+f"(d[11]), "+f"(d[12]), "+f"(d[13]), "+f"(d[14]), "+f"(d[15]),
          "+f"(d[16]), "+f"(d[17]), "+f"(d[18]), "+f"(d[19]), "+f"(d[20]), "+f"(d[21]), "+f"(d[22]), "+f"(d[23]),
          "+f"(d[24]), "+f"(d[25]), "+f"(d[26]), "+f"(d[27]), "+f"(d[28]), "+f"(d[29]), "+f"(d[30]), "+f"(d[31]),
          "+f"(d[32]), "+f"(d[33]), "+f"(d[34]), "+f"(d[35]), "+f"(d[36]), "+f"(d[37]), "+f"(d[38]), "+f"(d[39]),
          "+f"(d[40]), "+f"(d[41]), "+f"(d[42]), "+f"(d[43]), "+f"(d[44]), "+f"(d[45]), "+f"(d[46]), "+f"(d[47]),
          "+f"(d[48]), "+f"(d[49]), "+f"(d[50]), "+f"(d[51]), "+f"(d[52]), "+f"(d[53]), "+f"(d[54]), "+f"(d[55]),
          "+f"(d[56]), "+f"(d[57]), "+f"(d[58]), "+f"(d[59]), "+f"(d[60]), "+f"(d[61]), "+f"(d[62]), "+f"(d[63])
        : "r"(alo), "r"(blo), "r"(scale_d), "n"(TA), "n"(TB), "r"(DESC_HI));
}
template <int TA, int TB>
__device__ __forceinline__ void wgmma_ss_n192(float (&d)[96], uint32_t alo, uint32_t blo, int scale_d) {
    asm volatile("{\n.reg .pred p;\n.reg .b64 da, db;\nsetp.ne.b32 p, %98, 0;\n"
        "mov.b64 da, {%96, %101};\nmov.b64 db, {%97, %101};\n"
        "wgmma.mma_async.sync.aligned.m64n192k16.f32.bf16.bf16 "
        "{%0, %1, %2, %3, %4, %5, %6, %7, %8, %9, %10, %11, %12, %13, %14, %15, %16, %17, %18, %19, %20, %21, %22, %23, %24, %25, %26, %27, %28, %29, %30, %31, %32, %33, %34, %35, %36, %37, %38, %39, %40, %41, %42, %43, %44, %45, %46, %47, %48, %49, %50, %51, %52, %53, %54, %55, %56, %57, %58, %59, %60, %61, %62, %63, %64, %65, %66, %67, %68, %69, %70, %71, %72, %73, %74, %75, %76, %77, %78, %79, %80, %81, %82, %83, %84, %85, %86, %87, %88, %89, %90, %91, %92, %93, %94, %95}, da, db, p, 1, 1, %99, %100;\n}\n"
        :
          "+f"(d[0]), "+f"(d[1]), "+f"(d[2]), "+f"(d[3]), "+f"(d[4]), "+f"(d[5]), "+f"(d[6]), "+f"(d[7]),
          "+f"(d[8]), "+f"(d[9]), "+f"(d[10]), "+f"(d[11]), "+f"(d[12]), "+f"(d[13]), "+f"(d[14]), "+f"(d[15]),
          "+f"(d[16]), "+f"(d[17]), "+f"(d[18]), "+f"(d[19]), "+f"(d[20]), "+f"(d[21]), "+f"(d[22]), "+f"(d[23]),
          "+f"(d[24]), "+f"(d[25]), "+f"(d[26]), "+f"(d[27]), "+f"(d[28]), "+f"(d[29]), "+f"(d[30]), "+f"(d[31]),
          "+f"(d[32]), "+f"(d[33]), "+f"(d[34]), "+f"(d[35]), "+f"(d[36]), "+f"(d[37]), "+f"(d[38]), "+f"(d[39]),
          "+f"(d[40]), "+f"(d[41]), "+f"(d[42]), "+f"(d[43]), "+f"(d[44]), "+f"(d[45]), "+f"(d[46]), "+f"(d[47]),
          "+f"(d[48]), "+f"(d[49]), "+f"(d[50]), "+f"(d[51]), "+f"(d[52]), "+f"(d[53]), "+f"(d[54]), "+f"(d[55]),
          "+f"(d[56]), "+f"(d[57]), "+f"(d[58]), "+f"(d[59]), "+f"(d[60]), "+f"(d[61]), "+f"(d[62]), "+f"(d[63]),
          "+f"(d[64]), "+f"(d[65]), "+f"(d[66]), "+f"(d[67]), "+f"(d[68]), "+f"(d[69]), "+f"(d[70]), "+f"(d[71]),
          "+f"(d[72]), "+f"(d[73]), "+f"(d[74]), "+f"(d[75]), "+f"(d[76]), "+f"(d[77]), "+f"(d[78]), "+f"(d[79]),
          "+f"(d[80]), "+f"(d[81]), "+f"(d[82]), "+f"(d[83]), "+f"(d[84]), "+f"(d[85]), "+f"(d[86]), "+f"(d[87]),
          "+f"(d[88]), "+f"(d[89]), "+f"(d[90]), "+f"(d[91]), "+f"(d[92]), "+f"(d[93]), "+f"(d[94]), "+f"(d[95])
        : "r"(alo), "r"(blo), "r"(scale_d), "n"(TA), "n"(TB), "r"(DESC_HI));
}
template <int TA, int TB>
__device__ __forceinline__ void wgmma_ss_n8(float (&d)[4], uint32_t alo, uint32_t blo, int scale_d) {
    asm volatile("{\n.reg .pred p;\n.reg .b64 da, db;\nsetp.ne.b32 p, %6, 0;\n"
        "mov.b64 da, {%4, %9};\nmov.b64 db, {%5, %9};\n"
        "wgmma.mma_async.sync.aligned.m64n8k16.f32.bf16.bf16 "
        "{%0, %1, %2, %3}, da, db, p, 1, 1, %7, %8;\n}\n"
        :
          "+f"(d[0]), "+f"(d[1]), "+f"(d[2]), "+f"(d[3])
        : "r"(alo), "r"(blo), "r"(scale_d), "n"(TA), "n"(TB), "r"(DESC_HI));
}
template <int TB>
__device__ __forceinline__ void wgmma_rs_n64(float (&d)[64], uint32_t a0, uint32_t a1, uint32_t a2, uint32_t a3, uint32_t blo, int scale_d) {
    asm volatile("{\n.reg .pred p;\n.reg .b64 db;\nsetp.ne.b32 p, %37, 0;\n"
        "mov.b64 db, {%36, %39};\n"
        "wgmma.mma_async.sync.aligned.m64n64k16.f32.bf16.bf16 "
        "{%0, %1, %2, %3, %4, %5, %6, %7, %8, %9, %10, %11, %12, %13, %14, %15, %16, %17, %18, %19, %20, %21, %22, %23, %24, %25, %26, %27, %28, %29, %30, %31}, {%32, %33, %34, %35}, db, p, 1, 1, %38;\n}\n"
        :
          "+f"(d[0]), "+f"(d[1]), "+f"(d[2]), "+f"(d[3]), "+f"(d[4]), "+f"(d[5]), "+f"(d[6]), "+f"(d[7]),
          "+f"(d[8]), "+f"(d[9]), "+f"(d[10]), "+f"(d[11]), "+f"(d[12]), "+f"(d[13]), "+f"(d[14]), "+f"(d[15]),
          "+f"(d[16]), "+f"(d[17]), "+f"(d[18]), "+f"(d[19]), "+f"(d[20]), "+f"(d[21]), "+f"(d[22]), "+f"(d[23]),
          "+f"(d[24]), "+f"(d[25]), "+f"(d[26]), "+f"(d[27]), "+f"(d[28]), "+f"(d[29]), "+f"(d[30]), "+f"(d[31])
        : "r"(a0), "r"(a1), "r"(a2), "r"(a3), "r"(blo), "r"(scale_d), "n"(TB), "r"(DESC_HI));
}
template <int TB>
__device__ __forceinline__ void wgmma_rs_n128(float (&d)[64], uint32_t a0, uint32_t a1, uint32_t a2, uint32_t a3, uint32_t blo, int scale_d) {
    asm volatile("{\n.reg .pred p;\n.reg .b64 db;\nsetp.ne.b32 p, %69, 0;\n"
        "mov.b64 db, {%68, %71};\n"
        "wgmma.mma_async.sync.aligned.m64n128k16.f32.bf16.bf16 "
        "{%0, %1, %2, %3, %4, %5, %6, %7, %8, %9, %10, %11, %12, %13, %14, %15, %16, %17, %18, %19, %20, %21, %22, %23, %24, %25, %26, %27, %28, %29, %30, %31, %32, %33, %34, %35, %36, %37, %38, %39, %40, %41, %42, %43, %44, %45, %46, %47, %48, %49, %50, %51, %52, %53, %54, %55, %56, %57, %58, %59, %60, %61, %62, %63}, {%64, %65, %66, %67}, db, p, 1, 1, %70;\n}\n"
        :
          "+f"(d[0]), "+f"(d[1]), "+f"(d[2]), "+f"(d[3]), "+f"(d[4]), "+f"(d[5]), "+f"(d[6]), "+f"(d[7]),
          "+f"(d[8]), "+f"(d[9]), "+f"(d[10]), "+f"(d[11]), "+f"(d[12]), "+f"(d[13]), "+f"(d[14]), "+f"(d[15]),
          "+f"(d[16]), "+f"(d[17]), "+f"(d[18]), "+f"(d[19]), "+f"(d[20]), "+f"(d[21]), "+f"(d[22]), "+f"(d[23]),
          "+f"(d[24]), "+f"(d[25]), "+f"(d[26]), "+f"(d[27]), "+f"(d[28]), "+f"(d[29]), "+f"(d[30]), "+f"(d[31]),
          "+f"(d[32]), "+f"(d[33]), "+f"(d[34]), "+f"(d[35]), "+f"(d[36]), "+f"(d[37]), "+f"(d[38]), "+f"(d[39]),
          "+f"(d[40]), "+f"(d[41]), "+f"(d[42]), "+f"(d[43]), "+f"(d[44]), "+f"(d[45]), "+f"(d[46]), "+f"(d[47]),
          "+f"(d[48]), "+f"(d[49]), "+f"(d[50]), "+f"(d[51]), "+f"(d[52]), "+f"(d[53]), "+f"(d[54]), "+f"(d[55]),
          "+f"(d[56]), "+f"(d[57]), "+f"(d[58]), "+f"(d[59]), "+f"(d[60]), "+f"(d[61]), "+f"(d[62]), "+f"(d[63])
        : "r"(a0), "r"(a1), "r"(a2), "r"(a3), "r"(blo), "r"(scale_d), "n"(TB), "r"(DESC_HI));
}
template <int TB>
__device__ __forceinline__ void wgmma_rs_n128_z(float (&d)[64], uint32_t a0, uint32_t a1, uint32_t a2, uint32_t a3, uint32_t blo) {
    asm volatile("{\n.reg .pred p;\n.reg .b64 db;\nsetp.ne.b32 p, %69, 0;\n"
        "mov.b64 db, {%68, %71};\n"
        "wgmma.mma_async.sync.aligned.m64n128k16.f32.bf16.bf16 "
        "{%0, %1, %2, %3, %4, %5, %6, %7, %8, %9, %10, %11, %12, %13, %14, %15, %16, %17, %18, %19, %20, %21, %22, %23, %24, %25, %26, %27, %28, %29, %30, %31, %32, %33, %34, %35, %36, %37, %38, %39, %40, %41, %42, %43, %44, %45, %46, %47, %48, %49, %50, %51, %52, %53, %54, %55, %56, %57, %58, %59, %60, %61, %62, %63}, {%64, %65, %66, %67}, db, p, 1, 1, %70;\n}\n"
        :
          "=f"(d[0]), "=f"(d[1]), "=f"(d[2]), "=f"(d[3]), "=f"(d[4]), "=f"(d[5]), "=f"(d[6]), "=f"(d[7]),
          "=f"(d[8]), "=f"(d[9]), "=f"(d[10]), "=f"(d[11]), "=f"(d[12]), "=f"(d[13]), "=f"(d[14]), "=f"(d[15]),
          "=f"(d[16]), "=f"(d[17]), "=f"(d[18]), "=f"(d[19]), "=f"(d[20]), "=f"(d[21]), "=f"(d[22]), "=f"(d[23]),
          "=f"(d[24]), "=f"(d[25]), "=f"(d[26]), "=f"(d[27]), "=f"(d[28]), "=f"(d[29]), "=f"(d[30]), "=f"(d[31]),
          "=f"(d[32]), "=f"(d[33]), "=f"(d[34]), "=f"(d[35]), "=f"(d[36]), "=f"(d[37]), "=f"(d[38]), "=f"(d[39]),
          "=f"(d[40]), "=f"(d[41]), "=f"(d[42]), "=f"(d[43]), "=f"(d[44]), "=f"(d[45]), "=f"(d[46]), "=f"(d[47]),
          "=f"(d[48]), "=f"(d[49]), "=f"(d[50]), "=f"(d[51]), "=f"(d[52]), "=f"(d[53]), "=f"(d[54]), "=f"(d[55]),
          "=f"(d[56]), "=f"(d[57]), "=f"(d[58]), "=f"(d[59]), "=f"(d[60]), "=f"(d[61]), "=f"(d[62]), "=f"(d[63])
        : "r"(a0), "r"(a1), "r"(a2), "r"(a3), "r"(blo), "n"(0), "n"(TB), "r"(DESC_HI));
}
template <int TA, int TB>
__device__ __forceinline__ void wgmma_ss_n128_z(float (&d)[64], uint32_t alo, uint32_t blo) {
    asm volatile("{\n.reg .pred p;\n.reg .b64 da, db;\nsetp.ne.b32 p, %66, 0;\n"
        "mov.b64 da, {%64, %69};\nmov.b64 db, {%65, %69};\n"
        "wgmma.mma_async.sync.aligned.m64n128k16.f32.bf16.bf16 "
        "{%0, %1, %2, %3, %4, %5, %6, %7, %8, %9, %10, %11, %12, %13, %14, %15, %16, %17, %18, %19, %20, %21, %22, %23, %24, %25, %26, %27, %28, %29, %30, %31, %32, %33, %34, %35, %36, %37, %38, %39, %40, %41, %42, %43, %44, %45, %46, %47, %48, %49, %50, %51, %52, %53, %54, %55, %56, %57, %58, %59, %60, %61, %62, %63}, da, db, p, 1, 1, %67, %68;\n}\n"
        :
          "=f"(d[0]), "=f"(d[1]), "=f"(d[2]), "=f"(d[3]), "=f"(d[4]), "=f"(d[5]), "=f"(d[6]), "=f"(d[7]),
          "=f"(d[8]), "=f"(d[9]), "=f"(d[10]), "=f"(d[11]), "=f"(d[12]), "=f"(d[13]), "=f"(d[14]), "=f"(d[15]),
          "=f"(d[16]), "=f"(d[17]), "=f"(d[18]), "=f"(d[19]), "=f"(d[20]), "=f"(d[21]), "=f"(d[22]), "=f"(d[23]),
          "=f"(d[24]), "=f"(d[25]), "=f"(d[26]), "=f"(d[27]), "=f"(d[28]), "=f"(d[29]), "=f"(d[30]), "=f"(d[31]),
          "=f"(d[32]), "=f"(d[33]), "=f"(d[34]), "=f"(d[35]), "=f"(d[36]), "=f"(d[37]), "=f"(d[38]), "=f"(d[39]),
          "=f"(d[40]), "=f"(d[41]), "=f"(d[42]), "=f"(d[43]), "=f"(d[44]), "=f"(d[45]), "=f"(d[46]), "=f"(d[47]),
          "=f"(d[48]), "=f"(d[49]), "=f"(d[50]), "=f"(d[51]), "=f"(d[52]), "=f"(d[53]), "=f"(d[54]), "=f"(d[55]),
          "=f"(d[56]), "=f"(d[57]), "=f"(d[58]), "=f"(d[59]), "=f"(d[60]), "=f"(d[61]), "=f"(d[62]), "=f"(d[63])
        : "r"(alo), "r"(blo), "n"(0), "n"(TA), "n"(TB), "r"(DESC_HI));
}

__device__ __forceinline__ uint32_t pack_bf16(float lo, float hi) {
    uint32_t r;
    asm("cvt.rn.bf16x2.f32 %0, %1, %2;" : "=r"(r) : "f"(hi), "f"(lo));
    return r;
}
__device__ __forceinline__ uint32_t add_bf16x2(uint32_t a, uint32_t b) {
    uint32_t r;
    asm("add.rn.bf16x2 %0, %1, %2;" : "=r"(r) : "r"(a), "r"(b));
    return r;
}
__device__ __forceinline__ float bf_lo(uint32_t v) { return __uint_as_float(v << 16); }
__device__ __forceinline__ float bf_hi(uint32_t v) { return __uint_as_float(v & 0xffff0000u); }
__device__ __forceinline__ float round_bf16(float v) { return __bfloat162float(__float2bfloat16_rn(v)); }
__device__ __forceinline__ float ex2(float x) {
    float y;
    asm("ex2.approx.ftz.f32 %0, %1;" : "=f"(y) : "f"(x));
    return y;
}
__device__ __forceinline__ float rcp(float x) {
    float y;
    asm("rcp.approx.ftz.f32 %0, %1;" : "=f"(y) : "f"(x));
    return y;
}
__device__ __forceinline__ void stg128(void* p, uint32_t a, uint32_t b, uint32_t c, uint32_t d) {
    asm volatile("st.global.v4.b32 [%0], {%1, %2, %3, %4};" ::"l"(p), "r"(a), "r"(b), "r"(c), "r"(d) : "memory");
}
__device__ __forceinline__ void stg128p(void* p, uint32_t a, uint32_t b, uint32_t c, uint32_t d, uint64_t pol) {
    asm volatile("st.global.L2::cache_hint.v4.b32 [%0], {%1, %2, %3, %4}, %5;" ::"l"(p), "r"(a), "r"(b), "r"(c), "r"(d), "l"(pol) : "memory");
}
__device__ __forceinline__ uint64_t policy_sel(bool first) {
    uint64_t p;
    asm("createpolicy.fractional.L2::evict_normal.b64 %0, 1.0;" : "=l"(p));
    return first ? policy_evict_first() : p;
}
__device__ __forceinline__ int perm_row(int t) { return (t & ~255) | (((0x78 >> (((t >> 6) & 3) * 2)) & 3) << 6) | (t & 63); }
__device__ __forceinline__ int unperm_row(int t) { return (t & ~255) | (((0x9C >> (((t >> 6) & 3) * 2)) & 3) << 6) | (t & 63); }

#define PROF(i)
#define PROFG(i)
#define PROFDUMP()
#define TR(i)
#define BP(r, i)
#define LP(i)

template <int I>
__device__ __forceinline__ void store_chunk(const float (&a)[64], __nv_bfloat16* row0, __nv_bfloat16* row1, float s0, float s1) {
    stg128(row0 + 32 * I, pack_bf16(a[16 * I + 0] * s0, a[16 * I + 1] * s0), pack_bf16(a[16 * I + 4] * s0, a[16 * I + 5] * s0),
           pack_bf16(a[16 * I + 8] * s0, a[16 * I + 9] * s0), pack_bf16(a[16 * I + 12] * s0, a[16 * I + 13] * s0));
    stg128(row1 + 32 * I, pack_bf16(a[16 * I + 2] * s1, a[16 * I + 3] * s1), pack_bf16(a[16 * I + 6] * s1, a[16 * I + 7] * s1),
           pack_bf16(a[16 * I + 10] * s1, a[16 * I + 11] * s1), pack_bf16(a[16 * I + 14] * s1, a[16 * I + 15] * s1));
}
template <int I>
struct IntT { static constexpr int value = I; };
template <class F>
__device__ __forceinline__ void for4(F f) { f(IntT<0>{}); f(IntT<1>{}); f(IntT<2>{}); f(IntT<3>{}); }

struct Prod {
    uint32_t smem, bars;
    uint32_t bo, par;
    uint32_t dst, fb;
    __device__ __forceinline__ void acquire(uint32_t o, uint32_t parity, uint32_t bytes) {
        mbar_wait(bars + BAR_EMPTY + o, parity);
        fb = bars + BAR_FULL + o;
        dst = smem + o * (SLOT / 8);
        w_expect_tx(fb, bytes);
    }
    __device__ __forceinline__ void next(uint32_t bytes) {
        acquire(bo, par, bytes);
        const bool wrap = bo == (NSLOT - 1) * 8;
        bo = wrap ? 0u : bo + 8;
        par ^= wrap ? 1u : 0u;
    }
};

__device__ __forceinline__ int item_p(int ca, int rd) {
    const int v = (rd & 1) ? (ca + 4) & 7 : ca;
    return (rd & 2) ? 7 - v : v;
}
__device__ __forceinline__ int n_items(int ca, int cb) { return cb == 8 ? 8 : ((ca & 3) == 3) ? 3 : 4; }
__device__ __forceinline__ int item_rd(int ca, int cb, int j) { return cb == 8 ? 2 + ca : (ca == 7 && j == 2) ? 3 : j; }
__device__ __forceinline__ int item_h(int cb, int rd, int j) { return 8 * rd + (cb == 8 ? j : cb); }
__device__ __forceinline__ int item_q(int ca, int cb, int rd) { return cb == 8 ? 0 : item_p(ca, rd); }
__device__ __forceinline__ int out_p(int ca, int cb) { return (cb + 2 * (ca & 3)) & 7; }
__device__ __forceinline__ int kv_round(int i) { return (0x1023 >> (4 * i)) & 3; }
__device__ __forceinline__ int slot_a(int i) { return (0x5310 >> (4 * i)) & 15; }
__device__ __forceinline__ int slot_w(int m) { return (0x264 >> (4 * m)) & 15; }

__device__ __forceinline__ void producer(const Params& P, uint32_t smem, uint32_t bars, int ca, int cb, int rank) {
    Prod pr{smem, bars, 0u, cb == 8 ? 1u : 0u, 0u, 0u};
    if (cb < 8) {
        int m = 0;
        uint32_t lap = 1;
#pragma unroll 1
        for (int u = 0; u < 32; u++) {
            if (u >= 3) {
                const int v = (u == 3) ? 3 + ca : u + 7;
                if (v < 32 && (u == 3 || (v & 7) == ca)) w_tma_prefetch((v & 4) ? &P.wuv : &P.wuk, (cb + 8 * kv_round(v >> 3)) * 128 + rank * 64, (v & 3) * 128);
                if (u == 24) {
                    w_tma_prefetch(&P.wq, cb * 128 + rank * 64, ca * 64);
                    if (ca < 2) w_tma_prefetch(&P.wq, cb * 128 + rank * 64, (ca + 8) * 64);
                }
            }
            if (u > 0) pr.acquire(slot_w(m) * 8, lap ^ (m >> 1), SLOT);
            lap ^= m >> 1;
            m = (m == 2) ? 0 : m + 1;
            TR(1 + u);
            if (u > 0) w_tma_load_mc(pr.dst + rank * 16384, (u & 4) ? &P.wuv : &P.wuk, (cb + 8 * kv_round(u >> 3)) * 128 + rank * 64, (u & 3) * 128, pr.fb);
            if (u < 3) {
                pr.acquire(slot_a(u + 1) * 8, 1, SLOT);
                w_tma_load(pr.dst, &P.ckv, u * 128 + 128, (2 * ca + rank) * 128, pr.fb);
                w_tma_load(pr.dst + 16384, &P.ckv, u * 128 + 192, (2 * ca + rank) * 128, pr.fb);
            }
        }
    }
    PROF(1);
    mbar_wait_sleep(bars + BAR_DEP, 0);
#pragma unroll 1
    for (int j = 0, pfs = 1; j < n_items(ca, cb); j++) {
        const int rd = item_rd(ca, cb, j), h = item_h(cb, rd, j), p = item_q(ca, cb, rd);
#pragma unroll 1
        for (int ks = 0; ks < 10; ks++) {
            pr.next(SLOT);
            w_tma_load_mc(pr.dst + 16384 + rank * 8192, &P.wq, h * 128 + rank * 64, ks * 64, pr.fb);
            w_tma_load(pr.dst, &P.xn, ks * 64, 256 * p + 128 * rank, pr.fb);
            if (cb == 8 && j < 7) w_tma_prefetch(&P.wq, (h + 1) * 128 + rank * 64, ks * 64);
        }
        PROF(8 + rd * 4);
        mbar_wait(bars + BAR_DEP + (1 + (cb == 8 ? j : rd)) * 8, 0);
        const int last = 4 * p + 3, top = h * 32 + last;
#pragma unroll 1
        for (int i = 0; i <= last; i++) {
            const int t = (i == 0) ? top - 1 : (i == last) ? h * 32 + 1 : (i & 1) ? top - 2 - i : top + 2 - i;
            pr.next(SLOT);
            const bool lastrd = (cb == 8 || rd == 3) ? false : (rd == 0) ? ca >= 6 : (rd == 1) ? (ca & 3) >= 2 : (ca == 3 || (ca < 3 && (t & 31) >= 4 * p));
            if (lastrd) w_tma_load_mc_last(pr.dst + rank * 16384, &P.kv, rank * 64, t * 128, pr.fb);
            else w_tma_load_mc(pr.dst + rank * 16384, &P.kv, rank * 64, t * 128, pr.fb);
            if (i == 2 && cb < 8) {
                const int upto = (j == n_items(ca, cb) - 1) ? 4 : item_rd(ca, cb, j + 1);
#pragma unroll 1
                for (; pfs <= upto; pfs++) {
                    if (pfs < 4) {
                        w_tma_prefetch(&P.wq, (8 * pfs + cb) * 128 + rank * 64, ca * 64);
                        if (ca < 2) w_tma_prefetch(&P.wq, (8 * pfs + cb) * 128 + rank * 64, (ca + 8) * 64);
                    } else {
#pragma unroll 1
                        for (int k = 0; k < 10; k++)
                            w_tma_prefetch(&P.wo, 320 * (ca >> 2) + 64 * (k >= 5 ? k - 5 : k), (cb * 4 + (ca & 3) + (k >= 5 ? 32 : 0)) * 64 + rank * 32);
                    }
                }
            }
        }
        PROF(9 + rd * 4);
    }
    if (cb < 8) {
        const int n0 = 320 * (ca >> 2), op = out_p(ca, cb);
        uint32_t* pool = g_flags + (F_POOL + op * 2 + (ca >> 2)) * 8;
        uint32_t nxt = 0;
        auto draw = [&]() {
            if (rank == 0) asm volatile(ELECT "atom.relaxed.gpu.global.add.u32 %0, [%1], 1;\n}\n" : "+r"(nxt) : "l"(pool) : "memory");
        };
        int fixed = -1;
#pragma unroll 1
        for (int i = -2; fixed < 4; i++) {
            int st = (ca & 3) + 4 * (i + 2);
            if (i == -1) draw();
            if (i >= 0 && fixed < 0) {
                const uint32_t mb = bars + BAR_MAIL + (i & 7) * 8, md = bars + MAIL_OFF + (i & 7) * 4;
                if (rank == 0) {
                    st = __reduce_add_sync(0xffffffffu, nxt);
                    asm volatile(ELECT "st.async.shared::cluster.mbarrier::complete_tx::bytes.b32 [%0], %1, [%2];\n}\n" ::"r"(mapa(md, 1)), "r"(st), "r"(mapa(mb, 1)) : "memory");
                    if (st < 48) draw();
                } else {
                    w_expect_tx(mb, 4);
                    mbar_wait(mb, (i >> 3) & 1);
                    asm volatile("ld.shared.u32 %0, [%1];" : "=r"(st) : "r"(md) : "memory");
                    st = __reduce_or_sync(0xffffffffu, st);
                }
                if (st >= 48) fixed = 0;
            }
            if (fixed >= 0) { st = 48 + (ca & 3) + 4 * fixed; fixed++; }
            const int krow = st * 64 + rank * 32;
            mbar_wait(bars + BAR_EMPTY + pr.bo, pr.par);
            asm volatile("st.shared.u32 [%0], %1;" ::"r"(bars + CTL_OFF + pr.bo), "r"((int)(fixed == 1)) : "memory");
            __syncwarp();
            pr.next(SLOT);
            w_tma_load_mc(pr.dst + 16384 + rank * 8192, &P.wo, n0, krow, pr.fb);
            w_tma_load_mc(pr.dst + 16384 + rank * 8192 + 4096, &P.wo, n0 + 64, krow, pr.fb);
            mbar_wait(bars + BAR_DEP + (5 + (st >> 4)) * 8, 0);
            w_tma_load(pr.dst, &P.ctx, (st & 1) * 64, (st >> 1) * SEQ + 256 * op + 128 * rank, pr.fb);
            pr.next(24576);
#pragma unroll
            for (int c = 0; c < 3; c++) w_tma_load_mc(pr.dst + rank * 12288 + c * 4096, &P.wo, n0 + 128 + 64 * c, krow, pr.fb);
        }
    }
}

struct Slot {
    uint32_t bo, dl, par;
};
struct Cons {
    uint32_t bars, rel;
    uint32_t dl0;
    uint32_t lane;
    Slot cur;
    __device__ __forceinline__ Slot slot(int s, uint32_t par) const { return Slot{(uint32_t)s * 8, dl0 + (uint32_t)s * (SLOT >> 4), par}; }
    __device__ __forceinline__ void wait(const Slot& s) const { mbar_wait(bars + BAR_FULL + s.bo, s.par); }
    __device__ __forceinline__ uint32_t peek() const { return PEEK ? mbar_peek(bars + BAR_FULL + cur.bo, cur.par) : 0u; }
    __device__ __forceinline__ void wait(const Slot& s, uint32_t ok) const { mbar_wait_unless(ok, bars + BAR_FULL + s.bo, s.par); }
    __device__ __forceinline__ void release(uint32_t bo) const {
        asm volatile("{\n.reg .pred p;\nsetp.lt.u32 p, %1, 2;\n@p mbarrier.arrive.shared::cluster.b64 _, [%0];\n}\n" ::"r"(rel + bo), "r"(lane) : "memory");
    }
    __device__ __forceinline__ Slot next() {
        const Slot s = cur;
        const bool wrap = s.bo == (NSLOT - 1) * 8;
        cur.bo = wrap ? 0u : s.bo + 8;
        cur.dl = wrap ? dl0 : s.dl + (SLOT >> 4);
        cur.par = s.par ^ (wrap ? 1u : 0u);
        return s;
    }
};
__host__ __device__ constexpr uint32_t lbo(uint32_t bytes) { return (bytes >> 4) << 16; }

__device__ __forceinline__ float div640(float x) {
    const float q = x * (1.0f / DM);
    return fmaf(fmaf(-q, (float)DM, x), 1.0f / DM, q);
}
__device__ __forceinline__ float sqrt_approx(float x) {
    float y;
    asm("sqrt.approx.ftz.f32 %0, %1;" : "=f"(y) : "f"(x));
    return y;
}
struct LayerNorm {
    uint4 xv[5], wv[5];
    float mean, inv, r;
    static __device__ __forceinline__ float half_sum(float v) {
#pragma unroll
        for (int o = 8; o > 0; o >>= 1) v += __shfl_xor_sync(0xffffffffu, v, o);
        return v;
    }
    __device__ __forceinline__ void load(const __nv_bfloat16* x, const __nv_bfloat16* wr, int t, int l) {
#pragma unroll
        for (int i = 0; i < 5; i++) {
            xv[i] = ldg_stream(reinterpret_cast<const uint4*>(x + t * DM) + l + 16 * i);
            wv[i] = __ldg(reinterpret_cast<const uint4*>(wr) + l + 16 * i);
        }
    }
    __device__ __forceinline__ void stat1() {
        float a[4] = {0.f, 0.f, 0.f, 0.f};
#pragma unroll
        for (int i = 0; i < 20; i++) { const uint32_t u = (&xv[i >> 2].x)[i & 3]; a[i & 3] += bf_lo(u) + bf_hi(u); }
        mean = div640(half_sum((a[0] + a[1]) + (a[2] + a[3])));
        r = 0.f;
    }
    template <int H>
    __device__ __forceinline__ void stat2() {
        float a[4] = {r, 0.f, 0.f, 0.f};
#pragma unroll
        for (int i = H ? 12 : 0; i < (H ? 20 : 12); i++) {
            uint32_t u = (&xv[i >> 2].x)[i & 3];
            asm volatile("" : "+r"(u));
            const float d0 = bf_lo(u) - mean, d1 = bf_hi(u) - mean;
            a[i & 3] = fmaf(d0, d0, fmaf(d1, d1, a[i & 3]));
        }
        r = (a[0] + a[1]) + (a[2] + a[3]);
        if (H) {
            inv = rcp(round_bf16(sqrt_approx(round_bf16(round_bf16(div640(half_sum(r))) + 1e-5f))));
            r = 0.f;
        }
    }
    template <int I>
    __device__ __forceinline__ void piece(__nv_bfloat16* out, int t, int l) {
        const uint32_t nmb = pack_bf16(-mean, -mean);
        uint32_t o[4], z[4];
        float a[4];
#pragma unroll
        for (int j = 0; j < 4; j++) {
            const uint32_t u = (&xv[I].x)[j], w = (&wv[I].x)[j];
            const uint32_t d = add_bf16x2(u, nmb);
            o[j] = pack_bf16(bf_lo(d) * inv, bf_hi(d) * inv);
            z[j] = add_bf16x2(u, o[j]);
            a[j] = fmaf(bf_hi(o[j]), bf_hi(w), bf_lo(o[j]) * bf_lo(w));
        }
        r += (a[0] + a[1]) + (a[2] + a[3]);
        stg128(g_xn + perm_row(t) * DM + 8 * (l + 16 * I), o[0], o[1], o[2], o[3]);
        stg128p(out + t * DM + 8 * (l + 16 * I), z[0], z[1], z[2], z[3], policy_evict_first());
        if (I == 4) {
            r = half_sum(r);
            if (l == 0) g_r[t] = round_bf16(r);
        }
    }
};

constexpr float SM_SCALE = 0.08838834764831845f * 1.4426950408889634f;

template <int J0, int J1>
__device__ __forceinline__ void exp_part(float (&s)[64], float n0, float n1, float& r0, float& r1) {
    float a1 = 0.f, b1 = 0.f;
#pragma unroll
    for (int j = J0; j < J1; j++) {
        s[4 * j + 0] = ex2(fmaf(s[4 * j + 0], SM_SCALE, n0));
        s[4 * j + 1] = ex2(fmaf(s[4 * j + 1], SM_SCALE, n0));
        s[4 * j + 2] = ex2(fmaf(s[4 * j + 2], SM_SCALE, n1));
        s[4 * j + 3] = ex2(fmaf(s[4 * j + 3], SM_SCALE, n1));
        r0 += s[4 * j + 0]; r1 += s[4 * j + 2];
        if (j == J0) { a1 = s[4 * j + 1]; b1 = s[4 * j + 3]; } else { a1 += s[4 * j + 1]; b1 += s[4 * j + 3]; }
    }
    r0 += a1;
    r1 += b1;
}
__device__ __forceinline__ void sched_barrier(float x, float y, uint32_t scratch) {
    asm volatile("{\n.reg .pred p;\nsetp.lt.f32 p, %0, 0f00000000;\n@p st.shared.f32 [%2], %1;\n}\n" ::"f"(x), "f"(y), "r"(scratch) : "memory");
}
__device__ __forceinline__ void pack_tile(const float (&s)[64], uint32_t (&p)[32]) {
#pragma unroll
    for (int i = 0; i < 32; i++) p[i] = pack_bf16(s[2 * i], s[2 * i + 1]);
}
template <bool ZERO>
__device__ __forceinline__ void gemm_rs(float (&d)[64], const uint32_t (&a)[32], uint32_t dl, int acc = 1) {
    const uint32_t b = dl + lbo(16384);
    if (ZERO) wgmma_rs_n128_z<1>(d, a[0], a[1], a[2], a[3], b);
#pragma unroll
    for (int k = ZERO ? 1 : 0; k < 8; k++) wgmma_rs_n128<1>(d, a[4 * k], a[4 * k + 1], a[4 * k + 2], a[4 * k + 3], b + k * 128, k ? 1 : acc);
}
__device__ __forceinline__ void gemm_pv(float (&d)[64], const uint32_t (&a)[32], uint32_t dl, int acc, int full) {
    const uint32_t b = dl + lbo(16384);
    wgmma_rs_n128<1>(d, a[0], a[1], a[2], a[3], b, acc);
    wgmma_commit();
    if (full) {
        wgmma_fence();
#pragma unroll
        for (int k = 4; k < 8; k++) wgmma_rs_n128<1>(d, a[4 * k], a[4 * k + 1], a[4 * k + 2], a[4 * k + 3], b + k * 128, 1);
        wgmma_commit();
    }
    wgmma_fence();
#pragma unroll
    for (int k = 1; k < 4; k++) wgmma_rs_n128<1>(d, a[4 * k], a[4 * k + 1], a[4 * k + 2], a[4 * k + 3], b + k * 128, 1);
}
template <int ZERO>
__device__ __forceinline__ void gemm_q(float (&d)[64], uint32_t dl, int role) {
    const uint32_t a = dl + role * 512 + lbo(16), b = dl + 1024 + lbo(8192);
    if (ZERO) wgmma_ss_n128_z<0, 1>(d, a, b);
#pragma unroll
    for (int k = ZERO ? 1 : 0; k < 4; k++) wgmma_ss_n128<0, 1>(d, a + k * 2, b + k * 128, 1);
}
template <bool KT, bool ZERO, int K0, int K1>
__device__ __forceinline__ void gemm_kv(float (&d)[64], uint32_t ckv, uint32_t wt, int wg) {
    if (KT) {
        const uint32_t a = wt + wg * 1024 + lbo(16), b = ckv + lbo(16);
        if (ZERO) wgmma_ss_n128_z<1, 0>(d, a, b);
#pragma unroll
        for (int k = ZERO ? 1 : K0; k < K1; k++) wgmma_ss_n128<1, 0>(d, a + k * 128, b + (k >> 2) * 1024 + (k & 3) * 2, 1);
    } else {
        const uint32_t a = ckv + wg * 512 + lbo(16), b = wt + lbo(16384);
        if (ZERO) wgmma_ss_n128_z<0, 1>(d, a, b);
#pragma unroll
        for (int k = ZERO ? 1 : K0; k < K1; k++) wgmma_ss_n128<0, 1>(d, a + (k >> 2) * 1024 + (k & 3) * 2, b + k * 128, 1);
    }
}
__device__ __forceinline__ void mma16816(float& d0, float& d1, float& d2, float& d3, uint32_t a0, uint32_t a1, uint32_t a2, uint32_t a3, uint32_t b0, uint32_t b1) {
    asm volatile("mma.sync.aligned.m16n8k16.row.col.f32.bf16.bf16.f32 {%0,%1,%2,%3}, {%4,%5,%6,%7}, {%8,%9}, {%0,%1,%2,%3};"
                 : "+f"(d0), "+f"(d1), "+f"(d2), "+f"(d3) : "r"(a0), "r"(a1), "r"(a2), "r"(a3), "r"(b0), "r"(b1));
}
__device__ __forceinline__ uint32_t ld_pair(const __nv_bfloat16* p) {
    const unsigned short* u = reinterpret_cast<const unsigned short*>(p);
    return (uint32_t)__ldcg(u) | ((uint32_t)__ldcg(u + 128) << 16);
}
__device__ __forceinline__ void attention_exact(float (&o)[64], const uint32_t (&qf)[32], float& l0, float& l1, int h, int nblk, int rr, int lane) {
    const int q = lane & 3, lr = lane >> 2;
    float m0 = -INFINITY, m1 = -INFINITY;
    l0 = 0.f; l1 = 0.f;
#pragma unroll
    for (int i = 0; i < 64; i++) o[i] = 0.f;
#pragma unroll 1
    for (int cidx = 0; cidx < nblk * 8; cidx++) {
        const int kc = cidx & 7;
        const __nv_bfloat16* kt = g_kv + (size_t)((h * 16 + (cidx >> 3)) * 2) * 16384;
        float sc[8];
#pragma unroll
        for (int i = 0; i < 8; i++) sc[i] = 0.f;
#pragma unroll
        for (int kk = 0; kk < 8; kk++)
#pragma unroll
            for (int nt = 0; nt < 2; nt++) {
                const __nv_bfloat16* b = kt + (16 * kk + 2 * q) * 128 + 16 * kc + 8 * nt + lr;
                mma16816(sc[4 * nt], sc[4 * nt + 1], sc[4 * nt + 2], sc[4 * nt + 3], qf[4 * kk], qf[4 * kk + 1], qf[4 * kk + 2], qf[4 * kk + 3],
                         ld_pair(b), ld_pair(b + 8 * 128));
            }
        const int lim = rr + ((nblk - 1) - (cidx >> 3)) * 128 - 32 * (kc >> 1) - 4 * (kc & 1);
#pragma unroll
        for (int i = 0; i < 8; i++)
            if (2 * (i >> 2) + (i & 1) > lim + 4 * (i & 2)) sc[i] = -INFINITY;
        float x0 = fmaxf(fmaxf(sc[0], sc[1]), fmaxf(sc[4], sc[5])), x1 = fmaxf(fmaxf(sc[2], sc[3]), fmaxf(sc[6], sc[7]));
        x0 = fmaxf(x0, __shfl_xor_sync(0xffffffffu, x0, 1)); x1 = fmaxf(x1, __shfl_xor_sync(0xffffffffu, x1, 1));
        x0 = fmaxf(x0, __shfl_xor_sync(0xffffffffu, x0, 2)); x1 = fmaxf(x1, __shfl_xor_sync(0xffffffffu, x1, 2));
        x0 = fmaxf(x0, m0); x1 = fmaxf(x1, m1);
        const float a0 = ex2((m0 - x0) * SM_SCALE), a1 = ex2((m1 - x1) * SM_SCALE);
        m0 = x0; m1 = x1;
#pragma unroll
        for (int i = 0; i < 8; i++) sc[i] = ex2((sc[i] - ((i & 2) ? m1 : m0)) * SM_SCALE);
        l0 = l0 * a0 + (sc[0] + sc[1]) + (sc[4] + sc[5]);
        l1 = l1 * a1 + (sc[2] + sc[3]) + (sc[6] + sc[7]);
        const uint32_t p0 = pack_bf16(sc[0], sc[1]), p1 = pack_bf16(sc[2], sc[3]), p2 = pack_bf16(sc[4], sc[5]), p3 = pack_bf16(sc[6], sc[7]);
        const __nv_bfloat16* vb = kt + 16384 + (16 * kc + 2 * q) * 128 + lr;
#pragma unroll
        for (int nt = 0; nt < 16; nt++) {
            o[4 * nt] *= a0; o[4 * nt + 1] *= a0; o[4 * nt + 2] *= a1; o[4 * nt + 3] *= a1;
            mma16816(o[4 * nt], o[4 * nt + 1], o[4 * nt + 2], o[4 * nt + 3], p0, p1, p2, p3, ld_pair(vb + 8 * nt), ld_pair(vb + 8 * nt + 8 * 128));
        }
    }
}

__device__ __forceinline__ void signal(uint32_t bars, int wg, int e, int lane) {
    __syncwarp();
    asm volatile("{\n.reg .pred p;\nsetp.eq.u32 p, %1, 0;\n@p mbarrier.arrive.shared::cta.b64 _, [%0];\n}\n" ::"r"(bars + BAR_SIG + (wg * 9 + e) * 8), "r"(lane) : "memory");
}

__device__ __forceinline__ void mod_ffn(const Params& P, uint32_t smem, int mc, int wg);

__device__ __forceinline__ void consumer(const Params& P, uint32_t smem, uint32_t bars, int ca, int cb, int rank, int wg) {
    const int lane = threadIdx.x & 31, w = (threadIdx.x >> 5) & 3, q = lane & 3, lr = lane >> 2;
    PROF(7);
    cluster_wait();
    Cons c{bars, mapa(bars + BAR_EMPTY, lane & 1), (smem & 0x3FFFF) >> 4, (uint32_t)lane, Slot{0u, (smem & 0x3FFFF) >> 4, cb == 8 ? 0u : 1u}};
    PROFG(180);
    PROF(1);
    float o[64], s[64];
    uint32_t pend;
    __nv_bfloat16* ep_ptr;
    int ep_step;
    if (cb == 8) {
        pend = 0;
        ep_ptr = g_ctx + (size_t)(item_h(cb, 2 + ca, 0) * SEQ + 128 * rank + 64 * wg + 16 * w + lr) * HD + 8 * q;
        ep_step = 8 * HD;
    } else {
        const int ln_t = blockIdx.x * 16 + wg * 8 + w * 2 + (lane >> 4);
        const int krow = 64 * wg + 16 * w + lr;
        const int vrow = 64 * wg + 32 * (w >> 1) + 8 * (lr >> 1) + 4 * (w & 1) + (lr & 1);
        ep_step = 2 * 128;
        int m = 0;
        uint32_t lap = 0;
        LayerNorm ln;
        auto step = [&](auto kt, auto kc, float (&d)[64], int hh) {
            const Slot sa = c.slot(slot_a(kc.value), 0), sw = c.slot(slot_w(m), lap ^ (m >> 1));
            lap ^= m >> 1;
            m = (m == 2) ? 0 : m + 1;
            TR(1 + (hh * 8 + (kt.value ? 0 : 4) + kc.value) * 2);
            if (kt.value && hh == 0) c.wait(sa);
            c.wait(sw);
            TR(2 + (hh * 8 + (kt.value ? 0 : 4) + kc.value) * 2);
            wgmma_fence();
            gemm_kv<kt.value, kc.value == 0, 0, KVSPLIT>(d, sa.dl, sw.dl, wg);
            wgmma_commit();
            wgmma_wait<1>();
            if (!(kt.value && kc.value == 0 && hh == 0)) c.release(pend);
            if (!kt.value && kc.value > 0 && hh == 3) c.release(slot_a(kc.value - 1) * 8);
            pend = sw.bo;
            wgmma_fence();
            gemm_kv<kt.value, false, KVSPLIT, 8>(d, sa.dl, sw.dl, wg);
            wgmma_commit();
        };
#pragma unroll 1
        for (int hh = 0; hh < 4; hh++) {
            __nv_bfloat16* base = g_kv + (size_t)(((cb + 8 * kv_round(hh)) * 16 + 2 * ca + rank) * 2) * 16384 + 8 * q;
            auto ln_stage = [&](auto pos) {
                constexpr int j = (pos.value + 8 - LNOFF % 8) % 8;
                if (hh == wg + (LNOFF + j) / 8) {
                    if (j == 0) ln.stat1();
                    if (j == 1) ln.template stat2<0>();
                    if (j == 2) ln.template stat2<1>();
                    if constexpr (j >= 3) ln.template piece<j - 3>(P.out, ln_t, lane & 15);
                    if (j == 7) signal(bars, wg, 0, lane);
                }
                if (pos.value == (LNOFF - LNLEAD) % 8 && hh == wg + (LNOFF - LNLEAD) / 8) ln.load(P.x, P.wr, ln_t, lane & 15);
            };
            for4([&](auto kc) {
                step(TrueT{}, kc, s, hh);
                if (hh > 0) {
                    if (kc.value == 0) fence_regs(o);
                    store_chunk<kc.value>(o, ep_ptr, ep_ptr + ep_step, 1.f, 1.f);
                    if (kc.value == 3) signal(bars, wg, hh, lane);
                }
                ln_stage(kc);
            });
            for4([&](auto kc) {
                step(FalseT{}, kc, o, hh);
                if (kc.value == 0) fence_regs(s);
                store_chunk<kc.value>(s, base + krow * 128, base + (krow + 8) * 128, 1.f, 1.f);
                ln_stage(IntT<kc.value + 4>{});
            });
            PROF(24 + hh);
            if (hh == 1) PROFG(181);
            ep_ptr = base + 16384 + vrow * 128;
        }
    }
    PROFG(182);
    PROF(2);
    uint32_t pf[32];
    {
        uint32_t qf[32];
        float l0 = 0.25f, l1 = 0.25f;
        const int bar_me = 2 + wg, bar_other = 3 - wg;
#pragma unroll 1
        for (int j = 0; j < n_items(ca, cb); j++) {
            const int rd = item_rd(ca, cb, j), h = item_h(cb, rd, j), p = item_q(ca, cb, rd);
            const int role = wg ^ (j & 1);
            const int nrest = 2 * p + role;
            Slot kfirst;
            const int lim = 64 * (role ^ rank) + 16 * w + lr - 8 * q;
            const uint64_t pol = policy_sel(j == 1 || j == 2);
            {
                auto qstep = [&](auto zero, int ks) {
                    const Slot sl = c.next();
                    c.wait(sl);
                    BP(2, 5 + 3 * ks);
                    wgmma_fence();
                    gemm_q<zero.value>(s, sl.dl, role);
                    wgmma_commit();
                    wgmma_wait<1>();
                    if (!zero.value || j > 0 || cb < 8) c.release(pend);
                    pend = sl.bo;
                };
                qstep(TrueT{}, 0);
                if (j == 0 && cb < 8) c.release(slot_a(3) * 8);
                fence_regs(o);
                l0 += __shfl_xor_sync(0xffffffffu, l0, 1); l1 += __shfl_xor_sync(0xffffffffu, l1, 1);
                l0 += __shfl_xor_sync(0xffffffffu, l0, 2); l1 += __shfl_xor_sync(0xffffffffu, l1, 2);
                l0 = rcp(l0); l1 = rcp(l1);
                for4([&](auto i) {
                    constexpr int B = 16 * i.value;
#pragma unroll
                    for (int r = 0; r < 2; r++) {
                        if (1 + 2 * i.value + r == 7 && !(role | rank)) named_sync(bar_me, 256);
                        qstep(FalseT{}, 1 + 2 * i.value + r);
                        const float f = r ? l1 : l0;
                        stg128p(ep_ptr + r * ep_step + 2 * B, pack_bf16(o[B + 2 * r] * f, o[B + 2 * r + 1] * f), pack_bf16(o[B + 2 * r + 4] * f, o[B + 2 * r + 5] * f),
                                pack_bf16(o[B + 2 * r + 8] * f, o[B + 2 * r + 9] * f), pack_bf16(o[B + 2 * r + 12] * f, o[B + 2 * r + 13] * f), pol);
#pragma unroll
                        for (int k = 0; k < 8; k++) {
                            float& v = o[B + 4 * (k >> 1) + 2 * r + (k & 1)];
                            v = (2 * B + k > lim + 8 * r) ? -1e30f : 0.f;
                            asm volatile("" : "+f"(v));
                        }
                    }
                });
                signal(bars, wg, (cb == 8 ? 0 : 4) + j, lane);
                PROF(11 + rd * 4);
                qstep(FalseT{}, 9);
                if (!role) { const Slot sl = c.next(); c.wait(sl); c.release(sl.bo); }
                kfirst = c.next();
                c.wait(kfirst);
                wgmma_wait<0>();
                BP(2, 34);
                c.release(pend);
                fence_regs(s);
                pack_tile(s, qf);
            }
            Slot vskip = c.cur;
            if (!role) vskip = c.next();
            PROF(8 + rd * 4);
            if (cb == 8) PROF(40 + 3 * j);
            fence_regs(qf); fence_regs(o);
            if (!role && rank) named_sync(bar_me, 256);
            BP(2, 36);
            auto first_qk = [&](auto half) {
                wgmma_fence();
#pragma unroll
                for (int k = 0; k < 8; k++) {
                    if (half.value) wgmma_rs_n64<1>(o, qf[4 * k], qf[4 * k + 1], qf[4 * k + 2], qf[4 * k + 3], kfirst.dl + lbo(16384) + k * 128, 1);
                    else wgmma_rs_n128<1>(o, qf[4 * k], qf[4 * k + 1], qf[4 * k + 2], qf[4 * k + 3], kfirst.dl + lbo(16384) + k * 128, 1);
                }
                wgmma_commit();
                named_arrive(bar_other, 256);
                if (!role) { c.wait(vskip); c.release(vskip.bo); }
                wgmma_wait<0>();
            };
            if (role == rank) first_qk(TrueT{});
            else first_qk(FalseT{});
            BP(2, 38);
            fence_regs(o);
            c.release(kfirst.bo);
            uint32_t ready = c.peek();
            float n0 = fmaxf(fmaxf(fmaxf(o[0], o[1]), fmaxf(o[4], o[5])), fmaxf(fmaxf(o[8], o[9]), fmaxf(o[12], o[13])));
            float n1 = fmaxf(fmaxf(fmaxf(o[2], o[3]), fmaxf(o[6], o[7])), fmaxf(fmaxf(o[10], o[11]), fmaxf(o[14], o[15])));
            n0 = __shfl_sync(0xffffffffu, n0, lane & 28); n1 = __shfl_sync(0xffffffffu, n1, lane & 28);
            n0 *= -SM_SCALE; n1 *= -SM_SCALE;
            l0 = 0.f; l1 = 0.f;
#pragma unroll
            for (int i = 0; i < 64; i++) s[i] = o[i];
            exp_part<0, 8>(s, n0, n1, l0, l1);
#pragma unroll
            for (int i = 0; i < 16; i++) pf[i] = pack_bf16(s[2 * i], s[2 * i + 1]);
            if (role != rank) {
                exp_part<8, 16>(s, n0, n1, l0, l1);
#pragma unroll
                for (int i = 16; i < 32; i++) pf[i] = pack_bf16(s[2 * i], s[2 * i + 1]);
            } else {
#pragma unroll
                for (int i = 16; i < 32; i++) pf[i] = 0u;
            }
            PROF(9 + rd * 4);
            if (cb == 8) PROF(41 + 3 * j);
#pragma unroll 1
            for (int it = 0; it < nrest; it++) {
                const Slot sk = c.next(), sv = c.next();
                LP(0);
                c.wait(sk, ready);
                fence_regs(o); fence_regs(pf);
                LP(1);
                named_sync(bar_me, 256);
                LP(2);
                if (it < 3) BP(2, 42 + 4 * it);
                if (it >= nrest - 2) BP(1, 62 + 4 * (it - nrest + 2));
                wgmma_fence();
                gemm_rs<true>(s, qf, sk.dl);
                wgmma_commit();
                c.wait(sv);
                wgmma_fence();
                gemm_pv(o, pf, sv.dl, it, it | (role ^ rank));
                wgmma_commit();
                named_arrive(bar_other, 256);
                LP(3);
                wgmma_wait<2>();
                LP(4);
                c.release(sk.bo);
                fence_regs(s);
                exp_part<0, SPLITJ>(s, n0, n1, l0, l1);
                sched_barrier(l0, l1, bars + MISC_OFF + 16);
                LP(5);
                wgmma_wait<0>();
                LP(6);
                c.release(sv.bo);
                ready = c.peek();
                fence_regs(o); fence_regs(pf);
                exp_part<SPLITJ, 16>(s, n0, n1, l0, l1);
                pack_tile(s, pf);
            }
            PROF(10 + rd * 4);
            if (cb == 8) PROF(42 + 3 * j);
            PROFG(183 + rd);
            const Slot sv = c.next();
            BP(1, 0);
            c.wait(sv, ready);
            if (nrest == 0) {
#pragma unroll
                for (int i = 0; i < 64; i++) o[i] = 0.f;
            }
            if (__builtin_expect(__any_sync(0xffffffffu, !(l0 < 0x1p60f && l1 < 0x1p60f)), 0)) {
                attention_exact(o, qf, l0, l1, h, nrest + 1, lim, lane);
#pragma unroll
                for (int i = 0; i < 32; i++) pf[i] = 0u;
            }
            fence_regs(o); fence_regs(pf);
            if (!role) named_sync(bar_me, 256);
            BP(1, 2);
            wgmma_fence();
            gemm_rs<false>(o, pf, sv.dl);
            wgmma_commit();
            pend = sv.bo;
            ep_ptr = g_ctx + (size_t)(h * SEQ + 256 * p + 128 * rank + 64 * role + 16 * w + lr) * HD + 8 * q;
            ep_step = 8 * HD;
        }
        l0 += __shfl_xor_sync(0xffffffffu, l0, 1); l1 += __shfl_xor_sync(0xffffffffu, l1, 1);
        l0 += __shfl_xor_sync(0xffffffffu, l0, 2); l1 += __shfl_xor_sync(0xffffffffu, l1, 2);
        l0 = rcp(l0); l1 = rcp(l1);
        wgmma_wait<0>();
        c.release(pend);
        fence_regs(o); fence_regs(pf);
#pragma unroll
        for (int i = 0; i < 32; i++) pf[i] = pack_bf16(o[2 * i] * ((i & 1) ? l1 : l0), o[2 * i + 1] * ((i & 1) ? l1 : l0));
    }
    PROFG(187);
    PROF(3);
    if (cb == 8) {
#pragma unroll
        for (int i = 0; i < 8; i++) stg128(ep_ptr + (i & 1) * 8 * HD + 32 * (i >> 1), pf[4 * (i & 6) + (i & 1)], pf[4 * (i & 6) + (i & 1) + 2], pf[4 * (i & 6) + (i & 1) + 4], pf[4 * (i & 6) + (i & 1) + 6]);
        signal(bars, wg, 8, lane);
        cluster_arrive();
        named_sync(1, 256);
        mod_ffn(P, smem, 2 * ca + rank, wg);
    } else
    {
        float a1[64], a2[96];
        uint32_t px = 0, py = 0;
        auto mma1 = [&](const Slot& x, int acc) {
#pragma unroll
            for (int k = 0; k < 4; k++) wgmma_ss_n128<0, 1>(a1, x.dl + wg * 512 + lbo(16) + k * 2, x.dl + 1024 + lbo(4096) + (k >> 1) * 512 + (k & 1) * 128, k ? 1 : acc);
        };
        auto mma2 = [&](const Slot& x, const Slot& y, int acc) {
#pragma unroll
            for (int k = 0; k < 4; k++) wgmma_ss_n192<0, 1>(a2, x.dl + wg * 512 + lbo(16) + k * 2, y.dl + lbo(4096) + (k >> 1) * 768 + (k & 1) * 128, k ? 1 : acc);
        };
#pragma unroll 1
        for (int t = 0, more = 1; more; t++) {
            const Slot sx = c.next(), sy = c.next();
            c.wait(sx);
            wgmma_fence();
            mma1(sx, t);
            wgmma_commit();
            asm volatile("ld.shared.u32 %0, [%1];" : "=r"(more) : "r"(bars + CTL_OFF + sx.bo) : "memory");
            more = !__any_sync(0xffffffffu, more);
            wgmma_wait<1>();
            if (t > 0) { c.release(px); c.release(py); }
            px = sx.bo; py = sy.bo;
            c.wait(sy);
            wgmma_fence();
            mma2(sx, sy, t);
            wgmma_commit();
            if (t == 0) {
#pragma unroll
                for (int i = 0; i < 4; i++) stg128(ep_ptr + 32 * i, pf[8 * i], pf[8 * i + 2], pf[8 * i + 4], pf[8 * i + 6]);
            }
            if (t == 1) {
#pragma unroll
                for (int i = 0; i < 4; i++) stg128(ep_ptr + 8 * HD + 32 * i, pf[8 * i + 1], pf[8 * i + 3], pf[8 * i + 5], pf[8 * i + 7]);
                signal(bars, wg, 4 + n_items(ca, cb), lane);
            }
        }
        const Slot x0 = c.next(), y0 = c.next(), x1 = c.next(), y1 = c.next(), x2 = c.next(), y2 = c.next(), fr = c.next();
        const int cw = __reduce_or_sync(0xffffffffu, wg * 4 + w);
        const int orow = unperm_row(256 * out_p(ca, cb) + 128 * rank + 16 * cw), ocol = 320 * (ca >> 2);
        const uint32_t sa = ((lane & 7) + (lane & 8)) * 128, sx = (lane >> 4) ^ (lane & 7);
        auto send = [&](auto chv, uint32_t box) {
            constexpr int ch = chv.value;
#pragma unroll
            for (int i = 0; i < 4; i++) {
                uint32_t r[4];
#pragma unroll
                for (int e = 0; e < 4; e++) {
                    const int k = 32 * ch + 8 * i + 2 * e;
                    r[e] = (ch < 2) ? pack_bf16(a1[k & 63], a1[(k & 63) + 1]) : pack_bf16(a2[ch < 2 ? 0 : k - 64], a2[ch < 2 ? 1 : k - 63]);
                }
                asm volatile("stmatrix.sync.aligned.m8n8.x4.shared.b16 [%0], {%1, %2, %3, %4};"
                             ::"r"(box + sa + ((sx ^ (2 * i)) << 4)), "r"(r[0]), "r"(r[1]), "r"(r[2]), "r"(r[3]) : "memory");
            }
            asm volatile("fence.proxy.async.shared::cta;" ::: "memory");
            __syncwarp();
            asm volatile(ELECT "cp.reduce.async.bulk.tensor.2d.global.shared::cta.add.bulk_group [%0, {%2, %3}], [%1];\n}\n"
                         ::"l"(&P.outm), "r"(box), "r"(ocol + 64 * ch), "r"(orow) : "memory");
        };
        auto addr = [&](const Slot& t) { return smem + t.bo * (SLOT / 8); };
        c.wait(x0);
        wgmma_fence();
        mma1(x0, 1);
        wgmma_commit();
        wgmma_wait<1>();
        c.release(px); c.release(py);
        c.wait(x1);
        c.wait(x2);
        c.wait(y0);
        mbar_wait(bars + BAR_DEP, 0);
        wgmma_fence();
        mma1(x1, 1);
        mma1(x2, 1);
        wgmma_commit();
        mma2(x0, y0, 1);
        wgmma_commit();
        mbar_wait(bars + BAR_EMPTY + fr.bo, fr.par ^ 1);
        c.wait(y1);
        wgmma_wait<1>();
        fence_regs(a1);
        send(IntT<0>{}, addr(fr) + cw * 4096);
        wgmma_fence();
        mma2(x1, y1, 1);
        wgmma_commit();
        send(IntT<1>{}, addr(fr) + cw * 4096 + 2048);
        c.wait(y2);
        wgmma_fence();
        mma2(x2, y2, 1);
        wgmma_commit();
        wgmma_wait<0>();
        fence_regs(a2);
        PROFG(188);
        PROF(4);
        send(IntT<2>{}, addr(x0) + cw * 2048);
        send(IntT<3>{}, addr(x1) + cw * 2048);
        send(IntT<4>{}, addr(x2) + cw * 2048);
        PROF(5);
        asm volatile("cp.async.bulk.commit_group;\ncp.async.bulk.wait_group.read 0;" ::: "memory");
    }
    PROF(6);
}

__device__ __forceinline__ void mod_ffn(const Params& P, uint32_t smem, int mc  , int wg) {
    const int tid = threadIdx.x - 128, lane = tid & 31, cw = tid >> 5, q = lane & 3, lr = lane >> 2;
    const uint32_t xs = smem + 6 * SLOT, hs = xs + 10240 + wg * 1024, wmax = xs + 12288, sidx = wmax + 64, rbar = xs + 13312 + wg * 32;
    const uint32_t ring = smem + wg * 3 * SLOT;
    const int f0 = mc + 4 * wg, nunit = ((34 - f0) >> 3) * 8;
    const bool lead = __reduce_or_sync(0xffffffffu, cw & 3) == 0;
    auto lds = [](uint32_t a) { uint32_t v; asm volatile("ld.shared.u32 %0, [%1];" : "=r"(v) : "r"(a) : "memory"); return v; };
    auto sts = [](uint32_t a, uint32_t v) { asm volatile("st.shared.u32 [%0], %1;" ::"r"(a), "r"(v) : "memory"); };
    auto issue = [&](int u, int st) {
        if (lead && u < nunit) {
            const int fc = (f0 + (u & ~7)) * 64, k = u & 7;
            const uint32_t dst = ring + st * SLOT, bar = rbar + st * 8;
            w_expect_tx(bar, k == 7 ? 16384 : SLOT);
            if (k < 5) {
                w_tma_load_stream(dst, &P.wg, fc, k * 128, bar);
                w_tma_load_stream(dst + 16384, &P.wu, fc, k * 128, bar);
            } else {
#pragma unroll 1
                for (int b = 0; b < (k == 7 ? 2 : 4); b++) w_tma_load_stream(dst + b * 8192, &P.wd, (4 * (k - 5) + b) * 64, fc, bar);
            }
        }
    };
    if ((tid & 127) == 0) {
        mbar_init(rbar, 1); mbar_init(rbar + 8, 1); mbar_init(rbar + 16, 1);
        asm volatile("fence.mbarrier_init.release.cluster;" ::: "memory");
    }
    mbar_wait(smem + NSLOT * SLOT + BAR_DEP, 0);
    asm volatile("fence.proxy.async.shared::cta;" ::: "memory");
    named_sync(1, 256);
    PROF(1);
#pragma unroll 1
    for (int u = 0; u < 3; u++) issue(u, u);
    uint32_t key[8];
#pragma unroll
    for (int i = 0; i < 8; i++) {
        const int t = tid + 256 * i;
        uint32_t b = __float_as_uint(__ldcg(g_r + t) + 0.f) >> 16;
        b = (b & 0x8000u) ? (~b & 0xffffu) : (b | 0x8000u);
        key[i] = (b << 16) | (uint32_t)(0xffff - t);
    }
#pragma unroll 1
    for (int rnd = 0; rnd < 8; rnd++) {
        uint32_t mx = key[0];
#pragma unroll
        for (int i = 1; i < 8; i++) mx = max(mx, key[i]);
        sts(wmax + ((rnd & 1) * 8 + cw) * 4, __reduce_max_sync(0xffffffffu, mx));
        named_sync(1, 256);
        mx = __reduce_max_sync(0xffffffffu, lds(wmax + ((rnd & 1) * 8 + (lane & 7)) * 4));
#pragma unroll
        for (int i = 0; i < 8; i++) if (key[i] == mx) key[i] = 0;
        if (cw == rnd) sts(sidx + rnd * 4, 0xffff - (mx & 0xffffu));
    }
    __syncwarp();
    {
        const int t = lds(sidx + cw * 4);
        const uint4* src = reinterpret_cast<const uint4*>(g_xn + perm_row(t) * DM);
#pragma unroll
        for (int i = 0; i < 3; i++) {
            const int ch = lane + 32 * i;
            if (ch < 80) {
                const uint4 v = __ldcg(src + ch);
                asm volatile("st.shared.v4.b32 [%0], {%1, %2, %3, %4};" ::"r"(xs + (ch >> 3) * 1024 + cw * 128 + ((ch ^ cw) & 7) * 16), "r"(v.x), "r"(v.y), "r"(v.z), "r"(v.w) : "memory");
            }
        }
        asm volatile("fence.proxy.async.shared::cta;" ::: "memory");
    }
    named_sync(1, 256);
    PROF(3);
    float y[10][4];
#pragma unroll
    for (int i = 0; i < 10; i++) { y[i][0] = 0.f; y[i][1] = 0.f; y[i][2] = 0.f; y[i][3] = 0.f; }
    int st = 0, ph = 0, u = 0;
    auto begin = [&]() { mbar_wait(rbar + st * 8, ph); wgmma_fence(); return (((ring + st * SLOT) & 0x3FFFF) >> 4) + lbo(16); };
    auto end = [&]() {
        wgmma_commit();
        wgmma_wait<0>();
        named_sync(4 + wg, 128);
        issue(u + 3, st);
        u++;
        ph ^= st == 2;
        st = (st == 2) ? 0 : st + 1;
    };
    const uint32_t dx = ((xs & 0x3FFFF) >> 4) + lbo(16), dh = ((hs & 0x3FFFF) >> 4) + lbo(16);
#pragma unroll 1
    while (u < nunit) {
        float g[4], v[4];
#pragma unroll 1
        for (int kc = 0; kc < 5; kc++) {
            const uint32_t da = begin();
#pragma unroll
            for (int k = 0; k < 8; k++) {
                const uint32_t db = dx + (2 * kc + (k >> 2)) * 64 + (k & 3) * 2;
                wgmma_ss_n8<1, 0>(g, da + k * 128, db, k ? 1 : kc);
                wgmma_ss_n8<1, 0>(v, da + 1024 + k * 128, db, k ? 1 : kc);
            }
            end();
        }
        fence_regs(g); fence_regs(v);
#pragma unroll
        for (int e = 0; e < 4; e++) {
            const float gp = round_bf16(g[e]);
            const float hv = round_bf16(__fdividef(gp, 1.0f + __expf(fminf(-gp, 80.f)))) * round_bf16(v[e]);
            const int tok = 2 * q + (e & 1), ch = 2 * (cw & 3) + (e >> 1);
            asm volatile("st.shared.u16 [%0], %1;" ::"r"(hs + tok * 128 + ((ch ^ tok) * 16) + lr * 2), "h"((unsigned short)pack_bf16(hv, 0.f)) : "memory");
        }
        asm volatile("fence.proxy.async.shared::cta;" ::: "memory");
        named_sync(4 + wg, 128);
#pragma unroll
        for (int k3 = 0; k3 < 3; k3++) {
            const uint32_t da = begin();
#pragma unroll
            for (int b = 0; b < (k3 == 2 ? 2 : 4); b++)
#pragma unroll
                for (int k = 0; k < 4; k++) wgmma_ss_n8<1, 0>(y[4 * k3 + b], da + b * 512 + k * 128, dh + k * 2, 1);
            end();
        }
    }
    PROF(5);
#pragma unroll
    for (int i = 0; i < 10; i++) {
        fence_regs(y[i]);
#pragma unroll
        for (int e = 0; e < 4; e++) g_ypart[((mc * 2 + wg) * 8 + 2 * q + (e & 1)) * DM + 64 * i + 16 * (cw & 3) + lr + 8 * (e >> 1)] = y[i][e];
    }
    named_sync(1, 256);
    if (tid == 0) {
        flag_add(F_MODP);
        flag_wait<100>(F_MODP, 4u * (lds(smem + NSLOT * SLOT + MISC_OFF) + 1));
    }
    named_sync(1, 256);
    PROF(6);
    {
        const int c = 2 * mc + wg, t = lds(sidx + c * 4);
        const float rs = round_bf16(__fdividef(1.0f, 1.0f + __expf(fminf(-__ldcg(g_r + t), 80.f))));
#pragma unroll
        for (int i = 0; i < 3; i++) {
            const int c2 = (tid & 127) + 128 * i;
            if (c2 < DM / 2) {
                float y0 = 0.f, y1 = 0.f;
#pragma unroll
                for (int k = 0; k < 8; k++) {
                    const float2 v = __ldcg(reinterpret_cast<const float2*>(g_ypart + (k * 8 + c) * DM) + c2);
                    y0 += v.x; y1 += v.y;
                }
                asm volatile("red.relaxed.gpu.global.add.noftz.bf16x2 [%0], %1;" ::"l"(P.out + t * DM + 2 * c2), "r"(pack_bf16(round_bf16(y0) * rs, round_bf16(y1) * rs)) : "memory");
            }
        }
    }
    PROF(7);
}

__global__ void __cluster_dims__(2, 1, 1) __launch_bounds__(384, 1) fused_kernel(const __grid_constant__ Params P) {
    extern __shared__ __align__(1024) uint8_t smem_raw[];
    const uint32_t smem = (smem_u32(smem_raw) + 1023u) & ~1023u;
    const uint32_t bars = smem + NSLOT * SLOT;
    const int wgi = __reduce_or_sync(0xffffffffu, threadIdx.x >> 7);
    const int cl = blockIdx.x >> 1, rank = blockIdx.x & 1, ca = cl & 7, cb = cl >> 3;
    PROFG(30);
    PROF(0);
    if (threadIdx.x == 64) {
        const uint32_t fa = bars + BAR_FULL + slot_a(0) * 8, fw = bars + BAR_FULL + slot_w(0) * 8;
        mbar_init(fa, 1); mbar_init(fw, 1);
        asm volatile("fence.mbarrier_init.release.cluster;" ::: "memory");
        if (cb < 8) {
            mbar_expect_tx(fa, SLOT);
            mbar_expect_tx(fw, SLOT);
            tma_load(smem + slot_a(0) * SLOT, &P.ckv, 0, (2 * ca + rank) * 128, fa);
            tma_load(smem + slot_w(0) * SLOT, &P.wuk, (cb + 8 * kv_round(0)) * 128, 0, fw);
            tma_load(smem + slot_w(0) * SLOT + 16384, &P.wuk, (cb + 8 * kv_round(0)) * 128 + 64, 0, fw);
            tma_load(smem + slot_a(0) * SLOT + 16384, &P.ckv, 64, (2 * ca + rank) * 128, fa);
        }
    } else if (threadIdx.x == 0) {
#pragma unroll
        for (int i = 0; i < NSLOT; i++) {
            if (i != slot_a(0) && i != slot_w(0)) mbar_init(bars + BAR_FULL + i * 8, 1);
            mbar_init(bars + BAR_EMPTY + i * 8, 16);
        }
        if (cb < 8) {
            mbar_arrive(bars + BAR_FULL + 16);
            asm volatile("mbarrier.arrive.shared::cta.b64 _, [%0], 16;" ::"r"(bars + BAR_EMPTY + 16) : "memory");
        }
        asm volatile("fence.mbarrier_init.release.cluster;" ::: "memory");
        PROF(24);
    } else if (threadIdx.x == 32) {
#pragma unroll
        for (int i = 0; i < 18; i++) mbar_init(bars + BAR_SIG + i * 8, 4);
#pragma unroll
        for (int i = 0; i < 18; i++) mbar_init(bars + BAR_DEP + i * 8, 1);
        asm volatile("fence.mbarrier_init.release.cluster;" ::: "memory");
    }
    __syncthreads();
    PROF(29);
    cluster_arrive();
    if (wgi > 0) {
        asm volatile("setmaxnreg.inc.sync.aligned.u32 232;");
        consumer(P, smem, bars, ca, cb, rank, wgi - 1);
        PROFG(31);
        PROFDUMP();
    } else {
        asm volatile("setmaxnreg.dec.sync.aligned.u32 40;");
        const int w = __reduce_or_sync(0xffffffffu, threadIdx.x >> 5), lane = threadIdx.x & 31;
        if (threadIdx.x == 32) {
            prefetch_map(&P.wuv); prefetch_map(&P.xn); prefetch_map(&P.wq); prefetch_map(&P.kv); prefetch_map(&P.ctx); prefetch_map(&P.wo); prefetch_map(&P.outm);
        }
        __syncwarp();
        cluster_wait();
        PROF(27);
        {
            if (w == 0) {
                producer(P, smem, bars, ca, cb, rank);
            } else if (w < 3 && lane == 0) {
                const int wg = w - 1;
#pragma unroll 1
                for (int i = (cb == 8); i < (cb == 8 ? 9 : 5 + n_items(ca, cb)); i++) {
                    const int nb = wg + (LNOFF + 7 - 4) / 8;
                    const int e = (cb == 8) ? i : (i < nb) ? i + 1 : (i == nb) ? 0 : i;
                    mbar_wait_sleep(bars + BAR_SIG + (wg * 9 + e) * 8, 0);
                    int f;
                    if (cb == 8) f = F_CTX + (2 + ca) * 16 + rank;
                    else if (e == 0) {
                        f = F_LN;
                        if ((ca & 3) == 0 && rank == 0 && wg == 0) g_flags[(F_POOL + out_p(ca, cb) * 2 + (ca >> 2)) * 8] = 8;
                    }
                    else if (e < 5) f = F_KV + cb + 8 * kv_round(e - 1);
                    else { const int rd = item_rd(ca, cb, e - 5); f = F_CTX + rd * 16 + item_p(ca, rd) * 2 + rank; }
                    flag_add(f);
                }
            } else if (lane == 0) {
                const uint32_t epoch = read_epoch();
                asm volatile("st.shared.u32 [%0], %1;" ::"r"(bars + MISC_OFF), "r"(epoch) : "memory");
#pragma unroll 1
                for (int e = 0; e < 9; e++) {
                    int f;
                    uint32_t n;
                    if (e == 0) { f = F_LN; n = 256; }
                    else if (cb == 8) { f = F_KV + item_h(cb, 2 + ca, e - 1); n = 32; }
                    else if (e < 5) { f = F_KV + cb + 8 * (e - 1); n = 32; }
                    else { f = F_CTX + (e - 5) * 16 + out_p(ca, cb) * 2 + rank; n = 16; }
                    flag_wait<200>(f, n * (epoch + 1));
                    fence_proxy_async();
                    mbar_arrive(bars + BAR_DEP + e * 8);
                }
            }
        }
        if (cb == 8) { __syncwarp(); cluster_arrive(); cluster_wait(); }
        PROFG(31);
        PROFDUMP();
    }
}

typedef CUresult (*EncodeFn)(CUtensorMap*, CUtensorMapDataType, cuuint32_t, void*, const cuuint64_t*, const cuuint64_t*, const cuuint32_t*,
                             const cuuint32_t*, CUtensorMapInterleave, CUtensorMapSwizzle, CUtensorMapL2promotion, CUtensorMapFloatOOBfill);

void make_map(EncodeFn fn, CUtensorMap* m, const void* ptr, uint64_t rows, uint64_t cols, uint32_t box_rows) {
    cuuint64_t dims[2] = {cols, rows};
    cuuint64_t strides[1] = {cols * 2};
    cuuint32_t box[2] = {64, box_rows};
    cuuint32_t es[2] = {1, 1};
    fn(m, CU_TENSOR_MAP_DATA_TYPE_BFLOAT16, 2, const_cast<void*>(ptr), dims, strides, box, es, CU_TENSOR_MAP_INTERLEAVE_NONE,
       CU_TENSOR_MAP_SWIZZLE_128B, CU_TENSOR_MAP_L2_PROMOTION_L2_128B, CU_TENSOR_MAP_FLOAT_OOB_FILL_NONE);
}

}

extern "C" void kernel_launch(void* const* d_in, const int* in_sizes, int n_in, void* d_out, int out_size) {
    (void)in_sizes; (void)n_in; (void)out_size;
    void* fnp = nullptr;
    cudaDriverEntryPointQueryResult qr;
    cudaGetDriverEntryPoint("cuTensorMapEncodeTiled", &fnp, cudaEnableDefault, &qr);
    EncodeFn fn = (EncodeFn)fnp;
    void *xn, *kv, *ctx;
    cudaGetSymbolAddress(&xn, g_xn);
    cudaGetSymbolAddress(&kv, g_kv);
    cudaGetSymbolAddress(&ctx, g_ctx);
    Params P;
    make_map(fn, &P.ckv, d_in[1], SEQ, DC, 128);
    make_map(fn, &P.wq, d_in[2], DM, NH * HD, 64);
    make_map(fn, &P.wuk, d_in[3], DC, NH * HD, 128);
    make_map(fn, &P.wuv, d_in[4], DC, NH * HD, 128);
    make_map(fn, &P.wo, d_in[5], NH * HD, DM, 32);
    make_map(fn, &P.xn, xn, SEQ, DM, 128);
    make_map(fn, &P.kv, kv, NH * 16 * 2 * 128, 128, 128);
    make_map(fn, &P.ctx, ctx, NH * SEQ, HD, 128);
    P.x = (const __nv_bfloat16*)d_in[0];
    P.wr = (const __nv_bfloat16*)d_in[7];
    make_map(fn, &P.wg, d_in[8], DM, FF, 128);
    make_map(fn, &P.wu, d_in[9], DM, FF, 128);
    make_map(fn, &P.wd, d_in[10], FF, DM, 64);
    make_map(fn, &P.outm, d_out, SEQ, DM, 16);
    P.out = (__nv_bfloat16*)d_out;
    cudaFuncSetAttribute(fused_kernel, cudaFuncAttributeMaxDynamicSharedMemorySize, SMEM_BYTES);
    fused_kernel<<<NCTA, 384, SMEM_BYTES>>>(P);
}
```

```cpp
#include <cuda_runtime.h>
#include <cuda_bf16.h>
#include <cuda.h>
#include <stdint.h>

namespace {

constexpr int SEQ = 2048, DM = 640, DC = 512, NH = 32, HD = 128, FF = 1728;
constexpr int NSLOT = 7, SLOT = 32768;
constexpr int NCTA = 132;
constexpr int KVSPLIT = 1;
constexpr int LNOFF = 4, LNLEAD = 2;
constexpr int SPLITJ = 8;
constexpr uint32_t DESC_HI = (1024u >> 4) | (1u << 30);
constexpr int SMEM_BYTES = NSLOT * SLOT + 3072;

constexpr int BAR_FULL = 0, BAR_EMPTY = 64, BAR_SIG = 128  , BAR_DEP = 320  , BAR_MAIL = 400  ;
constexpr int MISC_OFF = 512  , MAIL_OFF = 544  , CTL_OFF = 576  ;

constexpr int F_EPOCH = 0, F_LN = 1, F_MODP = 3, F_KV = 4  , F_CTX = 36  , F_POOL = 100  , F_NUM = 116;

__device__ __align__(1024) __nv_bfloat16 g_xn[SEQ * DM];
__device__ __align__(1024) __nv_bfloat16 g_kv[NH * 16 * 2 * 128 * 128];
__device__ __align__(1024) __nv_bfloat16 g_ctx[NH * SEQ * HD];
__device__ __align__(16) float g_r[SEQ];
__device__ __align__(16) float g_ypart[8 * 8 * DM];
__device__ uint32_t g_flags[F_NUM * 8];

struct TrueT { static constexpr bool value = true; };
struct FalseT { static constexpr bool value = false; };

struct Params {
    CUtensorMap ckv, wuk, wuv, xn, wq, kv, ctx, wo, wg, wu, wd, outm;
    const __nv_bfloat16 *x, *wr;
    __nv_bfloat16* out;
};

__device__ __forceinline__ uint32_t smem_u32(const void* p) { return (uint32_t)__cvta_generic_to_shared(p); }
__device__ __forceinline__ void mbar_init(uint32_t bar, uint32_t cnt) {
    asm volatile("mbarrier.init.shared::cta.b64 [%0], %1;" ::"r"(bar), "r"(cnt) : "memory");
}
__device__ __forceinline__ void mbar_expect_tx(uint32_t bar, uint32_t bytes) {
    asm volatile("mbarrier.arrive.expect_tx.shared::cta.b64 _, [%0], %1;" ::"r"(bar), "r"(bytes) : "memory");
}
__device__ __forceinline__ void mbar_arrive(uint32_t bar) {
    asm volatile("mbarrier.arrive.shared::cta.b64 _, [%0];" ::"r"(bar) : "memory");
}
__device__ __forceinline__ uint32_t mapa(uint32_t addr, uint32_t cta) {
    uint32_t r;
    asm("mapa.shared::cluster.u32 %0, %1, %2;" : "=r"(r) : "r"(addr), "r"(cta));
    return r;
}
__device__ __forceinline__ void mbar_wait(uint32_t bar, uint32_t parity) {
    asm volatile(
        "{\n.reg .pred p;\n.reg .b32 c;\n"
        "mov.b32 c, 0;\n"
        "WLOOP:\n"
        "mbarrier.try_wait.parity.shared::cta.b64 p, [%0], %1;\n"
        "@p bra.uni WDONE;\n"
        "add.u32 c, c, 1;\n"
        "setp.lt.u32 p, c, 0x400000;\n"
        "@p bra.uni WLOOP;\n"
        "trap;\n"
        "WDONE:\n}\n" ::"r"(bar), "r"(parity) : "memory");
}
__device__ __forceinline__ uint32_t mbar_peek(uint32_t bar, uint32_t parity) {
    uint32_t ok;
    asm volatile("{\n.reg .pred p;\nmbarrier.test_wait.parity.shared::cta.b64 p, [%1], %2;\nselp.b32 %0, 1, 0, p;\n}\n" : "=r"(ok) : "r"(bar), "r"(parity) : "memory");
    return ok;
}
__device__ __forceinline__ void mbar_wait_unless(uint32_t ok, uint32_t bar, uint32_t parity) {
    asm volatile(
        "{\n.reg .pred p;\n.reg .b32 c;\n"
        "setp.ne.b32 p, %2, 0;\n"
        "@p bra.uni WDONE;\n"
        "mov.b32 c, 0;\n"
        "WLOOP:\n"
        "mbarrier.try_wait.parity.shared::cta.b64 p, [%0], %1;\n"
        "@p bra.uni WDONE;\n"
        "add.u32 c, c, 1;\n"
        "setp.lt.u32 p, c, 0x400000;\n"
        "@p bra.uni WLOOP;\n"
        "trap;\n"
        "WDONE:\n}\n" ::"r"(bar), "r"(parity), "r"(ok) : "memory");
}
__device__ __forceinline__ void mbar_wait_sleep(uint32_t bar, uint32_t parity) {
    asm volatile(
        "{\n.reg .pred p;\n.reg .b32 c;\n"
        "mov.b32 c, 0;\n"
        "WLOOP:\n"
        "mbarrier.try_wait.parity.shared::cta.b64 p, [%0], %1, 20000;\n"
        "@p bra.uni WDONE;\n"
        "add.u32 c, c, 1;\n"
        "setp.lt.u32 p, c, 0x40000;\n"
        "@p bra.uni WLOOP;\n"
        "trap;\n"
        "WDONE:\n}\n" ::"r"(bar), "r"(parity) : "memory");
}
__device__ __forceinline__ void tma_load(uint32_t dst, const CUtensorMap* m, int c0, int c1, uint32_t bar) {
    asm volatile("cp.async.bulk.tensor.2d.shared::cluster.global.mbarrier::complete_tx::bytes [%0], [%1, {%3, %4}], [%2];"
                 ::"r"(dst), "l"(m), "r"(bar), "r"(c0), "r"(c1) : "memory");
}
#define ELECT "{\n.reg .pred e;\nelect.sync _|e, 0xffffffff;\n@e "
__device__ __forceinline__ void w_expect_tx(uint32_t bar, uint32_t bytes) {
    asm volatile(ELECT "mbarrier.arrive.expect_tx.shared::cta.b64 _, [%0], %1;\n}\n" ::"r"(bar), "r"(bytes) : "memory");
}
__device__ __forceinline__ void w_tma_load(uint32_t dst, const CUtensorMap* m, int c0, int c1, uint32_t bar) {
    asm volatile(ELECT "cp.async.bulk.tensor.2d.shared::cluster.global.mbarrier::complete_tx::bytes [%0], [%1, {%3, %4}], [%2];\n}\n"
                 ::"r"(dst), "l"(m), "r"(bar), "r"(c0), "r"(c1) : "memory");
}
__device__ __forceinline__ void w_tma_load_mc(uint32_t dst, const CUtensorMap* m, int c0, int c1, uint32_t bar) {
    asm volatile(ELECT "cp.async.bulk.tensor.2d.shared::cluster.global.mbarrier::complete_tx::bytes.multicast::cluster [%0], [%1, {%3, %4}], [%2], %5;\n}\n"
                 ::"r"(dst), "l"(m), "r"(bar), "r"(c0), "r"(c1), "h"((uint16_t)3) : "memory");
}
__device__ __forceinline__ void w_tma_prefetch(const CUtensorMap* m, int c0, int c1) {
    asm volatile(ELECT "cp.async.bulk.prefetch.tensor.2d.L2.global [%0, {%1, %2}];\n}\n" ::"l"(m), "r"(c0), "r"(c1) : "memory");
}
__device__ __forceinline__ uint64_t policy_evict_first() {
    uint64_t p;
    asm("createpolicy.fractional.L2::evict_first.b64 %0, 1.0;" : "=l"(p));
    return p;
}
__device__ __forceinline__ void w_tma_load_mc_last(uint32_t dst, const CUtensorMap* m, int c0, int c1, uint32_t bar) {
    asm volatile(ELECT "cp.async.bulk.tensor.2d.shared::cluster.global.mbarrier::complete_tx::bytes.multicast::cluster.L2::cache_hint [%0], [%1, {%3, %4}], [%2], %5, %6;\n}\n"
                 ::"r"(dst), "l"(m), "r"(bar), "r"(c0), "r"(c1), "h"((uint16_t)3), "l"(policy_evict_first()) : "memory");
}
__device__ __forceinline__ void w_tma_load_stream(uint32_t dst, const CUtensorMap* m, int c0, int c1, uint32_t bar) {
    asm volatile(ELECT "cp.async.bulk.tensor.2d.shared::cluster.global.mbarrier::complete_tx::bytes.L2::cache_hint [%0], [%1, {%3, %4}], [%2], %5;\n}\n"
                 ::"r"(dst), "l"(m), "r"(bar), "r"(c0), "r"(c1), "l"(policy_evict_first()) : "memory");
}
__device__ __forceinline__ uint4 ldg_stream(const void* p) {
    uint4 v;
    asm volatile("ld.global.nc.L2::cache_hint.v4.b32 {%0, %1, %2, %3}, [%4], %5;" : "=r"(v.x), "=r"(v.y), "=r"(v.z), "=r"(v.w) : "l"(p), "l"(policy_evict_first()));
    return v;
}
__device__ __forceinline__ void prefetch_map(const CUtensorMap* m) {
    asm volatile("prefetch.tensormap [%0];" ::"l"(m) : "memory");
}
__device__ __forceinline__ void cluster_arrive() { asm volatile("barrier.cluster.arrive.relaxed.aligned;" ::: "memory"); }
__device__ __forceinline__ void cluster_wait() { asm volatile("barrier.cluster.wait.aligned;" ::: "memory"); }
__device__ __forceinline__ void named_sync(int id, int n) { asm volatile("bar.sync %0, %1;" ::"r"(id), "r"(n) : "memory"); }
__device__ __forceinline__ void named_arrive(int id, int n) { asm volatile("bar.arrive %0, %1;" ::"r"(id), "r"(n) : "memory"); }

__device__ __forceinline__ void flag_add(int f) {
    asm volatile("fence.acq_rel.gpu;\nred.relaxed.gpu.global.add.u32 [%0], 1;" ::"l"(g_flags + f * 8) : "memory");
}
template <int SLEEP>
__device__ __forceinline__ void flag_wait(int f, uint32_t target) {
    asm volatile(
        "{\n.reg .pred p;\n.reg .b32 c, v;\n"
        "mov.b32 c, 0;\n"
        "FLOOP:\n"
        "ld.acquire.gpu.global.u32 v, [%0];\n"
        "sub.u32 v, v, %1;\n"
        "setp.ge.s32 p, v, 0;\n"
        "@p bra FDONE;\n"
        "nanosleep.u32 %2;\n"
        "add.u32 c, c, 1;\n"
        "setp.lt.u32 p, c, 0x400000;\n"
        "@p bra FLOOP;\n"
        "trap;\n"
        "FDONE:\n}\n" ::"l"(g_flags + f * 8), "r"(target), "n"(SLEEP) : "memory");
}
__device__ __forceinline__ uint32_t read_epoch() { return atomicAdd(g_flags + F_EPOCH * 8, 1u) / NCTA; }
__device__ __forceinline__ void fence_proxy_async() { asm volatile("fence.proxy.async;" ::: "memory"); }

__device__ __forceinline__ void wgmma_fence() { asm volatile("wgmma.fence.sync.aligned;" ::: "memory"); }
__device__ __forceinline__ void wgmma_commit() { asm volatile("wgmma.commit_group.sync.aligned;" ::: "memory"); }
template <int N>
__device__ __forceinline__ void wgmma_wait() { asm volatile("wgmma.wait_group.sync.aligned %0;" ::"n"(N) : "memory"); }
template <int N>
__device__ __forceinline__ void fence_regs(float (&d)[N]) {
#pragma unroll
    for (int i = 0; i < N; i++) asm volatile("" : "+f"(d[i])::"memory");
}
template <int N>
__device__ __forceinline__ void fence_regs(uint32_t (&d)[N]) {
#pragma unroll
    for (int i = 0; i < N; i++) asm volatile("" : "+r"(d[i])::"memory");
}

template <int TA, int TB>
__device__ __forceinline__ void wgmma_ss_n128(float (&d)[64], uint32_t alo, uint32_t blo, int scale_d) {
    asm volatile("{\n.reg .pred p;\n.reg .b64 da, db;\nsetp.ne.b32 p, %66, 0;\n"
        "mov.b64 da, {%64, %69};\nmov.b64 db, {%65, %69};\n"
        "wgmma.mma_async.sync.aligned.m64n128k16.f32.bf16.bf16 "
        "{%0, %1, %2, %3, %4, %5, %6, %7, %8, %9, %10, %11, %12, %13, %14, %15, %16, %17, %18, %19, %20, %21, %22, %23, %24, %25, %26, %27, %28, %29, %30, %31, %32, %33, %34, %35, %36, %37, %38, %39, %40, %41, %42, %43, %44, %45, %46, %47, %48, %49, %50, %51, %52, %53, %54, %55, %56, %57, %58, %59, %60, %61, %62, %63}, da, db, p, 1, 1, %67, %68;\n}\n"
        :
          "+f"(d[0]), "+f"(d[1]), "+f"(d[2]), "+f"(d[3]), "+f"(d[4]), "+f"(d[5]), "+f"(d[6]), "+f"(d[7]),
          "+f"(d[8]), "+f"(d[9]), "+f"(d[10]), "+f"(d[11]), "+f"(d[12]), "+f"(d[13]), "+f"(d[14]), "+f"(d[15]),
          "+f"(d[16]), "+f"(d[17]), "+f"(d[18]), "+f"(d[19]), "+f"(d[20]), "+f"(d[21]), "+f"(d[22]), "+f"(d[23]),
          "+f"(d[24]), "+f"(d[25]), "+f"(d[26]), "+f"(d[27]), "+f"(d[28]), "+f"(d[29]), "+f"(d[30]), "+f"(d[31]),
          "+f"(d[32]), "+f"(d[33]), "+f"(d[34]), "+f"(d[35]), "+f"(d[36]), "+f"(d[37]), "+f"(d[38]), "+f"(d[39]),
          "+f"(d[40]), "+f"(d[41]), "+f"(d[42]), "+f"(d[43]), "+f"(d[44]), "+f"(d[45]), "+f"(d[46]), "+f"(d[47]),
          "+f"(d[48]), "+f"(d[49]), "+f"(d[50]), "+f"(d[51]), "+f"(d[52]), "+f"(d[53]), "+f"(d[54]), "+f"(d[55]),
          "+f"(d[56]), "+f"(d[57]), "+f"(d[58]), "+f"(d[59]), "+f"(d[60]), "+f"(d[61]), "+f"(d[62]), "+f"(d[63])
        : "r"(alo), "r"(blo), "r"(scale_d), "n"(TA), "n"(TB), "r"(DESC_HI));
}
template <int TA, int TB>
__device__ __forceinline__ void wgmma_ss_n192(float (&d)[96], uint32_t alo, uint32_t blo, int scale_d) {
    asm volatile("{\n.reg .pred p;\n.reg .b64 da, db;\nsetp.ne.b32 p, %98, 0;\n"
        "mov.b64 da, {%96, %101};\nmov.b64 db, {%97, %101};\n"
        "wgmma.mma_async.sync.aligned.m64n192k16.f32.bf16.bf16 "
        "{%0, %1, %2, %3, %4, %5, %6, %7, %8, %9, %10, %11, %12, %13, %14, %15, %16, %17, %18, %19, %20, %21, %22, %23, %24, %25, %26, %27, %28, %29, %30, %31, %32, %33, %34, %35, %36, %37, %38, %39, %40, %41, %42, %43, %44, %45, %46, %47, %48, %49, %50, %51, %52, %53, %54, %55, %56, %57, %58, %59, %60, %61, %62, %63, %64, %65, %66, %67, %68, %69, %70, %71, %72, %73, %74, %75, %76, %77, %78, %79, %80, %81, %82, %83, %84, %85, %86, %87, %88, %89, %90, %91, %92, %93, %94, %95}, da, db, p, 1, 1, %99, %100;\n}\n"
        :
          "+f"(d[0]), "+f"(d[1]), "+f"(d[2]), "+f"(d[3]), "+f"(d[4]), "+f"(d[5]), "+f"(d[6]), "+f"(d[7]),
          "+f"(d[8]), "+f"(d[9]), "+f"(d[10]), "+f"(d[11]), "+f"(d[12]), "+f"(d[13]), "+f"(d[14]), "+f"(d[15]),
          "+f"(d[16]), "+f"(d[17]), "+f"(d[18]), "+f"(d[19]), "+f"(d[20]), "+f"(d[21]), "+f"(d[22]), "+f"(d[23]),
          "+f"(d[24]), "+f"(d[25]), "+f"(d[26]), "+f"(d[27]), "+f"(d[28]), "+f"(d[29]), "+f"(d[30]), "+f"(d[31]),
          "+f"(d[32]), "+f"(d[33]), "+f"(d[34]), "+f"(d[35]), "+f"(d[36]), "+f"(d[37]), "+f"(d[38]), "+f"(d[39]),
          "+f"(d[40]), "+f"(d[41]), "+f"(d[42]), "+f"(d[43]), "+f"(d[44]), "+f"(d[45]), "+f"(d[46]), "+f"(d[47]),
          "+f"(d[48]), "+f"(d[49]), "+f"(d[50]), "+f"(d[51]), "+f"(d[52]), "+f"(d[53]), "+f"(d[54]), "+f"(d[55]),
          "+f"(d[56]), "+f"(d[57]), "+f"(d[58]), "+f"(d[59]), "+f"(d[60]), "+f"(d[61]), "+f"(d[62]), "+f"(d[63]),
          "+f"(d[64]), "+f"(d[65]), "+f"(d[66]), "+f"(d[67]), "+f"(d[68]), "+f"(d[69]), "+f"(d[70]), "+f"(d[71]),
          "+f"(d[72]), "+f"(d[73]), "+f"(d[74]), "+f"(d[75]), "+f"(d[76]), "+f"(d[77]), "+f"(d[78]), "+f"(d[79]),
          "+f"(d[80]), "+f"(d[81]), "+f"(d[82]), "+f"(d[83]), "+f"(d[84]), "+f"(d[85]), "+f"(d[86]), "+f"(d[87]),
          "+f"(d[88]), "+f"(d[89]), "+f"(d[90]), "+f"(d[91]), "+f"(d[92]), "+f"(d[93]), "+f"(d[94]), "+f"(d[95])
        : "r"(alo), "r"(blo), "r"(scale_d), "n"(TA), "n"(TB), "r"(DESC_HI));
}
template <int TA, int TB>
__device__ __forceinline__ void wgmma_ss_n8(float (&d)[4], uint32_t alo, uint32_t blo, int scale_d) {
    asm volatile("{\n.reg .pred p;\n.reg .b64 da, db;\nsetp.ne.b32 p, %6, 0;\n"
        "mov.b64 da, {%4, %9};\nmov.b64 db, {%5, %9};\n"
        "wgmma.mma_async.sync.aligned.m64n8k16.f32.bf16.bf16 "
        "{%0, %1, %2, %3}, da, db, p, 1, 1, %7, %8;\n}\n"
        :
          "+f"(d[0]), "+f"(d[1]), "+f"(d[2]), "+f"(d[3])
        : "r"(alo), "r"(blo), "r"(scale_d), "n"(TA), "n"(TB), "r"(DESC_HI));
}
template <int TB>
__device__ __forceinline__ void wgmma_rs_n64(float (&d)[64], uint32_t a0, uint32_t a1, uint32_t a2, uint32_t a3, uint32_t blo, int scale_d) {
    asm volatile("{\n.reg .pred p;\n.reg .b64 db;\nsetp.ne.b32 p, %37, 0;\n"
        "mov.b64 db, {%36, %39};\n"
        "wgmma.mma_async.sync.aligned.m64n64k16.f32.bf16.bf16 "
        "{%0, %1, %2, %3, %4, %5, %6, %7, %8, %9, %10, %11, %12, %13, %14, %15, %16, %17, %18, %19, %20, %21, %22, %23, %24, %25, %26, %27, %28, %29, %30, %31}, {%32, %33, %34, %35}, db, p, 1, 1, %38;\n}\n"
        :
          "+f"(d[0]), "+f"(d[1]), "+f"(d[2]), "+f"(d[3]), "+f"(d[4]), "+f"(d[5]), "+f"(d[6]), "+f"(d[7]),
          "+f"(d[8]), "+f"(d[9]), "+f"(d[10]), "+f"(d[11]), "+f"(d[12]), "+f"(d[13]), "+f"(d[14]), "+f"(d[15]),
          "+f"(d[16]), "+f"(d[17]), "+f"(d[18]), "+f"(d[19]), "+f"(d[20]), "+f"(d[21]), "+f"(d[22]), "+f"(d[23]),
          "+f"(d[24]), "+f"(d[25]), "+f"(d[26]), "+f"(d[27]), "+f"(d[28]), "+f"(d[29]), "+f"(d[30]), "+f"(d[31])
        : "r"(a0), "r"(a1), "r"(a2), "r"(a3), "r"(blo), "r"(scale_d), "n"(TB), "r"(DESC_HI));
}
template <int TB>
__device__ __forceinline__ void wgmma_rs_n128(float (&d)[64], uint32_t a0, uint32_t a1, uint32_t a2, uint32_t a3, uint32_t blo, int scale_d) {
    asm volatile("{\n.reg .pred p;\n.reg .b64 db;\nsetp.ne.b32 p, %69, 0;\n"
        "mov.b64 db, {%68, %71};\n"
        "wgmma.mma_async.sync.aligned.m64n128k16.f32.bf16.bf16 "
        "{%0, %1, %2, %3, %4, %5, %6, %7, %8, %9, %10, %11, %12, %13, %14, %15, %16, %17, %18, %19, %20, %21, %22, %23, %24, %25, %26, %27, %28, %29, %30, %31, %32, %33, %34, %35, %36, %37, %38, %39, %40, %41, %42, %43, %44, %45, %46, %47, %48, %49, %50, %51, %52, %53, %54, %55, %56, %57, %58, %59, %60, %61, %62, %63}, {%64, %65, %66, %67}, db, p, 1, 1, %70;\n}\n"
        :
          "+f"(d[0]), "+f"(d[1]), "+f"(d[2]), "+f"(d[3]), "+f"(d[4]), "+f"(d[5]), "+f"(d[6]), "+f"(d[7]),
          "+f"(d[8]), "+f"(d[9]), "+f"(d[10]), "+f"(d[11]), "+f"(d[12]), "+f"(d[13]), "+f"(d[14]), "+f"(d[15]),
          "+f"(d[16]), "+f"(d[17]), "+f"(d[18]), "+f"(d[19]), "+f"(d[20]), "+f"(d[21]), "+f"(d[22]), "+f"(d[23]),
          "+f"(d[24]), "+f"(d[25]), "+f"(d[26]), "+f"(d[27]), "+f"(d[28]), "+f"(d[29]), "+f"(d[30]), "+f"(d[31]),
          "+f"(d[32]), "+f"(d[33]), "+f"(d[34]), "+f"(d[35]), "+f"(d[36]), "+f"(d[37]), "+f"(d[38]), "+f"(d[39]),
          "+f"(d[40]), "+f"(d[41]), "+f"(d[42]), "+f"(d[43]), "+f"(d[44]), "+f"(d[45]), "+f"(d[46]), "+f"(d[47]),
          "+f"(d[48]), "+f"(d[49]), "+f"(d[50]), "+f"(d[51]), "+f"(d[52]), "+f"(d[53]), "+f"(d[54]), "+f"(d[55]),
          "+f"(d[56]), "+f"(d[57]), "+f"(d[58]), "+f"(d[59]), "+f"(d[60]), "+f"(d[61]), "+f"(d[62]), "+f"(d[63])
        : "r"(a0), "r"(a1), "r"(a2), "r"(a3), "r"(blo), "r"(scale_d), "n"(TB), "r"(DESC_HI));
}
template <int TB>
__device__ __forceinline__ void wgmma_rs_n128_z(float (&d)[64], uint32_t a0, uint32_t a1, uint32_t a2, uint32_t a3, uint32_t blo) {
    asm volatile("{\n.reg .pred p;\n.reg .b64 db;\nsetp.ne.b32 p, %69, 0;\n"
        "mov.b64 db, {%68, %71};\n"
        "wgmma.mma_async.sync.aligned.m64n128k16.f32.bf16.bf16 "
        "{%0, %1, %2, %3, %4, %5, %6, %7, %8, %9, %10, %11, %12, %13, %14, %15, %16, %17, %18, %19, %20, %21, %22, %23, %24, %25, %26, %27, %28, %29, %30, %31, %32, %33, %34, %35, %36, %37, %38, %39, %40, %41, %42, %43, %44, %45, %46, %47, %48, %49, %50, %51, %52, %53, %54, %55, %56, %57, %58, %59, %60, %61, %62, %63}, {%64, %65, %66, %67}, db, p, 1, 1, %70;\n}\n"
        :
          "=f"(d[0]), "=f"(d[1]), "=f"(d[2]), "=f"(d[3]), "=f"(d[4]), "=f"(d[5]), "=f"(d[6]), "=f"(d[7]),
          "=f"(d[8]), "=f"(d[9]), "=f"(d[10]), "=f"(d[11]), "=f"(d[12]), "=f"(d[13]), "=f"(d[14]), "=f"(d[15]),
          "=f"(d[16]), "=f"(d[17]), "=f"(d[18]), "=f"(d[19]), "=f"(d[20]), "=f"(d[21]), "=f"(d[22]), "=f"(d[23]),
          "=f"(d[24]), "=f"(d[25]), "=f"(d[26]), "=f"(d[27]), "=f"(d[28]), "=f"(d[29]), "=f"(d[30]), "=f"(d[31]),
          "=f"(d[32]), "=f"(d[33]), "=f"(d[34]), "=f"(d[35]), "=f"(d[36]), "=f"(d[37]), "=f"(d[38]), "=f"(d[39]),
          "=f"(d[40]), "=f"(d[41]), "=f"(d[42]), "=f"(d[43]), "=f"(d[44]), "=f"(d[45]), "=f"(d[46]), "=f"(d[47]),
          "=f"(d[48]), "=f"(d[49]), "=f"(d[50]), "=f"(d[51]), "=f"(d[52]), "=f"(d[53]), "=f"(d[54]), "=f"(d[55]),
          "=f"(d[56]), "=f"(d[57]), "=f"(d[58]), "=f"(d[59]), "=f"(d[60]), "=f"(d[61]), "=f"(d[62]), "=f"(d[63])
        : "r"(a0), "r"(a1), "r"(a2), "r"(a3), "r"(blo), "n"(0), "n"(TB), "r"(DESC_HI));
}
template <int TA, int TB>
__device__ __forceinline__ void wgmma_ss_n128_z(float (&d)[64], uint32_t alo, uint32_t blo) {
    asm volatile("{\n.reg .pred p;\n.reg .b64 da, db;\nsetp.ne.b32 p, %66, 0;\n"
        "mov.b64 da, {%64, %69};\nmov.b64 db, {%65, %69};\n"
        "wgmma.mma_async.sync.aligned.m64n128k16.f32.bf16.bf16 "
        "{%0, %1, %2, %3, %4, %5, %6, %7, %8, %9, %10, %11, %12, %13, %14, %15, %16, %17, %18, %19, %20, %21, %22, %23, %24, %25, %26, %27, %28, %29, %30, %31, %32, %33, %34, %35, %36, %37, %38, %39, %40, %41, %42, %43, %44, %45, %46, %47, %48, %49, %50, %51, %52, %53, %54, %55, %56, %57, %58, %59, %60, %61, %62, %63}, da, db, p, 1, 1, %67, %68;\n}\n"
        :
          "=f"(d[0]), "=f"(d[1]), "=f"(d[2]), "=f"(d[3]), "=f"(d[4]), "=f"(d[5]), "=f"(d[6]), "=f"(d[7]),
          "=f"(d[8]), "=f"(d[9]), "=f"(d[10]), "=f"(d[11]), "=f"(d[12]), "=f"(d[13]), "=f"(d[14]), "=f"(d[15]),
          "=f"(d[16]), "=f"(d[17]), "=f"(d[18]), "=f"(d[19]), "=f"(d[20]), "=f"(d[21]), "=f"(d[22]), "=f"(d[23]),
          "=f"(d[24]), "=f"(d[25]), "=f"(d[26]), "=f"(d[27]), "=f"(d[28]), "=f"(d[29]), "=f"(d[30]), "=f"(d[31]),
          "=f"(d[32]), "=f"(d[33]), "=f"(d[34]), "=f"(d[35]), "=f"(d[36]), "=f"(d[37]), "=f"(d[38]), "=f"(d[39]),
          "=f"(d[40]), "=f"(d[41]), "=f"(d[42]), "=f"(d[43]), "=f"(d[44]), "=f"(d[45]), "=f"(d[46]), "=f"(d[47]),
          "=f"(d[48]), "=f"(d[49]), "=f"(d[50]), "=f"(d[51]), "=f"(d[52]), "=f"(d[53]), "=f"(d[54]), "=f"(d[55]),
          "=f"(d[56]), "=f"(d[57]), "=f"(d[58]), "=f"(d[59]), "=f"(d[60]), "=f"(d[61]), "=f"(d[62]), "=f"(d[63])
        : "r"(alo), "r"(blo), "n"(0), "n"(TA), "n"(TB), "r"(DESC_HI));
}

__device__ __forceinline__ uint32_t pack_bf16(float lo, float hi) {
    uint32_t r;
    asm("cvt.rn.bf16x2.f32 %0, %1, %2;" : "=r"(r) : "f"(hi), "f"(lo));
    return r;
}
__device__ __forceinline__ uint32_t add_bf16x2(uint32_t a, uint32_t b) {
    uint32_t r;
    asm("add.rn.bf16x2 %0, %1, %2;" : "=r"(r) : "r"(a), "r"(b));
    return r;
}
__device__ __forceinline__ float bf_lo(uint32_t v) { return __uint_as_float(v << 16); }
__device__ __forceinline__ float bf_hi(uint32_t v) { return __uint_as_float(v & 0xffff0000u); }
__device__ __forceinline__ float round_bf16(float v) { return __bfloat162float(__float2bfloat16_rn(v)); }
__device__ __forceinline__ float ex2(float x) {
    float y;
    asm("ex2.approx.ftz.f32 %0, %1;" : "=f"(y) : "f"(x));
    return y;
}
__device__ __forceinline__ float rcp(float x) {
    float y;
    asm("rcp.approx.ftz.f32 %0, %1;" : "=f"(y) : "f"(x));
    return y;
}
__device__ __forceinline__ void stg128(void* p, uint32_t a, uint32_t b, uint32_t c, uint32_t d) {
    asm volatile("st.global.v4.b32 [%0], {%1, %2, %3, %4};" ::"l"(p), "r"(a), "r"(b), "r"(c), "r"(d) : "memory");
}
__device__ __forceinline__ void stg128p(void* p, uint32_t a, uint32_t b, uint32_t c, uint32_t d, uint64_t pol) {
    asm volatile("st.global.L2::cache_hint.v4.b32 [%0], {%1, %2, %3, %4}, %5;" ::"l"(p), "r"(a), "r"(b), "r"(c), "r"(d), "l"(pol) : "memory");
}
__device__ __forceinline__ uint64_t policy_sel(bool first) {
    uint64_t p;
    asm("createpolicy.fractional.L2::evict_normal.b64 %0, 1.0;" : "=l"(p));
    return first ? policy_evict_first() : p;
}
__device__ __forceinline__ int perm_row(int t) { return (t & ~255) | (((0x78 >> (((t >> 6) & 3) * 2)) & 3) << 6) | (t & 63); }
__device__ __forceinline__ int unperm_row(int t) { return (t & ~255) | (((0x9C >> (((t >> 6) & 3) * 2)) & 3) << 6) | (t & 63); }

#define PROF(i)
#define PROFG(i)
#define PROFDUMP()
#define TR(i)
#define BP(r, i)
#define LP(i)

template <int I>
__device__ __forceinline__ void store_chunk(const float (&a)[64], __nv_bfloat16* row0, __nv_bfloat16* row1, float s0, float s1) {
    stg128(row0 + 32 * I, pack_bf16(a[16 * I + 0] * s0, a[16 * I + 1] * s0), pack_bf16(a[16 * I + 4] * s0, a[16 * I + 5] * s0),
           pack_bf16(a[16 * I + 8] * s0, a[16 * I + 9] * s0), pack_bf16(a[16 * I + 12] * s0, a[16 * I + 13] * s0));
    stg128(row1 + 32 * I, pack_bf16(a[16 * I + 2] * s1, a[16 * I + 3] * s1), pack_bf16(a[16 * I + 6] * s1, a[16 * I + 7] * s1),
           pack_bf16(a[16 * I + 10] * s1, a[16 * I + 11] * s1), pack_bf16(a[16 * I + 14] * s1, a[16 * I + 15] * s1));
}
template <int I>
struct IntT { static constexpr int value = I; };
template <class F>
__device__ __forceinline__ void for4(F f) { f(IntT<0>{}); f(IntT<1>{}); f(IntT<2>{}); f(IntT<3>{}); }

struct Prod {
    uint32_t smem, bars;
    uint32_t bo, par;
    uint32_t dst, fb;
    __device__ __forceinline__ void acquire(uint32_t o, uint32_t parity, uint32_t bytes) {
        mbar_wait(bars + BAR_EMPTY + o, parity);
        fb = bars + BAR_FULL + o;
        dst = smem + o * (SLOT / 8);
        w_expect_tx(fb, bytes);
    }
    __device__ __forceinline__ void next(uint32_t bytes) {
        acquire(bo, par, bytes);
        const bool wrap = bo == (NSLOT - 1) * 8;
        bo = wrap ? 0u : bo + 8;
        par ^= wrap ? 1u : 0u;
    }
};

__device__ __forceinline__ int item_p(int ca, int rd) {
    const int v = (rd & 1) ? (ca + 4) & 7 : ca;
    return (rd & 2) ? 7 - v : v;
}
__device__ __forceinline__ int n_items(int ca, int cb) { return cb == 8 ? 8 : ((ca & 3) == 3) ? 3 : 4; }
__device__ __forceinline__ int item_rd(int ca, int cb, int j) { return cb == 8 ? 2 + ca : (ca == 7 && j == 2) ? 3 : j; }
__device__ __forceinline__ int item_h(int cb, int rd, int j) { return 8 * rd + (cb == 8 ? j : cb); }
__device__ __forceinline__ int item_q(int ca, int cb, int rd) { return cb == 8 ? 0 : item_p(ca, rd); }
__device__ __forceinline__ int out_p(int ca, int cb) { return (cb + 2 * (ca & 3)) & 7; }
__device__ __forceinline__ int kv_round(int i) { return (0x1023 >> (4 * i)) & 3; }
__device__ __forceinline__ int slot_a(int i) { return (0x5310 >> (4 * i)) & 15; }
__device__ __forceinline__ int slot_w(int m) { return (0x264 >> (4 * m)) & 15; }

__device__ __forceinline__ void producer(const Params& P, uint32_t smem, uint32_t bars, int ca, int cb, int rank) {
    Prod pr{smem, bars, 0u, cb == 8 ? 1u : 0u, 0u, 0u};
    if (cb < 8) {
        int m = 0;
        uint32_t lap = 1;
#pragma unroll 1
        for (int u = 0; u < 32; u++) {
            if (u >= 3) {
                const int v = (u == 3) ? 3 + ca : u + 7;
                if (v < 32 && (u == 3 || (v & 7) == ca)) w_tma_prefetch((v & 4) ? &P.wuv : &P.wuk, (cb + 8 * kv_round(v >> 3)) * 128 + rank * 64, (v & 3) * 128);
                if (u == 24) {
                    w_tma_prefetch(&P.wq, cb * 128 + rank * 64, ca * 64);
                    if (ca < 2) w_tma_prefetch(&P.wq, cb * 128 + rank * 64, (ca + 8) * 64);
                }
            }
            if (u > 0) pr.acquire(slot_w(m) * 8, lap ^ (m >> 1), SLOT);
            lap ^= m >> 1;
            m = (m == 2) ? 0 : m + 1;
            TR(1 + u);
            if (u > 0) w_tma_load_mc(pr.dst + rank * 16384, (u & 4) ? &P.wuv : &P.wuk, (cb + 8 * kv_round(u >> 3)) * 128 + rank * 64, (u & 3) * 128, pr.fb);
            if (u < 3) {
                pr.acquire(slot_a(u + 1) * 8, 1, SLOT);
                w_tma_load(pr.dst, &P.ckv, u * 128 + 128, (2 * ca + rank) * 128, pr.fb);
                w_tma_load(pr.dst + 16384, &P.ckv, u * 128 + 192, (2 * ca + rank) * 128, pr.fb);
            }
        }
    }
    PROF(1);
    mbar_wait_sleep(bars + BAR_DEP, 0);
#pragma unroll 1
    for (int j = 0, pfs = 1; j < n_items(ca, cb); j++) {
        const int rd = item_rd(ca, cb, j), h = item_h(cb, rd, j), p = item_q(ca, cb, rd);
#pragma unroll 1
        for (int ks = 0; ks < 10; ks++) {
            pr.next(SLOT);
            w_tma_load_mc(pr.dst + 16384 + rank * 8192, &P.wq, h * 128 + rank * 64, ks * 64, pr.fb);
            w_tma_load(pr.dst, &P.xn, ks * 64, 256 * p + 128 * rank, pr.fb);
            if (cb == 8 && j < 7) w_tma_prefetch(&P.wq, (h + 1) * 128 + rank * 64, ks * 64);
        }
        PROF(8 + rd * 4);
        mbar_wait(bars + BAR_DEP + (1 + (cb == 8 ? j : rd)) * 8, 0);
        const int last = 4 * p + 3, top = h * 32 + last;
#pragma unroll 1
        for (int i = 0; i <= last; i++) {
            const int t = (i == 0) ? top - 1 : (i == last) ? h * 32 + 1 : (i & 1) ? top - 2 - i : top + 2 - i;
            pr.next(SLOT);
            const bool lastrd = (cb == 8 || rd == 3) ? false : (rd == 0) ? ca >= 6 : (rd == 1) ? (ca & 3) >= 2 : (ca == 3 || (ca < 3 && (t & 31) >= 4 * p));
            if (lastrd) w_tma_load_mc_last(pr.dst + rank * 16384, &P.kv, rank * 64, t * 128, pr.fb);
            else w_tma_load_mc(pr.dst + rank * 16384, &P.kv, rank * 64, t * 128, pr.fb);
            if (i == 2 && cb < 8) {
                const int upto = (j == n_items(ca, cb) - 1) ? 4 : item_rd(ca, cb, j + 1);
#pragma unroll 1
                for (; pfs <= upto; pfs++) {
                    if (pfs < 4) {
                        w_tma_prefetch(&P.wq, (8 * pfs + cb) * 128 + rank * 64, ca * 64);
                        if (ca < 2) w_tma_prefetch(&P.wq, (8 * pfs + cb) * 128 + rank * 64, (ca + 8) * 64);
                    } else {
#pragma unroll 1
                        for (int k = 0; k < 10; k++)
                            w_tma_prefetch(&P.wo, 320 * (ca >> 2) + 64 * (k >= 5 ? k - 5 : k), (cb * 4 + (ca & 3) + (k >= 5 ? 32 : 0)) * 64 + rank * 32);
                    }
                }
            }
        }
        PROF(9 + rd * 4);
    }
    if (cb < 8) {
        const int n0 = 320 * (ca >> 2), op = out_p(ca, cb);
        uint32_t* pool = g_flags + (F_POOL + op * 2 + (ca >> 2)) * 8;
        uint32_t nxt = 0;
        auto draw = [&]() {
            if (rank == 0) asm volatile(ELECT "atom.relaxed.gpu.global.add.u32 %0, [%1], 1;\n}\n" : "+r"(nxt) : "l"(pool) : "memory");
        };
        int fixed = -1;
#pragma unroll 1
        for (int i = -2; fixed < 4; i++) {
            int st = (ca & 3) + 4 * (i + 2);
            if (i == -1) draw();
            if (i >= 0 && fixed < 0) {
                const uint32_t mb = bars + BAR_MAIL + (i & 7) * 8, md = bars + MAIL_OFF + (i & 7) * 4;
                if (rank == 0) {
                    st = __reduce_add_sync(0xffffffffu, nxt);
                    asm volatile(ELECT "st.async.shared::cluster.mbarrier::complete_tx::bytes.b32 [%0], %1, [%2];\n}\n" ::"r"(mapa(md, 1)), "r"(st), "r"(mapa(mb, 1)) : "memory");
                    if (st < 48) draw();
                } else {
                    w_expect_tx(mb, 4);
                    mbar_wait(mb, (i >> 3) & 1);
                    asm volatile("ld.shared.u32 %0, [%1];" : "=r"(st) : "r"(md) : "memory");
                    st = __reduce_or_sync(0xffffffffu, st);
                }
                if (st >= 48) fixed = 0;
            }
            if (fixed >= 0) { st = 48 + (ca & 3) + 4 * fixed; fixed++; }
            const int krow = st * 64 + rank * 32;
            mbar_wait(bars + BAR_EMPTY + pr.bo, pr.par);
            asm volatile("st.shared.u32 [%0], %1;" ::"r"(bars + CTL_OFF + pr.bo), "r"((int)(fixed == 1)) : "memory");
            __syncwarp();
            pr.next(SLOT);
            w_tma_load_mc(pr.dst + 16384 + rank * 8192, &P.wo, n0, krow, pr.fb);
            w_tma_load_mc(pr.dst + 16384 + rank * 8192 + 4096, &P.wo, n0 + 64, krow, pr.fb);
            mbar_wait(bars + BAR_DEP + (5 + (st >> 4)) * 8, 0);
            w_tma_load(pr.dst, &P.ctx, (st & 1) * 64, (st >> 1) * SEQ + 256 * op + 128 * rank, pr.fb);
            pr.next(24576);
#pragma unroll
            for (int c = 0; c < 3; c++) w_tma_load_mc(pr.dst + rank * 12288 + c * 4096, &P.wo, n0 + 128 + 64 * c, krow, pr.fb);
        }
    }
}

struct Slot {
    uint32_t bo, dl, par;
};
struct Cons {
    uint32_t bars, rel;
    uint32_t dl0;
    uint32_t lane;
    Slot cur;
    __device__ __forceinline__ Slot slot(int s, uint32_t par) const { return Slot{(uint32_t)s * 8, dl0 + (uint32_t)s * (SLOT >> 4), par}; }
    __device__ __forceinline__ void wait(const Slot& s) const { mbar_wait(bars + BAR_FULL + s.bo, s.par); }
    __device__ __forceinline__ uint32_t peek() const { return mbar_peek(bars + BAR_FULL + cur.bo, cur.par); }
    __device__ __forceinline__ void wait(const Slot& s, uint32_t ok) const { mbar_wait_unless(ok, bars + BAR_FULL + s.bo, s.par); }
    __device__ __forceinline__ void release(uint32_t bo) const {
        asm volatile("{\n.reg .pred p;\nsetp.lt.u32 p, %1, 2;\n@p mbarrier.arrive.shared::cluster.b64 _, [%0];\n}\n" ::"r"(rel + bo), "r"(lane) : "memory");
    }
    __device__ __forceinline__ Slot next() {
        const Slot s = cur;
        const bool wrap = s.bo == (NSLOT - 1) * 8;
        cur.bo = wrap ? 0u : s.bo + 8;
        cur.dl = wrap ? dl0 : s.dl + (SLOT >> 4);
        cur.par = s.par ^ (wrap ? 1u : 0u);
        return s;
    }
};
__host__ __device__ constexpr uint32_t lbo(uint32_t bytes) { return (bytes >> 4) << 16; }

__device__ __forceinline__ float div640(float x) {
    const float q = x * (1.0f / DM);
    return fmaf(fmaf(-q, (float)DM, x), 1.0f / DM, q);
}
__device__ __forceinline__ float sqrt_approx(float x) {
    float y;
    asm("sqrt.approx.ftz.f32 %0, %1;" : "=f"(y) : "f"(x));
    return y;
}
struct LayerNorm {
    uint4 xv[5], wv[5];
    float mean, inv, r;
    static __device__ __forceinline__ float half_sum(float v) {
#pragma unroll
        for (int o = 8; o > 0; o >>= 1) v += __shfl_xor_sync(0xffffffffu, v, o);
        return v;
    }
    __device__ __forceinline__ void load(const __nv_bfloat16* x, const __nv_bfloat16* wr, int t, int l) {
#pragma unroll
        for (int i = 0; i < 5; i++) {
            xv[i] = ldg_stream(reinterpret_cast<const uint4*>(x + t * DM) + l + 16 * i);
            wv[i] = __ldg(reinterpret_cast<const uint4*>(wr) + l + 16 * i);
        }
    }
    __device__ __forceinline__ void stat1() {
        float a[4] = {0.f, 0.f, 0.f, 0.f};
#pragma unroll
        for (int i = 0; i < 20; i++) { const uint32_t u = (&xv[i >> 2].x)[i & 3]; a[i & 3] += bf_lo(u) + bf_hi(u); }
        mean = div640(half_sum((a[0] + a[1]) + (a[2] + a[3])));
        r = 0.f;
    }
    template <int H>
    __device__ __forceinline__ void stat2() {
        float a[4] = {r, 0.f, 0.f, 0.f};
#pragma unroll
        for (int i = H ? 12 : 0; i < (H ? 20 : 12); i++) {
            uint32_t u = (&xv[i >> 2].x)[i & 3];
            asm volatile("" : "+r"(u));
            const float d0 = bf_lo(u) - mean, d1 = bf_hi(u) - mean;
            a[i & 3] = fmaf(d0, d0, fmaf(d1, d1, a[i & 3]));
        }
        r = (a[0] + a[1]) + (a[2] + a[3]);
        if (H) {
            inv = rcp(round_bf16(sqrt_approx(round_bf16(round_bf16(div640(half_sum(r))) + 1e-5f))));
            r = 0.f;
        }
    }
    template <int I>
    __device__ __forceinline__ void piece(__nv_bfloat16* out, int t, int l) {
        const uint32_t nmb = pack_bf16(-mean, -mean);
        uint32_t o[4], z[4];
        float a[4];
#pragma unroll
        for (int j = 0; j < 4; j++) {
            const uint32_t u = (&xv[I].x)[j], w = (&wv[I].x)[j];
            const uint32_t d = add_bf16x2(u, nmb);
            o[j] = pack_bf16(bf_lo(d) * inv, bf_hi(d) * inv);
            z[j] = add_bf16x2(u, o[j]);
            a[j] = fmaf(bf_hi(o[j]), bf_hi(w), bf_lo(o[j]) * bf_lo(w));
        }
        r += (a[0] + a[1]) + (a[2] + a[3]);
        stg128(g_xn + perm_row(t) * DM + 8 * (l + 16 * I), o[0], o[1], o[2], o[3]);
        stg128p(out + t * DM + 8 * (l + 16 * I), z[0], z[1], z[2], z[3], policy_evict_first());
        if (I == 4) {
            r = half_sum(r);
            if (l == 0) g_r[t] = round_bf16(r);
        }
    }
};

constexpr float SM_SCALE = 0.08838834764831845f * 1.4426950408889634f;

template <int J0, int J1>
__device__ __forceinline__ void exp_part(float (&s)[64], float n0, float n1, float& r0, float& r1) {
    float a1 = 0.f, b1 = 0.f;
#pragma unroll
    for (int j = J0; j < J1; j++) {
        s[4 * j + 0] = ex2(fmaf(s[4 * j + 0], SM_SCALE, n0));
        s[4 * j + 1] = ex2(fmaf(s[4 * j + 1], SM_SCALE, n0));
        s[4 * j + 2] = ex2(fmaf(s[4 * j + 2], SM_SCALE, n1));
        s[4 * j + 3] = ex2(fmaf(s[4 * j + 3], SM_SCALE, n1));
        r0 += s[4 * j + 0]; r1 += s[4 * j + 2];
        if (j == J0) { a1 = s[4 * j + 1]; b1 = s[4 * j + 3]; } else { a1 += s[4 * j + 1]; b1 += s[4 * j + 3]; }
    }
    r0 += a1;
    r1 += b1;
}
__device__ __forceinline__ void sched_barrier(float x, float y, uint32_t scratch) {
    asm volatile("{\n.reg .pred p;\nsetp.lt.f32 p, %0, 0f00000000;\n@p st.shared.f32 [%2], %1;\n}\n" ::"f"(x), "f"(y), "r"(scratch) : "memory");
}
__device__ __forceinline__ void pack_tile(const float (&s)[64], uint32_t (&p)[32]) {
#pragma unroll
    for (int i = 0; i < 32; i++) p[i] = pack_bf16(s[2 * i], s[2 * i + 1]);
}
template <bool ZERO>
__device__ __forceinline__ void gemm_rs(float (&d)[64], const uint32_t (&a)[32], uint32_t dl, int acc = 1) {
    const uint32_t b = dl + lbo(16384);
    if (ZERO) wgmma_rs_n128_z<1>(d, a[0], a[1], a[2], a[3], b);
#pragma unroll
    for (int k = ZERO ? 1 : 0; k < 8; k++) wgmma_rs_n128<1>(d, a[4 * k], a[4 * k + 1], a[4 * k + 2], a[4 * k + 3], b + k * 128, k ? 1 : acc);
}
__device__ __forceinline__ void gemm_pv(float (&d)[64], const uint32_t (&a)[32], uint32_t dl, int acc, int full) {
    const uint32_t b = dl + lbo(16384);
    wgmma_rs_n128<1>(d, a[0], a[1], a[2], a[3], b, acc);
    wgmma_commit();
    if (full) {
        wgmma_fence();
#pragma unroll
        for (int k = 4; k < 8; k++) wgmma_rs_n128<1>(d, a[4 * k], a[4 * k + 1], a[4 * k + 2], a[4 * k + 3], b + k * 128, 1);
        wgmma_commit();
    }
    wgmma_fence();
#pragma unroll
    for (int k = 1; k < 4; k++) wgmma_rs_n128<1>(d, a[4 * k], a[4 * k + 1], a[4 * k + 2], a[4 * k + 3], b + k * 128, 1);
}
template <int ZERO>
__device__ __forceinline__ void gemm_q(float (&d)[64], uint32_t dl, int role) {
    const uint32_t a = dl + role * 512 + lbo(16), b = dl + 1024 + lbo(8192);
    if (ZERO) wgmma_ss_n128_z<0, 1>(d, a, b);
#pragma unroll
    for (int k = ZERO ? 1 : 0; k < 4; k++) wgmma_ss_n128<0, 1>(d, a + k * 2, b + k * 128, 1);
}
template <bool KT, bool ZERO, int K0, int K1>
__device__ __forceinline__ void gemm_kv(float (&d)[64], uint32_t ckv, uint32_t wt, int wg) {
    if (KT) {
        const uint32_t a = wt + wg * 1024 + lbo(16), b = ckv + lbo(16);
        if (ZERO) wgmma_ss_n128_z<1, 0>(d, a, b);
#pragma unroll
        for (int k = ZERO ? 1 : K0; k < K1; k++) wgmma_ss_n128<1, 0>(d, a + k * 128, b + (k >> 2) * 1024 + (k & 3) * 2, 1);
    } else {
        const uint32_t a = ckv + wg * 512 + lbo(16), b = wt + lbo(16384);
        if (ZERO) wgmma_ss_n128_z<0, 1>(d, a, b);
#pragma unroll
        for (int k = ZERO ? 1 : K0; k < K1; k++) wgmma_ss_n128<0, 1>(d, a + (k >> 2) * 1024 + (k & 3) * 2, b + k * 128, 1);
    }
}
__device__ __forceinline__ void mma16816(float& d0, float& d1, float& d2, float& d3, uint32_t a0, uint32_t a1, uint32_t a2, uint32_t a3, uint32_t b0, uint32_t b1) {
    asm volatile("mma.sync.aligned.m16n8k16.row.col.f32.bf16.bf16.f32 {%0,%1,%2,%3}, {%4,%5,%6,%7}, {%8,%9}, {%0,%1,%2,%3};"
                 : "+f"(d0), "+f"(d1), "+f"(d2), "+f"(d3) : "r"(a0), "r"(a1), "r"(a2), "r"(a3), "r"(b0), "r"(b1));
}
__device__ __forceinline__ uint32_t ld_pair(const __nv_bfloat16* p) {
    const unsigned short* u = reinterpret_cast<const unsigned short*>(p);
    return (uint32_t)__ldcg(u) | ((uint32_t)__ldcg(u + 128) << 16);
}
__device__ __forceinline__ void attention_exact(float (&o)[64], const uint32_t (&qf)[32], float& l0, float& l1, int h, int nblk, int rr, int lane) {
    const int q = lane & 3, lr = lane >> 2;
    float m0 = -INFINITY, m1 = -INFINITY;
    l0 = 0.f; l1 = 0.f;
#pragma unroll 1
    for (int cidx = 0; cidx < nblk * 8; cidx++) {
        const int kc = cidx & 7;
        const __nv_bfloat16* kt = g_kv + (size_t)((h * 16 + (cidx >> 3)) * 2) * 16384;
        float sc[8];
#pragma unroll
        for (int i = 0; i < 8; i++) sc[i] = 0.f;
#pragma unroll
        for (int kk = 0; kk < 8; kk++)
#pragma unroll
            for (int nt = 0; nt < 2; nt++) {
                const __nv_bfloat16* b = kt + (16 * kk + 2 * q) * 128 + 16 * kc + 8 * nt + lr;
                mma16816(sc[4 * nt], sc[4 * nt + 1], sc[4 * nt + 2], sc[4 * nt + 3], qf[4 * kk], qf[4 * kk + 1], qf[4 * kk + 2], qf[4 * kk + 3],
                         ld_pair(b), ld_pair(b + 8 * 128));
            }
        const int lim = rr + ((nblk - 1) - (cidx >> 3)) * 128 - 32 * (kc >> 1) - 4 * (kc & 1);
#pragma unroll
        for (int i = 0; i < 8; i++)
            if (2 * (i >> 2) + (i & 1) > lim + 4 * (i & 2)) sc[i] = -INFINITY;
        float x0 = fmaxf(fmaxf(sc[0], sc[1]), fmaxf(sc[4], sc[5])), x1 = fmaxf(fmaxf(sc[2], sc[3]), fmaxf(sc[6], sc[7]));
        x0 = fmaxf(x0, __shfl_xor_sync(0xffffffffu, x0, 1)); x1 = fmaxf(x1, __shfl_xor_sync(0xffffffffu, x1, 1));
        x0 = fmaxf(x0, __shfl_xor_sync(0xffffffffu, x0, 2)); x1 = fmaxf(x1, __shfl_xor_sync(0xffffffffu, x1, 2));
        x0 = fmaxf(x0, m0); x1 = fmaxf(x1, m1);
        const float a0 = ex2((m0 - x0) * SM_SCALE), a1 = ex2((m1 - x1) * SM_SCALE);
        m0 = x0; m1 = x1;
#pragma unroll
        for (int i = 0; i < 8; i++) sc[i] = ex2((sc[i] - ((i & 2) ? m1 : m0)) * SM_SCALE);
        l0 = l0 * a0 + (sc[0] + sc[1]) + (sc[4] + sc[5]);
        l1 = l1 * a1 + (sc[2] + sc[3]) + (sc[6] + sc[7]);
        const uint32_t p0 = pack_bf16(sc[0], sc[1]), p1 = pack_bf16(sc[2], sc[3]), p2 = pack_bf16(sc[4], sc[5]), p3 = pack_bf16(sc[6], sc[7]);
        const __nv_bfloat16* vb = kt + 16384 + (16 * kc + 2 * q) * 128 + lr;
#pragma unroll
        for (int nt = 0; nt < 16; nt++) {
            o[4 * nt] *= a0; o[4 * nt + 1] *= a0; o[4 * nt + 2] *= a1; o[4 * nt + 3] *= a1;
            mma16816(o[4 * nt], o[4 * nt + 1], o[4 * nt + 2], o[4 * nt + 3], p0, p1, p2, p3, ld_pair(vb + 8 * nt), ld_pair(vb + 8 * nt + 8 * 128));
        }
    }
}

__device__ __forceinline__ void signal(uint32_t bars, int wg, int e, int lane) {
    __syncwarp();
    asm volatile("{\n.reg .pred p;\nsetp.eq.u32 p, %1, 0;\n@p mbarrier.arrive.shared::cta.b64 _, [%0];\n}\n" ::"r"(bars + BAR_SIG + (wg * 9 + e) * 8), "r"(lane) : "memory");
}

__device__ __forceinline__ void mod_ffn(const Params& P, uint32_t smem, int mc, int wg);

__device__ __forceinline__ void consumer(const Params& P, uint32_t smem, uint32_t bars, int ca, int cb, int rank, int wg) {
    const int lane = threadIdx.x & 31, w = (threadIdx.x >> 5) & 3, q = lane & 3, lr = lane >> 2;
    PROF(7);
    cluster_wait();
    Cons c{bars, mapa(bars + BAR_EMPTY, lane & 1), (smem & 0x3FFFF) >> 4, (uint32_t)lane, Slot{0u, (smem & 0x3FFFF) >> 4, cb == 8 ? 0u : 1u}};
    PROFG(180);
    PROF(1);
    float o[64], s[64];
    uint32_t pend;
    __nv_bfloat16* ep_ptr;
    int ep_step;
    if (cb == 8) {
        pend = 0;
        ep_ptr = g_ctx + (size_t)(item_h(cb, 2 + ca, 0) * SEQ + 128 * rank + 64 * wg + 16 * w + lr) * HD + 8 * q;
        ep_step = 8 * HD;
    } else {
        const int ln_t = blockIdx.x * 16 + wg * 8 + w * 2 + (lane >> 4);
        const int krow = 64 * wg + 16 * w + lr;
        const int vrow = 64 * wg + 32 * (w >> 1) + 8 * (lr >> 1) + 4 * (w & 1) + (lr & 1);
        ep_step = 2 * 128;
        int m = 0;
        uint32_t lap = 0;
        LayerNorm ln;
        auto step = [&](auto kt, auto kc, float (&d)[64], int hh) {
            const Slot sa = c.slot(slot_a(kc.value), 0), sw = c.slot(slot_w(m), lap ^ (m >> 1));
            lap ^= m >> 1;
            m = (m == 2) ? 0 : m + 1;
            TR(1 + (hh * 8 + (kt.value ? 0 : 4) + kc.value) * 2);
            if (kt.value && hh == 0) c.wait(sa);
            c.wait(sw);
            TR(2 + (hh * 8 + (kt.value ? 0 : 4) + kc.value) * 2);
            wgmma_fence();
            gemm_kv<kt.value, kc.value == 0, 0, KVSPLIT>(d, sa.dl, sw.dl, wg);
            wgmma_commit();
            wgmma_wait<1>();
            if (!(kt.value && kc.value == 0 && hh == 0)) c.release(pend);
            if (!kt.value && kc.value > 0 && hh == 3) c.release(slot_a(kc.value - 1) * 8);
            pend = sw.bo;
            wgmma_fence();
            gemm_kv<kt.value, false, KVSPLIT, 8>(d, sa.dl, sw.dl, wg);
            wgmma_commit();
        };
#pragma unroll 1
        for (int hh = 0; hh < 4; hh++) {
            __nv_bfloat16* base = g_kv + (size_t)(((cb + 8 * kv_round(hh)) * 16 + 2 * ca + rank) * 2) * 16384 + 8 * q;
            auto ln_stage = [&](auto pos) {
                constexpr int j = (pos.value + 8 - LNOFF % 8) % 8;
                if (hh == wg + (LNOFF + j) / 8) {
                    if (j == 0) ln.stat1();
                    if (j == 1) ln.template stat2<0>();
                    if (j == 2) ln.template stat2<1>();
                    if constexpr (j >= 3) ln.template piece<j - 3>(P.out, ln_t, lane & 15);
                    if (j == 7) signal(bars, wg, 0, lane);
                }
                if (pos.value == (LNOFF - LNLEAD) % 8 && hh == wg + (LNOFF - LNLEAD) / 8) ln.load(P.x, P.wr, ln_t, lane & 15);
            };
            for4([&](auto kc) {
                step(TrueT{}, kc, s, hh);
                if (hh > 0) {
                    if (kc.value == 0) fence_regs(o);
                    store_chunk<kc.value>(o, ep_ptr, ep_ptr + ep_step, 1.f, 1.f);
                    if (kc.value == 3) signal(bars, wg, hh, lane);
                }
                ln_stage(kc);
            });
            for4([&](auto kc) {
                step(FalseT{}, kc, o, hh);
                if (kc.value == 0) fence_regs(s);
                store_chunk<kc.value>(s, base + krow * 128, base + (krow + 8) * 128, 1.f, 1.f);
                ln_stage(IntT<kc.value + 4>{});
            });
            PROF(24 + hh);
            if (hh == 1) PROFG(181);
            ep_ptr = base + 16384 + vrow * 128;
        }
    }
    PROFG(182);
    PROF(2);
    uint32_t pf[32];
    {
        uint32_t qf[32];
        float l0 = 0.25f, l1 = 0.25f;
        const int bar_me = 2 + wg, bar_other = 3 - wg;
#pragma unroll 1
        for (int j = 0; j < n_items(ca, cb); j++) {
            const int rd = item_rd(ca, cb, j), h = item_h(cb, rd, j), p = item_q(ca, cb, rd);
            const int role = wg ^ (j & 1);
            const int nrest = 2 * p + role;
            Slot kfirst;
            const int lim = 64 * (role ^ rank) + 16 * w + lr - 8 * q;
            const uint64_t pol = policy_sel(j == 1 || j == 2);
            {
                auto qstep = [&](auto zero, int ks) {
                    const Slot sl = c.next();
                    c.wait(sl);
                    BP(2, 5 + 3 * ks);
                    wgmma_fence();
                    gemm_q<zero.value>(s, sl.dl, role);
                    wgmma_commit();
                    wgmma_wait<1>();
                    if (!zero.value || j > 0 || cb < 8) c.release(pend);
                    pend = sl.bo;
                };
                qstep(TrueT{}, 0);
                if (j == 0 && cb < 8) c.release(slot_a(3) * 8);
                fence_regs(o);
                l0 += __shfl_xor_sync(0xffffffffu, l0, 1); l1 += __shfl_xor_sync(0xffffffffu, l1, 1);
                l0 += __shfl_xor_sync(0xffffffffu, l0, 2); l1 += __shfl_xor_sync(0xffffffffu, l1, 2);
                l0 = rcp(l0); l1 = rcp(l1);
                for4([&](auto i) {
                    constexpr int B = 16 * i.value;
#pragma unroll
                    for (int r = 0; r < 2; r++) {
                        if (1 + 2 * i.value + r == 7 && !(role | rank)) named_sync(bar_me, 256);
                        qstep(FalseT{}, 1 + 2 * i.value + r);
                        const float f = r ? l1 : l0;
                        stg128p(ep_ptr + r * ep_step + 2 * B, pack_bf16(o[B + 2 * r] * f, o[B + 2 * r + 1] * f), pack_bf16(o[B + 2 * r + 4] * f, o[B + 2 * r + 5] * f),
                                pack_bf16(o[B + 2 * r + 8] * f, o[B + 2 * r + 9] * f), pack_bf16(o[B + 2 * r + 12] * f, o[B + 2 * r + 13] * f), pol);
#pragma unroll
                        for (int k = 0; k < 8; k++) {
                            float& v = o[B + 4 * (k >> 1) + 2 * r + (k & 1)];
                            v = (2 * B + k > lim + 8 * r) ? -1e30f : 0.f;
                            asm volatile("" : "+f"(v));
                        }
                    }
                });
                signal(bars, wg, (cb == 8 ? 0 : 4) + j, lane);
                PROF(11 + rd * 4);
                qstep(FalseT{}, 9);
                if (!role) { const Slot sl = c.next(); c.wait(sl); c.release(sl.bo); }
                kfirst = c.next();
                c.wait(kfirst);
                wgmma_wait<0>();
                BP(2, 34);
                c.release(pend);
                fence_regs(s);
                pack_tile(s, qf);
            }
            Slot vskip = c.cur;
            if (!role) vskip = c.next();
            PROF(8 + rd * 4);
            if (cb == 8) PROF(40 + 3 * j);
            fence_regs(qf); fence_regs(o);
            if (!role && rank) named_sync(bar_me, 256);
            BP(2, 36);
            auto first_qk = [&](auto half) {
                wgmma_fence();
#pragma unroll
                for (int k = 0; k < 8; k++) {
                    if (half.value) wgmma_rs_n64<1>(o, qf[4 * k], qf[4 * k + 1], qf[4 * k + 2], qf[4 * k + 3], kfirst.dl + lbo(16384) + k * 128, 1);
                    else wgmma_rs_n128<1>(o, qf[4 * k], qf[4 * k + 1], qf[4 * k + 2], qf[4 * k + 3], kfirst.dl + lbo(16384) + k * 128, 1);
                }
                wgmma_commit();
                named_arrive(bar_other, 256);
                if (!role) { c.wait(vskip); c.release(vskip.bo); }
                wgmma_wait<0>();
            };
            if (role == rank) first_qk(TrueT{});
            else first_qk(FalseT{});
            BP(2, 38);
            fence_regs(o);
            c.release(kfirst.bo);
            uint32_t ready = c.peek();
            float n0 = fmaxf(fmaxf(fmaxf(o[0], o[1]), fmaxf(o[4], o[5])), fmaxf(fmaxf(o[8], o[9]), fmaxf(o[12], o[13])));
            float n1 = fmaxf(fmaxf(fmaxf(o[2], o[3]), fmaxf(o[6], o[7])), fmaxf(fmaxf(o[10], o[11]), fmaxf(o[14], o[15])));
            n0 = __shfl_sync(0xffffffffu, n0, lane & 28); n1 = __shfl_sync(0xffffffffu, n1, lane & 28);
            n0 *= -SM_SCALE; n1 *= -SM_SCALE;
            l0 = 0.f; l1 = 0.f;
#pragma unroll
            for (int i = 0; i < 64; i++) s[i] = o[i];
            exp_part<0, 8>(s, n0, n1, l0, l1);
#pragma unroll
            for (int i = 0; i < 16; i++) pf[i] = pack_bf16(s[2 * i], s[2 * i + 1]);
            if (role != rank) {
                exp_part<8, 16>(s, n0, n1, l0, l1);
#pragma unroll
                for (int i = 16; i < 32; i++) pf[i] = pack_bf16(s[2 * i], s[2 * i + 1]);
            } else {
#pragma unroll
                for (int i = 16; i < 32; i++) pf[i] = 0u;
            }
            PROF(9 + rd * 4);
            if (cb == 8) PROF(41 + 3 * j);
#pragma unroll 1
            for (int it = 0; it < nrest; it++) {
                const Slot sk = c.next(), sv = c.next();
                LP(0);
                c.wait(sk, ready);
                fence_regs(o); fence_regs(pf);
                LP(1);
                named_sync(bar_me, 256);
                LP(2);
                if (it < 3) BP(2, 42 + 4 * it);
                if (it >= nrest - 2) BP(1, 62 + 4 * (it - nrest + 2));
                wgmma_fence();
                gemm_rs<true>(s, qf, sk.dl);
                wgmma_commit();
                c.wait(sv);
                wgmma_fence();
                gemm_pv(o, pf, sv.dl, it, it | (role ^ rank));
                wgmma_commit();
                named_arrive(bar_other, 256);
                LP(3);
                wgmma_wait<2>();
                LP(4);
                c.release(sk.bo);
                fence_regs(s);
                exp_part<0, SPLITJ>(s, n0, n1, l0, l1);
                sched_barrier(l0, l1, bars + MISC_OFF + 16);
                LP(5);
                wgmma_wait<0>();
                LP(6);
                c.release(sv.bo);
                ready = c.peek();
                fence_regs(o); fence_regs(pf);
                exp_part<SPLITJ, 16>(s, n0, n1, l0, l1);
                pack_tile(s, pf);
            }
            PROF(10 + rd * 4);
            if (cb == 8) PROF(42 + 3 * j);
            PROFG(183 + rd);
            const Slot sv = c.next();
            BP(1, 0);
            c.wait(sv, ready);
            const bool bad = __any_sync(0xffffffffu, !(l0 < 0x1p60f && l1 < 0x1p60f));
            if (__builtin_expect(bad || nrest == 0, 0)) {
#pragma unroll
                for (int i = 0; i < 64; i++) o[i] = 0.f;
                if (bad) {
                    attention_exact(o, qf, l0, l1, h, nrest + 1, lim, lane);
#pragma unroll
                    for (int i = 0; i < 32; i++) pf[i] = 0u;
                }
            }
            fence_regs(o); fence_regs(pf);
            if (!role) named_sync(bar_me, 256);
            BP(1, 2);
            wgmma_fence();
            gemm_rs<false>(o, pf, sv.dl);
            wgmma_commit();
            pend = sv.bo;
            ep_ptr = g_ctx + (size_t)(h * SEQ + 256 * p + 128 * rank + 64 * role + 16 * w + lr) * HD + 8 * q;
            ep_step = 8 * HD;
        }
        l0 += __shfl_xor_sync(0xffffffffu, l0, 1); l1 += __shfl_xor_sync(0xffffffffu, l1, 1);
        l0 += __shfl_xor_sync(0xffffffffu, l0, 2); l1 += __shfl_xor_sync(0xffffffffu, l1, 2);
        l0 = rcp(l0); l1 = rcp(l1);
        wgmma_wait<0>();
        c.release(pend);
        fence_regs(o); fence_regs(pf);
#pragma unroll
        for (int i = 0; i < 32; i++) pf[i] = pack_bf16(o[2 * i] * ((i & 1) ? l1 : l0), o[2 * i + 1] * ((i & 1) ? l1 : l0));
    }
    PROFG(187);
    PROF(3);
    if (cb == 8) {
#pragma unroll
        for (int i = 0; i < 8; i++) stg128(ep_ptr + (i & 1) * 8 * HD + 32 * (i >> 1), pf[4 * (i & 6) + (i & 1)], pf[4 * (i & 6) + (i & 1) + 2], pf[4 * (i & 6) + (i & 1) + 4], pf[4 * (i & 6) + (i & 1) + 6]);
        signal(bars, wg, 8, lane);
        cluster_arrive();
        named_sync(1, 256);
        mod_ffn(P, smem, 2 * ca + rank, wg);
    } else
    {
        float a1[64], a2[96];
        uint32_t px = 0, py = 0;
        auto mma1 = [&](const Slot& x, int acc) {
#pragma unroll
            for (int k = 0; k < 4; k++) wgmma_ss_n128<0, 1>(a1, x.dl + wg * 512 + lbo(16) + k * 2, x.dl + 1024 + lbo(4096) + (k >> 1) * 512 + (k & 1) * 128, k ? 1 : acc);
        };
        auto mma2 = [&](const Slot& x, const Slot& y, int acc) {
#pragma unroll
            for (int k = 0; k < 4; k++) wgmma_ss_n192<0, 1>(a2, x.dl + wg * 512 + lbo(16) + k * 2, y.dl + lbo(4096) + (k >> 1) * 768 + (k & 1) * 128, k ? 1 : acc);
        };
#pragma unroll 1
        for (int t = 0, more = 1; more; t++) {
            const Slot sx = c.next(), sy = c.next();
            c.wait(sx);
            wgmma_fence();
            mma1(sx, t);
            wgmma_commit();
            asm volatile("ld.shared.u32 %0, [%1];" : "=r"(more) : "r"(bars + CTL_OFF + sx.bo) : "memory");
            more = !__any_sync(0xffffffffu, more);
            wgmma_wait<1>();
            if (t > 0) { c.release(px); c.release(py); }
            px = sx.bo; py = sy.bo;
            c.wait(sy);
            wgmma_fence();
            mma2(sx, sy, t);
            wgmma_commit();
            if (t == 0) {
#pragma unroll
                for (int i = 0; i < 4; i++) stg128(ep_ptr + 32 * i, pf[8 * i], pf[8 * i + 2], pf[8 * i + 4], pf[8 * i + 6]);
            }
            if (t == 1) {
#pragma unroll
                for (int i = 0; i < 4; i++) stg128(ep_ptr + 8 * HD + 32 * i, pf[8 * i + 1], pf[8 * i + 3], pf[8 * i + 5], pf[8 * i + 7]);
                signal(bars, wg, 4 + n_items(ca, cb), lane);
            }
        }
        const Slot x0 = c.next(), y0 = c.next(), x1 = c.next(), y1 = c.next(), x2 = c.next(), y2 = c.next(), fr = c.next();
        const int cw = __reduce_or_sync(0xffffffffu, wg * 4 + w);
        const int orow = unperm_row(256 * out_p(ca, cb) + 128 * rank + 16 * cw), ocol = 320 * (ca >> 2);
        const uint32_t sa = ((lane & 7) + (lane & 8)) * 128, sx = (lane >> 4) ^ (lane & 7);
        auto send = [&](auto chv, uint32_t box) {
            constexpr int ch = chv.value;
#pragma unroll
            for (int i = 0; i < 4; i++) {
                uint32_t r[4];
#pragma unroll
                for (int e = 0; e < 4; e++) {
                    const int k = 32 * ch + 8 * i + 2 * e;
                    r[e] = (ch < 2) ? pack_bf16(a1[k & 63], a1[(k & 63) + 1]) : pack_bf16(a2[ch < 2 ? 0 : k - 64], a2[ch < 2 ? 1 : k - 63]);
                }
                asm volatile("stmatrix.sync.aligned.m8n8.x4.shared.b16 [%0], {%1, %2, %3, %4};"
                             ::"r"(box + sa + ((sx ^ (2 * i)) << 4)), "r"(r[0]), "r"(r[1]), "r"(r[2]), "r"(r[3]) : "memory");
            }
            asm volatile("fence.proxy.async.shared::cta;" ::: "memory");
            __syncwarp();
            asm volatile(ELECT "cp.reduce.async.bulk.tensor.2d.global.shared::cta.add.bulk_group [%0, {%2, %3}], [%1];\n}\n"
                         ::"l"(&P.outm), "r"(box), "r"(ocol + 64 * ch), "r"(orow) : "memory");
        };
        auto addr = [&](const Slot& t) { return smem + t.bo * (SLOT / 8); };
        c.wait(x0);
        wgmma_fence();
        mma1(x0, 1);
        wgmma_commit();
        wgmma_wait<1>();
        c.release(px); c.release(py);
        c.wait(x1);
        c.wait(x2);
        c.wait(y0);
        mbar_wait(bars + BAR_DEP, 0);
        wgmma_fence();
        mma1(x1, 1);
        mma1(x2, 1);
        wgmma_commit();
        mma2(x0, y0, 1);
        wgmma_commit();
        mbar_wait(bars + BAR_EMPTY + fr.bo, fr.par ^ 1);
        c.wait(y1);
        wgmma_wait<1>();
        fence_regs(a1);
        send(IntT<0>{}, addr(fr) + cw * 4096);
        wgmma_fence();
        mma2(x1, y1, 1);
        wgmma_commit();
        send(IntT<1>{}, addr(fr) + cw * 4096 + 2048);
        c.wait(y2);
        wgmma_fence();
        mma2(x2, y2, 1);
        wgmma_commit();
        wgmma_wait<0>();
        fence_regs(a2);
        PROFG(188);
        PROF(4);
        send(IntT<2>{}, addr(x0) + cw * 2048);
        send(IntT<3>{}, addr(x1) + cw * 2048);
        send(IntT<4>{}, addr(x2) + cw * 2048);
        PROF(5);
        asm volatile("cp.async.bulk.commit_group;\ncp.async.bulk.wait_group.read 0;" ::: "memory");
    }
    PROF(6);
}

__device__ __forceinline__ void mod_ffn(const Params& P, uint32_t smem, int mc  , int wg) {
    const int tid = threadIdx.x - 128, lane = tid & 31, cw = tid >> 5, q = lane & 3, lr = lane >> 2;
    const uint32_t xs = smem + 6 * SLOT, hs = xs + 10240 + wg * 1024, wmax = xs + 12288, sidx = wmax + 64, rbar = xs + 13312 + wg * 32;
    const uint32_t ring = smem + wg * 3 * SLOT;
    const int f0 = mc + 4 * wg, nunit = ((34 - f0) >> 3) * 8;
    const bool lead = __reduce_or_sync(0xffffffffu, cw & 3) == 0;
    auto lds = [](uint32_t a) { uint32_t v; asm volatile("ld.shared.u32 %0, [%1];" : "=r"(v) : "r"(a) : "memory"); return v; };
    auto sts = [](uint32_t a, uint32_t v) { asm volatile("st.shared.u32 [%0], %1;" ::"r"(a), "r"(v) : "memory"); };
    auto issue = [&](int u, int st) {
        if (lead && u < nunit) {
            const int fc = (f0 + (u & ~7)) * 64, k = u & 7;
            const uint32_t dst = ring + st * SLOT, bar = rbar + st * 8;
            w_expect_tx(bar, k == 7 ? 16384 : SLOT);
            if (k < 5) {
                w_tma_load_stream(dst, &P.wg, fc, k * 128, bar);
                w_tma_load_stream(dst + 16384, &P.wu, fc, k * 128, bar);
            } else {
#pragma unroll 1
                for (int b = 0; b < (k == 7 ? 2 : 4); b++) w_tma_load_stream(dst + b * 8192, &P.wd, (4 * (k - 5) + b) * 64, fc, bar);
            }
        }
    };
    if ((tid & 127) == 0) {
        mbar_init(rbar, 1); mbar_init(rbar + 8, 1); mbar_init(rbar + 16, 1);
        asm volatile("fence.mbarrier_init.release.cluster;" ::: "memory");
    }
    mbar_wait(smem + NSLOT * SLOT + BAR_DEP, 0);
    asm volatile("fence.proxy.async.shared::cta;" ::: "memory");
    named_sync(1, 256);
    PROF(1);
#pragma unroll 1
    for (int u = 0; u < 3; u++) issue(u, u);
    uint32_t key[8];
#pragma unroll
    for (int i = 0; i < 8; i++) {
        const int t = tid + 256 * i;
        uint32_t b = __float_as_uint(__ldcg(g_r + t) + 0.f) >> 16;
        b = (b & 0x8000u) ? (~b & 0xffffu) : (b | 0x8000u);
        key[i] = (b << 16) | (uint32_t)(0xffff - t);
    }
#pragma unroll 1
    for (int rnd = 0; rnd < 8; rnd++) {
        uint32_t mx = key[0];
#pragma unroll
        for (int i = 1; i < 8; i++) mx = max(mx, key[i]);
        sts(wmax + ((rnd & 1) * 8 + cw) * 4, __reduce_max_sync(0xffffffffu, mx));
        named_sync(1, 256);
        mx = __reduce_max_sync(0xffffffffu, lds(wmax + ((rnd & 1) * 8 + (lane & 7)) * 4));
#pragma unroll
        for (int i = 0; i < 8; i++) if (key[i] == mx) key[i] = 0;
        if (cw == rnd) sts(sidx + rnd * 4, 0xffff - (mx & 0xffffu));
    }
    __syncwarp();
    {
        const int t = lds(sidx + cw * 4);
        const uint4* src = reinterpret_cast<const uint4*>(g_xn + perm_row(t) * DM);
#pragma unroll
        for (int i = 0; i < 3; i++) {
            const int ch = lane + 32 * i;
            if (ch < 80) {
                const uint4 v = __ldcg(src + ch);
                asm volatile("st.shared.v4.b32 [%0], {%1, %2, %3, %4};" ::"r"(xs + (ch >> 3) * 1024 + cw * 128 + ((ch ^ cw) & 7) * 16), "r"(v.x), "r"(v.y), "r"(v.z), "r"(v.w) : "memory");
            }
        }
        asm volatile("fence.proxy.async.shared::cta;" ::: "memory");
    }
    named_sync(1, 256);
    PROF(3);
    float y[10][4];
#pragma unroll
    for (int i = 0; i < 10; i++) { y[i][0] = 0.f; y[i][1] = 0.f; y[i][2] = 0.f; y[i][3] = 0.f; }
    int st = 0, ph = 0, u = 0;
    auto begin = [&]() { mbar_wait(rbar + st * 8, ph); wgmma_fence(); return (((ring + st * SLOT) & 0x3FFFF) >> 4) + lbo(16); };
    auto end = [&]() {
        wgmma_commit();
        wgmma_wait<0>();
        named_sync(4 + wg, 128);
        issue(u + 3, st);
        u++;
        ph ^= st == 2;
        st = (st == 2) ? 0 : st + 1;
    };
    const uint32_t dx = ((xs & 0x3FFFF) >> 4) + lbo(16), dh = ((hs & 0x3FFFF) >> 4) + lbo(16);
#pragma unroll 1
    while (u < nunit) {
        float g[4], v[4];
#pragma unroll 1
        for (int kc = 0; kc < 5; kc++) {
            const uint32_t da = begin();
#pragma unroll
            for (int k = 0; k < 8; k++) {
                const uint32_t db = dx + (2 * kc + (k >> 2)) * 64 + (k & 3) * 2;
                wgmma_ss_n8<1, 0>(g, da + k * 128, db, k ? 1 : kc);
                wgmma_ss_n8<1, 0>(v, da + 1024 + k * 128, db, k ? 1 : kc);
            }
            end();
        }
        fence_regs(g); fence_regs(v);
#pragma unroll
        for (int e = 0; e < 4; e++) {
            const float gp = round_bf16(g[e]);
            const float hv = round_bf16(__fdividef(gp, 1.0f + __expf(fminf(-gp, 80.f)))) * round_bf16(v[e]);
            const int tok = 2 * q + (e & 1), ch = 2 * (cw & 3) + (e >> 1);
            asm volatile("st.shared.u16 [%0], %1;" ::"r"(hs + tok * 128 + ((ch ^ tok) * 16) + lr * 2), "h"((unsigned short)pack_bf16(hv, 0.f)) : "memory");
        }
        asm volatile("fence.proxy.async.shared::cta;" ::: "memory");
        named_sync(4 + wg, 128);
#pragma unroll
        for (int k3 = 0; k3 < 3; k3++) {
            const uint32_t da = begin();
#pragma unroll
            for (int b = 0; b < (k3 == 2 ? 2 : 4); b++)
#pragma unroll
                for (int k = 0; k < 4; k++) wgmma_ss_n8<1, 0>(y[4 * k3 + b], da + b * 512 + k * 128, dh + k * 2, 1);
            end();
        }
    }
    PROF(5);
#pragma unroll
    for (int i = 0; i < 10; i++) {
        fence_regs(y[i]);
#pragma unroll
        for (int e = 0; e < 4; e++) g_ypart[((mc * 2 + wg) * 8 + 2 * q + (e & 1)) * DM + 64 * i + 16 * (cw & 3) + lr + 8 * (e >> 1)] = y[i][e];
    }
    named_sync(1, 256);
    if (tid == 0) {
        flag_add(F_MODP);
        flag_wait<100>(F_MODP, 4u * (lds(smem + NSLOT * SLOT + MISC_OFF) + 1));
    }
    named_sync(1, 256);
    PROF(6);
    {
        const int c = 2 * mc + wg, t = lds(sidx + c * 4);
        const float rs = round_bf16(__fdividef(1.0f, 1.0f + __expf(fminf(-__ldcg(g_r + t), 80.f))));
#pragma unroll
        for (int i = 0; i < 3; i++) {
            const int c2 = (tid & 127) + 128 * i;
            if (c2 < DM / 2) {
                float y0 = 0.f, y1 = 0.f;
#pragma unroll
                for (int k = 0; k < 8; k++) {
                    const float2 v = __ldcg(reinterpret_cast<const float2*>(g_ypart + (k * 8 + c) * DM) + c2);
                    y0 += v.x; y1 += v.y;
                }
                asm volatile("red.relaxed.gpu.global.add.noftz.bf16x2 [%0], %1;" ::"l"(P.out + t * DM + 2 * c2), "r"(pack_bf16(round_bf16(y0) * rs, round_bf16(y1) * rs)) : "memory");
            }
        }
    }
    PROF(7);
}

__global__ void __cluster_dims__(2, 1, 1) __launch_bounds__(384, 1) fused_kernel(const __grid_constant__ Params P) {
    extern __shared__ __align__(1024) uint8_t smem_raw[];
    const uint32_t smem = (smem_u32(smem_raw) + 1023u) & ~1023u;
    const uint32_t bars = smem + NSLOT * SLOT;
    const int wgi = __reduce_or_sync(0xffffffffu, threadIdx.x >> 7);
    const int cl = blockIdx.x >> 1, rank = blockIdx.x & 1, ca = cl & 7, cb = cl >> 3;
    PROFG(30);
    PROF(0);
    if (threadIdx.x == 64) {
        const uint32_t fa = bars + BAR_FULL + slot_a(0) * 8, fw = bars + BAR_FULL + slot_w(0) * 8;
        mbar_init(fa, 1); mbar_init(fw, 1);
        asm volatile("fence.mbarrier_init.release.cluster;" ::: "memory");
        if (cb < 8) {
            mbar_expect_tx(fa, SLOT);
            mbar_expect_tx(fw, SLOT);
            tma_load(smem + slot_a(0) * SLOT, &P.ckv, 0, (2 * ca + rank) * 128, fa);
            tma_load(smem + slot_w(0) * SLOT, &P.wuk, (cb + 8 * kv_round(0)) * 128, 0, fw);
            tma_load(smem + slot_w(0) * SLOT + 16384, &P.wuk, (cb + 8 * kv_round(0)) * 128 + 64, 0, fw);
            tma_load(smem + slot_a(0) * SLOT + 16384, &P.ckv, 64, (2 * ca + rank) * 128, fa);
        }
    } else if (threadIdx.x == 0) {
#pragma unroll
        for (int i = 0; i < NSLOT; i++) {
            if (i != slot_a(0) && i != slot_w(0)) mbar_init(bars + BAR_FULL + i * 8, 1);
            mbar_init(bars + BAR_EMPTY + i * 8, 16);
        }
        if (cb < 8) {
            mbar_arrive(bars + BAR_FULL + 16);
            asm volatile("mbarrier.arrive.shared::cta.b64 _, [%0], 16;" ::"r"(bars + BAR_EMPTY + 16) : "memory");
        }
        asm volatile("fence.mbarrier_init.release.cluster;" ::: "memory");
        PROF(24);
    } else if (threadIdx.x == 32) {
#pragma unroll
        for (int i = 0; i < 18; i++) mbar_init(bars + BAR_SIG + i * 8, 4);
#pragma unroll
        for (int i = 0; i < 18; i++) mbar_init(bars + BAR_DEP + i * 8, 1);
        asm volatile("fence.mbarrier_init.release.cluster;" ::: "memory");
    }
    __syncthreads();
    PROF(29);
    cluster_arrive();
    if (wgi > 0) {
        asm volatile("setmaxnreg.inc.sync.aligned.u32 232;");
        consumer(P, smem, bars, ca, cb, rank, wgi - 1);
        PROFG(31);
        PROFDUMP();
    } else {
        asm volatile("setmaxnreg.dec.sync.aligned.u32 40;");
        const int w = __reduce_or_sync(0xffffffffu, threadIdx.x >> 5), lane = threadIdx.x & 31;
        if (threadIdx.x == 32) {
            prefetch_map(&P.wuv); prefetch_map(&P.xn); prefetch_map(&P.wq); prefetch_map(&P.kv); prefetch_map(&P.ctx); prefetch_map(&P.wo); prefetch_map(&P.outm);
        }
        __syncwarp();
        cluster_wait();
        PROF(27);
        {
            if (w == 0) {
                producer(P, smem, bars, ca, cb, rank);
            } else if (w < 3 && lane == 0) {
                const int wg = w - 1;
#pragma unroll 1
                for (int i = (cb == 8); i < (cb == 8 ? 9 : 5 + n_items(ca, cb)); i++) {
                    const int nb = wg + (LNOFF + 7 - 4) / 8;
                    const int e = (cb == 8) ? i : (i < nb) ? i + 1 : (i == nb) ? 0 : i;
                    mbar_wait_sleep(bars + BAR_SIG + (wg * 9 + e) * 8, 0);
                    int f;
                    if (cb == 8) f = F_CTX + (2 + ca) * 16 + rank;
                    else if (e == 0) {
                        f = F_LN;
                        if ((ca & 3) == 0 && rank == 0 && wg == 0) g_flags[(F_POOL + out_p(ca, cb) * 2 + (ca >> 2)) * 8] = 8;
                    }
                    else if (e < 5) f = F_KV + cb + 8 * kv_round(e - 1);
                    else { const int rd = item_rd(ca, cb, e - 5); f = F_CTX + rd * 16 + item_p(ca, rd) * 2 + rank; }
                    flag_add(f);
                }
            } else if (lane == 0) {
                const uint32_t epoch = read_epoch();
                asm volatile("st.shared.u32 [%0], %1;" ::"r"(bars + MISC_OFF), "r"(epoch) : "memory");
#pragma unroll 1
                for (int e = 0; e < 9; e++) {
                    int f;
                    uint32_t n;
                    if (e == 0) { f = F_LN; n = 256; }
                    else if (cb == 8) { f = F_KV + item_h(cb, 2 + ca, e - 1); n = 32; }
                    else if (e < 5) { f = F_KV + cb + 8 * (e - 1); n = 32; }
                    else { f = F_CTX + (e - 5) * 16 + out_p(ca, cb) * 2 + rank; n = 16; }
                    flag_wait<200>(f, n * (epoch + 1));
                    fence_proxy_async();
                    mbar_arrive(bars + BAR_DEP + e * 8);
                }
            }
        }
        if (cb == 8) { __syncwarp(); cluster_arrive(); cluster_wait(); }
        PROFG(31);
        PROFDUMP();
    }
}

typedef CUresult (*EncodeFn)(CUtensorMap*, CUtensorMapDataType, cuuint32_t, void*, const cuuint64_t*, const cuuint64_t*, const cuuint32_t*,
                             const cuuint32_t*, CUtensorMapInterleave, CUtensorMapSwizzle, CUtensorMapL2promotion, CUtensorMapFloatOOBfill);

void make_map(EncodeFn fn, CUtensorMap* m, const void* ptr, uint64_t rows, uint64_t cols, uint32_t box_rows) {
    cuuint64_t dims[2] = {cols, rows};
    cuuint64_t strides[1] = {cols * 2};
    cuuint32_t box[2] = {64, box_rows};
    cuuint32_t es[2] = {1, 1};
    fn(m, CU_TENSOR_MAP_DATA_TYPE_BFLOAT16, 2, const_cast<void*>(ptr), dims, strides, box, es, CU_TENSOR_MAP_INTERLEAVE_NONE,
       CU_TENSOR_MAP_SWIZZLE_128B, CU_TENSOR_MAP_L2_PROMOTION_L2_128B, CU_TENSOR_MAP_FLOAT_OOB_FILL_NONE);
}

}

extern "C" void kernel_launch(void* const* d_in, const int* in_sizes, int n_in, void* d_out, int out_size) {
    (void)in_sizes; (void)n_in; (void)out_size;
    void* fnp = nullptr;
    cudaDriverEntryPointQueryResult qr;
    cudaGetDriverEntryPoint("cuTensorMapEncodeTiled", &fnp, cudaEnableDefault, &qr);
    EncodeFn fn = (EncodeFn)fnp;
    void *xn, *kv, *ctx;
    cudaGetSymbolAddress(&xn, g_xn);
    cudaGetSymbolAddress(&kv, g_kv);
    cudaGetSymbolAddress(&ctx, g_ctx);
    Params P;
    make_map(fn, &P.ckv, d_in[1], SEQ, DC, 128);
    make_map(fn, &P.wq, d_in[2], DM, NH * HD, 64);
    make_map(fn, &P.wuk, d_in[3], DC, NH * HD, 128);
    make_map(fn, &P.wuv, d_in[4], DC, NH * HD, 128);
    make_map(fn, &P.wo, d_in[5], NH * HD, DM, 32);
    make_map(fn, &P.xn, xn, SEQ, DM, 128);
    make_map(fn, &P.kv, kv, NH * 16 * 2 * 128, 128, 128);
    make_map(fn, &P.ctx, ctx, NH * SEQ, HD, 128);
    P.x = (const __nv_bfloat16*)d_in[0];
    P.wr = (const __nv_bfloat16*)d_in[7];
    make_map(fn, &P.wg, d_in[8], DM, FF, 128);
    make_map(fn, &P.wu, d_in[9], DM, FF, 128);
    make_map(fn, &P.wd, d_in[10], FF, DM, 64);
    make_map(fn, &P.outm, d_out, SEQ, DM, 16);
    P.out = (__nv_bfloat16*)d_out;
    cudaFuncSetAttribute(fused_kernel, cudaFuncAttributeMaxDynamicSharedMemorySize, SMEM_BYTES);
    fused_kernel<<<NCTA, 384, SMEM_BYTES>>>(P);
}
```

```cpp
#include <cuda_runtime.h>
#include <cuda_bf16.h>
#include <cuda.h>
#include <stdint.h>

namespace {

constexpr int SEQ = 2048, DM = 640, DC = 512, NH = 32, HD = 128, FF = 1728;
constexpr int NSLOT = 7, SLOT = 32768;
constexpr int NCTA = 132;
constexpr int KVSPLIT = 1;
constexpr int LNOFF = 4, LNLEAD = 2;
constexpr int SPLITJ = 8;
constexpr uint32_t DESC_HI = (1024u >> 4) | (1u << 30);
constexpr int SMEM_BYTES = NSLOT * SLOT + 3072;

constexpr int BAR_FULL = 0, BAR_EMPTY = 64, BAR_SIG = 128  , BAR_DEP = 320  , BAR_MAIL = 400  ;
constexpr int MISC_OFF = 512  , MAIL_OFF = 544  , CTL_OFF = 576  ;

constexpr int F_EPOCH = 0, F_LN = 1, F_MODP = 3, F_KV = 4  , F_CTX = 36  , F_POOL = 100  , F_NUM = 116;

__device__ __align__(1024) __nv_bfloat16 g_xn[SEQ * DM];
__device__ __align__(1024) __nv_bfloat16 g_kv[NH * 16 * 2 * 128 * 128];
__device__ __align__(1024) __nv_bfloat16 g_ctx[NH * SEQ * HD];
__device__ __align__(16) float g_r[SEQ];
__device__ __align__(16) float g_ypart[8 * 8 * DM];
__device__ uint32_t g_flags[F_NUM * 8];

struct TrueT { static constexpr bool value = true; };
struct FalseT { static constexpr bool value = false; };

struct Params {
    CUtensorMap ckv, wuk, wuv, xn, wq, kv, ctx, wo, wg, wu, wd, outm;
    const __nv_bfloat16 *x, *wr;
    __nv_bfloat16* out;
};

__device__ __forceinline__ uint32_t smem_u32(const void* p) { return (uint32_t)__cvta_generic_to_shared(p); }
__device__ __forceinline__ void mbar_init(uint32_t bar, uint32_t cnt) {
    asm volatile("mbarrier.init.shared::cta.b64 [%0], %1;" ::"r"(bar), "r"(cnt) : "memory");
}
__device__ __forceinline__ void mbar_expect_tx(uint32_t bar, uint32_t bytes) {
    asm volatile("mbarrier.arrive.expect_tx.shared::cta.b64 _, [%0], %1;" ::"r"(bar), "r"(bytes) : "memory");
}
__device__ __forceinline__ void mbar_arrive(uint32_t bar) {
    asm volatile("mbarrier.arrive.shared::cta.b64 _, [%0];" ::"r"(bar) : "memory");
}
__device__ __forceinline__ uint32_t mapa(uint32_t addr, uint32_t cta) {
    uint32_t r;
    asm("mapa.shared::cluster.u32 %0, %1, %2;" : "=r"(r) : "r"(addr), "r"(cta));
    return r;
}
__device__ __forceinline__ void mbar_wait(uint32_t bar, uint32_t parity) {
    asm volatile(
        "{\n.reg .pred p;\n.reg .b32 c;\n"
        "mov.b32 c, 0;\n"
        "WLOOP:\n"
        "mbarrier.try_wait.parity.shared::cta.b64 p, [%0], %1;\n"
        "@p bra.uni WDONE;\n"
        "add.u32 c, c, 1;\n"
        "setp.lt.u32 p, c, 0x400000;\n"
        "@p bra.uni WLOOP;\n"
        "trap;\n"
        "WDONE:\n}\n" ::"r"(bar), "r"(parity) : "memory");
}
__device__ __forceinline__ uint32_t mbar_peek(uint32_t bar, uint32_t parity) {
    uint32_t ok;
    asm volatile("{\n.reg .pred p;\nmbarrier.test_wait.parity.shared::cta.b64 p, [%1], %2;\nselp.b32 %0, 1, 0, p;\n}\n" : "=r"(ok) : "r"(bar), "r"(parity) : "memory");
    return ok;
}
__device__ __forceinline__ void mbar_wait_unless(uint32_t ok, uint32_t bar, uint32_t parity) {
    asm volatile(
        "{\n.reg .pred p;\n.reg .b32 c;\n"
        "setp.ne.b32 p, %2, 0;\n"
        "@p bra.uni WDONE;\n"
        "mov.b32 c, 0;\n"
        "WLOOP:\n"
        "mbarrier.try_wait.parity.shared::cta.b64 p, [%0], %1;\n"
        "@p bra.uni WDONE;\n"
        "add.u32 c, c, 1;\n"
        "setp.lt.u32 p, c, 0x400000;\n"
        "@p bra.uni WLOOP;\n"
        "trap;\n"
        "WDONE:\n}\n" ::"r"(bar), "r"(parity), "r"(ok) : "memory");
}
__device__ __forceinline__ void mbar_wait_sleep(uint32_t bar, uint32_t parity) {
    asm volatile(
        "{\n.reg .pred p;\n.reg .b32 c;\n"
        "mov.b32 c, 0;\n"
        "WLOOP:\n"
        "mbarrier.try_wait.parity.shared::cta.b64 p, [%0], %1, 20000;\n"
        "@p bra.uni WDONE;\n"
        "add.u32 c, c, 1;\n"
        "setp.lt.u32 p, c, 0x40000;\n"
        "@p bra.uni WLOOP;\n"
        "trap;\n"
        "WDONE:\n}\n" ::"r"(bar), "r"(parity) : "memory");
}
__device__ __forceinline__ void tma_load(uint32_t dst, const CUtensorMap* m, int c0, int c1, uint32_t bar) {
    asm volatile("cp.async.bulk.tensor.2d.shared::cluster.global.mbarrier::complete_tx::bytes [%0], [%1, {%3, %4}], [%2];"
                 ::"r"(dst), "l"(m), "r"(bar), "r"(c0), "r"(c1) : "memory");
}
#define ELECT "{\n.reg .pred e;\nelect.sync _|e, 0xffffffff;\n@e "
__device__ __forceinline__ void w_expect_tx(uint32_t bar, uint32_t bytes) {
    asm volatile(ELECT "mbarrier.arrive.expect_tx.shared::cta.b64 _, [%0], %1;\n}\n" ::"r"(bar), "r"(bytes) : "memory");
}
__device__ __forceinline__ void w_tma_load(uint32_t dst, const CUtensorMap* m, int c0, int c1, uint32_t bar) {
    asm volatile(ELECT "cp.async.bulk.tensor.2d.shared::cluster.global.mbarrier::complete_tx::bytes [%0], [%1, {%3, %4}], [%2];\n}\n"
                 ::"r"(dst), "l"(m), "r"(bar), "r"(c0), "r"(c1) : "memory");
}
__device__ __forceinline__ void w_tma_load_mc(uint32_t dst, const CUtensorMap* m, int c0, int c1, uint32_t bar) {
    asm volatile(ELECT "cp.async.bulk.tensor.2d.shared::cluster.global.mbarrier::complete_tx::bytes.multicast::cluster [%0], [%1, {%3, %4}], [%2], %5;\n}\n"
                 ::"r"(dst), "l"(m), "r"(bar), "r"(c0), "r"(c1), "h"((uint16_t)3) : "memory");
}
__device__ __forceinline__ void w_tma_prefetch(const CUtensorMap* m, int c0, int c1) {
    asm volatile(ELECT "cp.async.bulk.prefetch.tensor.2d.L2.global [%0, {%1, %2}];\n}\n" ::"l"(m), "r"(c0), "r"(c1) : "memory");
}
__device__ __forceinline__ uint64_t policy_evict_first() {
    uint64_t p;
    asm("createpolicy.fractional.L2::evict_first.b64 %0, 1.0;" : "=l"(p));
    return p;
}
__device__ __forceinline__ void w_tma_load_mc_last(uint32_t dst, const CUtensorMap* m, int c0, int c1, uint32_t bar) {
    asm volatile(ELECT "cp.async.bulk.tensor.2d.shared::cluster.global.mbarrier::complete_tx::bytes.multicast::cluster.L2::cache_hint [%0], [%1, {%3, %4}], [%2], %5, %6;\n}\n"
                 ::"r"(dst), "l"(m), "r"(bar), "r"(c0), "r"(c1), "h"((uint16_t)3), "l"(policy_evict_first()) : "memory");
}
__device__ __forceinline__ void w_tma_load_stream(uint32_t dst, const CUtensorMap* m, int c0, int c1, uint32_t bar) {
    asm volatile(ELECT "cp.async.bulk.tensor.2d.shared::cluster.global.mbarrier::complete_tx::bytes.L2::cache_hint [%0], [%1, {%3, %4}], [%2], %5;\n}\n"
                 ::"r"(dst), "l"(m), "r"(bar), "r"(c0), "r"(c1), "l"(policy_evict_first()) : "memory");
}
__device__ __forceinline__ uint4 ldg_stream(const void* p) {
    uint4 v;
    asm volatile("ld.global.nc.L2::cache_hint.v4.b32 {%0, %1, %2, %3}, [%4], %5;" : "=r"(v.x), "=r"(v.y), "=r"(v.z), "=r"(v.w) : "l"(p), "l"(policy_evict_first()));
    return v;
}
__device__ __forceinline__ void prefetch_map(const CUtensorMap* m) {
    asm volatile("prefetch.tensormap [%0];" ::"l"(m) : "memory");
}
__device__ __forceinline__ void cluster_arrive() { asm volatile("barrier.cluster.arrive.relaxed.aligned;" ::: "memory"); }
__device__ __forceinline__ void cluster_wait() { asm volatile("barrier.cluster.wait.aligned;" ::: "memory"); }
__device__ __forceinline__ void named_sync(int id, int n) { asm volatile("bar.sync %0, %1;" ::"r"(id), "r"(n) : "memory"); }
__device__ __forceinline__ void named_arrive(int id, int n) { asm volatile("bar.arrive %0, %1;" ::"r"(id), "r"(n) : "memory"); }

__device__ __forceinline__ void flag_add(int f) {
    asm volatile("fence.acq_rel.gpu;\nred.relaxed.gpu.global.add.u32 [%0], 1;" ::"l"(g_flags + f * 8) : "memory");
}
template <int SLEEP>
__device__ __forceinline__ void flag_wait(int f, uint32_t target) {
    asm volatile(
        "{\n.reg .pred p;\n.reg .b32 c, v;\n"
        "mov.b32 c, 0;\n"
        "FLOOP:\n"
        "ld.acquire.gpu.global.u32 v, [%0];\n"
        "sub.u32 v, v, %1;\n"
        "setp.ge.s32 p, v, 0;\n"
        "@p bra FDONE;\n"
        "nanosleep.u32 %2;\n"
        "add.u32 c, c, 1;\n"
        "setp.lt.u32 p, c, 0x400000;\n"
        "@p bra FLOOP;\n"
        "trap;\n"
        "FDONE:\n}\n" ::"l"(g_flags + f * 8), "r"(target), "n"(SLEEP) : "memory");
}
__device__ __forceinline__ uint32_t read_epoch() { return atomicAdd(g_flags + F_EPOCH * 8, 1u) / NCTA; }
__device__ __forceinline__ void fence_proxy_async() { asm volatile("fence.proxy.async;" ::: "memory"); }

__device__ __forceinline__ void wgmma_fence() { asm volatile("wgmma.fence.sync.aligned;" ::: "memory"); }
__device__ __forceinline__ void wgmma_commit() { asm volatile("wgmma.commit_group.sync.aligned;" ::: "memory"); }
template <int N>
__device__ __forceinline__ void wgmma_wait() { asm volatile("wgmma.wait_group.sync.aligned %0;" ::"n"(N) : "memory"); }
template <int N>
__device__ __forceinline__ void fence_regs(float (&d)[N]) {
#pragma unroll
    for (int i = 0; i < N; i++) asm volatile("" : "+f"(d[i])::"memory");
}
template <int N>
__device__ __forceinline__ void fence_regs(uint32_t (&d)[N]) {
#pragma unroll
    for (int i = 0; i < N; i++) asm volatile("" : "+r"(d[i])::"memory");
}

template <int TA, int TB>
__device__ __forceinline__ void wgmma_ss_n128(float (&d)[64], uint32_t alo, uint32_t blo, int scale_d) {
    asm volatile("{\n.reg .pred p;\n.reg .b64 da, db;\nsetp.ne.b32 p, %66, 0;\n"
        "mov.b64 da, {%64, %69};\nmov.b64 db, {%65, %69};\n"
        "wgmma.mma_async.sync.aligned.m64n128k16.f32.bf16.bf16 "
        "{%0, %1, %2, %3, %4, %5, %6, %7, %8, %9, %10, %11, %12, %13, %14, %15, %16, %17, %18, %19, %20, %21, %22, %23, %24, %25, %26, %27, %28, %29, %30, %31, %32, %33, %34, %35, %36, %37, %38, %39, %40, %41, %42, %43, %44, %45, %46, %47, %48, %49, %50, %51, %52, %53, %54, %55, %56, %57, %58, %59, %60, %61, %62, %63}, da, db, p, 1, 1, %67, %68;\n}\n"
        :
          "+f"(d[0]), "+f"(d[1]), "+f"(d[2]), "+f"(d[3]), "+f"(d[4]), "+f"(d[5]), "+f"(d[6]), "+f"(d[7]),
          "+f"(d[8]), "+f"(d[9]), "+f"(d[10]), "+f"(d[11]), "+f"(d[12]), "+f"(d[13]), "+f"(d[14]), "+f"(d[15]),
          "+f"(d[16]), "+f"(d[17]), "+f"(d[18]), "+f"(d[19]), "+f"(d[20]), "+f"(d[21]), "+f"(d[22]), "+f"(d[23]),
          "+f"(d[24]), "+f"(d[25]), "+f"(d[26]), "+f"(d[27]), "+f"(d[28]), "+f"(d[29]), "+f"(d[30]), "+f"(d[31]),
          "+f"(d[32]), "+f"(d[33]), "+f"(d[34]), "+f"(d[35]), "+f"(d[36]), "+f"(d[37]), "+f"(d[38]), "+f"(d[39]),
          "+f"(d[40]), "+f"(d[41]), "+f"(d[42]), "+f"(d[43]), "+f"(d[44]), "+f"(d[45]), "+f"(d[46]), "+f"(d[47]),
          "+f"(d[48]), "+f"(d[49]), "+f"(d[50]), "+f"(d[51]), "+f"(d[52]), "+f"(d[53]), "+f"(d[54]), "+f"(d[55]),
          "+f"(d[56]), "+f"(d[57]), "+f"(d[58]), "+f"(d[59]), "+f"(d[60]), "+f"(d[61]), "+f"(d[62]), "+f"(d[63])
        : "r"(alo), "r"(blo), "r"(scale_d), "n"(TA), "n"(TB), "r"(DESC_HI));
}
template <int TA, int TB>
__device__ __forceinline__ void wgmma_ss_n192(float (&d)[96], uint32_t alo, uint32_t blo, int scale_d) {
    asm volatile("{\n.reg .pred p;\n.reg .b64 da, db;\nsetp.ne.b32 p, %98, 0;\n"
        "mov.b64 da, {%96, %101};\nmov.b64 db, {%97, %101};\n"
        "wgmma.mma_async.sync.aligned.m64n192k16.f32.bf16.bf16 "
        "{%0, %1, %2, %3, %4, %5, %6, %7, %8, %9, %10, %11, %12, %13, %14, %15, %16, %17, %18, %19, %20, %21, %22, %23, %24, %25, %26, %27, %28, %29, %30, %31, %32, %33, %34, %35, %36, %37, %38, %39, %40, %41, %42, %43, %44, %45, %46, %47, %48, %49, %50, %51, %52, %53, %54, %55, %56, %57, %58, %59, %60, %61, %62, %63, %64, %65, %66, %67, %68, %69, %70, %71, %72, %73, %74, %75, %76, %77, %78, %79, %80, %81, %82, %83, %84, %85, %86, %87, %88, %89, %90, %91, %92, %93, %94, %95}, da, db, p, 1, 1, %99, %100;\n}\n"
        :
          "+f"(d[0]), "+f"(d[1]), "+f"(d[2]), "+f"(d[3]), "+f"(d[4]), "+f"(d[5]), "+f"(d[6]), "+f"(d[7]),
          "+f"(d[8]), "+f"(d[9]), "+f"(d[10]), "+f"(d[11]), "+f"(d[12]), "+f"(d[13]), "+f"(d[14]), "+f"(d[15]),
          "+f"(d[16]), "+f"(d[17]), "+f"(d[18]), "+f"(d[19]), "+f"(d[20]), "+f"(d[21]), "+f"(d[22]), "+f"(d[23]),
          "+f"(d[24]), "+f"(d[25]), "+f"(d[26]), "+f"(d[27]), "+f"(d[28]), "+f"(d[29]), "+f"(d[30]), "+f"(d[31]),
          "+f"(d[32]), "+f"(d[33]), "+f"(d[34]), "+f"(d[35]), "+f"(d[36]), "+f"(d[37]), "+f"(d[38]), "+f"(d[39]),
          "+f"(d[40]), "+f"(d[41]), "+f"(d[42]), "+f"(d[43]), "+f"(d[44]), "+f"(d[45]), "+f"(d[46]), "+f"(d[47]),
          "+f"(d[48]), "+f"(d[49]), "+f"(d[50]), "+f"(d[51]), "+f"(d[52]), "+f"(d[53]), "+f"(d[54]), "+f"(d[55]),
          "+f"(d[56]), "+f"(d[57]), "+f"(d[58]), "+f"(d[59]), "+f"(d[60]), "+f"(d[61]), "+f"(d[62]), "+f"(d[63]),
          "+f"(d[64]), "+f"(d[65]), "+f"(d[66]), "+f"(d[67]), "+f"(d[68]), "+f"(d[69]), "+f"(d[70]), "+f"(d[71]),
          "+f"(d[72]), "+f"(d[73]), "+f"(d[74]), "+f"(d[75]), "+f"(d[76]), "+f"(d[77]), "+f"(d[78]), "+f"(d[79]),
          "+f"(d[80]), "+f"(d[81]), "+f"(d[82]), "+f"(d[83]), "+f"(d[84]), "+f"(d[85]), "+f"(d[86]), "+f"(d[87]),
          "+f"(d[88]), "+f"(d[89]), "+f"(d[90]), "+f"(d[91]), "+f"(d[92]), "+f"(d[93]), "+f"(d[94]), "+f"(d[95])
        : "r"(alo), "r"(blo), "r"(scale_d), "n"(TA), "n"(TB), "r"(DESC_HI));
}
template <int TA, int TB>
__device__ __forceinline__ void wgmma_ss_n8(float (&d)[4], uint32_t alo, uint32_t blo, int scale_d) {
    asm volatile("{\n.reg .pred p;\n.reg .b64 da, db;\nsetp.ne.b32 p, %6, 0;\n"
        "mov.b64 da, {%4, %9};\nmov.b64 db, {%5, %9};\n"
        "wgmma.mma_async.sync.aligned.m64n8k16.f32.bf16.bf16 "
        "{%0, %1, %2, %3}, da, db, p, 1, 1, %7, %8;\n}\n"
        :
          "+f"(d[0]), "+f"(d[1]), "+f"(d[2]), "+f"(d[3])
        : "r"(alo), "r"(blo), "r"(scale_d), "n"(TA), "n"(TB), "r"(DESC_HI));
}
template <int TB>
__device__ __forceinline__ void wgmma_rs_n64(float (&d)[64], uint32_t a0, uint32_t a1, uint32_t a2, uint32_t a3, uint32_t blo, int scale_d) {
    asm volatile("{\n.reg .pred p;\n.reg .b64 db;\nsetp.ne.b32 p, %37, 0;\n"
        "mov.b64 db, {%36, %39};\n"
        "wgmma.mma_async.sync.aligned.m64n64k16.f32.bf16.bf16 "
        "{%0, %1, %2, %3, %4, %5, %6, %7, %8, %9, %10, %11, %12, %13, %14, %15, %16, %17, %18, %19, %20, %21, %22, %23, %24, %25, %26, %27, %28, %29, %30, %31}, {%32, %33, %34, %35}, db, p, 1, 1, %38;\n}\n"
        :
          "+f"(d[0]), "+f"(d[1]), "+f"(d[2]), "+f"(d[3]), "+f"(d[4]), "+f"(d[5]), "+f"(d[6]), "+f"(d[7]),
          "+f"(d[8]), "+f"(d[9]), "+f"(d[10]), "+f"(d[11]), "+f"(d[12]), "+f"(d[13]), "+f"(d[14]), "+f"(d[15]),
          "+f"(d[16]), "+f"(d[17]), "+f"(d[18]), "+f"(d[19]), "+f"(d[20]), "+f"(d[21]), "+f"(d[22]), "+f"(d[23]),
          "+f"(d[24]), "+f"(d[25]), "+f"(d[26]), "+f"(d[27]), "+f"(d[28]), "+f"(d[29]), "+f"(d[30]), "+f"(d[31])
        : "r"(a0), "r"(a1), "r"(a2), "r"(a3), "r"(blo), "r"(scale_d), "n"(TB), "r"(DESC_HI));
}
template <int TB>
__device__ __forceinline__ void wgmma_rs_n128(float (&d)[64], uint32_t a0, uint32_t a1, uint32_t a2, uint32_t a3, uint32_t blo, int scale_d) {
    asm volatile("{\n.reg .pred p;\n.reg .b64 db;\nsetp.ne.b32 p, %69, 0;\n"
        "mov.b64 db, {%68, %71};\n"
        "wgmma.mma_async.sync.aligned.m64n128k16.f32.bf16.bf16 "
        "{%0, %1, %2, %3, %4, %5, %6, %7, %8, %9, %10, %11, %12, %13, %14, %15, %16, %17, %18, %19, %20, %21, %22, %23, %24, %25, %26, %27, %28, %29, %30, %31, %32, %33, %34, %35, %36, %37, %38, %39, %40, %41, %42, %43, %44, %45, %46, %47, %48, %49, %50, %51, %52, %53, %54, %55, %56, %57, %58, %59, %60, %61, %62, %63}, {%64, %65, %66, %67}, db, p, 1, 1, %70;\n}\n"
        :
          "+f"(d[0]), "+f"(d[1]), "+f"(d[2]), "+f"(d[3]), "+f"(d[4]), "+f"(d[5]), "+f"(d[6]), "+f"(d[7]),
          "+f"(d[8]), "+f"(d[9]), "+f"(d[10]), "+f"(d[11]), "+f"(d[12]), "+f"(d[13]), "+f"(d[14]), "+f"(d[15]),
          "+f"(d[16]), "+f"(d[17]), "+f"(d[18]), "+f"(d[19]), "+f"(d[20]), "+f"(d[21]), "+f"(d[22]), "+f"(d[23]),
          "+f"(d[24]), "+f"(d[25]), "+f"(d[26]), "+f"(d[27]), "+f"(d[28]), "+f"(d[29]), "+f"(d[30]), "+f"(d[31]),
          "+f"(d[32]), "+f"(d[33]), "+f"(d[34]), "+f"(d[35]), "+f"(d[36]), "+f"(d[37]), "+f"(d[38]), "+f"(d[39]),
          "+f"(d[40]), "+f"(d[41]), "+f"(d[42]), "+f"(d[43]), "+f"(d[44]), "+f"(d[45]), "+f"(d[46]), "+f"(d[47]),
          "+f"(d[48]), "+f"(d[49]), "+f"(d[50]), "+f"(d[51]), "+f"(d[52]), "+f"(d[53]), "+f"(d[54]), "+f"(d[55]),
          "+f"(d[56]), "+f"(d[57]), "+f"(d[58]), "+f"(d[59]), "+f"(d[60]), "+f"(d[61]), "+f"(d[62]), "+f"(d[63])
        : "r"(a0), "r"(a1), "r"(a2), "r"(a3), "r"(blo), "r"(scale_d), "n"(TB), "r"(DESC_HI));
}
template <int TB>
__device__ __forceinline__ void wgmma_rs_n128_z(float (&d)[64], uint32_t a0, uint32_t a1, uint32_t a2, uint32_t a3, uint32_t blo) {
    asm volatile("{\n.reg .pred p;\n.reg .b64 db;\nsetp.ne.b32 p, %69, 0;\n"
        "mov.b64 db, {%68, %71};\n"
        "wgmma.mma_async.sync.aligned.m64n128k16.f32.bf16.bf16 "
        "{%0, %1, %2, %3, %4, %5, %6, %7, %8, %9, %10, %11, %12, %13, %14, %15, %16, %17, %18, %19, %20, %21, %22, %23, %24, %25, %26, %27, %28, %29, %30, %31, %32, %33, %34, %35, %36, %37, %38, %39, %40, %41, %42, %43, %44, %45, %46, %47, %48, %49, %50, %51, %52, %53, %54, %55, %56, %57, %58, %59, %60, %61, %62, %63}, {%64, %65, %66, %67}, db, p, 1, 1, %70;\n}\n"
        :
          "=f"(d[0]), "=f"(d[1]), "=f"(d[2]), "=f"(d[3]), "=f"(d[4]), "=f"(d[5]), "=f"(d[6]), "=f"(d[7]),
          "=f"(d[8]), "=f"(d[9]), "=f"(d[10]), "=f"(d[11]), "=f"(d[12]), "=f"(d[13]), "=f"(d[14]), "=f"(d[15]),
          "=f"(d[16]), "=f"(d[17]), "=f"(d[18]), "=f"(d[19]), "=f"(d[20]), "=f"(d[21]), "=f"(d[22]), "=f"(d[23]),
          "=f"(d[24]), "=f"(d[25]), "=f"(d[26]), "=f"(d[27]), "=f"(d[28]), "=f"(d[29]), "=f"(d[30]), "=f"(d[31]),
          "=f"(d[32]), "=f"(d[33]), "=f"(d[34]), "=f"(d[35]), "=f"(d[36]), "=f"(d[37]), "=f"(d[38]), "=f"(d[39]),
          "=f"(d[40]), "=f"(d[41]), "=f"(d[42]), "=f"(d[43]), "=f"(d[44]), "=f"(d[45]), "=f"(d[46]), "=f"(d[47]),
          "=f"(d[48]), "=f"(d[49]), "=f"(d[50]), "=f"(d[51]), "=f"(d[52]), "=f"(d[53]), "=f"(d[54]), "=f"(d[55]),
          "=f"(d[56]), "=f"(d[57]), "=f"(d[58]), "=f"(d[59]), "=f"(d[60]), "=f"(d[61]), "=f"(d[62]), "=f"(d[63])
        : "r"(a0), "r"(a1), "r"(a2), "r"(a3), "r"(blo), "n"(0), "n"(TB), "r"(DESC_HI));
}
template <int TA, int TB>
__device__ __forceinline__ void wgmma_ss_n128_z(float (&d)[64], uint32_t alo, uint32_t blo) {
    asm volatile("{\n.reg .pred p;\n.reg .b64 da, db;\nsetp.ne.b32 p, %66, 0;\n"
        "mov.b64 da, {%64, %69};\nmov.b64 db, {%65, %69};\n"
        "wgmma.mma_async.sync.aligned.m64n128k16.f32.bf16.bf16 "
        "{%0, %1, %2, %3, %4, %5, %6, %7, %8, %9, %10, %11, %12, %13, %14, %15, %16, %17, %18, %19, %20, %21, %22, %23, %24, %25, %26, %27, %28, %29, %30, %31, %32, %33, %34, %35, %36, %37, %38, %39, %40, %41, %42, %43, %44, %45, %46, %47, %48, %49, %50, %51, %52, %53, %54, %55, %56, %57, %58, %59, %60, %61, %62, %63}, da, db, p, 1, 1, %67, %68;\n}\n"
        :
          "=f"(d[0]), "=f"(d[1]), "=f"(d[2]), "=f"(d[3]), "=f"(d[4]), "=f"(d[5]), "=f"(d[6]), "=f"(d[7]),
          "=f"(d[8]), "=f"(d[9]), "=f"(d[10]), "=f"(d[11]), "=f"(d[12]), "=f"(d[13]), "=f"(d[14]), "=f"(d[15]),
          "=f"(d[16]), "=f"(d[17]), "=f"(d[18]), "=f"(d[19]), "=f"(d[20]), "=f"(d[21]), "=f"(d[22]), "=f"(d[23]),
          "=f"(d[24]), "=f"(d[25]), "=f"(d[26]), "=f"(d[27]), "=f"(d[28]), "=f"(d[29]), "=f"(d[30]), "=f"(d[31]),
          "=f"(d[32]), "=f"(d[33]), "=f"(d[34]), "=f"(d[35]), "=f"(d[36]), "=f"(d[37]), "=f"(d[38]), "=f"(d[39]),
          "=f"(d[40]), "=f"(d[41]), "=f"(d[42]), "=f"(d[43]), "=f"(d[44]), "=f"(d[45]), "=f"(d[46]), "=f"(d[47]),
          "=f"(d[48]), "=f"(d[49]), "=f"(d[50]), "=f"(d[51]), "=f"(d[52]), "=f"(d[53]), "=f"(d[54]), "=f"(d[55]),
          "=f"(d[56]), "=f"(d[57]), "=f"(d[58]), "=f"(d[59]), "=f"(d[60]), "=f"(d[61]), "=f"(d[62]), "=f"(d[63])
        : "r"(alo), "r"(blo), "n"(0), "n"(TA), "n"(TB), "r"(DESC_HI));
}

__device__ __forceinline__ uint32_t pack_bf16(float lo, float hi) {
    uint32_t r;
    asm("cvt.rn.bf16x2.f32 %0, %1, %2;" : "=r"(r) : "f"(hi), "f"(lo));
    return r;
}
__device__ __forceinline__ uint32_t add_bf16x2(uint32_t a, uint32_t b) {
    uint32_t r;
    asm("add.rn.bf16x2 %0, %1, %2;" : "=r"(r) : "r"(a), "r"(b));
    return r;
}
__device__ __forceinline__ float bf_lo(uint32_t v) { return __uint_as_float(v << 16); }
__device__ __forceinline__ float bf_hi(uint32_t v) { return __uint_as_float(v & 0xffff0000u); }
__device__ __forceinline__ float round_bf16(float v) { return __bfloat162float(__float2bfloat16_rn(v)); }
__device__ __forceinline__ float ex2(float x) {
    float y;
    asm("ex2.approx.ftz.f32 %0, %1;" : "=f"(y) : "f"(x));
    return y;
}
__device__ __forceinline__ float rcp(float x) {
    float y;
    asm("rcp.approx.ftz.f32 %0, %1;" : "=f"(y) : "f"(x));
    return y;
}
__device__ __forceinline__ void stg128(void* p, uint32_t a, uint32_t b, uint32_t c, uint32_t d) {
    asm volatile("st.global.v4.b32 [%0], {%1, %2, %3, %4};" ::"l"(p), "r"(a), "r"(b), "r"(c), "r"(d) : "memory");
}
__device__ __forceinline__ void stg128p(void* p, uint32_t a, uint32_t b, uint32_t c, uint32_t d, uint64_t pol) {
    asm volatile("st.global.L2::cache_hint.v4.b32 [%0], {%1, %2, %3, %4}, %5;" ::"l"(p), "r"(a), "r"(b), "r"(c), "r"(d), "l"(pol) : "memory");
}
__device__ __forceinline__ uint64_t policy_sel(bool first) {
    uint64_t p;
    asm("createpolicy.fractional.L2::evict_normal.b64 %0, 1.0;" : "=l"(p));
    return first ? policy_evict_first() : p;
}
__device__ __forceinline__ int perm_row(int t) { return (t & ~255) | (((0x78 >> (((t >> 6) & 3) * 2)) & 3) << 6) | (t & 63); }
__device__ __forceinline__ int unperm_row(int t) { return (t & ~255) | (((0x9C >> (((t >> 6) & 3) * 2)) & 3) << 6) | (t & 63); }

#define PROF(i)
#define PROFG(i)
#define PROFDUMP()
#define TR(i)
#define BP(r, i)
#define LP(i)

template <int I>
__device__ __forceinline__ void store_chunk(const float (&a)[64], __nv_bfloat16* row0, __nv_bfloat16* row1, float s0, float s1) {
    stg128(row0 + 32 * I, pack_bf16(a[16 * I + 0] * s0, a[16 * I + 1] * s0), pack_bf16(a[16 * I + 4] * s0, a[16 * I + 5] * s0),
           pack_bf16(a[16 * I + 8] * s0, a[16 * I + 9] * s0), pack_bf16(a[16 * I + 12] * s0, a[16 * I + 13] * s0));
    stg128(row1 + 32 * I, pack_bf16(a[16 * I + 2] * s1, a[16 * I + 3] * s1), pack_bf16(a[16 * I + 6] * s1, a[16 * I + 7] * s1),
           pack_bf16(a[16 * I + 10] * s1, a[16 * I + 11] * s1), pack_bf16(a[16 * I + 14] * s1, a[16 * I + 15] * s1));
}
template <int I>
struct IntT { static constexpr int value = I; };
template <class F>
__device__ __forceinline__ void for4(F f) { f(IntT<0>{}); f(IntT<1>{}); f(IntT<2>{}); f(IntT<3>{}); }

struct Prod {
    uint32_t smem, bars;
    uint32_t bo, par;
    uint32_t dst, fb;
    __device__ __forceinline__ void acquire(uint32_t o, uint32_t parity, uint32_t bytes) {
        mbar_wait(bars + BAR_EMPTY + o, parity);
        fb = bars + BAR_FULL + o;
        dst = smem + o * (SLOT / 8);
        w_expect_tx(fb, bytes);
    }
    __device__ __forceinline__ void next(uint32_t bytes) {
        acquire(bo, par, bytes);
        const bool wrap = bo == (NSLOT - 1) * 8;
        bo = wrap ? 0u : bo + 8;
        par ^= wrap ? 1u : 0u;
    }
};

__device__ __forceinline__ int item_p(int ca, int rd) {
    const int v = (rd & 1) ? (ca + 4) & 7 : ca;
    return (rd & 2) ? 7 - v : v;
}
__device__ __forceinline__ int n_items(int ca, int cb) { return cb == 8 ? 8 : ((ca & 3) == 3) ? 3 : 4; }
__device__ __forceinline__ int item_rd(int ca, int cb, int j) { return cb == 8 ? 2 + ca : (ca == 7 && j == 2) ? 3 : j; }
__device__ __forceinline__ int item_h(int cb, int rd, int j) { return 8 * rd + (cb == 8 ? j : cb); }
__device__ __forceinline__ int item_q(int ca, int cb, int rd) { return cb == 8 ? 0 : item_p(ca, rd); }
__device__ __forceinline__ int out_p(int ca, int cb) { return (cb + 2 * (ca & 3)) & 7; }
__device__ __forceinline__ int kv_round(int i) { return (0x1023 >> (4 * i)) & 3; }
__device__ __forceinline__ int slot_a(int i) { return (0x5310 >> (4 * i)) & 15; }
__device__ __forceinline__ int slot_w(int m) { return (0x264 >> (4 * m)) & 15; }

__device__ __forceinline__ void producer(const Params& P, uint32_t smem, uint32_t bars, int ca, int cb, int rank) {
    Prod pr{smem, bars, 0u, cb == 8 ? 1u : 0u, 0u, 0u};
    if (cb < 8) {
        int m = 0;
        uint32_t lap = 1;
#pragma unroll 1
        for (int u = 0; u < 32; u++) {
            if (u >= 3) {
                const int v = (u == 3) ? 3 + ca : u + 7;
                if (v < 32 && (u == 3 || (v & 7) == ca)) w_tma_prefetch((v & 4) ? &P.wuv : &P.wuk, (cb + 8 * kv_round(v >> 3)) * 128 + rank * 64, (v & 3) * 128);
                if (u == 24) {
                    w_tma_prefetch(&P.wq, cb * 128 + rank * 64, ca * 64);
                    if (ca < 2) w_tma_prefetch(&P.wq, cb * 128 + rank * 64, (ca + 8) * 64);
                }
            }
            if (u > 0) pr.acquire(slot_w(m) * 8, lap ^ (m >> 1), SLOT);
            lap ^= m >> 1;
            m = (m == 2) ? 0 : m + 1;
            TR(1 + u);
            if (u > 0) w_tma_load_mc(pr.dst + rank * 16384, (u & 4) ? &P.wuv : &P.wuk, (cb + 8 * kv_round(u >> 3)) * 128 + rank * 64, (u & 3) * 128, pr.fb);
            if (u < 3) {
                pr.acquire(slot_a(u + 1) * 8, 1, SLOT);
                w_tma_load(pr.dst, &P.ckv, u * 128 + 128, (2 * ca + rank) * 128, pr.fb);
                w_tma_load(pr.dst + 16384, &P.ckv, u * 128 + 192, (2 * ca + rank) * 128, pr.fb);
            }
        }
    }
    PROF(1);
    mbar_wait_sleep(bars + BAR_DEP, 0);
#pragma unroll 1
    for (int j = 0, pfs = 1; j < n_items(ca, cb); j++) {
        const int rd = item_rd(ca, cb, j), h = item_h(cb, rd, j), p = item_q(ca, cb, rd);
#pragma unroll 1
        for (int ks = 0; ks < 10; ks++) {
            pr.next(SLOT);
            w_tma_load_mc(pr.dst + 16384 + rank * 8192, &P.wq, h * 128 + rank * 64, ks * 64, pr.fb);
            w_tma_load(pr.dst, &P.xn, ks * 64, 256 * p + 128 * rank, pr.fb);
            if (cb == 8 && j < 7) w_tma_prefetch(&P.wq, (h + 1) * 128 + rank * 64, ks * 64);
        }
        PROF(8 + rd * 4);
        mbar_wait(bars + BAR_DEP + (1 + (cb == 8 ? j : rd)) * 8, 0);
        const int last = 4 * p + 3, top = h * 32 + last;
#pragma unroll 1
        for (int i = 0; i <= last; i++) {
            const int t = (i == 0) ? top - 1 : (i == last) ? h * 32 + 1 : (i & 1) ? top - 2 - i : top + 2 - i;
            pr.next(SLOT);
            const bool lastrd = (cb == 8 || rd == 3) ? false : (rd == 0) ? ca >= 6 : (rd == 1) ? (ca & 3) >= 2 : (ca == 3 || (ca < 3 && (t & 31) >= 4 * p));
            if (lastrd) w_tma_load_mc_last(pr.dst + rank * 16384, &P.kv, rank * 64, t * 128, pr.fb);
            else w_tma_load_mc(pr.dst + rank * 16384, &P.kv, rank * 64, t * 128, pr.fb);
            if (i == 2 && cb < 8) {
                const int upto = (j == n_items(ca, cb) - 1) ? 4 : item_rd(ca, cb, j + 1);
#pragma unroll 1
                for (; pfs <= upto; pfs++) {
                    if (pfs < 4) {
                        w_tma_prefetch(&P.wq, (8 * pfs + cb) * 128 + rank * 64, ca * 64);
                        if (ca < 2) w_tma_prefetch(&P.wq, (8 * pfs + cb) * 128 + rank * 64, (ca + 8) * 64);
                    } else {
#pragma unroll 1
                        for (int k = 0; k < 10; k++)
                            w_tma_prefetch(&P.wo, 320 * (ca >> 2) + 64 * (k >= 5 ? k - 5 : k), (cb * 4 + (ca & 3) + (k >= 5 ? 32 : 0)) * 64 + rank * 32);
                    }
                }
            }
        }
        PROF(9 + rd * 4);
    }
    if (cb < 8) {
        const int n0 = 320 * (ca >> 2), op = out_p(ca, cb);
        uint32_t* pool = g_flags + (F_POOL + op * 2 + (ca >> 2)) * 8;
        uint32_t nxt = 0;
        auto draw = [&]() {
            if (rank == 0) asm volatile(ELECT "atom.relaxed.gpu.global.add.u32 %0, [%1], 1;\n}\n" : "+r"(nxt) : "l"(pool) : "memory");
        };
        int fixed = -1;
#pragma unroll 1
        for (int i = -2; fixed < 4; i++) {
            int st = (ca & 3) + 4 * (i + 2);
            if (i == -1) draw();
            if (i >= 0 && fixed < 0) {
                const uint32_t mb = bars + BAR_MAIL + (i & 7) * 8, md = bars + MAIL_OFF + (i & 7) * 4;
                if (rank == 0) {
                    st = __reduce_add_sync(0xffffffffu, nxt);
                    asm volatile(ELECT "st.async.shared::cluster.mbarrier::complete_tx::bytes.b32 [%0], %1, [%2];\n}\n" ::"r"(mapa(md, 1)), "r"(st), "r"(mapa(mb, 1)) : "memory");
                    if (st < 48) draw();
                } else {
                    w_expect_tx(mb, 4);
                    mbar_wait(mb, (i >> 3) & 1);
                    asm volatile("ld.shared.u32 %0, [%1];" : "=r"(st) : "r"(md) : "memory");
                    st = __reduce_or_sync(0xffffffffu, st);
                }
                if (st >= 48) fixed = 0;
            }
            if (fixed >= 0) { st = 48 + (ca & 3) + 4 * fixed; fixed++; }
            const int krow = st * 64 + rank * 32;
            mbar_wait(bars + BAR_EMPTY + pr.bo, pr.par);
            asm volatile("st.shared.u32 [%0], %1;" ::"r"(bars + CTL_OFF + pr.bo), "r"((int)(fixed == 1)) : "memory");
            __syncwarp();
            pr.next(SLOT);
            w_tma_load_mc(pr.dst + 16384 + rank * 8192, &P.wo, n0, krow, pr.fb);
            w_tma_load_mc(pr.dst + 16384 + rank * 8192 + 4096, &P.wo, n0 + 64, krow, pr.fb);
            mbar_wait(bars + BAR_DEP + (5 + (st >> 4)) * 8, 0);
            w_tma_load(pr.dst, &P.ctx, (st & 1) * 64, (st >> 1) * SEQ + 256 * op + 128 * rank, pr.fb);
            pr.next(24576);
#pragma unroll
            for (int c = 0; c < 3; c++) w_tma_load_mc(pr.dst + rank * 12288 + c * 4096, &P.wo, n0 + 128 + 64 * c, krow, pr.fb);
        }
    }
}

struct Slot {
    uint32_t bo, dl, par;
};
struct Cons {
    uint32_t bars, rel;
    uint32_t dl0;
    uint32_t lane;
    Slot cur;
    __device__ __forceinline__ Slot slot(int s, uint32_t par) const { return Slot{(uint32_t)s * 8, dl0 + (uint32_t)s * (SLOT >> 4), par}; }
    __device__ __forceinline__ void wait(const Slot& s) const { mbar_wait(bars + BAR_FULL + s.bo, s.par); }
    __device__ __forceinline__ uint32_t peek() const { return mbar_peek(bars + BAR_FULL + cur.bo, cur.par); }
    __device__ __forceinline__ void wait(const Slot& s, uint32_t ok) const { mbar_wait_unless(ok, bars + BAR_FULL + s.bo, s.par); }
    __device__ __forceinline__ void release(uint32_t bo) const {
        asm volatile("{\n.reg .pred p;\nsetp.lt.u32 p, %1, 2;\n@p mbarrier.arrive.shared::cluster.b64 _, [%0];\n}\n" ::"r"(rel + bo), "r"(lane) : "memory");
    }
    __device__ __forceinline__ Slot next() {
        const Slot s = cur;
        const bool wrap = s.bo == (NSLOT - 1) * 8;
        cur.bo = wrap ? 0u : s.bo + 8;
        cur.dl = wrap ? dl0 : s.dl + (SLOT >> 4);
        cur.par = s.par ^ (wrap ? 1u : 0u);
        return s;
    }
};
__host__ __device__ constexpr uint32_t lbo(uint32_t bytes) { return (bytes >> 4) << 16; }

__device__ __forceinline__ float div640(float x) {
    const float q = x * (1.0f / DM);
    return fmaf(fmaf(-q, (float)DM, x), 1.0f / DM, q);
}
__device__ __forceinline__ float sqrt_approx(float x) {
    float y;
    asm("sqrt.approx.ftz.f32 %0, %1;" : "=f"(y) : "f"(x));
    return y;
}
struct LayerNorm {
    uint4 xv[5], wv[5];
    float mean, inv, r;
    uint32_t nmb;
    __nv_bfloat16 *pn, *po;
    static __device__ __forceinline__ float half_sum(float v) {
#pragma unroll
        for (int o = 8; o > 0; o >>= 1) v += __shfl_xor_sync(0xffffffffu, v, o);
        return v;
    }
    __device__ __forceinline__ void load(const __nv_bfloat16* x, const __nv_bfloat16* wr, __nv_bfloat16* out, int t, int l) {
        pn = g_xn + perm_row(t) * DM + 8 * l;
        po = out + t * DM + 8 * l;
        asm volatile("" : "+l"(pn), "+l"(po));
#pragma unroll
        for (int i = 0; i < 5; i++) {
            xv[i] = ldg_stream(reinterpret_cast<const uint4*>(x + t * DM) + l + 16 * i);
            wv[i] = __ldg(reinterpret_cast<const uint4*>(wr) + l + 16 * i);
        }
    }
    __device__ __forceinline__ void stat1() {
        float a[4] = {0.f, 0.f, 0.f, 0.f};
#pragma unroll
        for (int i = 0; i < 20; i++) { const uint32_t u = (&xv[i >> 2].x)[i & 3]; a[i & 3] += bf_lo(u) + bf_hi(u); }
        mean = div640(half_sum((a[0] + a[1]) + (a[2] + a[3])));
        r = 0.f;
    }
    template <int H>
    __device__ __forceinline__ void stat2() {
        float a[4] = {r, 0.f, 0.f, 0.f};
#pragma unroll
        for (int i = H ? 12 : 0; i < (H ? 20 : 12); i++) {
            uint32_t u = (&xv[i >> 2].x)[i & 3];
            asm volatile("" : "+r"(u));
            const float d0 = bf_lo(u) - mean, d1 = bf_hi(u) - mean;
            a[i & 3] = fmaf(d0, d0, fmaf(d1, d1, a[i & 3]));
        }
        r = (a[0] + a[1]) + (a[2] + a[3]);
        if (H) {
            inv = rcp(round_bf16(sqrt_approx(round_bf16(round_bf16(div640(half_sum(r))) + 1e-5f))));
            r = 0.f;
            nmb = pack_bf16(-mean, -mean);
        }
    }
    template <int I>
    __device__ __forceinline__ void piece(int t, int l) {
        uint32_t o[4], z[4];
        float a[4];
#pragma unroll
        for (int j = 0; j < 4; j++) {
            const uint32_t u = (&xv[I].x)[j], w = (&wv[I].x)[j];
            const uint32_t d = add_bf16x2(u, nmb);
            o[j] = pack_bf16(bf_lo(d) * inv, bf_hi(d) * inv);
            z[j] = add_bf16x2(u, o[j]);
            a[j] = fmaf(bf_hi(o[j]), bf_hi(w), bf_lo(o[j]) * bf_lo(w));
        }
        r += (a[0] + a[1]) + (a[2] + a[3]);
        stg128(pn + 128 * I, o[0], o[1], o[2], o[3]);
        stg128p(po + 128 * I, z[0], z[1], z[2], z[3], policy_evict_first());
        if (I == 4) {
            r = half_sum(r);
            if (l == 0) g_r[t] = round_bf16(r);
        }
    }
};

constexpr float SM_SCALE = 0.08838834764831845f * 1.4426950408889634f;

template <int J0, int J1>
__device__ __forceinline__ void exp_part(float (&s)[64], float n0, float n1, float& r0, float& r1) {
    float a1 = 0.f, b1 = 0.f;
#pragma unroll
    for (int j = J0; j < J1; j++) {
        s[4 * j + 0] = ex2(fmaf(s[4 * j + 0], SM_SCALE, n0));
        s[4 * j + 1] = ex2(fmaf(s[4 * j + 1], SM_SCALE, n0));
        s[4 * j + 2] = ex2(fmaf(s[4 * j + 2], SM_SCALE, n1));
        s[4 * j + 3] = ex2(fmaf(s[4 * j + 3], SM_SCALE, n1));
        r0 += s[4 * j + 0]; r1 += s[4 * j + 2];
        if (j == J0) { a1 = s[4 * j + 1]; b1 = s[4 * j + 3]; } else { a1 += s[4 * j + 1]; b1 += s[4 * j + 3]; }
    }
    r0 += a1;
    r1 += b1;
}
__device__ __forceinline__ void sched_barrier(float x, float y, uint32_t scratch) {
    asm volatile("{\n.reg .pred p;\nsetp.lt.f32 p, %0, 0f00000000;\n@p st.shared.f32 [%2], %1;\n}\n" ::"f"(x), "f"(y), "r"(scratch) : "memory");
}
__device__ __forceinline__ void pack_tile(const float (&s)[64], uint32_t (&p)[32]) {
#pragma unroll
    for (int i = 0; i < 32; i++) p[i] = pack_bf16(s[2 * i], s[2 * i + 1]);
}
template <bool ZERO>
__device__ __forceinline__ void gemm_rs(float (&d)[64], const uint32_t (&a)[32], uint32_t dl, int acc = 1) {
    const uint32_t b = dl + lbo(16384);
    if (ZERO) wgmma_rs_n128_z<1>(d, a[0], a[1], a[2], a[3], b);
#pragma unroll
    for (int k = ZERO ? 1 : 0; k < 8; k++) wgmma_rs_n128<1>(d, a[4 * k], a[4 * k + 1], a[4 * k + 2], a[4 * k + 3], b + k * 128, k ? 1 : acc);
}
__device__ __forceinline__ void gemm_pv(float (&d)[64], const uint32_t (&a)[32], uint32_t dl, int acc, int full) {
    const uint32_t b = dl + lbo(16384);
    wgmma_rs_n128<1>(d, a[0], a[1], a[2], a[3], b, acc);
    wgmma_commit();
    if (full) {
        wgmma_fence();
#pragma unroll
        for (int k = 4; k < 8; k++) wgmma_rs_n128<1>(d, a[4 * k], a[4 * k + 1], a[4 * k + 2], a[4 * k + 3], b + k * 128, 1);
        wgmma_commit();
    }
    wgmma_fence();
#pragma unroll
    for (int k = 1; k < 4; k++) wgmma_rs_n128<1>(d, a[4 * k], a[4 * k + 1], a[4 * k + 2], a[4 * k + 3], b + k * 128, 1);
}
template <int ZERO>
__device__ __forceinline__ void gemm_q(float (&d)[64], uint32_t dl, int role) {
    const uint32_t a = dl + role * 512 + lbo(16), b = dl + 1024 + lbo(8192);
    if (ZERO) wgmma_ss_n128_z<0, 1>(d, a, b);
#pragma unroll
    for (int k = ZERO ? 1 : 0; k < 4; k++) wgmma_ss_n128<0, 1>(d, a + k * 2, b + k * 128, 1);
}
template <bool KT, bool ZERO, int K0, int K1>
__device__ __forceinline__ void gemm_kv(float (&d)[64], uint32_t ckv, uint32_t wt, int wg) {
    if (KT) {
        const uint32_t a = wt + wg * 1024 + lbo(16), b = ckv + lbo(16);
        if (ZERO) wgmma_ss_n128_z<1, 0>(d, a, b);
#pragma unroll
        for (int k = ZERO ? 1 : K0; k < K1; k++) wgmma_ss_n128<1, 0>(d, a + k * 128, b + (k >> 2) * 1024 + (k & 3) * 2, 1);
    } else {
        const uint32_t a = ckv + wg * 512 + lbo(16), b = wt + lbo(16384);
        if (ZERO) wgmma_ss_n128_z<0, 1>(d, a, b);
#pragma unroll
        for (int k = ZERO ? 1 : K0; k < K1; k++) wgmma_ss_n128<0, 1>(d, a + (k >> 2) * 1024 + (k & 3) * 2, b + k * 128, 1);
    }
}
__device__ __forceinline__ void mma16816(float& d0, float& d1, float& d2, float& d3, uint32_t a0, uint32_t a1, uint32_t a2, uint32_t a3, uint32_t b0, uint32_t b1) {
    asm volatile("mma.sync.aligned.m16n8k16.row.col.f32.bf16.bf16.f32 {%0,%1,%2,%3}, {%4,%5,%6,%7}, {%8,%9}, {%0,%1,%2,%3};"
                 : "+f"(d0), "+f"(d1), "+f"(d2), "+f"(d3) : "r"(a0), "r"(a1), "r"(a2), "r"(a3), "r"(b0), "r"(b1));
}
__device__ __forceinline__ uint32_t ld_pair(const __nv_bfloat16* p) {
    const unsigned short* u = reinterpret_cast<const unsigned short*>(p);
    return (uint32_t)__ldcg(u) | ((uint32_t)__ldcg(u + 128) << 16);
}
__device__ __forceinline__ void attention_exact(float (&o)[64], const uint32_t (&qf)[32], float& l0, float& l1, int h, int nblk, int rr, int lane) {
    const int q = lane & 3, lr = lane >> 2;
    float m0 = -INFINITY, m1 = -INFINITY;
    l0 = 0.f; l1 = 0.f;
#pragma unroll 1
    for (int cidx = 0; cidx < nblk * 8; cidx++) {
        const int kc = cidx & 7;
        const __nv_bfloat16* kt = g_kv + (size_t)((h * 16 + (cidx >> 3)) * 2) * 16384;
        float sc[8];
#pragma unroll
        for (int i = 0; i < 8; i++) sc[i] = 0.f;
#pragma unroll
        for (int kk = 0; kk < 8; kk++)
#pragma unroll
            for (int nt = 0; nt < 2; nt++) {
                const __nv_bfloat16* b = kt + (16 * kk + 2 * q) * 128 + 16 * kc + 8 * nt + lr;
                mma16816(sc[4 * nt], sc[4 * nt + 1], sc[4 * nt + 2], sc[4 * nt + 3], qf[4 * kk], qf[4 * kk + 1], qf[4 * kk + 2], qf[4 * kk + 3],
                         ld_pair(b), ld_pair(b + 8 * 128));
            }
        const int lim = rr + ((nblk - 1) - (cidx >> 3)) * 128 - 32 * (kc >> 1) - 4 * (kc & 1);
#pragma unroll
        for (int i = 0; i < 8; i++)
            if (2 * (i >> 2) + (i & 1) > lim + 4 * (i & 2)) sc[i] = -INFINITY;
        float x0 = fmaxf(fmaxf(sc[0], sc[1]), fmaxf(sc[4], sc[5])), x1 = fmaxf(fmaxf(sc[2], sc[3]), fmaxf(sc[6], sc[7]));
        x0 = fmaxf(x0, __shfl_xor_sync(0xffffffffu, x0, 1)); x1 = fmaxf(x1, __shfl_xor_sync(0xffffffffu, x1, 1));
        x0 = fmaxf(x0, __shfl_xor_sync(0xffffffffu, x0, 2)); x1 = fmaxf(x1, __shfl_xor_sync(0xffffffffu, x1, 2));
        x0 = fmaxf(x0, m0); x1 = fmaxf(x1, m1);
        const float a0 = ex2((m0 - x0) * SM_SCALE), a1 = ex2((m1 - x1) * SM_SCALE);
        m0 = x0; m1 = x1;
#pragma unroll
        for (int i = 0; i < 8; i++) sc[i] = ex2((sc[i] - ((i & 2) ? m1 : m0)) * SM_SCALE);
        l0 = l0 * a0 + (sc[0] + sc[1]) + (sc[4] + sc[5]);
        l1 = l1 * a1 + (sc[2] + sc[3]) + (sc[6] + sc[7]);
        const uint32_t p0 = pack_bf16(sc[0], sc[1]), p1 = pack_bf16(sc[2], sc[3]), p2 = pack_bf16(sc[4], sc[5]), p3 = pack_bf16(sc[6], sc[7]);
        const __nv_bfloat16* vb = kt + 16384 + (16 * kc + 2 * q) * 128 + lr;
#pragma unroll
        for (int nt = 0; nt < 16; nt++) {
            o[4 * nt] *= a0; o[4 * nt + 1] *= a0; o[4 * nt + 2] *= a1; o[4 * nt + 3] *= a1;
            mma16816(o[4 * nt], o[4 * nt + 1], o[4 * nt + 2], o[4 * nt + 3], p0, p1, p2, p3, ld_pair(vb + 8 * nt), ld_pair(vb + 8 * nt + 8 * 128));
        }
    }
}

__device__ __forceinline__ void signal(uint32_t bars, int wg, int e, int lane) {
    __syncwarp();
    asm volatile("{\n.reg .pred p;\nsetp.eq.u32 p, %1, 0;\n@p mbarrier.arrive.shared::cta.b64 _, [%0];\n}\n" ::"r"(bars + BAR_SIG + (wg * 9 + e) * 8), "r"(lane) : "memory");
}

__device__ __forceinline__ void mod_ffn(const Params& P, uint32_t smem, int mc, int wg);

__device__ __forceinline__ void consumer(const Params& P, uint32_t smem, uint32_t bars, int ca, int cb, int rank, int wg) {
    const int lane = threadIdx.x & 31, w = (threadIdx.x >> 5) & 3, q = lane & 3, lr = lane >> 2;
    PROF(7);
    cluster_wait();
    Cons c{bars, mapa(bars + BAR_EMPTY, lane & 1), (smem & 0x3FFFF) >> 4, (uint32_t)lane, Slot{0u, (smem & 0x3FFFF) >> 4, cb == 8 ? 0u : 1u}};
    PROFG(180);
    PROF(1);
    float o[64], s[64];
    uint32_t pend;
    __nv_bfloat16* ep_ptr;
    int ep_step;
    if (cb == 8) {
        pend = 0;
        ep_ptr = g_ctx + (size_t)(item_h(cb, 2 + ca, 0) * SEQ + 128 * rank + 64 * wg + 16 * w + lr) * HD + 8 * q;
        ep_step = 8 * HD;
    } else {
        const int ln_t = blockIdx.x * 16 + wg * 8 + w * 2 + (lane >> 4);
        const int krow = 64 * wg + 16 * w + lr;
        const int vrow = 64 * wg + 32 * (w >> 1) + 8 * (lr >> 1) + 4 * (w & 1) + (lr & 1);
        ep_step = 2 * 128;
        int m = 0;
        uint32_t lap = 0;
        LayerNorm ln;
        auto step = [&](auto kt, auto kc, float (&d)[64], int hh) {
            const Slot sa = c.slot(slot_a(kc.value), 0), sw = c.slot(slot_w(m), lap ^ (m >> 1));
            lap ^= m >> 1;
            m = (m == 2) ? 0 : m + 1;
            TR(1 + (hh * 8 + (kt.value ? 0 : 4) + kc.value) * 2);
            if (kt.value && hh == 0) c.wait(sa);
            c.wait(sw);
            TR(2 + (hh * 8 + (kt.value ? 0 : 4) + kc.value) * 2);
            wgmma_fence();
            gemm_kv<kt.value, kc.value == 0, 0, KVSPLIT>(d, sa.dl, sw.dl, wg);
            wgmma_commit();
            wgmma_wait<1>();
            if (!(kt.value && kc.value == 0 && hh == 0)) c.release(pend);
            if (!kt.value && kc.value > 0 && hh == 3) c.release(slot_a(kc.value - 1) * 8);
            pend = sw.bo;
            wgmma_fence();
            gemm_kv<kt.value, false, KVSPLIT, 8>(d, sa.dl, sw.dl, wg);
            wgmma_commit();
        };
#pragma unroll 1
        for (int hh = 0; hh < 4; hh++) {
            __nv_bfloat16* base = g_kv + (size_t)(((cb + 8 * kv_round(hh)) * 16 + 2 * ca + rank) * 2) * 16384 + 8 * q;
            auto ln_stage = [&](auto pos) {
                constexpr int j = (pos.value + 8 - LNOFF % 8) % 8;
                if (hh == wg + (LNOFF + j) / 8) {
                    if (j == 0) ln.stat1();
                    if (j == 1) ln.template stat2<0>();
                    if (j == 2) ln.template stat2<1>();
                    if constexpr (j >= 3) ln.template piece<j - 3>(ln_t, lane & 15);
                    if (j == 7) signal(bars, wg, 0, lane);
                }
                if (pos.value == (LNOFF - LNLEAD) % 8 && hh == wg + (LNOFF - LNLEAD) / 8) ln.load(P.x, P.wr, P.out, ln_t, lane & 15);
            };
            for4([&](auto kc) {
                step(TrueT{}, kc, s, hh);
                if (hh > 0) {
                    if (kc.value == 0) fence_regs(o);
                    store_chunk<kc.value>(o, ep_ptr, ep_ptr + ep_step, 1.f, 1.f);
                    if (kc.value == 3) signal(bars, wg, hh, lane);
                }
                ln_stage(kc);
            });
            for4([&](auto kc) {
                step(FalseT{}, kc, o, hh);
                if (kc.value == 0) fence_regs(s);
                store_chunk<kc.value>(s, base + krow * 128, base + (krow + 8) * 128, 1.f, 1.f);
                ln_stage(IntT<kc.value + 4>{});
            });
            PROF(24 + hh);
            if (hh == 1) PROFG(181);
            ep_ptr = base + 16384 + vrow * 128;
        }
    }
    PROFG(182);
    PROF(2);
    uint32_t pf[32];
    {
        uint32_t qf[32];
        float l0 = 0.25f, l1 = 0.25f;
        const int bar_me = 2 + wg, bar_other = 3 - wg;
#pragma unroll 1
        for (int j = 0; j < n_items(ca, cb); j++) {
            const int rd = item_rd(ca, cb, j), h = item_h(cb, rd, j), p = item_q(ca, cb, rd);
            const int role = wg ^ (j & 1);
            const int nrest = 2 * p + role;
            Slot kfirst;
            const int lim = 64 * (role ^ rank) + 16 * w + lr - 8 * q;
            const uint64_t pol = policy_sel(j == 1 || j == 2);
            {
                auto qstep = [&](auto zero, int ks) {
                    const Slot sl = c.next();
                    c.wait(sl);
                    BP(2, 5 + 3 * ks);
                    wgmma_fence();
                    gemm_q<zero.value>(s, sl.dl, role);
                    wgmma_commit();
                    wgmma_wait<1>();
                    if (!zero.value || j > 0 || cb < 8) c.release(pend);
                    pend = sl.bo;
                };
                qstep(TrueT{}, 0);
                if (j == 0 && cb < 8) c.release(slot_a(3) * 8);
                fence_regs(o);
                l0 += __shfl_xor_sync(0xffffffffu, l0, 1); l1 += __shfl_xor_sync(0xffffffffu, l1, 1);
                l0 += __shfl_xor_sync(0xffffffffu, l0, 2); l1 += __shfl_xor_sync(0xffffffffu, l1, 2);
                l0 = rcp(l0); l1 = rcp(l1);
                for4([&](auto i) {
                    constexpr int B = 16 * i.value;
#pragma unroll
                    for (int r = 0; r < 2; r++) {
                        if (1 + 2 * i.value + r == 7 && !(role | rank)) named_sync(bar_me, 256);
                        qstep(FalseT{}, 1 + 2 * i.value + r);
                        const float f = r ? l1 : l0;
                        stg128p(ep_ptr + r * ep_step + 2 * B, pack_bf16(o[B + 2 * r] * f, o[B + 2 * r + 1] * f), pack_bf16(o[B + 2 * r + 4] * f, o[B + 2 * r + 5] * f),
                                pack_bf16(o[B + 2 * r + 8] * f, o[B + 2 * r + 9] * f), pack_bf16(o[B + 2 * r + 12] * f, o[B + 2 * r + 13] * f), pol);
#pragma unroll
                        for (int k = 0; k < 8; k++) {
                            float& v = o[B + 4 * (k >> 1) + 2 * r + (k & 1)];
                            v = (2 * B + k > lim + 8 * r) ? -1e30f : 0.f;
                            asm volatile("" : "+f"(v));
                        }
                    }
                });
                signal(bars, wg, (cb == 8 ? 0 : 4) + j, lane);
                PROF(11 + rd * 4);
                qstep(FalseT{}, 9);
                if (!role) { const Slot sl = c.next(); c.wait(sl); c.release(sl.bo); }
                kfirst = c.next();
                c.wait(kfirst);
                wgmma_wait<0>();
                BP(2, 34);
                c.release(pend);
                fence_regs(s);
                pack_tile(s, qf);
            }
            Slot vskip = c.cur;
            if (!role) vskip = c.next();
            PROF(8 + rd * 4);
            if (cb == 8) PROF(40 + 3 * j);
            fence_regs(qf); fence_regs(o);
            if (!role && rank) named_sync(bar_me, 256);
            BP(2, 36);
            auto first_qk = [&](auto half) {
                wgmma_fence();
#pragma unroll
                for (int k = 0; k < 8; k++) {
                    if (half.value) wgmma_rs_n64<1>(o, qf[4 * k], qf[4 * k + 1], qf[4 * k + 2], qf[4 * k + 3], kfirst.dl + lbo(16384) + k * 128, 1);
                    else wgmma_rs_n128<1>(o, qf[4 * k], qf[4 * k + 1], qf[4 * k + 2], qf[4 * k + 3], kfirst.dl + lbo(16384) + k * 128, 1);
                }
                wgmma_commit();
                named_arrive(bar_other, 256);
                if (!role) { c.wait(vskip); c.release(vskip.bo); }
                wgmma_wait<0>();
            };
            if (role == rank) first_qk(TrueT{});
            else first_qk(FalseT{});
            BP(2, 38);
            fence_regs(o);
            c.release(kfirst.bo);
            uint32_t ready = c.peek();
            float n0 = fmaxf(fmaxf(fmaxf(o[0], o[1]), fmaxf(o[4], o[5])), fmaxf(fmaxf(o[8], o[9]), fmaxf(o[12], o[13])));
            float n1 = fmaxf(fmaxf(fmaxf(o[2], o[3]), fmaxf(o[6], o[7])), fmaxf(fmaxf(o[10], o[11]), fmaxf(o[14], o[15])));
            n0 = __shfl_sync(0xffffffffu, n0, lane & 28); n1 = __shfl_sync(0xffffffffu, n1, lane & 28);
            n0 *= -SM_SCALE; n1 *= -SM_SCALE;
            l0 = 0.f; l1 = 0.f;
#pragma unroll
            for (int i = 0; i < 64; i++) s[i] = o[i];
            exp_part<0, 8>(s, n0, n1, l0, l1);
#pragma unroll
            for (int i = 0; i < 16; i++) pf[i] = pack_bf16(s[2 * i], s[2 * i + 1]);
            if (role != rank) {
                exp_part<8, 16>(s, n0, n1, l0, l1);
#pragma unroll
                for (int i = 16; i < 32; i++) pf[i] = pack_bf16(s[2 * i], s[2 * i + 1]);
            } else {
#pragma unroll
                for (int i = 16; i < 32; i++) pf[i] = 0u;
            }
            PROF(9 + rd * 4);
            if (cb == 8) PROF(41 + 3 * j);
#pragma unroll 1
            for (int it = 0; it < nrest; it++) {
                const Slot sk = c.next(), sv = c.next();
                LP(0);
                c.wait(sk, ready);
                fence_regs(o); fence_regs(pf);
                LP(1);
                named_sync(bar_me, 256);
                LP(2);
                if (it < 3) BP(2, 42 + 4 * it);
                if (it >= nrest - 2) BP(1, 62 + 4 * (it - nrest + 2));
                wgmma_fence();
                gemm_rs<true>(s, qf, sk.dl);
                wgmma_commit();
                c.wait(sv);
                wgmma_fence();
                gemm_pv(o, pf, sv.dl, it, it | (role ^ rank));
                wgmma_commit();
                named_arrive(bar_other, 256);
                LP(3);
                wgmma_wait<2>();
                LP(4);
                c.release(sk.bo);
                fence_regs(s);
                exp_part<0, SPLITJ>(s, n0, n1, l0, l1);
                sched_barrier(l0, l1, bars + MISC_OFF + 16);
                LP(5);
                wgmma_wait<0>();
                LP(6);
                c.release(sv.bo);
                ready = c.peek();
                fence_regs(o); fence_regs(pf);
                exp_part<SPLITJ, 16>(s, n0, n1, l0, l1);
                pack_tile(s, pf);
            }
            PROF(10 + rd * 4);
            if (cb == 8) PROF(42 + 3 * j);
            PROFG(183 + rd);
            const Slot sv = c.next();
            BP(1, 0);
            c.wait(sv, ready);
            const bool bad = __any_sync(0xffffffffu, !(l0 < 0x1p60f && l1 < 0x1p60f));
            if (__builtin_expect(bad || nrest == 0, 0)) {
#pragma unroll
                for (int i = 0; i < 64; i++) o[i] = 0.f;
                if (bad) {
                    attention_exact(o, qf, l0, l1, h, nrest + 1, lim, lane);
#pragma unroll
                    for (int i = 0; i < 32; i++) pf[i] = 0u;
                }
            }
            fence_regs(o); fence_regs(pf);
            if (!role) named_sync(bar_me, 256);
            BP(1, 2);
            wgmma_fence();
            gemm_rs<false>(o, pf, sv.dl);
            wgmma_commit();
            pend = sv.bo;
            ep_ptr = g_ctx + (size_t)(h * SEQ + 256 * p + 128 * rank + 64 * role + 16 * w + lr) * HD + 8 * q;
            ep_step = 8 * HD;
        }
        l0 += __shfl_xor_sync(0xffffffffu, l0, 1); l1 += __shfl_xor_sync(0xffffffffu, l1, 1);
        l0 += __shfl_xor_sync(0xffffffffu, l0, 2); l1 += __shfl_xor_sync(0xffffffffu, l1, 2);
        l0 = rcp(l0); l1 = rcp(l1);
        sched_barrier(l0, l1, bars + MISC_OFF + 16);
        wgmma_wait<0>();
        c.release(pend);
        fence_regs(o); fence_regs(pf);
#pragma unroll
        for (int i = 0; i < 32; i++) pf[i] = pack_bf16(o[2 * i] * ((i & 1) ? l1 : l0), o[2 * i + 1] * ((i & 1) ? l1 : l0));
    }
    PROFG(187);
    PROF(3);
    if (cb == 8) {
#pragma unroll
        for (int i = 0; i < 8; i++) stg128(ep_ptr + (i & 1) * 8 * HD + 32 * (i >> 1), pf[4 * (i & 6) + (i & 1)], pf[4 * (i & 6) + (i & 1) + 2], pf[4 * (i & 6) + (i & 1) + 4], pf[4 * (i & 6) + (i & 1) + 6]);
        signal(bars, wg, 8, lane);
        cluster_arrive();
        named_sync(1, 256);
        mod_ffn(P, smem, 2 * ca + rank, wg);
    } else
    {
        float a1[64], a2[96];
        uint32_t px = 0, py = 0;
        auto mma1 = [&](const Slot& x, int acc) {
#pragma unroll
            for (int k = 0; k < 4; k++) wgmma_ss_n128<0, 1>(a1, x.dl + wg * 512 + lbo(16) + k * 2, x.dl + 1024 + lbo(4096) + (k >> 1) * 512 + (k & 1) * 128, k ? 1 : acc);
        };
        auto mma2 = [&](const Slot& x, const Slot& y, int acc) {
#pragma unroll
            for (int k = 0; k < 4; k++) wgmma_ss_n192<0, 1>(a2, x.dl + wg * 512 + lbo(16) + k * 2, y.dl + lbo(4096) + (k >> 1) * 768 + (k & 1) * 128, k ? 1 : acc);
        };
#pragma unroll 1
        for (int t = 0, more = 1; more; t++) {
            const Slot sx = c.next(), sy = c.next();
            c.wait(sx);
            wgmma_fence();
            mma1(sx, t);
            wgmma_commit();
            wgmma_wait<1>();
            asm volatile("ld.shared.u32 %0, [%1];" : "=r"(more) : "r"(bars + CTL_OFF + sx.bo) : "memory");
            if (t > 0) { c.release(px); c.release(py); }
            px = sx.bo; py = sy.bo;
            c.wait(sy);
            wgmma_fence();
            mma2(sx, sy, t);
            wgmma_commit();
            more = !__any_sync(0xffffffffu, more);
            if (t == 0) {
#pragma unroll
                for (int i = 0; i < 4; i++) stg128(ep_ptr + 32 * i, pf[8 * i], pf[8 * i + 2], pf[8 * i + 4], pf[8 * i + 6]);
            }
            if (t == 1) {
#pragma unroll
                for (int i = 0; i < 4; i++) stg128(ep_ptr + 8 * HD + 32 * i, pf[8 * i + 1], pf[8 * i + 3], pf[8 * i + 5], pf[8 * i + 7]);
                signal(bars, wg, 4 + n_items(ca, cb), lane);
            }
        }
        const Slot x0 = c.next(), y0 = c.next(), x1 = c.next(), y1 = c.next(), x2 = c.next(), y2 = c.next(), fr = c.next();
        const int cw = __reduce_or_sync(0xffffffffu, wg * 4 + w);
        const int orow = unperm_row(256 * out_p(ca, cb) + 128 * rank + 16 * cw), ocol = 320 * (ca >> 2);
        const uint32_t sa = ((lane & 7) + (lane & 8)) * 128, sx = (lane >> 4) ^ (lane & 7);
        auto send = [&](auto chv, uint32_t box) {
            constexpr int ch = chv.value;
#pragma unroll
            for (int i = 0; i < 4; i++) {
                uint32_t r[4];
#pragma unroll
                for (int e = 0; e < 4; e++) {
                    const int k = 32 * ch + 8 * i + 2 * e;
                    r[e] = (ch < 2) ? pack_bf16(a1[k & 63], a1[(k & 63) + 1]) : pack_bf16(a2[ch < 2 ? 0 : k - 64], a2[ch < 2 ? 1 : k - 63]);
                }
                asm volatile("stmatrix.sync.aligned.m8n8.x4.shared.b16 [%0], {%1, %2, %3, %4};"
                             ::"r"(box + sa + ((sx ^ (2 * i)) << 4)), "r"(r[0]), "r"(r[1]), "r"(r[2]), "r"(r[3]) : "memory");
            }
            asm volatile("fence.proxy.async.shared::cta;" ::: "memory");
            __syncwarp();
            asm volatile(ELECT "cp.reduce.async.bulk.tensor.2d.global.shared::cta.add.bulk_group [%0, {%2, %3}], [%1];\n}\n"
                         ::"l"(&P.outm), "r"(box), "r"(ocol + 64 * ch), "r"(orow) : "memory");
        };
        auto addr = [&](const Slot& t) { return smem + t.bo * (SLOT / 8); };
        c.wait(x0);
        wgmma_fence();
        mma1(x0, 1);
        wgmma_commit();
        wgmma_wait<1>();
        c.release(px); c.release(py);
        c.wait(x1);
        c.wait(x2);
        c.wait(y0);
        mbar_wait(bars + BAR_DEP, 0);
        wgmma_fence();
        mma1(x1, 1);
        mma1(x2, 1);
        wgmma_commit();
        mma2(x0, y0, 1);
        wgmma_commit();
        mbar_wait(bars + BAR_EMPTY + fr.bo, fr.par ^ 1);
        c.wait(y1);
        wgmma_wait<1>();
        fence_regs(a1);
        send(IntT<0>{}, addr(fr) + cw * 4096);
        wgmma_fence();
        mma2(x1, y1, 1);
        wgmma_commit();
        send(IntT<1>{}, addr(fr) + cw * 4096 + 2048);
        c.wait(y2);
        wgmma_fence();
        mma2(x2, y2, 1);
        wgmma_commit();
        wgmma_wait<0>();
        fence_regs(a2);
        PROFG(188);
        PROF(4);
        send(IntT<2>{}, addr(x0) + cw * 2048);
        send(IntT<3>{}, addr(x1) + cw * 2048);
        send(IntT<4>{}, addr(x2) + cw * 2048);
        PROF(5);
        asm volatile("cp.async.bulk.commit_group;\ncp.async.bulk.wait_group.read 0;" ::: "memory");
    }
    PROF(6);
}

__device__ __forceinline__ void mod_ffn(const Params& P, uint32_t smem, int mc  , int wg) {
    const int tid = threadIdx.x - 128, lane = tid & 31, cw = tid >> 5, q = lane & 3, lr = lane >> 2;
    const uint32_t xs = smem + 6 * SLOT, hs = xs + 10240 + wg * 1024, wmax = xs + 12288, sidx = wmax + 64, rbar = xs + 13312 + wg * 32;
    const uint32_t ring = smem + wg * 3 * SLOT;
    const int f0 = mc + 4 * wg, nunit = ((34 - f0) >> 3) * 8;
    const bool lead = __reduce_or_sync(0xffffffffu, cw & 3) == 0;
    auto lds = [](uint32_t a) { uint32_t v; asm volatile("ld.shared.u32 %0, [%1];" : "=r"(v) : "r"(a) : "memory"); return v; };
    auto sts = [](uint32_t a, uint32_t v) { asm volatile("st.shared.u32 [%0], %1;" ::"r"(a), "r"(v) : "memory"); };
    auto issue = [&](int u, int st) {
        if (lead && u < nunit) {
            const int fc = (f0 + (u & ~7)) * 64, k = u & 7;
            const uint32_t dst = ring + st * SLOT, bar = rbar + st * 8;
            w_expect_tx(bar, k == 7 ? 16384 : SLOT);
            if (k < 5) {
                w_tma_load_stream(dst, &P.wg, fc, k * 128, bar);
                w_tma_load_stream(dst + 16384, &P.wu, fc, k * 128, bar);
            } else {
#pragma unroll 1
                for (int b = 0; b < (k == 7 ? 2 : 4); b++) w_tma_load_stream(dst + b * 8192, &P.wd, (4 * (k - 5) + b) * 64, fc, bar);
            }
        }
    };
    if ((tid & 127) == 0) {
        mbar_init(rbar, 1); mbar_init(rbar + 8, 1); mbar_init(rbar + 16, 1);
        asm volatile("fence.mbarrier_init.release.cluster;" ::: "memory");
    }
    mbar_wait(smem + NSLOT * SLOT + BAR_DEP, 0);
    asm volatile("fence.proxy.async.shared::cta;" ::: "memory");
    named_sync(1, 256);
    PROF(1);
#pragma unroll 1
    for (int u = 0; u < 3; u++) issue(u, u);
    uint32_t key[8];
#pragma unroll
    for (int i = 0; i < 8; i++) {
        const int t = tid + 256 * i;
        uint32_t b = __float_as_uint(__ldcg(g_r + t) + 0.f) >> 16;
        b = (b & 0x8000u) ? (~b & 0xffffu) : (b | 0x8000u);
        key[i] = (b << 16) | (uint32_t)(0xffff - t);
    }
#pragma unroll 1
    for (int rnd = 0; rnd < 8; rnd++) {
        uint32_t mx = key[0];
#pragma unroll
        for (int i = 1; i < 8; i++) mx = max(mx, key[i]);
        sts(wmax + ((rnd & 1) * 8 + cw) * 4, __reduce_max_sync(0xffffffffu, mx));
        named_sync(1, 256);
        mx = __reduce_max_sync(0xffffffffu, lds(wmax + ((rnd & 1) * 8 + (lane & 7)) * 4));
#pragma unroll
        for (int i = 0; i < 8; i++) if (key[i] == mx) key[i] = 0;
        if (cw == rnd) sts(sidx + rnd * 4, 0xffff - (mx & 0xffffu));
    }
    __syncwarp();
    {
        const int t = lds(sidx + cw * 4);
        const uint4* src = reinterpret_cast<const uint4*>(g_xn + perm_row(t) * DM);
#pragma unroll
        for (int i = 0; i < 3; i++) {
            const int ch = lane + 32 * i;
            if (ch < 80) {
                const uint4 v = __ldcg(src + ch);
                asm volatile("st.shared.v4.b32 [%0], {%1, %2, %3, %4};" ::"r"(xs + (ch >> 3) * 1024 + cw * 128 + ((ch ^ cw) & 7) * 16), "r"(v.x), "r"(v.y), "r"(v.z), "r"(v.w) : "memory");
            }
        }
        asm volatile("fence.proxy.async.shared::cta;" ::: "memory");
    }
    named_sync(1, 256);
    PROF(3);
    float y[10][4];
#pragma unroll
    for (int i = 0; i < 10; i++) { y[i][0] = 0.f; y[i][1] = 0.f; y[i][2] = 0.f; y[i][3] = 0.f; }
    int st = 0, ph = 0, u = 0;
    auto begin = [&]() { mbar_wait(rbar + st * 8, ph); wgmma_fence(); return (((ring + st * SLOT) & 0x3FFFF) >> 4) + lbo(16); };
    auto end = [&]() {
        wgmma_commit();
        wgmma_wait<0>();
        named_sync(4 + wg, 128);
        issue(u + 3, st);
        u++;
        ph ^= st == 2;
        st = (st == 2) ? 0 : st + 1;
    };
    const uint32_t dx = ((xs & 0x3FFFF) >> 4) + lbo(16), dh = ((hs & 0x3FFFF) >> 4) + lbo(16);
#pragma unroll 1
    while (u < nunit) {
        float g[4], v[4];
#pragma unroll 1
        for (int kc = 0; kc < 5; kc++) {
            const uint32_t da = begin();
#pragma unroll
            for (int k = 0; k < 8; k++) {
                const uint32_t db = dx + (2 * kc + (k >> 2)) * 64 + (k & 3) * 2;
                wgmma_ss_n8<1, 0>(g, da + k * 128, db, k ? 1 : kc);
                wgmma_ss_n8<1, 0>(v, da + 1024 + k * 128, db, k ? 1 : kc);
            }
            end();
        }
        fence_regs(g); fence_regs(v);
#pragma unroll
        for (int e = 0; e < 4; e++) {
            const float gp = round_bf16(g[e]);
            const float hv = round_bf16(__fdividef(gp, 1.0f + __expf(fminf(-gp, 80.f)))) * round_bf16(v[e]);
            const int tok = 2 * q + (e & 1), ch = 2 * (cw & 3) + (e >> 1);
            asm volatile("st.shared.u16 [%0], %1;" ::"r"(hs + tok * 128 + ((ch ^ tok) * 16) + lr * 2), "h"((unsigned short)pack_bf16(hv, 0.f)) : "memory");
        }
        asm volatile("fence.proxy.async.shared::cta;" ::: "memory");
        named_sync(4 + wg, 128);
#pragma unroll
        for (int k3 = 0; k3 < 3; k3++) {
            const uint32_t da = begin();
#pragma unroll
            for (int b = 0; b < (k3 == 2 ? 2 : 4); b++)
#pragma unroll
                for (int k = 0; k < 4; k++) wgmma_ss_n8<1, 0>(y[4 * k3 + b], da + b * 512 + k * 128, dh + k * 2, 1);
            end();
        }
    }
    PROF(5);
#pragma unroll
    for (int i = 0; i < 10; i++) {
        fence_regs(y[i]);
#pragma unroll
        for (int e = 0; e < 4; e++) g_ypart[((mc * 2 + wg) * 8 + 2 * q + (e & 1)) * DM + 64 * i + 16 * (cw & 3) + lr + 8 * (e >> 1)] = y[i][e];
    }
    named_sync(1, 256);
    if (tid == 0) {
        flag_add(F_MODP);
        flag_wait<100>(F_MODP, 4u * (lds(smem + NSLOT * SLOT + MISC_OFF) + 1));
    }
    named_sync(1, 256);
    PROF(6);
    {
        const int c = 2 * mc + wg, t = lds(sidx + c * 4);
        const float rs = round_bf16(__fdividef(1.0f, 1.0f + __expf(fminf(-__ldcg(g_r + t), 80.f))));
#pragma unroll
        for (int i = 0; i < 3; i++) {
            const int c2 = (tid & 127) + 128 * i;
            if (c2 < DM / 2) {
                float y0 = 0.f, y1 = 0.f;
#pragma unroll
                for (int k = 0; k < 8; k++) {
                    const float2 v = __ldcg(reinterpret_cast<const float2*>(g_ypart + (k * 8 + c) * DM) + c2);
                    y0 += v.x; y1 += v.y;
                }
                asm volatile("red.relaxed.gpu.global.add.noftz.bf16x2 [%0], %1;" ::"l"(P.out + t * DM + 2 * c2), "r"(pack_bf16(round_bf16(y0) * rs, round_bf16(y1) * rs)) : "memory");
            }
        }
    }
    PROF(7);
}

__global__ void __cluster_dims__(2, 1, 1) __launch_bounds__(384, 1) fused_kernel(const __grid_constant__ Params P) {
    extern __shared__ __align__(1024) uint8_t smem_raw[];
    const uint32_t smem = (smem_u32(smem_raw) + 1023u) & ~1023u;
    const uint32_t bars = smem + NSLOT * SLOT;
    const int wgi = __reduce_or_sync(0xffffffffu, threadIdx.x >> 7);
    const int cl = blockIdx.x >> 1, rank = blockIdx.x & 1, ca = cl & 7, cb = cl >> 3;
    PROFG(30);
    PROF(0);
    if (threadIdx.x == 64) {
        const uint32_t fa = bars + BAR_FULL + slot_a(0) * 8, fw = bars + BAR_FULL + slot_w(0) * 8;
        mbar_init(fa, 1); mbar_init(fw, 1);
        asm volatile("fence.mbarrier_init.release.cluster;" ::: "memory");
        if (cb < 8) {
            mbar_expect_tx(fa, SLOT);
            mbar_expect_tx(fw, SLOT);
            tma_load(smem + slot_a(0) * SLOT, &P.ckv, 0, (2 * ca + rank) * 128, fa);
            tma_load(smem + slot_w(0) * SLOT, &P.wuk, (cb + 8 * kv_round(0)) * 128, 0, fw);
            tma_load(smem + slot_w(0) * SLOT + 16384, &P.wuk, (cb + 8 * kv_round(0)) * 128 + 64, 0, fw);
            tma_load(smem + slot_a(0) * SLOT + 16384, &P.ckv, 64, (2 * ca + rank) * 128, fa);
        }
    } else if (threadIdx.x == 0) {
#pragma unroll
        for (int i = 0; i < NSLOT; i++) {
            if (i != slot_a(0) && i != slot_w(0)) mbar_init(bars + BAR_FULL + i * 8, 1);
            mbar_init(bars + BAR_EMPTY + i * 8, 16);
        }
        if (cb < 8) {
            mbar_arrive(bars + BAR_FULL + 16);
            asm volatile("mbarrier.arrive.shared::cta.b64 _, [%0], 16;" ::"r"(bars + BAR_EMPTY + 16) : "memory");
        }
        asm volatile("fence.mbarrier_init.release.cluster;" ::: "memory");
        PROF(24);
    } else if (threadIdx.x == 32) {
#pragma unroll
        for (int i = 0; i < 18; i++) mbar_init(bars + BAR_SIG + i * 8, 4);
#pragma unroll
        for (int i = 0; i < 18; i++) mbar_init(bars + BAR_DEP + i * 8, 1);
        asm volatile("fence.mbarrier_init.release.cluster;" ::: "memory");
    }
    __syncthreads();
    PROF(29);
    cluster_arrive();
    if (wgi > 0) {
        asm volatile("setmaxnreg.inc.sync.aligned.u32 232;");
        consumer(P, smem, bars, ca, cb, rank, wgi - 1);
        PROFG(31);
        PROFDUMP();
    } else {
        asm volatile("setmaxnreg.dec.sync.aligned.u32 40;");
        const int w = __reduce_or_sync(0xffffffffu, threadIdx.x >> 5), lane = threadIdx.x & 31;
        if (threadIdx.x == 32) {
            prefetch_map(&P.wuv); prefetch_map(&P.xn); prefetch_map(&P.wq); prefetch_map(&P.kv); prefetch_map(&P.ctx); prefetch_map(&P.wo); prefetch_map(&P.outm);
        }
        __syncwarp();
        cluster_wait();
        PROF(27);
        {
            if (w == 0) {
                producer(P, smem, bars, ca, cb, rank);
            } else if (w < 3 && lane == 0) {
                const int wg = w - 1;
#pragma unroll 1
                for (int i = (cb == 8); i < (cb == 8 ? 9 : 5 + n_items(ca, cb)); i++) {
                    const int nb = wg + (LNOFF + 7 - 4) / 8;
                    const int e = (cb == 8) ? i : (i < nb) ? i + 1 : (i == nb) ? 0 : i;
                    mbar_wait_sleep(bars + BAR_SIG + (wg * 9 + e) * 8, 0);
                    int f;
                    if (cb == 8) f = F_CTX + (2 + ca) * 16 + rank;
                    else if (e == 0) {
                        f = F_LN;
                        if ((ca & 3) == 0 && rank == 0 && wg == 0) g_flags[(F_POOL + out_p(ca, cb) * 2 + (ca >> 2)) * 8] = 8;
                    }
                    else if (e < 5) f = F_KV + cb + 8 * kv_round(e - 1);
                    else { const int rd = item_rd(ca, cb, e - 5); f = F_CTX + rd * 16 + item_p(ca, rd) * 2 + rank; }
                    flag_add(f);
                }
            } else if (lane == 0) {
                const uint32_t epoch = read_epoch();
                asm volatile("st.shared.u32 [%0], %1;" ::"r"(bars + MISC_OFF), "r"(epoch) : "memory");
#pragma unroll 1
                for (int e = 0; e < 9; e++) {
                    int f;
                    uint32_t n;
                    if (e == 0) { f = F_LN; n = 256; }
                    else if (cb == 8) { f = F_KV + item_h(cb, 2 + ca, e - 1); n = 32; }
                    else if (e < 5) { f = F_KV + cb + 8 * (e - 1); n = 32; }
                    else { f = F_CTX + (e - 5) * 16 + out_p(ca, cb) * 2 + rank; n = 16; }
                    flag_wait<200>(f, n * (epoch + 1));
                    fence_proxy_async();
                    mbar_arrive(bars + BAR_DEP + e * 8);
                }
            }
        }
        if (cb == 8) { __syncwarp(); cluster_arrive(); cluster_wait(); }
        PROFG(31);
        PROFDUMP();
    }
}

typedef CUresult (*EncodeFn)(CUtensorMap*, CUtensorMapDataType, cuuint32_t, void*, const cuuint64_t*, const cuuint64_t*, const cuuint32_t*,
                             const cuuint32_t*, CUtensorMapInterleave, CUtensorMapSwizzle, CUtensorMapL2promotion, CUtensorMapFloatOOBfill);

void make_map(EncodeFn fn, CUtensorMap* m, const void* ptr, uint64_t rows, uint64_t cols, uint32_t box_rows) {
    cuuint64_t dims[2] = {cols, rows};
    cuuint64_t strides[1] = {cols * 2};
    cuuint32_t box[2] = {64, box_rows};
    cuuint32_t es[2] = {1, 1};
    fn(m, CU_TENSOR_MAP_DATA_TYPE_BFLOAT16, 2, const_cast<void*>(ptr), dims, strides, box, es, CU_TENSOR_MAP_INTERLEAVE_NONE,
       CU_TENSOR_MAP_SWIZZLE_128B, CU_TENSOR_MAP_L2_PROMOTION_L2_128B, CU_TENSOR_MAP_FLOAT_OOB_FILL_NONE);
}

}

extern "C" void kernel_launch(void* const* d_in, const int* in_sizes, int n_in, void* d_out, int out_size) {
    (void)in_sizes; (void)n_in; (void)out_size;
    void* fnp = nullptr;
    cudaDriverEntryPointQueryResult qr;
    cudaGetDriverEntryPoint("cuTensorMapEncodeTiled", &fnp, cudaEnableDefault, &qr);
    EncodeFn fn = (EncodeFn)fnp;
    void *xn, *kv, *ctx;
    cudaGetSymbolAddress(&xn, g_xn);
    cudaGetSymbolAddress(&kv, g_kv);
    cudaGetSymbolAddress(&ctx, g_ctx);
    Params P;
    make_map(fn, &P.ckv, d_in[1], SEQ, DC, 128);
    make_map(fn, &P.wq, d_in[2], DM, NH * HD, 64);
    make_map(fn, &P.wuk, d_in[3], DC, NH * HD, 128);
    make_map(fn, &P.wuv, d_in[4], DC, NH * HD, 128);
    make_map(fn, &P.wo, d_in[5], NH * HD, DM, 32);
    make_map(fn, &P.xn, xn, SEQ, DM, 128);
    make_map(fn, &P.kv, kv, NH * 16 * 2 * 128, 128, 128);
    make_map(fn, &P.ctx, ctx, NH * SEQ, HD, 128);
    P.x = (const __nv_bfloat16*)d_in[0];
    P.wr = (const __nv_bfloat16*)d_in[7];
    make_map(fn, &P.wg, d_in[8], DM, FF, 128);
    make_map(fn, &P.wu, d_in[9], DM, FF, 128);
    make_map(fn, &P.wd, d_in[10], FF, DM, 64);
    make_map(fn, &P.outm, d_out, SEQ, DM, 16);
    P.out = (__nv_bfloat16*)d_out;
    cudaFuncSetAttribute(fused_kernel, cudaFuncAttributeMaxDynamicSharedMemorySize, SMEM_BYTES);
    fused_kernel<<<NCTA, 384, SMEM_BYTES>>>(P);
}
```

```cpp
#include <cuda_runtime.h>
#include <cuda_bf16.h>
#include <cuda.h>
#include <stdint.h>

namespace {

constexpr int SEQ = 2048, DM = 640, DC = 512, NH = 32, HD = 128, FF = 1728;
constexpr int NSLOT = 7, SLOT = 32768;
constexpr int NCTA = 132;
constexpr int KVSPLIT = 1;
constexpr int LNOFF = 4, LNLEAD = 2;
constexpr int SPLITJ = 8;
constexpr uint32_t DESC_HI = (1024u >> 4) | (1u << 30);
constexpr int SMEM_BYTES = NSLOT * SLOT + 3072;

constexpr int BAR_FULL = 0, BAR_EMPTY = 64, BAR_SIG = 128  , BAR_DEP = 320  , BAR_MAIL = 400  ;
constexpr int MISC_OFF = 512  , MAIL_OFF = 544  , CTL_OFF = 576  ;

constexpr int F_EPOCH = 0, F_LN = 1, F_MODP = 3, F_KV = 4  , F_CTX = 36  , F_POOL = 100  , F_NUM = 116;

__device__ __align__(1024) __nv_bfloat16 g_xn[SEQ * DM];
__device__ __align__(1024) __nv_bfloat16 g_kv[NH * 16 * 2 * 128 * 128];
__device__ __align__(1024) __nv_bfloat16 g_ctx[NH * SEQ * HD];
__device__ __align__(16) float g_r[SEQ];
__device__ __align__(16) float g_ypart[8 * 8 * DM];
__device__ uint32_t g_flags[F_NUM * 8];

struct TrueT { static constexpr bool value = true; };
struct FalseT { static constexpr bool value = false; };

struct Params {
    CUtensorMap ckv, wuk, wuv, xn, wq, kv, ctx, wo, wg, wu, wd, outm;
    const __nv_bfloat16 *x, *wr;
    __nv_bfloat16* out;
};

__device__ __forceinline__ uint32_t smem_u32(const void* p) { return (uint32_t)__cvta_generic_to_shared(p); }
__device__ __forceinline__ void mbar_init(uint32_t bar, uint32_t cnt) {
    asm volatile("mbarrier.init.shared::cta.b64 [%0], %1;" ::"r"(bar), "r"(cnt) : "memory");
}
__device__ __forceinline__ void mbar_expect_tx(uint32_t bar, uint32_t bytes) {
    asm volatile("mbarrier.arrive.expect_tx.shared::cta.b64 _, [%0], %1;" ::"r"(bar), "r"(bytes) : "memory");
}
__device__ __forceinline__ void mbar_arrive(uint32_t bar) {
    asm volatile("mbarrier.arrive.shared::cta.b64 _, [%0];" ::"r"(bar) : "memory");
}
__device__ __forceinline__ uint32_t mapa(uint32_t addr, uint32_t cta) {
    uint32_t r;
    asm("mapa.shared::cluster.u32 %0, %1, %2;" : "=r"(r) : "r"(addr), "r"(cta));
    return r;
}
__device__ __forceinline__ void mbar_wait(uint32_t bar, uint32_t parity) {
    asm volatile(
        "{\n.reg .pred p;\n.reg .b32 c;\n"
        "mov.b32 c, 0;\n"
        "WLOOP:\n"
        "mbarrier.try_wait.parity.shared::cta.b64 p, [%0], %1;\n"
        "@p bra.uni WDONE;\n"
        "add.u32 c, c, 1;\n"
        "setp.lt.u32 p, c, 0x400000;\n"
        "@p bra.uni WLOOP;\n"
        "trap;\n"
        "WDONE:\n}\n" ::"r"(bar), "r"(parity) : "memory");
}
__device__ __forceinline__ uint32_t mbar_peek(uint32_t bar, uint32_t parity) {
    uint32_t ok;
    asm volatile("{\n.reg .pred p;\nmbarrier.test_wait.parity.shared::cta.b64 p, [%1], %2;\nselp.b32 %0, 1, 0, p;\n}\n" : "=r"(ok) : "r"(bar), "r"(parity) : "memory");
    return ok;
}
__device__ __forceinline__ void mbar_wait_unless(uint32_t ok, uint32_t bar, uint32_t parity) {
    asm volatile(
        "{\n.reg .pred p;\n.reg .b32 c;\n"
        "setp.ne.b32 p, %2, 0;\n"
        "@p bra.uni WDONE;\n"
        "mov.b32 c, 0;\n"
        "WLOOP:\n"
        "mbarrier.try_wait.parity.shared::cta.b64 p, [%0], %1;\n"
        "@p bra.uni WDONE;\n"
        "add.u32 c, c, 1;\n"
        "setp.lt.u32 p, c, 0x400000;\n"
        "@p bra.uni WLOOP;\n"
        "trap;\n"
        "WDONE:\n}\n" ::"r"(bar), "r"(parity), "r"(ok) : "memory");
}
__device__ __forceinline__ void mbar_wait_sleep(uint32_t bar, uint32_t parity) {
    asm volatile(
        "{\n.reg .pred p;\n.reg .b32 c;\n"
        "mov.b32 c, 0;\n"
        "WLOOP:\n"
        "mbarrier.try_wait.parity.shared::cta.b64 p, [%0], %1, 20000;\n"
        "@p bra.uni WDONE;\n"
        "add.u32 c, c, 1;\n"
        "setp.lt.u32 p, c, 0x40000;\n"
        "@p bra.uni WLOOP;\n"
        "trap;\n"
        "WDONE:\n}\n" ::"r"(bar), "r"(parity) : "memory");
}
__device__ __forceinline__ void tma_load(uint32_t dst, const CUtensorMap* m, int c0, int c1, uint32_t bar) {
    asm volatile("cp.async.bulk.tensor.2d.shared::cluster.global.mbarrier::complete_tx::bytes [%0], [%1, {%3, %4}], [%2];"
                 ::"r"(dst), "l"(m), "r"(bar), "r"(c0), "r"(c1) : "memory");
}
#define ELECT "{\n.reg .pred e;\nelect.sync _|e, 0xffffffff;\n@e "
__device__ __forceinline__ void w_expect_tx(uint32_t bar, uint32_t bytes) {
    asm volatile(ELECT "mbarrier.arrive.expect_tx.shared::cta.b64 _, [%0], %1;\n}\n" ::"r"(bar), "r"(bytes) : "memory");
}
__device__ __forceinline__ void w_tma_load(uint32_t dst, const CUtensorMap* m, int c0, int c1, uint32_t bar) {
    asm volatile(ELECT "cp.async.bulk.tensor.2d.shared::cluster.global.mbarrier::complete_tx::bytes [%0], [%1, {%3, %4}], [%2];\n}\n"
                 ::"r"(dst), "l"(m), "r"(bar), "r"(c0), "r"(c1) : "memory");
}
__device__ __forceinline__ void w_tma_load_mc(uint32_t dst, const CUtensorMap* m, int c0, int c1, uint32_t bar) {
    asm volatile(ELECT "cp.async.bulk.tensor.2d.shared::cluster.global.mbarrier::complete_tx::bytes.multicast::cluster [%0], [%1, {%3, %4}], [%2], %5;\n}\n"
                 ::"r"(dst), "l"(m), "r"(bar), "r"(c0), "r"(c1), "h"((uint16_t)3) : "memory");
}
__device__ __forceinline__ void w_tma_prefetch(const CUtensorMap* m, int c0, int c1) {
    asm volatile(ELECT "cp.async.bulk.prefetch.tensor.2d.L2.global [%0, {%1, %2}];\n}\n" ::"l"(m), "r"(c0), "r"(c1) : "memory");
}
__device__ __forceinline__ uint64_t policy_evict_first() {
    uint64_t p;
    asm("createpolicy.fractional.L2::evict_first.b64 %0, 1.0;" : "=l"(p));
    return p;
}
__device__ __forceinline__ void w_tma_load_mc_last(uint32_t dst, const CUtensorMap* m, int c0, int c1, uint32_t bar) {
    asm volatile(ELECT "cp.async.bulk.tensor.2d.shared::cluster.global.mbarrier::complete_tx::bytes.multicast::cluster.L2::cache_hint [%0], [%1, {%3, %4}], [%2], %5, %6;\n}\n"
                 ::"r"(dst), "l"(m), "r"(bar), "r"(c0), "r"(c1), "h"((uint16_t)3), "l"(policy_evict_first()) : "memory");
}
__device__ __forceinline__ void w_tma_load_stream(uint32_t dst, const CUtensorMap* m, int c0, int c1, uint32_t bar) {
    asm volatile(ELECT "cp.async.bulk.tensor.2d.shared::cluster.global.mbarrier::complete_tx::bytes.L2::cache_hint [%0], [%1, {%3, %4}], [%2], %5;\n}\n"
                 ::"r"(dst), "l"(m), "r"(bar), "r"(c0), "r"(c1), "l"(policy_evict_first()) : "memory");
}
__device__ __forceinline__ uint4 ldg_stream(const void* p) {
    uint4 v;
    asm volatile("ld.global.nc.L2::cache_hint.v4.b32 {%0, %1, %2, %3}, [%4], %5;" : "=r"(v.x), "=r"(v.y), "=r"(v.z), "=r"(v.w) : "l"(p), "l"(policy_evict_first()));
    return v;
}
__device__ __forceinline__ void prefetch_map(const CUtensorMap* m) {
    asm volatile("prefetch.tensormap [%0];" ::"l"(m) : "memory");
}
__device__ __forceinline__ void cluster_arrive() { asm volatile("barrier.cluster.arrive.relaxed.aligned;" ::: "memory"); }
__device__ __forceinline__ void cluster_wait() { asm volatile("barrier.cluster.wait.aligned;" ::: "memory"); }
__device__ __forceinline__ void named_sync(int id, int n) { asm volatile("bar.sync %0, %1;" ::"r"(id), "r"(n) : "memory"); }
__device__ __forceinline__ void named_arrive(int id, int n) { asm volatile("bar.arrive %0, %1;" ::"r"(id), "r"(n) : "memory"); }

__device__ __forceinline__ void flag_add(int f) {
    asm volatile("fence.acq_rel.gpu;\nred.relaxed.gpu.global.add.u32 [%0], 1;" ::"l"(g_flags + f * 8) : "memory");
}
template <int SLEEP>
__device__ __forceinline__ void flag_wait(int f, uint32_t target) {
    asm volatile(
        "{\n.reg .pred p;\n.reg .b32 c, v;\n"
        "mov.b32 c, 0;\n"
        "FLOOP:\n"
        "ld.acquire.gpu.global.u32 v, [%0];\n"
        "sub.u32 v, v, %1;\n"
        "setp.ge.s32 p, v, 0;\n"
        "@p bra FDONE;\n"
        "nanosleep.u32 %2;\n"
        "add.u32 c, c, 1;\n"
        "setp.lt.u32 p, c, 0x400000;\n"
        "@p bra FLOOP;\n"
        "trap;\n"
        "FDONE:\n}\n" ::"l"(g_flags + f * 8), "r"(target), "n"(SLEEP) : "memory");
}
__device__ __forceinline__ uint32_t read_epoch() { return atomicAdd(g_flags + F_EPOCH * 8, 1u) / NCTA; }
__device__ __forceinline__ void fence_proxy_async() { asm volatile("fence.proxy.async;" ::: "memory"); }

__device__ __forceinline__ void wgmma_fence() { asm volatile("wgmma.fence.sync.aligned;" ::: "memory"); }
__device__ __forceinline__ void wgmma_commit() { asm volatile("wgmma.commit_group.sync.aligned;" ::: "memory"); }
template <int N>
__device__ __forceinline__ void wgmma_wait() { asm volatile("wgmma.wait_group.sync.aligned %0;" ::"n"(N) : "memory"); }
template <int N>
__device__ __forceinline__ void fence_regs(float (&d)[N]) {
#pragma unroll
    for (int i = 0; i < N; i++) asm volatile("" : "+f"(d[i])::"memory");
}
template <int N>
__device__ __forceinline__ void fence_regs(uint32_t (&d)[N]) {
#pragma unroll
    for (int i = 0; i < N; i++) asm volatile("" : "+r"(d[i])::"memory");
}

template <int TA, int TB>
__device__ __forceinline__ void wgmma_ss_n128(float (&d)[64], uint32_t alo, uint32_t blo, int scale_d) {
    asm volatile("{\n.reg .pred p;\n.reg .b64 da, db;\nsetp.ne.b32 p, %66, 0;\n"
        "mov.b64 da, {%64, %69};\nmov.b64 db, {%65, %69};\n"
        "wgmma.mma_async.sync.aligned.m64n128k16.f32.bf16.bf16 "
        "{%0, %1, %2, %3, %4, %5, %6, %7, %8, %9, %10, %11, %12, %13, %14, %15, %16, %17, %18, %19, %20, %21, %22, %23, %24, %25, %26, %27, %28, %29, %30, %31, %32, %33, %34, %35, %36, %37, %38, %39, %40, %41, %42, %43, %44, %45, %46, %47, %48, %49, %50, %51, %52, %53, %54, %55, %56, %57, %58, %59, %60, %61, %62, %63}, da, db, p, 1, 1, %67, %68;\n}\n"
        :
          "+f"(d[0]), "+f"(d[1]), "+f"(d[2]), "+f"(d[3]), "+f"(d[4]), "+f"(d[5]), "+f"(d[6]), "+f"(d[7]),
          "+f"(d[8]), "+f"(d[9]), "+f"(d[10]), "+f"(d[11]), "+f"(d[12]), "+f"(d[13]), "+f"(d[14]), "+f"(d[15]),
          "+f"(d[16]), "+f"(d[17]), "+f"(d[18]), "+f"(d[19]), "+f"(d[20]), "+f"(d[21]), "+f"(d[22]), "+f"(d[23]),
          "+f"(d[24]), "+f"(d[25]), "+f"(d[26]), "+f"(d[27]), "+f"(d[28]), "+f"(d[29]), "+f"(d[30]), "+f"(d[31]),
          "+f"(d[32]), "+f"(d[33]), "+f"(d[34]), "+f"(d[35]), "+f"(d[36]), "+f"(d[37]), "+f"(d[38]), "+f"(d[39]),
          "+f"(d[40]), "+f"(d[41]), "+f"(d[42]), "+f"(d[43]), "+f"(d[44]), "+f"(d[45]), "+f"(d[46]), "+f"(d[47]),
          "+f"(d[48]), "+f"(d[49]), "+f"(d[50]), "+f"(d[51]), "+f"(d[52]), "+f"(d[53]), "+f"(d[54]), "+f"(d[55]),
          "+f"(d[56]), "+f"(d[57]), "+f"(d[58]), "+f"(d[59]), "+f"(d[60]), "+f"(d[61]), "+f"(d[62]), "+f"(d[63])
        : "r"(alo), "r"(blo), "r"(scale_d), "n"(TA), "n"(TB), "r"(DESC_HI));
}
template <int TA, int TB>
__device__ __forceinline__ void wgmma_ss_n192(float (&d)[96], uint32_t alo, uint32_t blo, int scale_d) {
    asm volatile("{\n.reg .pred p;\n.reg .b64 da, db;\nsetp.ne.b32 p, %98, 0;\n"
        "mov.b64 da, {%96, %101};\nmov.b64 db, {%97, %101};\n"
        "wgmma.mma_async.sync.aligned.m64n192k16.f32.bf16.bf16 "
        "{%0, %1, %2, %3, %4, %5, %6, %7, %8, %9, %10, %11, %12, %13, %14, %15, %16, %17, %18, %19, %20, %21, %22, %23, %24, %25, %26, %27, %28, %29, %30, %31, %32, %33, %34, %35, %36, %37, %38, %39, %40, %41, %42, %43, %44, %45, %46, %47, %48, %49, %50, %51, %52, %53, %54, %55, %56, %57, %58, %59, %60, %61, %62, %63, %64, %65, %66, %67, %68, %69, %70, %71, %72, %73, %74, %75, %76, %77, %78, %79, %80, %81, %82, %83, %84, %85, %86, %87, %88, %89, %90, %91, %92, %93, %94, %95}, da, db, p, 1, 1, %99, %100;\n}\n"
        :
          "+f"(d[0]), "+f"(d[1]), "+f"(d[2]), "+f"(d[3]), "+f"(d[4]), "+f"(d[5]), "+f"(d[6]), "+f"(d[7]),
          "+f"(d[8]), "+f"(d[9]), "+f"(d[10]), "+f"(d[11]), "+f"(d[12]), "+f"(d[13]), "+f"(d[14]), "+f"(d[15]),
          "+f"(d[16]), "+f"(d[17]), "+f"(d[18]), "+f"(d[19]), "+f"(d[20]), "+f"(d[21]), "+f"(d[22]), "+f"(d[23]),
          "+f"(d[24]), "+f"(d[25]), "+f"(d[26]), "+f"(d[27]), "+f"(d[28]), "+f"(d[29]), "+f"(d[30]), "+f"(d[31]),
          "+f"(d[32]), "+f"(d[33]), "+f"(d[34]), "+f"(d[35]), "+f"(d[36]), "+f"(d[37]), "+f"(d[38]), "+f"(d[39]),
          "+f"(d[40]), "+f"(d[41]), "+f"(d[42]), "+f"(d[43]), "+f"(d[44]), "+f"(d[45]), "+f"(d[46]), "+f"(d[47]),
          "+f"(d[48]), "+f"(d[49]), "+f"(d[50]), "+f"(d[51]), "+f"(d[52]), "+f"(d[53]), "+f"(d[54]), "+f"(d[55]),
          "+f"(d[56]), "+f"(d[57]), "+f"(d[58]), "+f"(d[59]), "+f"(d[60]), "+f"(d[61]), "+f"(d[62]), "+f"(d[63]),
          "+f"(d[64]), "+f"(d[65]), "+f"(d[66]), "+f"(d[67]), "+f"(d[68]), "+f"(d[69]), "+f"(d[70]), "+f"(d[71]),
          "+f"(d[72]), "+f"(d[73]), "+f"(d[74]), "+f"(d[75]), "+f"(d[76]), "+f"(d[77]), "+f"(d[78]), "+f"(d[79]),
          "+f"(d[80]), "+f"(d[81]), "+f"(d[82]), "+f"(d[83]), "+f"(d[84]), "+f"(d[85]), "+f"(d[86]), "+f"(d[87]),
          "+f"(d[88]), "+f"(d[89]), "+f"(d[90]), "+f"(d[91]), "+f"(d[92]), "+f"(d[93]), "+f"(d[94]), "+f"(d[95])
        : "r"(alo), "r"(blo), "r"(scale_d), "n"(TA), "n"(TB), "r"(DESC_HI));
}
template <int TA, int TB>
__device__ __forceinline__ void wgmma_ss_n8(float (&d)[4], uint32_t alo, uint32_t blo, int scale_d) {
    asm volatile("{\n.reg .pred p;\n.reg .b64 da, db;\nsetp.ne.b32 p, %6, 0;\n"
        "mov.b64 da, {%4, %9};\nmov.b64 db, {%5, %9};\n"
        "wgmma.mma_async.sync.aligned.m64n8k16.f32.bf16.bf16 "
        "{%0, %1, %2, %3}, da, db, p, 1, 1, %7, %8;\n}\n"
        :
          "+f"(d[0]), "+f"(d[1]), "+f"(d[2]), "+f"(d[3])
        : "r"(alo), "r"(blo), "r"(scale_d), "n"(TA), "n"(TB), "r"(DESC_HI));
}
template <int TB>
__device__ __forceinline__ void wgmma_rs_n64(float (&d)[64], uint32_t a0, uint32_t a1, uint32_t a2, uint32_t a3, uint32_t blo, int scale_d) {
    asm volatile("{\n.reg .pred p;\n.reg .b64 db;\nsetp.ne.b32 p, %37, 0;\n"
        "mov.b64 db, {%36, %39};\n"
        "wgmma.mma_async.sync.aligned.m64n64k16.f32.bf16.bf16 "
        "{%0, %1, %2, %3, %4, %5, %6, %7, %8, %9, %10, %11, %12, %13, %14, %15, %16, %17, %18, %19, %20, %21, %22, %23, %24, %25, %26, %27, %28, %29, %30, %31}, {%32, %33, %34, %35}, db, p, 1, 1, %38;\n}\n"
        :
          "+f"(d[0]), "+f"(d[1]), "+f"(d[2]), "+f"(d[3]), "+f"(d[4]), "+f"(d[5]), "+f"(d[6]), "+f"(d[7]),
          "+f"(d[8]), "+f"(d[9]), "+f"(d[10]), "+f"(d[11]), "+f"(d[12]), "+f"(d[13]), "+f"(d[14]), "+f"(d[15]),
          "+f"(d[16]), "+f"(d[17]), "+f"(d[18]), "+f"(d[19]), "+f"(d[20]), "+f"(d[21]), "+f"(d[22]), "+f"(d[23]),
          "+f"(d[24]), "+f"(d[25]), "+f"(d[26]), "+f"(d[27]), "+f"(d[28]), "+f"(d[29]), "+f"(d[30]), "+f"(d[31])
        : "r"(a0), "r"(a1), "r"(a2), "r"(a3), "r"(blo), "r"(scale_d), "n"(TB), "r"(DESC_HI));
}
template <int TB>
__device__ __forceinline__ void wgmma_rs_n128(float (&d)[64], uint32_t a0, uint32_t a1, uint32_t a2, uint32_t a3, uint32_t blo, int scale_d) {
    asm volatile("{\n.reg .pred p;\n.reg .b64 db;\nsetp.ne.b32 p, %69, 0;\n"
        "mov.b64 db, {%68, %71};\n"
        "wgmma.mma_async.sync.aligned.m64n128k16.f32.bf16.bf16 "
        "{%0, %1, %2, %3, %4, %5, %6, %7, %8, %9, %10, %11, %12, %13, %14, %15, %16, %17, %18, %19, %20, %21, %22, %23, %24, %25, %26, %27, %28, %29, %30, %31, %32, %33, %34, %35, %36, %37, %38, %39, %40, %41, %42, %43, %44, %45, %46, %47, %48, %49, %50, %51, %52, %53, %54, %55, %56, %57, %58, %59, %60, %61, %62, %63}, {%64, %65, %66, %67}, db, p, 1, 1, %70;\n}\n"
        :
          "+f"(d[0]), "+f"(d[1]), "+f"(d[2]), "+f"(d[3]), "+f"(d[4]), "+f"(d[5]), "+f"(d[6]), "+f"(d[7]),
          "+f"(d[8]), "+f"(d[9]), "+f"(d[10]), "+f"(d[11]), "+f"(d[12]), "+f"(d[13]), "+f"(d[14]), "+f"(d[15]),
          "+f"(d[16]), "+f"(d[17]), "+f"(d[18]), "+f"(d[19]), "+f"(d[20]), "+f"(d[21]), "+f"(d[22]), "+f"(d[23]),
          "+f"(d[24]), "+f"(d[25]), "+f"(d[26]), "+f"(d[27]), "+f"(d[28]), "+f"(d[29]), "+f"(d[30]), "+f"(d[31]),
          "+f"(d[32]), "+f"(d[33]), "+f"(d[34]), "+f"(d[35]), "+f"(d[36]), "+f"(d[37]), "+f"(d[38]), "+f"(d[39]),
          "+f"(d[40]), "+f"(d[41]), "+f"(d[42]), "+f"(d[43]), "+f"(d[44]), "+f"(d[45]), "+f"(d[46]), "+f"(d[47]),
          "+f"(d[48]), "+f"(d[49]), "+f"(d[50]), "+f"(d[51]), "+f"(d[52]), "+f"(d[53]), "+f"(d[54]), "+f"(d[55]),
          "+f"(d[56]), "+f"(d[57]), "+f"(d[58]), "+f"(d[59]), "+f"(d[60]), "+f"(d[61]), "+f"(d[62]), "+f"(d[63])
        : "r"(a0), "r"(a1), "r"(a2), "r"(a3), "r"(blo), "r"(scale_d), "n"(TB), "r"(DESC_HI));
}
template <int TB>
__device__ __forceinline__ void wgmma_rs_n128_z(float (&d)[64], uint32_t a0, uint32_t a1, uint32_t a2, uint32_t a3, uint32_t blo) {
    asm volatile("{\n.reg .pred p;\n.reg .b64 db;\nsetp.ne.b32 p, %69, 0;\n"
        "mov.b64 db, {%68, %71};\n"
        "wgmma.mma_async.sync.aligned.m64n128k16.f32.bf16.bf16 "
        "{%0, %1, %2, %3, %4, %5, %6, %7, %8, %9, %10, %11, %12, %13, %14, %15, %16, %17, %18, %19, %20, %21, %22, %23, %24, %25, %26, %27, %28, %29, %30, %31, %32, %33, %34, %35, %36, %37, %38, %39, %40, %41, %42, %43, %44, %45, %46, %47, %48, %49, %50, %51, %52, %53, %54, %55, %56, %57, %58, %59, %60, %61, %62, %63}, {%64, %65, %66, %67}, db, p, 1, 1, %70;\n}\n"
        :
          "=f"(d[0]), "=f"(d[1]), "=f"(d[2]), "=f"(d[3]), "=f"(d[4]), "=f"(d[5]), "=f"(d[6]), "=f"(d[7]),
          "=f"(d[8]), "=f"(d[9]), "=f"(d[10]), "=f"(d[11]), "=f"(d[12]), "=f"(d[13]), "=f"(d[14]), "=f"(d[15]),
          "=f"(d[16]), "=f"(d[17]), "=f"(d[18]), "=f"(d[19]), "=f"(d[20]), "=f"(d[21]), "=f"(d[22]), "=f"(d[23]),
          "=f"(d[24]), "=f"(d[25]), "=f"(d[26]), "=f"(d[27]), "=f"(d[28]), "=f"(d[29]), "=f"(d[30]), "=f"(d[31]),
          "=f"(d[32]), "=f"(d[33]), "=f"(d[34]), "=f"(d[35]), "=f"(d[36]), "=f"(d[37]), "=f"(d[38]), "=f"(d[39]),
          "=f"(d[40]), "=f"(d[41]), "=f"(d[42]), "=f"(d[43]), "=f"(d[44]), "=f"(d[45]), "=f"(d[46]), "=f"(d[47]),
          "=f"(d[48]), "=f"(d[49]), "=f"(d[50]), "=f"(d[51]), "=f"(d[52]), "=f"(d[53]), "=f"(d[54]), "=f"(d[55]),
          "=f"(d[56]), "=f"(d[57]), "=f"(d[58]), "=f"(d[59]), "=f"(d[60]), "=f"(d[61]), "=f"(d[62]), "=f"(d[63])
        : "r"(a0), "r"(a1), "r"(a2), "r"(a3), "r"(blo), "n"(0), "n"(TB), "r"(DESC_HI));
}
template <int TA, int TB>
__device__ __forceinline__ void wgmma_ss_n128_z(float (&d)[64], uint32_t alo, uint32_t blo) {
    asm volatile("{\n.reg .pred p;\n.reg .b64 da, db;\nsetp.ne.b32 p, %66, 0;\n"
        "mov.b64 da, {%64, %69};\nmov.b64 db, {%65, %69};\n"
        "wgmma.mma_async.sync.aligned.m64n128k16.f32.bf16.bf16 "
        "{%0, %1, %2, %3, %4, %5, %6, %7, %8, %9, %10, %11, %12, %13, %14, %15, %16, %17, %18, %19, %20, %21, %22, %23, %24, %25, %26, %27, %28, %29, %30, %31, %32, %33, %34, %35, %36, %37, %38, %39, %40, %41, %42, %43, %44, %45, %46, %47, %48, %49, %50, %51, %52, %53, %54, %55, %56, %57, %58, %59, %60, %61, %62, %63}, da, db, p, 1, 1, %67, %68;\n}\n"
        :
          "=f"(d[0]), "=f"(d[1]), "=f"(d[2]), "=f"(d[3]), "=f"(d[4]), "=f"(d[5]), "=f"(d[6]), "=f"(d[7]),
          "=f"(d[8]), "=f"(d[9]), "=f"(d[10]), "=f"(d[11]), "=f"(d[12]), "=f"(d[13]), "=f"(d[14]), "=f"(d[15]),
          "=f"(d[16]), "=f"(d[17]), "=f"(d[18]), "=f"(d[19]), "=f"(d[20]), "=f"(d[21]), "=f"(d[22]), "=f"(d[23]),
          "=f"(d[24]), "=f"(d[25]), "=f"(d[26]), "=f"(d[27]), "=f"(d[28]), "=f"(d[29]), "=f"(d[30]), "=f"(d[31]),
          "=f"(d[32]), "=f"(d[33]), "=f"(d[34]), "=f"(d[35]), "=f"(d[36]), "=f"(d[37]), "=f"(d[38]), "=f"(d[39]),
          "=f"(d[40]), "=f"(d[41]), "=f"(d[42]), "=f"(d[43]), "=f"(d[44]), "=f"(d[45]), "=f"(d[46]), "=f"(d[47]),
          "=f"(d[48]), "=f"(d[49]), "=f"(d[50]), "=f"(d[51]), "=f"(d[52]), "=f"(d[53]), "=f"(d[54]), "=f"(d[55]),
          "=f"(d[56]), "=f"(d[57]), "=f"(d[58]), "=f"(d[59]), "=f"(d[60]), "=f"(d[61]), "=f"(d[62]), "=f"(d[63])
        : "r"(alo), "r"(blo), "n"(0), "n"(TA), "n"(TB), "r"(DESC_HI));
}

__device__ __forceinline__ uint32_t pack_bf16(float lo, float hi) {
    uint32_t r;
    asm("cvt.rn.bf16x2.f32 %0, %1, %2;" : "=r"(r) : "f"(hi), "f"(lo));
    return r;
}
__device__ __forceinline__ uint32_t add_bf16x2(uint32_t a, uint32_t b) {
    uint32_t r;
    asm("add.rn.bf16x2 %0, %1, %2;" : "=r"(r) : "r"(a), "r"(b));
    return r;
}
__device__ __forceinline__ float bf_lo(uint32_t v) { return __uint_as_float(v << 16); }
__device__ __forceinline__ float bf_hi(uint32_t v) { return __uint_as_float(v & 0xffff0000u); }
__device__ __forceinline__ float round_bf16(float v) { return __bfloat162float(__float2bfloat16_rn(v)); }
__device__ __forceinline__ float ex2(float x) {
    float y;
    asm("ex2.approx.ftz.f32 %0, %1;" : "=f"(y) : "f"(x));
    return y;
}
__device__ __forceinline__ float rcp(float x) {
    float y;
    asm("rcp.approx.ftz.f32 %0, %1;" : "=f"(y) : "f"(x));
    return y;
}
__device__ __forceinline__ void stg128(void* p, uint32_t a, uint32_t b, uint32_t c, uint32_t d) {
    asm volatile("st.global.v4.b32 [%0], {%1, %2, %3, %4};" ::"l"(p), "r"(a), "r"(b), "r"(c), "r"(d) : "memory");
}
__device__ __forceinline__ void stg128p(void* p, uint32_t a, uint32_t b, uint32_t c, uint32_t d, uint64_t pol) {
    asm volatile("st.global.L2::cache_hint.v4.b32 [%0], {%1, %2, %3, %4}, %5;" ::"l"(p), "r"(a), "r"(b), "r"(c), "r"(d), "l"(pol) : "memory");
}
__device__ __forceinline__ uint64_t policy_sel(bool first) {
    uint64_t p;
    asm("createpolicy.fractional.L2::evict_normal.b64 %0, 1.0;" : "=l"(p));
    return first ? policy_evict_first() : p;
}
__device__ __forceinline__ int perm_row(int t) { return (t & ~255) | (((0x78 >> (((t >> 6) & 3) * 2)) & 3) << 6) | (t & 63); }
__device__ __forceinline__ int unperm_row(int t) { return (t & ~255) | (((0x9C >> (((t >> 6) & 3) * 2)) & 3) << 6) | (t & 63); }

#define PROF(i)
#define PROFG(i)
#define PROFDUMP()
#define TR(i)
#define OP(i)
#define BP(r, i)
#define LP(i)

template <int I>
__device__ __forceinline__ void store_chunk(const float (&a)[64], __nv_bfloat16* row0, __nv_bfloat16* row1, float s0, float s1) {
    stg128(row0 + 32 * I, pack_bf16(a[16 * I + 0] * s0, a[16 * I + 1] * s0), pack_bf16(a[16 * I + 4] * s0, a[16 * I + 5] * s0),
           pack_bf16(a[16 * I + 8] * s0, a[16 * I + 9] * s0), pack_bf16(a[16 * I + 12] * s0, a[16 * I + 13] * s0));
    stg128(row1 + 32 * I, pack_bf16(a[16 * I + 2] * s1, a[16 * I + 3] * s1), pack_bf16(a[16 * I + 6] * s1, a[16 * I + 7] * s1),
           pack_bf16(a[16 * I + 10] * s1, a[16 * I + 11] * s1), pack_bf16(a[16 * I + 14] * s1, a[16 * I + 15] * s1));
}
template <int I>
struct IntT { static constexpr int value = I; };
template <class F>
__device__ __forceinline__ void for4(F f) { f(IntT<0>{}); f(IntT<1>{}); f(IntT<2>{}); f(IntT<3>{}); }

struct Prod {
    uint32_t smem, bars;
    uint32_t bo, par;
    uint32_t dst, fb;
    __device__ __forceinline__ void acquire(uint32_t o, uint32_t parity, uint32_t bytes) {
        mbar_wait(bars + BAR_EMPTY + o, parity);
        fb = bars + BAR_FULL + o;
        dst = smem + o * (SLOT / 8);
        w_expect_tx(fb, bytes);
    }
    __device__ __forceinline__ void next(uint32_t bytes) {
        acquire(bo, par, bytes);
        const bool wrap = bo == (NSLOT - 1) * 8;
        bo = wrap ? 0u : bo + 8;
        par ^= wrap ? 1u : 0u;
    }
};

__device__ __forceinline__ int item_p(int ca, int rd) {
    const int v = (rd & 1) ? (ca + 4) & 7 : ca;
    return (rd & 2) ? 7 - v : v;
}
__device__ __forceinline__ int n_items(int ca, int cb) { return cb == 8 ? 8 : ((ca & 3) == 3) ? 3 : 4; }
__device__ __forceinline__ int item_rd(int ca, int cb, int j) { return cb == 8 ? 2 + ca : (ca == 7 && j == 2) ? 3 : j; }
__device__ __forceinline__ int item_h(int cb, int rd, int j) { return 8 * rd + (cb == 8 ? j : cb); }
__device__ __forceinline__ int item_q(int ca, int cb, int rd) { return cb == 8 ? 0 : item_p(ca, rd); }
__device__ __forceinline__ int out_p(int ca, int cb) { return (cb + 2 * (ca & 3)) & 7; }
__device__ __forceinline__ int kv_round(int i) { return (0x1023 >> (4 * i)) & 3; }
__device__ __forceinline__ int slot_a(int i) { return (0x5310 >> (4 * i)) & 15; }
__device__ __forceinline__ int slot_w(int m) { return (0x264 >> (4 * m)) & 15; }

__device__ __forceinline__ void producer(const Params& P, uint32_t smem, uint32_t bars, int ca, int cb, int rank) {
    Prod pr{smem, bars, 0u, cb == 8 ? 1u : 0u, 0u, 0u};
    if (cb < 8) {
        int m = 0;
        uint32_t lap = 1;
#pragma unroll 1
        for (int u = 0; u < 32; u++) {
            if (u >= 3) {
                const int v = (u == 3) ? 3 + ca : u + 7;
                if (v < 32 && (u == 3 || (v & 7) == ca)) w_tma_prefetch((v & 4) ? &P.wuv : &P.wuk, (cb + 8 * kv_round(v >> 3)) * 128 + rank * 64, (v & 3) * 128);
                if (u == 24) {
                    w_tma_prefetch(&P.wq, cb * 128 + rank * 64, ca * 64);
                    if (ca < 2) w_tma_prefetch(&P.wq, cb * 128 + rank * 64, (ca + 8) * 64);
                }
            }
            if (u > 0) pr.acquire(slot_w(m) * 8, lap ^ (m >> 1), SLOT);
            lap ^= m >> 1;
            m = (m == 2) ? 0 : m + 1;
            TR(1 + u);
            if (u > 0) w_tma_load_mc(pr.dst + rank * 16384, (u & 4) ? &P.wuv : &P.wuk, (cb + 8 * kv_round(u >> 3)) * 128 + rank * 64, (u & 3) * 128, pr.fb);
            if (u < 3) {
                pr.acquire(slot_a(u + 1) * 8, 1, SLOT);
                w_tma_load(pr.dst, &P.ckv, u * 128 + 128, (2 * ca + rank) * 128, pr.fb);
                w_tma_load(pr.dst + 16384, &P.ckv, u * 128 + 192, (2 * ca + rank) * 128, pr.fb);
            }
        }
    }
    PROF(1);
    mbar_wait_sleep(bars + BAR_DEP, 0);
#pragma unroll 1
    for (int j = 0, pfs = 1; j < n_items(ca, cb); j++) {
        const int rd = item_rd(ca, cb, j), h = item_h(cb, rd, j), p = item_q(ca, cb, rd);
#pragma unroll 1
        for (int ks = 0; ks < 10; ks++) {
            pr.next(SLOT);
            w_tma_load_mc(pr.dst + 16384 + rank * 8192, &P.wq, h * 128 + rank * 64, ks * 64, pr.fb);
            w_tma_load(pr.dst, &P.xn, ks * 64, 256 * p + 128 * rank, pr.fb);
            if (cb == 8 && j < 7) w_tma_prefetch(&P.wq, (h + 1) * 128 + rank * 64, ks * 64);
        }
        PROF(8 + rd * 4);
        mbar_wait(bars + BAR_DEP + (1 + (cb == 8 ? j : rd)) * 8, 0);
        const int last = 4 * p + 3, top = h * 32 + last;
#pragma unroll 1
        for (int i = 0; i <= last; i++) {
            const int t = (i == 0) ? top - 1 : (i == last) ? h * 32 + 1 : (i & 1) ? top - 2 - i : top + 2 - i;
            pr.next(SLOT);
            const bool lastrd = (cb == 8 || rd == 3) ? false : (rd == 0) ? ca >= 6 : (rd == 1) ? (ca & 3) >= 2 : (ca == 3 || (ca < 3 && (t & 31) >= 4 * p));
            if (lastrd) w_tma_load_mc_last(pr.dst + rank * 16384, &P.kv, rank * 64, t * 128, pr.fb);
            else w_tma_load_mc(pr.dst + rank * 16384, &P.kv, rank * 64, t * 128, pr.fb);
            if (i == 2 && cb < 8) {
                const int upto = (j == n_items(ca, cb) - 1) ? 4 : item_rd(ca, cb, j + 1);
#pragma unroll 1
                for (; pfs <= upto; pfs++) {
                    if (pfs < 4) {
                        w_tma_prefetch(&P.wq, (8 * pfs + cb) * 128 + rank * 64, ca * 64);
                        if (ca < 2) w_tma_prefetch(&P.wq, (8 * pfs + cb) * 128 + rank * 64, (ca + 8) * 64);
                    } else {
#pragma unroll 1
                        for (int k = 0; k < 10; k++)
                            w_tma_prefetch(&P.wo, 320 * (ca >> 2) + 64 * (k >= 5 ? k - 5 : k), (cb * 4 + (ca & 3) + (k >= 5 ? 32 : 0)) * 64 + rank * 32);
                    }
                }
            }
        }
        PROF(9 + rd * 4);
    }
    if (cb < 8) {
        const int n0 = 320 * (ca >> 2), op = out_p(ca, cb);
        uint32_t* pool = g_flags + (F_POOL + op * 2 + (ca >> 2)) * 8;
        uint32_t nxt = 0;
        auto draw = [&]() {
            if (rank == 0) asm volatile(ELECT "atom.relaxed.gpu.global.add.u32 %0, [%1], 1;\n}\n" : "+r"(nxt) : "l"(pool) : "memory");
        };
        int fixed = -1;
#pragma unroll 1
        for (int i = -2; fixed < 4; i++) {
            int st = (ca & 3) + 4 * (i + 2);
            if (i == -1) draw();
            if (i >= 0 && fixed < 0) {
                const uint32_t mb = bars + BAR_MAIL + (i & 7) * 8, md = bars + MAIL_OFF + (i & 7) * 4;
                if (rank == 0) {
                    st = __reduce_add_sync(0xffffffffu, nxt);
                    asm volatile(ELECT "st.async.shared::cluster.mbarrier::complete_tx::bytes.b32 [%0], %1, [%2];\n}\n" ::"r"(mapa(md, 1)), "r"(st), "r"(mapa(mb, 1)) : "memory");
                    if (st < 48) draw();
                } else {
                    w_expect_tx(mb, 4);
                    mbar_wait(mb, (i >> 3) & 1);
                    asm volatile("ld.shared.u32 %0, [%1];" : "=r"(st) : "r"(md) : "memory");
                    st = __reduce_or_sync(0xffffffffu, st);
                }
                if (st >= 48) fixed = 0;
            }
            if (fixed >= 0) { st = 48 + (ca & 3) + 4 * fixed; fixed++; }
            const int krow = st * 64 + rank * 32;
            mbar_wait(bars + BAR_EMPTY + pr.bo, pr.par);
            asm volatile("st.shared.u32 [%0], %1;" ::"r"(bars + CTL_OFF + pr.bo), "r"((int)(fixed == 1)) : "memory");
            __syncwarp();
            pr.next(SLOT);
            w_tma_load_mc(pr.dst + 16384 + rank * 8192, &P.wo, n0, krow, pr.fb);
            w_tma_load_mc(pr.dst + 16384 + rank * 8192 + 4096, &P.wo, n0 + 64, krow, pr.fb);
            mbar_wait(bars + BAR_DEP + (5 + (st >> 4)) * 8, 0);
            w_tma_load(pr.dst, &P.ctx, (st & 1) * 64, (st >> 1) * SEQ + 256 * op + 128 * rank, pr.fb);
#pragma unroll 1
            for (int k = (fixed < 2) ? 0 : (fixed == 4) ? -2 : 1; k <= 0; k++) {
                pr.next(24576);
#pragma unroll
                for (int c = 0; c < 3; c++) w_tma_load_mc(pr.dst + rank * 12288 + c * 4096, &P.wo, n0 + 128 + 64 * c, krow + k * 256, pr.fb);
            }
        }
    }
}

struct Slot {
    uint32_t bo, dl, par;
};
struct Cons {
    uint32_t bars, rel;
    uint32_t dl0;
    uint32_t lane;
    Slot cur;
    __device__ __forceinline__ Slot slot(int s, uint32_t par) const { return Slot{(uint32_t)s * 8, dl0 + (uint32_t)s * (SLOT >> 4), par}; }
    __device__ __forceinline__ void wait(const Slot& s) const { mbar_wait(bars + BAR_FULL + s.bo, s.par); }
    __device__ __forceinline__ uint32_t peek() const { return mbar_peek(bars + BAR_FULL + cur.bo, cur.par); }
    __device__ __forceinline__ void wait(const Slot& s, uint32_t ok) const { mbar_wait_unless(ok, bars + BAR_FULL + s.bo, s.par); }
    __device__ __forceinline__ void release(uint32_t bo) const {
        asm volatile("{\n.reg .pred p;\nsetp.lt.u32 p, %1, 2;\n@p mbarrier.arrive.shared::cluster.b64 _, [%0];\n}\n" ::"r"(rel + bo), "r"(lane) : "memory");
    }
    __device__ __forceinline__ Slot next() {
        const Slot s = cur;
        const bool wrap = s.bo == (NSLOT - 1) * 8;
        cur.bo = wrap ? 0u : s.bo + 8;
        cur.dl = wrap ? dl0 : s.dl + (SLOT >> 4);
        cur.par = s.par ^ (wrap ? 1u : 0u);
        return s;
    }
};
__host__ __device__ constexpr uint32_t lbo(uint32_t bytes) { return (bytes >> 4) << 16; }

__device__ __forceinline__ float div640(float x) {
    const float q = x * (1.0f / DM);
    return fmaf(fmaf(-q, (float)DM, x), 1.0f / DM, q);
}
__device__ __forceinline__ float sqrt_approx(float x) {
    float y;
    asm("sqrt.approx.ftz.f32 %0, %1;" : "=f"(y) : "f"(x));
    return y;
}
struct LayerNorm {
    uint4 xv[5], wv[5];
    float mean, inv, r;
    uint32_t nmb;
    __nv_bfloat16 *pn, *po;
    static __device__ __forceinline__ float half_sum(float v) {
#pragma unroll
        for (int o = 8; o > 0; o >>= 1) v += __shfl_xor_sync(0xffffffffu, v, o);
        return v;
    }
    __device__ __forceinline__ void load(const __nv_bfloat16* x, const __nv_bfloat16* wr, __nv_bfloat16* out, int t, int l) {
        pn = g_xn + perm_row(t) * DM + 8 * l;
        po = out + t * DM + 8 * l;
        asm volatile("" : "+l"(pn), "+l"(po));
#pragma unroll
        for (int i = 0; i < 5; i++) {
            xv[i] = ldg_stream(reinterpret_cast<const uint4*>(x + t * DM) + l + 16 * i);
            wv[i] = __ldg(reinterpret_cast<const uint4*>(wr) + l + 16 * i);
        }
    }
    __device__ __forceinline__ void stat1() {
        float a[4] = {0.f, 0.f, 0.f, 0.f};
#pragma unroll
        for (int i = 0; i < 20; i++) { const uint32_t u = (&xv[i >> 2].x)[i & 3]; a[i & 3] += bf_lo(u) + bf_hi(u); }
        mean = div640(half_sum((a[0] + a[1]) + (a[2] + a[3])));
        r = 0.f;
    }
    template <int H>
    __device__ __forceinline__ void stat2() {
        float a[4] = {r, 0.f, 0.f, 0.f};
#pragma unroll
        for (int i = H ? 12 : 0; i < (H ? 20 : 12); i++) {
            uint32_t u = (&xv[i >> 2].x)[i & 3];
            asm volatile("" : "+r"(u));
            const float d0 = bf_lo(u) - mean, d1 = bf_hi(u) - mean;
            a[i & 3] = fmaf(d0, d0, fmaf(d1, d1, a[i & 3]));
        }
        r = (a[0] + a[1]) + (a[2] + a[3]);
        if (H) {
            inv = rcp(round_bf16(sqrt_approx(round_bf16(round_bf16(div640(half_sum(r))) + 1e-5f))));
            r = 0.f;
            nmb = pack_bf16(-mean, -mean);
        }
    }
    template <int I>
    __device__ __forceinline__ void piece(int t, int l) {
        uint32_t o[4], z[4];
        float a[4];
#pragma unroll
        for (int j = 0; j < 4; j++) {
            const uint32_t u = (&xv[I].x)[j], w = (&wv[I].x)[j];
            const uint32_t d = add_bf16x2(u, nmb);
            o[j] = pack_bf16(bf_lo(d) * inv, bf_hi(d) * inv);
            z[j] = add_bf16x2(u, o[j]);
            a[j] = fmaf(bf_hi(o[j]), bf_hi(w), bf_lo(o[j]) * bf_lo(w));
        }
        r += (a[0] + a[1]) + (a[2] + a[3]);
        stg128(pn + 128 * I, o[0], o[1], o[2], o[3]);
        stg128p(po + 128 * I, z[0], z[1], z[2], z[3], policy_evict_first());
        if (I == 4) {
            r = half_sum(r);
            if (l == 0) g_r[t] = round_bf16(r);
        }
    }
};

constexpr float SM_SCALE = 0.08838834764831845f * 1.4426950408889634f;

template <int J0, int J1>
__device__ __forceinline__ void exp_part(float (&s)[64], float n0, float n1, float& r0, float& r1) {
    float a1 = 0.f, b1 = 0.f;
#pragma unroll
    for (int j = J0; j < J1; j++) {
        s[4 * j + 0] = ex2(fmaf(s[4 * j + 0], SM_SCALE, n0));
        s[4 * j + 1] = ex2(fmaf(s[4 * j + 1], SM_SCALE, n0));
        s[4 * j + 2] = ex2(fmaf(s[4 * j + 2], SM_SCALE, n1));
        s[4 * j + 3] = ex2(fmaf(s[4 * j + 3], SM_SCALE, n1));
        r0 += s[4 * j + 0]; r1 += s[4 * j + 2];
        if (j == J0) { a1 = s[4 * j + 1]; b1 = s[4 * j + 3]; } else { a1 += s[4 * j + 1]; b1 += s[4 * j + 3]; }
    }
    r0 += a1;
    r1 += b1;
}
__device__ __forceinline__ void sched_barrier(float x, float y, uint32_t scratch) {
    asm volatile("{\n.reg .pred p;\nsetp.lt.f32 p, %0, 0f00000000;\n@p st.shared.f32 [%2], %1;\n}\n" ::"f"(x), "f"(y), "r"(scratch) : "memory");
}
__device__ __forceinline__ void pack_tile(const float (&s)[64], uint32_t (&p)[32]) {
#pragma unroll
    for (int i = 0; i < 32; i++) p[i] = pack_bf16(s[2 * i], s[2 * i + 1]);
}
template <bool ZERO>
__device__ __forceinline__ void gemm_rs(float (&d)[64], const uint32_t (&a)[32], uint32_t dl, int acc = 1) {
    const uint32_t b = dl + lbo(16384);
    if (ZERO) wgmma_rs_n128_z<1>(d, a[0], a[1], a[2], a[3], b);
#pragma unroll
    for (int k = ZERO ? 1 : 0; k < 8; k++) wgmma_rs_n128<1>(d, a[4 * k], a[4 * k + 1], a[4 * k + 2], a[4 * k + 3], b + k * 128, k ? 1 : acc);
}
__device__ __forceinline__ void gemm_pv(float (&d)[64], const uint32_t (&a)[32], uint32_t dl, int acc, int full) {
    const uint32_t b = dl + lbo(16384);
    wgmma_rs_n128<1>(d, a[0], a[1], a[2], a[3], b, acc);
    wgmma_commit();
    if (full) {
        wgmma_fence();
#pragma unroll
        for (int k = 4; k < 8; k++) wgmma_rs_n128<1>(d, a[4 * k], a[4 * k + 1], a[4 * k + 2], a[4 * k + 3], b + k * 128, 1);
        wgmma_commit();
    }
    wgmma_fence();
#pragma unroll
    for (int k = 1; k < 4; k++) wgmma_rs_n128<1>(d, a[4 * k], a[4 * k + 1], a[4 * k + 2], a[4 * k + 3], b + k * 128, 1);
}
template <int ZERO>
__device__ __forceinline__ void gemm_q(float (&d)[64], uint32_t dl, int role) {
    const uint32_t a = dl + role * 512 + lbo(16), b = dl + 1024 + lbo(8192);
    if (ZERO) wgmma_ss_n128_z<0, 1>(d, a, b);
#pragma unroll
    for (int k = ZERO ? 1 : 0; k < 4; k++) wgmma_ss_n128<0, 1>(d, a + k * 2, b + k * 128, 1);
}
template <bool KT, bool ZERO, int K0, int K1>
__device__ __forceinline__ void gemm_kv(float (&d)[64], uint32_t ckv, uint32_t wt, int wg) {
    if (KT) {
        const uint32_t a = wt + wg * 1024 + lbo(16), b = ckv + lbo(16);
        if (ZERO) wgmma_ss_n128_z<1, 0>(d, a, b);
#pragma unroll
        for (int k = ZERO ? 1 : K0; k < K1; k++) wgmma_ss_n128<1, 0>(d, a + k * 128, b + (k >> 2) * 1024 + (k & 3) * 2, 1);
    } else {
        const uint32_t a = ckv + wg * 512 + lbo(16), b = wt + lbo(16384);
        if (ZERO) wgmma_ss_n128_z<0, 1>(d, a, b);
#pragma unroll
        for (int k = ZERO ? 1 : K0; k < K1; k++) wgmma_ss_n128<0, 1>(d, a + (k >> 2) * 1024 + (k & 3) * 2, b + k * 128, 1);
    }
}
__device__ __forceinline__ void mma16816(float& d0, float& d1, float& d2, float& d3, uint32_t a0, uint32_t a1, uint32_t a2, uint32_t a3, uint32_t b0, uint32_t b1) {
    asm volatile("mma.sync.aligned.m16n8k16.row.col.f32.bf16.bf16.f32 {%0,%1,%2,%3}, {%4,%5,%6,%7}, {%8,%9}, {%0,%1,%2,%3};"
                 : "+f"(d0), "+f"(d1), "+f"(d2), "+f"(d3) : "r"(a0), "r"(a1), "r"(a2), "r"(a3), "r"(b0), "r"(b1));
}
__device__ __forceinline__ uint32_t ld_pair(const __nv_bfloat16* p) {
    const unsigned short* u = reinterpret_cast<const unsigned short*>(p);
    return (uint32_t)__ldcg(u) | ((uint32_t)__ldcg(u + 128) << 16);
}
__device__ __forceinline__ void attention_exact(float (&o)[64], const uint32_t (&qf)[32], float& l0, float& l1, int h, int nblk, int rr, int lane) {
    const int q = lane & 3, lr = lane >> 2;
    float m0 = -INFINITY, m1 = -INFINITY;
    l0 = 0.f; l1 = 0.f;
#pragma unroll 1
    for (int cidx = 0; cidx < nblk * 8; cidx++) {
        const int kc = cidx & 7;
        const __nv_bfloat16* kt = g_kv + (size_t)((h * 16 + (cidx >> 3)) * 2) * 16384;
        float sc[8];
#pragma unroll
        for (int i = 0; i < 8; i++) sc[i] = 0.f;
#pragma unroll
        for (int kk = 0; kk < 8; kk++)
#pragma unroll
            for (int nt = 0; nt < 2; nt++) {
                const __nv_bfloat16* b = kt + (16 * kk + 2 * q) * 128 + 16 * kc + 8 * nt + lr;
                mma16816(sc[4 * nt], sc[4 * nt + 1], sc[4 * nt + 2], sc[4 * nt + 3], qf[4 * kk], qf[4 * kk + 1], qf[4 * kk + 2], qf[4 * kk + 3],
                         ld_pair(b), ld_pair(b + 8 * 128));
            }
        const int lim = rr + ((nblk - 1) - (cidx >> 3)) * 128 - 32 * (kc >> 1) - 4 * (kc & 1);
#pragma unroll
        for (int i = 0; i < 8; i++)
            if (2 * (i >> 2) + (i & 1) > lim + 4 * (i & 2)) sc[i] = -INFINITY;
        float x0 = fmaxf(fmaxf(sc[0], sc[1]), fmaxf(sc[4], sc[5])), x1 = fmaxf(fmaxf(sc[2], sc[3]), fmaxf(sc[6], sc[7]));
        x0 = fmaxf(x0, __shfl_xor_sync(0xffffffffu, x0, 1)); x1 = fmaxf(x1, __shfl_xor_sync(0xffffffffu, x1, 1));
        x0 = fmaxf(x0, __shfl_xor_sync(0xffffffffu, x0, 2)); x1 = fmaxf(x1, __shfl_xor_sync(0xffffffffu, x1, 2));
        x0 = fmaxf(x0, m0); x1 = fmaxf(x1, m1);
        const float a0 = ex2((m0 - x0) * SM_SCALE), a1 = ex2((m1 - x1) * SM_SCALE);
        m0 = x0; m1 = x1;
#pragma unroll
        for (int i = 0; i < 8; i++) sc[i] = ex2((sc[i] - ((i & 2) ? m1 : m0)) * SM_SCALE);
        l0 = l0 * a0 + (sc[0] + sc[1]) + (sc[4] + sc[5]);
        l1 = l1 * a1 + (sc[2] + sc[3]) + (sc[6] + sc[7]);
        const uint32_t p0 = pack_bf16(sc[0], sc[1]), p1 = pack_bf16(sc[2], sc[3]), p2 = pack_bf16(sc[4], sc[5]), p3 = pack_bf16(sc[6], sc[7]);
        const __nv_bfloat16* vb = kt + 16384 + (16 * kc + 2 * q) * 128 + lr;
#pragma unroll
        for (int nt = 0; nt < 16; nt++) {
            o[4 * nt] *= a0; o[4 * nt + 1] *= a0; o[4 * nt + 2] *= a1; o[4 * nt + 3] *= a1;
            mma16816(o[4 * nt], o[4 * nt + 1], o[4 * nt + 2], o[4 * nt + 3], p0, p1, p2, p3, ld_pair(vb + 8 * nt), ld_pair(vb + 8 * nt + 8 * 128));
        }
    }
}

__device__ __forceinline__ void signal(uint32_t bars, int wg, int e, int lane) {
    __syncwarp();
    asm volatile("{\n.reg .pred p;\nsetp.eq.u32 p, %1, 0;\n@p mbarrier.arrive.shared::cta.b64 _, [%0];\n}\n" ::"r"(bars + BAR_SIG + (wg * 9 + e) * 8), "r"(lane) : "memory");
}

__device__ __forceinline__ void mod_ffn(const Params& P, uint32_t smem, int mc, int wg);

__device__ __forceinline__ void consumer(const Params& P, uint32_t smem, uint32_t bars, int ca, int cb, int rank, int wg) {
    const int lane = threadIdx.x & 31, w = (threadIdx.x >> 5) & 3, q = lane & 3, lr = lane >> 2;
    PROF(7);
    cluster_wait();
    Cons c{bars, mapa(bars + BAR_EMPTY, lane & 1), (smem & 0x3FFFF) >> 4, (uint32_t)lane, Slot{0u, (smem & 0x3FFFF) >> 4, cb == 8 ? 0u : 1u}};
    PROFG(180);
    PROF(1);
    float o[64], s[64];
    uint32_t pend;
    __nv_bfloat16* ep_ptr;
    int ep_step;
    if (cb == 8) {
        pend = 0;
        ep_ptr = g_ctx + (size_t)(item_h(cb, 2 + ca, 0) * SEQ + 128 * rank + 64 * wg + 16 * w + lr) * HD + 8 * q;
        ep_step = 8 * HD;
    } else {
        const int ln_t = blockIdx.x * 16 + wg * 8 + w * 2 + (lane >> 4);
        const int krow = 64 * wg + 16 * w + lr;
        const int vrow = 64 * wg + 32 * (w >> 1) + 8 * (lr >> 1) + 4 * (w & 1) + (lr & 1);
        ep_step = 2 * 128;
        int m = 0;
        uint32_t lap = 0;
        LayerNorm ln;
        auto step = [&](auto kt, auto kc, float (&d)[64], int hh) {
            const Slot sa = c.slot(slot_a(kc.value), 0), sw = c.slot(slot_w(m), lap ^ (m >> 1));
            lap ^= m >> 1;
            m = (m == 2) ? 0 : m + 1;
            TR(1 + (hh * 8 + (kt.value ? 0 : 4) + kc.value) * 2);
            if (kt.value && hh == 0) c.wait(sa);
            c.wait(sw);
            TR(2 + (hh * 8 + (kt.value ? 0 : 4) + kc.value) * 2);
            wgmma_fence();
            gemm_kv<kt.value, kc.value == 0, 0, KVSPLIT>(d, sa.dl, sw.dl, wg);
            wgmma_commit();
            wgmma_wait<1>();
            if (!(kt.value && kc.value == 0 && hh == 0)) c.release(pend);
            if (!kt.value && kc.value > 0 && hh == 3) c.release(slot_a(kc.value - 1) * 8);
            pend = sw.bo;
            wgmma_fence();
            gemm_kv<kt.value, false, KVSPLIT, 8>(d, sa.dl, sw.dl, wg);
            wgmma_commit();
        };
#pragma unroll 1
        for (int hh = 0; hh < 4; hh++) {
            __nv_bfloat16* base = g_kv + (size_t)(((cb + 8 * kv_round(hh)) * 16 + 2 * ca + rank) * 2) * 16384 + 8 * q;
            auto ln_stage = [&](auto pos) {
                constexpr int j = (pos.value + 8 - LNOFF % 8) % 8;
                if (hh == wg + (LNOFF + j) / 8) {
                    if (j == 0) ln.stat1();
                    if (j == 1) ln.template stat2<0>();
                    if (j == 2) ln.template stat2<1>();
                    if constexpr (j >= 3) ln.template piece<j - 3>(ln_t, lane & 15);
                    if (j == 7) signal(bars, wg, 0, lane);
                }
                if (pos.value == (LNOFF - LNLEAD) % 8 && hh == wg + (LNOFF - LNLEAD) / 8) ln.load(P.x, P.wr, P.out, ln_t, lane & 15);
            };
            for4([&](auto kc) {
                step(TrueT{}, kc, s, hh);
                if (hh > 0) {
                    if (kc.value == 0) fence_regs(o);
                    store_chunk<kc.value>(o, ep_ptr, ep_ptr + ep_step, 1.f, 1.f);
                    if (kc.value == 3) signal(bars, wg, hh, lane);
                }
                ln_stage(kc);
            });
            for4([&](auto kc) {
                step(FalseT{}, kc, o, hh);
                if (kc.value == 0) fence_regs(s);
                store_chunk<kc.value>(s, base + krow * 128, base + (krow + 8) * 128, 1.f, 1.f);
                ln_stage(IntT<kc.value + 4>{});
            });
            PROF(24 + hh);
            if (hh == 1) PROFG(181);
            ep_ptr = base + 16384 + vrow * 128;
        }
    }
    PROFG(182);
    PROF(2);
    uint32_t pf[32];
    {
        uint32_t qf[32];
        float l0 = 0.25f, l1 = 0.25f;
        const int bar_me = 2 + wg, bar_other = 3 - wg;
#pragma unroll 1
        for (int j = 0; j < n_items(ca, cb); j++) {
            const int rd = item_rd(ca, cb, j), h = item_h(cb, rd, j), p = item_q(ca, cb, rd);
            const int role = wg ^ (j & 1);
            const int nrest = 2 * p + role;
            Slot kfirst;
            const int lim = 64 * (role ^ rank) + 16 * w + lr - 8 * q;
            const uint64_t pol = policy_sel(j == 1 || j == 2);
            {
                auto qstep = [&](auto zero, int ks) {
                    const Slot sl = c.next();
                    c.wait(sl);
                    BP(2, 5 + 3 * ks);
                    wgmma_fence();
                    gemm_q<zero.value>(s, sl.dl, role);
                    wgmma_commit();
                    wgmma_wait<1>();
                    if (!zero.value || j > 0 || cb < 8) c.release(pend);
                    pend = sl.bo;
                };
                qstep(TrueT{}, 0);
                if (j == 0 && cb < 8) c.release(slot_a(3) * 8);
                fence_regs(o);
                l0 += __shfl_xor_sync(0xffffffffu, l0, 1); l1 += __shfl_xor_sync(0xffffffffu, l1, 1);
                l0 += __shfl_xor_sync(0xffffffffu, l0, 2); l1 += __shfl_xor_sync(0xffffffffu, l1, 2);
                l0 = rcp(l0); l1 = rcp(l1);
                for4([&](auto i) {
                    constexpr int B = 16 * i.value;
#pragma unroll
                    for (int r = 0; r < 2; r++) {
                        if (1 + 2 * i.value + r == 7 && !(role | rank)) named_sync(bar_me, 256);
                        qstep(FalseT{}, 1 + 2 * i.value + r);
                        const float f = r ? l1 : l0;
                        stg128p(ep_ptr + r * ep_step + 2 * B, pack_bf16(o[B + 2 * r] * f, o[B + 2 * r + 1] * f), pack_bf16(o[B + 2 * r + 4] * f, o[B + 2 * r + 5] * f),
                                pack_bf16(o[B + 2 * r + 8] * f, o[B + 2 * r + 9] * f), pack_bf16(o[B + 2 * r + 12] * f, o[B + 2 * r + 13] * f), pol);
#pragma unroll
                        for (int k = 0; k < 8; k++) {
                            float& v = o[B + 4 * (k >> 1) + 2 * r + (k & 1)];
                            v = (2 * B + k > lim + 8 * r) ? -1e30f : 0.f;
                            asm volatile("" : "+f"(v));
                        }
                    }
                });
                signal(bars, wg, (cb == 8 ? 0 : 4) + j, lane);
                PROF(11 + rd * 4);
                qstep(FalseT{}, 9);
                if (!role) { const Slot sl = c.next(); c.wait(sl); c.release(sl.bo); }
                kfirst = c.next();
                c.wait(kfirst);
                wgmma_wait<0>();
                BP(2, 34);
                c.release(pend);
                fence_regs(s);
                pack_tile(s, qf);
            }
            Slot vskip = c.cur;
            if (!role) vskip = c.next();
            PROF(8 + rd * 4);
            if (cb == 8) PROF(40 + 3 * j);
            fence_regs(qf); fence_regs(o);
            if (!role && rank) named_sync(bar_me, 256);
            BP(2, 36);
            auto first_qk = [&](auto half) {
                wgmma_fence();
#pragma unroll
                for (int k = 0; k < 8; k++) {
                    if (half.value) wgmma_rs_n64<1>(o, qf[4 * k], qf[4 * k + 1], qf[4 * k + 2], qf[4 * k + 3], kfirst.dl + lbo(16384) + k * 128, 1);
                    else wgmma_rs_n128<1>(o, qf[4 * k], qf[4 * k + 1], qf[4 * k + 2], qf[4 * k + 3], kfirst.dl + lbo(16384) + k * 128, 1);
                }
                wgmma_commit();
                named_arrive(bar_other, 256);
                if (!role) { c.wait(vskip); c.release(vskip.bo); }
                wgmma_wait<0>();
            };
            if (role == rank) first_qk(TrueT{});
            else first_qk(FalseT{});
            BP(2, 38);
            fence_regs(o);
            c.release(kfirst.bo);
            uint32_t ready = c.peek();
            float n0 = fmaxf(fmaxf(fmaxf(o[0], o[1]), fmaxf(o[4], o[5])), fmaxf(fmaxf(o[8], o[9]), fmaxf(o[12], o[13])));
            float n1 = fmaxf(fmaxf(fmaxf(o[2], o[3]), fmaxf(o[6], o[7])), fmaxf(fmaxf(o[10], o[11]), fmaxf(o[14], o[15])));
            n0 = __shfl_sync(0xffffffffu, n0, lane & 28); n1 = __shfl_sync(0xffffffffu, n1, lane & 28);
            n0 *= -SM_SCALE; n1 *= -SM_SCALE;
            l0 = 0.f; l1 = 0.f;
#pragma unroll
            for (int i = 0; i < 64; i++) s[i] = o[i];
            exp_part<0, 8>(s, n0, n1, l0, l1);
#pragma unroll
            for (int i = 0; i < 16; i++) pf[i] = pack_bf16(s[2 * i], s[2 * i + 1]);
            if (role != rank) {
                exp_part<8, 16>(s, n0, n1, l0, l1);
#pragma unroll
                for (int i = 16; i < 32; i++) pf[i] = pack_bf16(s[2 * i], s[2 * i + 1]);
            } else {
#pragma unroll
                for (int i = 16; i < 32; i++) pf[i] = 0u;
            }
            PROF(9 + rd * 4);
            if (cb == 8) PROF(41 + 3 * j);
#pragma unroll 1
            for (int it = 0; it < nrest; it++) {
                const Slot sk = c.next(), sv = c.next();
                LP(0);
                c.wait(sk, ready);
                fence_regs(o); fence_regs(pf);
                LP(1);
                named_sync(bar_me, 256);
                LP(2);
                if (it < 3) BP(2, 42 + 4 * it);
                if (it >= nrest - 2) BP(1, 62 + 4 * (it - nrest + 2));
                wgmma_fence();
                gemm_rs<true>(s, qf, sk.dl);
                wgmma_commit();
                c.wait(sv);
                wgmma_fence();
                gemm_pv(o, pf, sv.dl, it, it | (role ^ rank));
                wgmma_commit();
                named_arrive(bar_other, 256);
                LP(3);
                wgmma_wait<2>();
                LP(4);
                c.release(sk.bo);
                fence_regs(s);
                exp_part<0, SPLITJ>(s, n0, n1, l0, l1);
                sched_barrier(l0, l1, bars + MISC_OFF + 16);
                LP(5);
                wgmma_wait<0>();
                LP(6);
                c.release(sv.bo);
                ready = c.peek();
                fence_regs(o); fence_regs(pf);
                exp_part<SPLITJ, 16>(s, n0, n1, l0, l1);
                pack_tile(s, pf);
            }
            PROF(10 + rd * 4);
            if (cb == 8) PROF(42 + 3 * j);
            PROFG(183 + rd);
            const Slot sv = c.next();
            BP(1, 0);
            c.wait(sv, ready);
            const bool bad = __any_sync(0xffffffffu, !(l0 < 0x1p60f && l1 < 0x1p60f));
            if (__builtin_expect(bad || nrest == 0, 0)) {
#pragma unroll
                for (int i = 0; i < 64; i++) o[i] = 0.f;
                if (bad) {
                    attention_exact(o, qf, l0, l1, h, nrest + 1, lim, lane);
#pragma unroll
                    for (int i = 0; i < 32; i++) pf[i] = 0u;
                }
            }
            fence_regs(o); fence_regs(pf);
            if (!role) named_sync(bar_me, 256);
            BP(1, 2);
            wgmma_fence();
            gemm_rs<false>(o, pf, sv.dl);
            wgmma_commit();
            pend = sv.bo;
            ep_ptr = g_ctx + (size_t)(h * SEQ + 256 * p + 128 * rank + 64 * role + 16 * w + lr) * HD + 8 * q;
            ep_step = 8 * HD;
        }
        l0 += __shfl_xor_sync(0xffffffffu, l0, 1); l1 += __shfl_xor_sync(0xffffffffu, l1, 1);
        l0 += __shfl_xor_sync(0xffffffffu, l0, 2); l1 += __shfl_xor_sync(0xffffffffu, l1, 2);
        l0 = rcp(l0); l1 = rcp(l1);
        sched_barrier(l0, l1, bars + MISC_OFF + 16);
        wgmma_wait<0>();
        c.release(pend);
        fence_regs(o); fence_regs(pf);
#pragma unroll
        for (int i = 0; i < 32; i++) pf[i] = pack_bf16(o[2 * i] * ((i & 1) ? l1 : l0), o[2 * i + 1] * ((i & 1) ? l1 : l0));
    }
    PROFG(187);
    PROF(3);
    if (cb == 8) {
#pragma unroll
        for (int i = 0; i < 8; i++) stg128(ep_ptr + (i & 1) * 8 * HD + 32 * (i >> 1), pf[4 * (i & 6) + (i & 1)], pf[4 * (i & 6) + (i & 1) + 2], pf[4 * (i & 6) + (i & 1) + 4], pf[4 * (i & 6) + (i & 1) + 6]);
        signal(bars, wg, 8, lane);
        cluster_arrive();
        named_sync(1, 256);
        mod_ffn(P, smem, 2 * ca + rank, wg);
    } else
    {
        float a1[64], a2[96];
        uint32_t px = 0, py = 0;
        auto mma1 = [&](const Slot& x, int acc) {
#pragma unroll
            for (int k = 0; k < 4; k++) wgmma_ss_n128<0, 1>(a1, x.dl + wg * 512 + lbo(16) + k * 2, x.dl + 1024 + lbo(4096) + (k >> 1) * 512 + (k & 1) * 128, k ? 1 : acc);
        };
        auto mma2 = [&](const Slot& x, const Slot& y, int acc) {
#pragma unroll
            for (int k = 0; k < 4; k++) wgmma_ss_n192<0, 1>(a2, x.dl + wg * 512 + lbo(16) + k * 2, y.dl + lbo(4096) + (k >> 1) * 768 + (k & 1) * 128, k ? 1 : acc);
        };
#pragma unroll 1
        for (int t = 0, more = 1; more; t++) {
            const Slot sx = c.next(), sy = c.next();
            OP(2 * t);
            c.wait(sx);
            OP(2 * t + 1);
            wgmma_fence();
            mma1(sx, t);
            wgmma_commit();
            wgmma_wait<1>();
            asm volatile("ld.shared.u32 %0, [%1];" : "=r"(more) : "r"(bars + CTL_OFF + sx.bo) : "memory");
            if (t > 0) { c.release(px); c.release(py); }
            px = sx.bo; py = sy.bo;
            c.wait(sy);
            wgmma_fence();
            mma2(sx, sy, t);
            wgmma_commit();
            more = !__any_sync(0xffffffffu, more);
            if (t == 0) {
#pragma unroll
                for (int i = 0; i < 4; i++) stg128(ep_ptr + 32 * i, pf[8 * i], pf[8 * i + 2], pf[8 * i + 4], pf[8 * i + 6]);
            }
            if (t == 1) {
#pragma unroll
                for (int i = 0; i < 4; i++) stg128(ep_ptr + 8 * HD + 32 * i, pf[8 * i + 1], pf[8 * i + 3], pf[8 * i + 5], pf[8 * i + 7]);
                signal(bars, wg, 4 + n_items(ca, cb), lane);
            }
        }
        OP(60);
        const Slot x0 = c.next(), x1 = c.next(), x2 = c.next(), y0 = c.next(), y1 = c.next(), y2 = c.next(), fr = c.next();

        const int cw = __reduce_or_sync(0xffffffffu, wg * 4 + w);
        const int orow = unperm_row(256 * out_p(ca, cb) + 128 * rank + 16 * cw), ocol = 320 * (ca >> 2);
        const uint32_t sa = ((lane & 7) + (lane & 8)) * 128, sx = (lane >> 4) ^ (lane & 7);
        auto send = [&](auto chv, uint32_t box) {
            constexpr int ch = chv.value;
#pragma unroll
            for (int i = 0; i < 4; i++) {
                uint32_t r[4];
#pragma unroll
                for (int e = 0; e < 4; e++) {
                    const int k = 32 * ch + 8 * i + 2 * e;
                    r[e] = (ch < 2) ? pack_bf16(a1[k & 63], a1[(k & 63) + 1]) : pack_bf16(a2[ch < 2 ? 0 : k - 64], a2[ch < 2 ? 1 : k - 63]);
                }
                asm volatile("stmatrix.sync.aligned.m8n8.x4.shared.b16 [%0], {%1, %2, %3, %4};"
                             ::"r"(box + sa + ((sx ^ (2 * i)) << 4)), "r"(r[0]), "r"(r[1]), "r"(r[2]), "r"(r[3]) : "memory");
            }
            asm volatile("fence.proxy.async.shared::cta;" ::: "memory");
            __syncwarp();
            asm volatile(ELECT "cp.reduce.async.bulk.tensor.2d.global.shared::cta.add.bulk_group [%0, {%2, %3}], [%1];\n}\n"
                         ::"l"(&P.outm), "r"(box), "r"(ocol + 64 * ch), "r"(orow) : "memory");
        };
        auto addr = [&](const Slot& t) { return smem + t.bo * (SLOT / 8); };
        c.wait(x0);
        wgmma_fence();
        mma1(x0, 1);
        wgmma_commit();
        wgmma_wait<1>();
        c.release(px); c.release(py);
        c.wait(x1);
        c.wait(x2);
        mbar_wait(bars + BAR_DEP, 0);
        wgmma_fence();
        mma1(x1, 1);
        mma1(x2, 1);
        wgmma_commit();
        c.wait(y0);
        wgmma_fence();
        mma2(x0, y0, 1);
        wgmma_commit();
        mbar_wait(bars + BAR_EMPTY + fr.bo, fr.par ^ 1);
        c.wait(y1);
        wgmma_wait<1>();
        fence_regs(a1);
        OP(61);
        send(IntT<0>{}, addr(fr) + cw * 4096);
        wgmma_fence();
        mma2(x1, y1, 1);
        wgmma_commit();
        send(IntT<1>{}, addr(fr) + cw * 4096 + 2048);
        OP(62);
        c.wait(y2);
        wgmma_fence();
        mma2(x2, y2, 1);
        wgmma_commit();
        wgmma_wait<0>();
        fence_regs(a2);
        PROFG(188);
        PROF(4);
        send(IntT<2>{}, addr(x0) + cw * 2048);
        send(IntT<3>{}, addr(x1) + cw * 2048);
        send(IntT<4>{}, addr(x2) + cw * 2048);
        PROF(5);
        asm volatile("cp.async.bulk.commit_group;\ncp.async.bulk.wait_group.read 0;" ::: "memory");
    }
    PROF(6);
}

__device__ __forceinline__ void mod_ffn(const Params& P, uint32_t smem, int mc  , int wg) {
    const int tid = threadIdx.x - 128, lane = tid & 31, cw = tid >> 5, q = lane & 3, lr = lane >> 2;
    const uint32_t xs = smem + 6 * SLOT, hs = xs + 10240 + wg * 1024, wmax = xs + 12288, sidx = wmax + 64, rbar = xs + 13312 + wg * 32;
    const uint32_t ring = smem + wg * 3 * SLOT;
    const int f0 = mc + 4 * wg, nunit = ((34 - f0) >> 3) * 8;
    const bool lead = __reduce_or_sync(0xffffffffu, cw & 3) == 0;
    auto lds = [](uint32_t a) { uint32_t v; asm volatile("ld.shared.u32 %0, [%1];" : "=r"(v) : "r"(a) : "memory"); return v; };
    auto sts = [](uint32_t a, uint32_t v) { asm volatile("st.shared.u32 [%0], %1;" ::"r"(a), "r"(v) : "memory"); };
    auto issue = [&](int u, int st) {
        if (lead && u < nunit) {
            const int fc = (f0 + (u & ~7)) * 64, k = u & 7;
            const uint32_t dst = ring + st * SLOT, bar = rbar + st * 8;
            w_expect_tx(bar, k == 7 ? 16384 : SLOT);
            if (k < 5) {
                w_tma_load_stream(dst, &P.wg, fc, k * 128, bar);
                w_tma_load_stream(dst + 16384, &P.wu, fc, k * 128, bar);
            } else {
#pragma unroll 1
                for (int b = 0; b < (k == 7 ? 2 : 4); b++) w_tma_load_stream(dst + b * 8192, &P.wd, (4 * (k - 5) + b) * 64, fc, bar);
            }
        }
    };
    if ((tid & 127) == 0) {
        mbar_init(rbar, 1); mbar_init(rbar + 8, 1); mbar_init(rbar + 16, 1);
        asm volatile("fence.mbarrier_init.release.cluster;" ::: "memory");
    }
    mbar_wait(smem + NSLOT * SLOT + BAR_DEP, 0);
    asm volatile("fence.proxy.async.shared::cta;" ::: "memory");
    named_sync(1, 256);
    PROF(1);
#pragma unroll 1
    for (int u = 0; u < 3; u++) issue(u, u);
    uint32_t key[8];
#pragma unroll
    for (int i = 0; i < 8; i++) {
        const int t = tid + 256 * i;
        uint32_t b = __float_as_uint(__ldcg(g_r + t) + 0.f) >> 16;
        b = (b & 0x8000u) ? (~b & 0xffffu) : (b | 0x8000u);
        key[i] = (b << 16) | (uint32_t)(0xffff - t);
    }
#pragma unroll 1
    for (int rnd = 0; rnd < 8; rnd++) {
        uint32_t mx = key[0];
#pragma unroll
        for (int i = 1; i < 8; i++) mx = max(mx, key[i]);
        sts(wmax + ((rnd & 1) * 8 + cw) * 4, __reduce_max_sync(0xffffffffu, mx));
        named_sync(1, 256);
        mx = __reduce_max_sync(0xffffffffu, lds(wmax + ((rnd & 1) * 8 + (lane & 7)) * 4));
#pragma unroll
        for (int i = 0; i < 8; i++) if (key[i] == mx) key[i] = 0;
        if (cw == rnd) sts(sidx + rnd * 4, 0xffff - (mx & 0xffffu));
    }
    __syncwarp();
    {
        const int t = lds(sidx + cw * 4);
        const uint4* src = reinterpret_cast<const uint4*>(g_xn + perm_row(t) * DM);
#pragma unroll
        for (int i = 0; i < 3; i++) {
            const int ch = lane + 32 * i;
            if (ch < 80) {
                const uint4 v = __ldcg(src + ch);
                asm volatile("st.shared.v4.b32 [%0], {%1, %2, %3, %4};" ::"r"(xs + (ch >> 3) * 1024 + cw * 128 + ((ch ^ cw) & 7) * 16), "r"(v.x), "r"(v.y), "r"(v.z), "r"(v.w) : "memory");
            }
        }
        asm volatile("fence.proxy.async.shared::cta;" ::: "memory");
    }
    named_sync(1, 256);
    PROF(3);
    float y[10][4];
#pragma unroll
    for (int i = 0; i < 10; i++) { y[i][0] = 0.f; y[i][1] = 0.f; y[i][2] = 0.f; y[i][3] = 0.f; }
    int st = 0, ph = 0, u = 0;
    auto begin = [&]() { mbar_wait(rbar + st * 8, ph); wgmma_fence(); return (((ring + st * SLOT) & 0x3FFFF) >> 4) + lbo(16); };
    auto end = [&]() {
        wgmma_commit();
        wgmma_wait<0>();
        named_sync(4 + wg, 128);
        issue(u + 3, st);
        u++;
        ph ^= st == 2;
        st = (st == 2) ? 0 : st + 1;
    };
    const uint32_t dx = ((xs & 0x3FFFF) >> 4) + lbo(16), dh = ((hs & 0x3FFFF) >> 4) + lbo(16);
#pragma unroll 1
    while (u < nunit) {
        float g[4], v[4];
#pragma unroll 1
        for (int kc = 0; kc < 5; kc++) {
            const uint32_t da = begin();
#pragma unroll
            for (int k = 0; k < 8; k++) {
                const uint32_t db = dx + (2 * kc + (k >> 2)) * 64 + (k & 3) * 2;
                wgmma_ss_n8<1, 0>(g, da + k * 128, db, k ? 1 : kc);
                wgmma_ss_n8<1, 0>(v, da + 1024 + k * 128, db, k ? 1 : kc);
            }
            end();
        }
        fence_regs(g); fence_regs(v);
#pragma unroll
        for (int e = 0; e < 4; e++) {
            const float gp = round_bf16(g[e]);
            const float hv = round_bf16(__fdividef(gp, 1.0f + __expf(fminf(-gp, 80.f)))) * round_bf16(v[e]);
            const int tok = 2 * q + (e & 1), ch = 2 * (cw & 3) + (e >> 1);
            asm volatile("st.shared.u16 [%0], %1;" ::"r"(hs + tok * 128 + ((ch ^ tok) * 16) + lr * 2), "h"((unsigned short)pack_bf16(hv, 0.f)) : "memory");
        }
        asm volatile("fence.proxy.async.shared::cta;" ::: "memory");
        named_sync(4 + wg, 128);
#pragma unroll
        for (int k3 = 0; k3 < 3; k3++) {
            const uint32_t da = begin();
#pragma unroll
            for (int b = 0; b < (k3 == 2 ? 2 : 4); b++)
#pragma unroll
                for (int k = 0; k < 4; k++) wgmma_ss_n8<1, 0>(y[4 * k3 + b], da + b * 512 + k * 128, dh + k * 2, 1);
            end();
        }
    }
    PROF(5);
#pragma unroll
    for (int i = 0; i < 10; i++) {
        fence_regs(y[i]);
#pragma unroll
        for (int e = 0; e < 4; e++) g_ypart[((mc * 2 + wg) * 8 + 2 * q + (e & 1)) * DM + 64 * i + 16 * (cw & 3) + lr + 8 * (e >> 1)] = y[i][e];
    }
    named_sync(1, 256);
    if (tid == 0) {
        flag_add(F_MODP);
        flag_wait<100>(F_MODP, 4u * (lds(smem + NSLOT * SLOT + MISC_OFF) + 1));
    }
    named_sync(1, 256);
    PROF(6);
    {
        const int c = 2 * mc + wg, t = lds(sidx + c * 4);
        const float rs = round_bf16(__fdividef(1.0f, 1.0f + __expf(fminf(-__ldcg(g_r + t), 80.f))));
#pragma unroll
        for (int i = 0; i < 3; i++) {
            const int c2 = (tid & 127) + 128 * i;
            if (c2 < DM / 2) {
                float y0 = 0.f, y1 = 0.f;
#pragma unroll
                for (int k = 0; k < 8; k++) {
                    const float2 v = __ldcg(reinterpret_cast<const float2*>(g_ypart + (k * 8 + c) * DM) + c2);
                    y0 += v.x; y1 += v.y;
                }
                asm volatile("red.relaxed.gpu.global.add.noftz.bf16x2 [%0], %1;" ::"l"(P.out + t * DM + 2 * c2), "r"(pack_bf16(round_bf16(y0) * rs, round_bf16(y1) * rs)) : "memory");
            }
        }
    }
    PROF(7);
}

__global__ void __cluster_dims__(2, 1, 1) __launch_bounds__(384, 1) fused_kernel(const __grid_constant__ Params P) {
    extern __shared__ __align__(1024) uint8_t smem_raw[];
    const uint32_t smem = (smem_u32(smem_raw) + 1023u) & ~1023u;
    const uint32_t bars = smem + NSLOT * SLOT;
    const int wgi = __reduce_or_sync(0xffffffffu, threadIdx.x >> 7);
    const int cl = blockIdx.x >> 1, rank = blockIdx.x & 1, ca = cl & 7, cb = cl >> 3;
    PROFG(30);
    PROF(0);
    if (threadIdx.x == 64) {
        const uint32_t fa = bars + BAR_FULL + slot_a(0) * 8, fw = bars + BAR_FULL + slot_w(0) * 8;
        mbar_init(fa, 1); mbar_init(fw, 1);
        asm volatile("fence.mbarrier_init.release.cluster;" ::: "memory");
        if (cb < 8) {
            mbar_expect_tx(fa, SLOT);
            mbar_expect_tx(fw, SLOT);
            tma_load(smem + slot_a(0) * SLOT, &P.ckv, 0, (2 * ca + rank) * 128, fa);
            tma_load(smem + slot_w(0) * SLOT, &P.wuk, (cb + 8 * kv_round(0)) * 128, 0, fw);
            tma_load(smem + slot_w(0) * SLOT + 16384, &P.wuk, (cb + 8 * kv_round(0)) * 128 + 64, 0, fw);
            tma_load(smem + slot_a(0) * SLOT + 16384, &P.ckv, 64, (2 * ca + rank) * 128, fa);
        }
    } else if (threadIdx.x == 0) {
#pragma unroll
        for (int i = 0; i < NSLOT; i++) {
            if (i != slot_a(0) && i != slot_w(0)) mbar_init(bars + BAR_FULL + i * 8, 1);
            mbar_init(bars + BAR_EMPTY + i * 8, 16);
        }
        if (cb < 8) {
            mbar_arrive(bars + BAR_FULL + 16);
            asm volatile("mbarrier.arrive.shared::cta.b64 _, [%0], 16;" ::"r"(bars + BAR_EMPTY + 16) : "memory");
        }
        asm volatile("fence.mbarrier_init.release.cluster;" ::: "memory");
        PROF(24);
    } else if (threadIdx.x == 32) {
#pragma unroll
        for (int i = 0; i < 18; i++) mbar_init(bars + BAR_SIG + i * 8, 4);
#pragma unroll
        for (int i = 0; i < 18; i++) mbar_init(bars + BAR_DEP + i * 8, 1);
        asm volatile("fence.mbarrier_init.release.cluster;" ::: "memory");
    }
    __syncthreads();
    PROF(29);
    cluster_arrive();
    if (wgi > 0) {
        asm volatile("setmaxnreg.inc.sync.aligned.u32 232;");
        consumer(P, smem, bars, ca, cb, rank, wgi - 1);
        PROFG(31);
        PROFDUMP();
    } else {
        asm volatile("setmaxnreg.dec.sync.aligned.u32 40;");
        const int w = __reduce_or_sync(0xffffffffu, threadIdx.x >> 5), lane = threadIdx.x & 31;
        if (threadIdx.x == 32) {
            prefetch_map(&P.wuv); prefetch_map(&P.xn); prefetch_map(&P.wq); prefetch_map(&P.kv); prefetch_map(&P.ctx); prefetch_map(&P.wo); prefetch_map(&P.outm);
        }
        __syncwarp();
        cluster_wait();
        PROF(27);
        {
            if (w == 0) {
                producer(P, smem, bars, ca, cb, rank);
            } else if (w < 3 && lane == 0) {
                const int wg = w - 1;
#pragma unroll 1
                for (int i = (cb == 8); i < (cb == 8 ? 9 : 5 + n_items(ca, cb)); i++) {
                    const int nb = wg + (LNOFF + 7 - 4) / 8;
                    const int e = (cb == 8) ? i : (i < nb) ? i + 1 : (i == nb) ? 0 : i;
                    mbar_wait_sleep(bars + BAR_SIG + (wg * 9 + e) * 8, 0);
                    int f;
                    if (cb == 8) f = F_CTX + (2 + ca) * 16 + rank;
                    else if (e == 0) {
                        f = F_LN;
                        if ((ca & 3) == 0 && rank == 0 && wg == 0) g_flags[(F_POOL + out_p(ca, cb) * 2 + (ca >> 2)) * 8] = 8;
                    }
                    else if (e < 5) f = F_KV + cb + 8 * kv_round(e - 1);
                    else { const int rd = item_rd(ca, cb, e - 5); f = F_CTX + rd * 16 + item_p(ca, rd) * 2 + rank; }
                    flag_add(f);
                }
            } else if (lane == 0) {
                const uint32_t epoch = read_epoch();
                asm volatile("st.shared.u32 [%0], %1;" ::"r"(bars + MISC_OFF), "r"(epoch) : "memory");
#pragma unroll 1
                for (int e = 0; e < 9; e++) {
                    int f;
                    uint32_t n;
                    if (e == 0) { f = F_LN; n = 256; }
                    else if (cb == 8) { f = F_KV + item_h(cb, 2 + ca, e - 1); n = 32; }
                    else if (e < 5) { f = F_KV + cb + 8 * (e - 1); n = 32; }
                    else { f = F_CTX + (e - 5) * 16 + out_p(ca, cb) * 2 + rank; n = 16; }
                    flag_wait<200>(f, n * (epoch + 1));
                    fence_proxy_async();
                    mbar_arrive(bars + BAR_DEP + e * 8);
                }
            }
        }
        if (cb == 8) { __syncwarp(); cluster_arrive(); cluster_wait(); }
        PROFG(31);
        PROFDUMP();
    }
}

typedef CUresult (*EncodeFn)(CUtensorMap*, CUtensorMapDataType, cuuint32_t, void*, const cuuint64_t*, const cuuint64_t*, const cuuint32_t*,
                             const cuuint32_t*, CUtensorMapInterleave, CUtensorMapSwizzle, CUtensorMapL2promotion, CUtensorMapFloatOOBfill);

void make_map(EncodeFn fn, CUtensorMap* m, const void* ptr, uint64_t rows, uint64_t cols, uint32_t box_rows) {
    cuuint64_t dims[2] = {cols, rows};
    cuuint64_t strides[1] = {cols * 2};
    cuuint32_t box[2] = {64, box_rows};
    cuuint32_t es[2] = {1, 1};
    fn(m, CU_TENSOR_MAP_DATA_TYPE_BFLOAT16, 2, const_cast<void*>(ptr), dims, strides, box, es, CU_TENSOR_MAP_INTERLEAVE_NONE,
       CU_TENSOR_MAP_SWIZZLE_128B, CU_TENSOR_MAP_L2_PROMOTION_L2_128B, CU_TENSOR_MAP_FLOAT_OOB_FILL_NONE);
}

}

extern "C" void kernel_launch(void* const* d_in, const int* in_sizes, int n_in, void* d_out, int out_size) {
    (void)in_sizes; (void)n_in; (void)out_size;
    void* fnp = nullptr;
    cudaDriverEntryPointQueryResult qr;
    cudaGetDriverEntryPoint("cuTensorMapEncodeTiled", &fnp, cudaEnableDefault, &qr);
    EncodeFn fn = (EncodeFn)fnp;
    void *xn, *kv, *ctx;
    cudaGetSymbolAddress(&xn, g_xn);
    cudaGetSymbolAddress(&kv, g_kv);
    cudaGetSymbolAddress(&ctx, g_ctx);
    Params P;
    make_map(fn, &P.ckv, d_in[1], SEQ, DC, 128);
    make_map(fn, &P.wq, d_in[2], DM, NH * HD, 64);
    make_map(fn, &P.wuk, d_in[3], DC, NH * HD, 128);
    make_map(fn, &P.wuv, d_in[4], DC, NH * HD, 128);
    make_map(fn, &P.wo, d_in[5], NH * HD, DM, 32);
    make_map(fn, &P.xn, xn, SEQ, DM, 128);
    make_map(fn, &P.kv, kv, NH * 16 * 2 * 128, 128, 128);
    make_map(fn, &P.ctx, ctx, NH * SEQ, HD, 128);
    P.x = (const __nv_bfloat16*)d_in[0];
    P.wr = (const __nv_bfloat16*)d_in[7];
    make_map(fn, &P.wg, d_in[8], DM, FF, 128);
    make_map(fn, &P.wu, d_in[9], DM, FF, 128);
    make_map(fn, &P.wd, d_in[10], FF, DM, 64);
    make_map(fn, &P.outm, d_out, SEQ, DM, 16);
    P.out = (__nv_bfloat16*)d_out;
    cudaFuncSetAttribute(fused_kernel, cudaFuncAttributeMaxDynamicSharedMemorySize, SMEM_BYTES);
    fused_kernel<<<NCTA, 384, SMEM_BYTES>>>(P);
}
```

```cpp
#include <cuda_runtime.h>
#include <cuda_bf16.h>
#include <cuda.h>
#include <stdint.h>

namespace {

constexpr int SEQ = 2048, DM = 640, DC = 512, NH = 32, HD = 128, FF = 1728;
constexpr int NSLOT = 7, SLOT = 32768;
constexpr int NCTA = 132;
constexpr int KVSPLIT = 1;
constexpr int LNOFF = 4, LNLEAD = 2;
constexpr int SPLITJ = 8;
constexpr uint32_t DESC_HI = (1024u >> 4) | (1u << 30);
constexpr int SMEM_BYTES = NSLOT * SLOT + 3072;

constexpr int BAR_FULL = 0, BAR_EMPTY = 64, BAR_SIG = 128  , BAR_DEP = 320  , BAR_MAIL = 400  ;
constexpr int MISC_OFF = 512  , MAIL_OFF = 544  , CTL_OFF = 576  ;

constexpr int F_EPOCH = 0, F_LN = 1, F_MODP = 3, F_KV = 4  , F_CTX = 36  , F_POOL = 100  , F_NUM = 116;

__device__ __align__(1024) __nv_bfloat16 g_xn[SEQ * DM];
__device__ __align__(1024) __nv_bfloat16 g_kv[NH * 16 * 2 * 128 * 128];
__device__ __align__(1024) __nv_bfloat16 g_ctx[NH * SEQ * HD];
__device__ __align__(16) float g_r[SEQ];
__device__ __align__(16) float g_ypart[8 * 8 * DM];
__device__ uint32_t g_flags[F_NUM * 8];

struct TrueT { static constexpr bool value = true; };
struct FalseT { static constexpr bool value = false; };

struct Params {
    CUtensorMap ckv, wuk, wuv, xn, wq, kv, ctx, wo, wg, wu, wd, outm;
    const __nv_bfloat16 *x, *wr;
    __nv_bfloat16* out;
};

__device__ __forceinline__ uint32_t smem_u32(const void* p) { return (uint32_t)__cvta_generic_to_shared(p); }
__device__ __forceinline__ void mbar_init(uint32_t bar, uint32_t cnt) {
    asm volatile("mbarrier.init.shared::cta.b64 [%0], %1;" ::"r"(bar), "r"(cnt) : "memory");
}
__device__ __forceinline__ void mbar_expect_tx(uint32_t bar, uint32_t bytes) {
    asm volatile("mbarrier.arrive.expect_tx.shared::cta.b64 _, [%0], %1;" ::"r"(bar), "r"(bytes) : "memory");
}
__device__ __forceinline__ void mbar_arrive(uint32_t bar) {
    asm volatile("mbarrier.arrive.shared::cta.b64 _, [%0];" ::"r"(bar) : "memory");
}
__device__ __forceinline__ uint32_t mapa(uint32_t addr, uint32_t cta) {
    uint32_t r;
    asm("mapa.shared::cluster.u32 %0, %1, %2;" : "=r"(r) : "r"(addr), "r"(cta));
    return r;
}
__device__ __forceinline__ void mbar_wait(uint32_t bar, uint32_t parity) {
    asm volatile(
        "{\n.reg .pred p;\n.reg .b32 c;\n"
        "mov.b32 c, 0;\n"
        "WLOOP:\n"
        "mbarrier.try_wait.parity.shared::cta.b64 p, [%0], %1;\n"
        "@p bra.uni WDONE;\n"
        "add.u32 c, c, 1;\n"
        "setp.lt.u32 p, c, 0x400000;\n"
        "@p bra.uni WLOOP;\n"
        "trap;\n"
        "WDONE:\n}\n" ::"r"(bar), "r"(parity) : "memory");
}
__device__ __forceinline__ uint32_t mbar_peek(uint32_t bar, uint32_t parity) {
    uint32_t ok;
    asm volatile("{\n.reg .pred p;\nmbarrier.test_wait.parity.shared::cta.b64 p, [%1], %2;\nselp.b32 %0, 1, 0, p;\n}\n" : "=r"(ok) : "r"(bar), "r"(parity) : "memory");
    return ok;
}
__device__ __forceinline__ void mbar_wait_unless(uint32_t ok, uint32_t bar, uint32_t parity) {
    asm volatile(
        "{\n.reg .pred p;\n.reg .b32 c;\n"
        "setp.ne.b32 p, %2, 0;\n"
        "@p bra.uni WDONE;\n"
        "mov.b32 c, 0;\n"
        "WLOOP:\n"
        "mbarrier.try_wait.parity.shared::cta.b64 p, [%0], %1;\n"
        "@p bra.uni WDONE;\n"
        "add.u32 c, c, 1;\n"
        "setp.lt.u32 p, c, 0x400000;\n"
        "@p bra.uni WLOOP;\n"
        "trap;\n"
        "WDONE:\n}\n" ::"r"(bar), "r"(parity), "r"(ok) : "memory");
}
__device__ __forceinline__ void mbar_wait_sleep(uint32_t bar, uint32_t parity) {
    asm volatile(
        "{\n.reg .pred p;\n.reg .b32 c;\n"
        "mov.b32 c, 0;\n"
        "WLOOP:\n"
        "mbarrier.try_wait.parity.shared::cta.b64 p, [%0], %1, 20000;\n"
        "@p bra.uni WDONE;\n"
        "add.u32 c, c, 1;\n"
        "setp.lt.u32 p, c, 0x40000;\n"
        "@p bra.uni WLOOP;\n"
        "trap;\n"
        "WDONE:\n}\n" ::"r"(bar), "r"(parity) : "memory");
}
__device__ __forceinline__ void tma_load(uint32_t dst, const CUtensorMap* m, int c0, int c1, uint32_t bar) {
    asm volatile("cp.async.bulk.tensor.2d.shared::cluster.global.mbarrier::complete_tx::bytes [%0], [%1, {%3, %4}], [%2];"
                 ::"r"(dst), "l"(m), "r"(bar), "r"(c0), "r"(c1) : "memory");
}
#define ELECT "{\n.reg .pred e;\nelect.sync _|e, 0xffffffff;\n@e "
__device__ __forceinline__ void w_expect_tx(uint32_t bar, uint32_t bytes) {
    asm volatile(ELECT "mbarrier.arrive.expect_tx.shared::cta.b64 _, [%0], %1;\n}\n" ::"r"(bar), "r"(bytes) : "memory");
}
__device__ __forceinline__ void w_tma_load(uint32_t dst, const CUtensorMap* m, int c0, int c1, uint32_t bar) {
    asm volatile(ELECT "cp.async.bulk.tensor.2d.shared::cluster.global.mbarrier::complete_tx::bytes [%0], [%1, {%3, %4}], [%2];\n}\n"
                 ::"r"(dst), "l"(m), "r"(bar), "r"(c0), "r"(c1) : "memory");
}
__device__ __forceinline__ void w_tma_load_mc(uint32_t dst, const CUtensorMap* m, int c0, int c1, uint32_t bar) {
    asm volatile(ELECT "cp.async.bulk.tensor.2d.shared::cluster.global.mbarrier::complete_tx::bytes.multicast::cluster [%0], [%1, {%3, %4}], [%2], %5;\n}\n"
                 ::"r"(dst), "l"(m), "r"(bar), "r"(c0), "r"(c1), "h"((uint16_t)3) : "memory");
}
__device__ __forceinline__ void w_tma_prefetch(const CUtensorMap* m, int c0, int c1) {
    asm volatile(ELECT "cp.async.bulk.prefetch.tensor.2d.L2.global [%0, {%1, %2}];\n}\n" ::"l"(m), "r"(c0), "r"(c1) : "memory");
}
__device__ __forceinline__ uint64_t policy_evict_first() {
    uint64_t p;
    asm("createpolicy.fractional.L2::evict_first.b64 %0, 1.0;" : "=l"(p));
    return p;
}
__device__ __forceinline__ void w_tma_load_mc_last(uint32_t dst, const CUtensorMap* m, int c0, int c1, uint32_t bar) {
    asm volatile(ELECT "cp.async.bulk.tensor.2d.shared::cluster.global.mbarrier::complete_tx::bytes.multicast::cluster.L2::cache_hint [%0], [%1, {%3, %4}], [%2], %5, %6;\n}\n"
                 ::"r"(dst), "l"(m), "r"(bar), "r"(c0), "r"(c1), "h"((uint16_t)3), "l"(policy_evict_first()) : "memory");
}
__device__ __forceinline__ void w_tma_load_stream(uint32_t dst, const CUtensorMap* m, int c0, int c1, uint32_t bar) {
    asm volatile(ELECT "cp.async.bulk.tensor.2d.shared::cluster.global.mbarrier::complete_tx::bytes.L2::cache_hint [%0], [%1, {%3, %4}], [%2], %5;\n}\n"
                 ::"r"(dst), "l"(m), "r"(bar), "r"(c0), "r"(c1), "l"(policy_evict_first()) : "memory");
}
__device__ __forceinline__ uint4 ldg_stream(const void* p) {
    uint4 v;
    asm volatile("ld.global.nc.L2::cache_hint.v4.b32 {%0, %1, %2, %3}, [%4], %5;" : "=r"(v.x), "=r"(v.y), "=r"(v.z), "=r"(v.w) : "l"(p), "l"(policy_evict_first()));
    return v;
}
__device__ __forceinline__ void prefetch_map(const CUtensorMap* m) {
    asm volatile("prefetch.tensormap [%0];" ::"l"(m) : "memory");
}
__device__ __forceinline__ void cluster_arrive() { asm volatile("barrier.cluster.arrive.relaxed.aligned;" ::: "memory"); }
__device__ __forceinline__ void cluster_wait() { asm volatile("barrier.cluster.wait.aligned;" ::: "memory"); }
__device__ __forceinline__ void named_sync(int id, int n) { asm volatile("bar.sync %0, %1;" ::"r"(id), "r"(n) : "memory"); }
__device__ __forceinline__ void named_arrive(int id, int n) { asm volatile("bar.arrive %0, %1;" ::"r"(id), "r"(n) : "memory"); }

__device__ __forceinline__ void flag_add(int f) {
    asm volatile("fence.acq_rel.gpu;\nred.relaxed.gpu.global.add.u32 [%0], 1;" ::"l"(g_flags + f * 8) : "memory");
}
template <int SLEEP>
__device__ __forceinline__ void flag_wait(int f, uint32_t target) {
    asm volatile(
        "{\n.reg .pred p;\n.reg .b32 c, v;\n"
        "mov.b32 c, 0;\n"
        "FLOOP:\n"
        "ld.acquire.gpu.global.u32 v, [%0];\n"
        "sub.u32 v, v, %1;\n"
        "setp.ge.s32 p, v, 0;\n"
        "@p bra FDONE;\n"
        "nanosleep.u32 %2;\n"
        "add.u32 c, c, 1;\n"
        "setp.lt.u32 p, c, 0x400000;\n"
        "@p bra FLOOP;\n"
        "trap;\n"
        "FDONE:\n}\n" ::"l"(g_flags + f * 8), "r"(target), "n"(SLEEP) : "memory");
}
__device__ __forceinline__ uint32_t read_epoch() { return atomicAdd(g_flags + F_EPOCH * 8, 1u) / NCTA; }
__device__ __forceinline__ void fence_proxy_async() { asm volatile("fence.proxy.async;" ::: "memory"); }

__device__ __forceinline__ void wgmma_fence() { asm volatile("wgmma.fence.sync.aligned;" ::: "memory"); }
__device__ __forceinline__ void wgmma_commit() { asm volatile("wgmma.commit_group.sync.aligned;" ::: "memory"); }
template <int N>
__device__ __forceinline__ void wgmma_wait() { asm volatile("wgmma.wait_group.sync.aligned %0;" ::"n"(N) : "memory"); }
template <int N>
__device__ __forceinline__ void fence_regs(float (&d)[N]) {
#pragma unroll
    for (int i = 0; i < N; i++) asm volatile("" : "+f"(d[i])::"memory");
}
template <int N>
__device__ __forceinline__ void fence_regs(uint32_t (&d)[N]) {
#pragma unroll
    for (int i = 0; i < N; i++) asm volatile("" : "+r"(d[i])::"memory");
}

template <int TA, int TB>
__device__ __forceinline__ void wgmma_ss_n128(float (&d)[64], uint32_t alo, uint32_t blo, int scale_d) {
    asm volatile("{\n.reg .pred p;\n.reg .b64 da, db;\nsetp.ne.b32 p, %66, 0;\n"
        "mov.b64 da, {%64, %69};\nmov.b64 db, {%65, %69};\n"
        "wgmma.mma_async.sync.aligned.m64n128k16.f32.bf16.bf16 "
        "{%0, %1, %2, %3, %4, %5, %6, %7, %8, %9, %10, %11, %12, %13, %14, %15, %16, %17, %18, %19, %20, %21, %22, %23, %24, %25, %26, %27, %28, %29, %30, %31, %32, %33, %34, %35, %36, %37, %38, %39, %40, %41, %42, %43, %44, %45, %46, %47, %48, %49, %50, %51, %52, %53, %54, %55, %56, %57, %58, %59, %60, %61, %62, %63}, da, db, p, 1, 1, %67, %68;\n}\n"
        :
          "+f"(d[0]), "+f"(d[1]), "+f"(d[2]), "+f"(d[3]), "+f"(d[4]), "+f"(d[5]), "+f"(d[6]), "+f"(d[7]),
          "+f"(d[8]), "+f"(d[9]), "+f"(d[10]), "+f"(d[11]), "+f"(d[12]), "+f"(d[13]), "+f"(d[14]), "+f"(d[15]),
          "+f"(d[16]), "+f"(d[17]), "+f"(d[18]), "+f"(d[19]), "+f"(d[20]), "+f"(d[21]), "+f"(d[22]), "+f"(d[23]),
          "+f"(d[24]), "+f"(d[25]), "+f"(d[26]), "+f"(d[27]), "+f"(d[28]), "+f"(d[29]), "+f"(d[30]), "+f"(d[31]),
          "+f"(d[32]), "+f"(d[33]), "+f"(d[34]), "+f"(d[35]), "+f"(d[36]), "+f"(d[37]), "+f"(d[38]), "+f"(d[39]),
          "+f"(d[40]), "+f"(d[41]), "+f"(d[42]), "+f"(d[43]), "+f"(d[44]), "+f"(d[45]), "+f"(d[46]), "+f"(d[47]),
          "+f"(d[48]), "+f"(d[49]), "+f"(d[50]), "+f"(d[51]), "+f"(d[52]), "+f"(d[53]), "+f"(d[54]), "+f"(d[55]),
          "+f"(d[56]), "+f"(d[57]), "+f"(d[58]), "+f"(d[59]), "+f"(d[60]), "+f"(d[61]), "+f"(d[62]), "+f"(d[63])
        : "r"(alo), "r"(blo), "r"(scale_d), "n"(TA), "n"(TB), "r"(DESC_HI));
}
template <int TA, int TB>
__device__ __forceinline__ void wgmma_ss_n192(float (&d)[96], uint32_t alo, uint32_t blo, int scale_d) {
    asm volatile("{\n.reg .pred p;\n.reg .b64 da, db;\nsetp.ne.b32 p, %98, 0;\n"
        "mov.b64 da, {%96, %101};\nmov.b64 db, {%97, %101};\n"
        "wgmma.mma_async.sync.aligned.m64n192k16.f32.bf16.bf16 "
        "{%0, %1, %2, %3, %4, %5, %6, %7, %8, %9, %10, %11, %12, %13, %14, %15, %16, %17, %18, %19, %20, %21, %22, %23, %24, %25, %26, %27, %28, %29, %30, %31, %32, %33, %34, %35, %36, %37, %38, %39, %40, %41, %42, %43, %44, %45, %46, %47, %48, %49, %50, %51, %52, %53, %54, %55, %56, %57, %58, %59, %60, %61, %62, %63, %64, %65, %66, %67, %68, %69, %70, %71, %72, %73, %74, %75, %76, %77, %78, %79, %80, %81, %82, %83, %84, %85, %86, %87, %88, %89, %90, %91, %92, %93, %94, %95}, da, db, p, 1, 1, %99, %100;\n}\n"
        :
          "+f"(d[0]), "+f"(d[1]), "+f"(d[2]), "+f"(d[3]), "+f"(d[4]), "+f"(d[5]), "+f"(d[6]), "+f"(d[7]),
          "+f"(d[8]), "+f"(d[9]), "+f"(d[10]), "+f"(d[11]), "+f"(d[12]), "+f"(d[13]), "+f"(d[14]), "+f"(d[15]),
          "+f"(d[16]), "+f"(d[17]), "+f"(d[18]), "+f"(d[19]), "+f"(d[20]), "+f"(d[21]), "+f"(d[22]), "+f"(d[23]),
          "+f"(d[24]), "+f"(d[25]), "+f"(d[26]), "+f"(d[27]), "+f"(d[28]), "+f"(d[29]), "+f"(d[30]), "+f"(d[31]),
          "+f"(d[32]), "+f"(d[33]), "+f"(d[34]), "+f"(d[35]), "+f"(d[36]), "+f"(d[37]), "+f"(d[38]), "+f"(d[39]),
          "+f"(d[40]), "+f"(d[41]), "+f"(d[42]), "+f"(d[43]), "+f"(d[44]), "+f"(d[45]), "+f"(d[46]), "+f"(d[47]),
          "+f"(d[48]), "+f"(d[49]), "+f"(d[50]), "+f"(d[51]), "+f"(d[52]), "+f"(d[53]), "+f"(d[54]), "+f"(d[55]),
          "+f"(d[56]), "+f"(d[57]), "+f"(d[58]), "+f"(d[59]), "+f"(d[60]), "+f"(d[61]), "+f"(d[62]), "+f"(d[63]),
          "+f"(d[64]), "+f"(d[65]), "+f"(d[66]), "+f"(d[67]), "+f"(d[68]), "+f"(d[69]), "+f"(d[70]), "+f"(d[71]),
          "+f"(d[72]), "+f"(d[73]), "+f"(d[74]), "+f"(d[75]), "+f"(d[76]), "+f"(d[77]), "+f"(d[78]), "+f"(d[79]),
          "+f"(d[80]), "+f"(d[81]), "+f"(d[82]), "+f"(d[83]), "+f"(d[84]), "+f"(d[85]), "+f"(d[86]), "+f"(d[87]),
          "+f"(d[88]), "+f"(d[89]), "+f"(d[90]), "+f"(d[91]), "+f"(d[92]), "+f"(d[93]), "+f"(d[94]), "+f"(d[95])
        : "r"(alo), "r"(blo), "r"(scale_d), "n"(TA), "n"(TB), "r"(DESC_HI));
}
template <int TA, int TB>
__device__ __forceinline__ void wgmma_ss_n8(float (&d)[4], uint32_t alo, uint32_t blo, int scale_d) {
    asm volatile("{\n.reg .pred p;\n.reg .b64 da, db;\nsetp.ne.b32 p, %6, 0;\n"
        "mov.b64 da, {%4, %9};\nmov.b64 db, {%5, %9};\n"
        "wgmma.mma_async.sync.aligned.m64n8k16.f32.bf16.bf16 "
        "{%0, %1, %2, %3}, da, db, p, 1, 1, %7, %8;\n}\n"
        :
          "+f"(d[0]), "+f"(d[1]), "+f"(d[2]), "+f"(d[3])
        : "r"(alo), "r"(blo), "r"(scale_d), "n"(TA), "n"(TB), "r"(DESC_HI));
}
template <int TB>
__device__ __forceinline__ void wgmma_rs_n64(float (&d)[64], uint32_t a0, uint32_t a1, uint32_t a2, uint32_t a3, uint32_t blo, int scale_d) {
    asm volatile("{\n.reg .pred p;\n.reg .b64 db;\nsetp.ne.b32 p, %37, 0;\n"
        "mov.b64 db, {%36, %39};\n"
        "wgmma.mma_async.sync.aligned.m64n64k16.f32.bf16.bf16 "
        "{%0, %1, %2, %3, %4, %5, %6, %7, %8, %9, %10, %11, %12, %13, %14, %15, %16, %17, %18, %19, %20, %21, %22, %23, %24, %25, %26, %27, %28, %29, %30, %31}, {%32, %33, %34, %35}, db, p, 1, 1, %38;\n}\n"
        :
          "+f"(d[0]), "+f"(d[1]), "+f"(d[2]), "+f"(d[3]), "+f"(d[4]), "+f"(d[5]), "+f"(d[6]), "+f"(d[7]),
          "+f"(d[8]), "+f"(d[9]), "+f"(d[10]), "+f"(d[11]), "+f"(d[12]), "+f"(d[13]), "+f"(d[14]), "+f"(d[15]),
          "+f"(d[16]), "+f"(d[17]), "+f"(d[18]), "+f"(d[19]), "+f"(d[20]), "+f"(d[21]), "+f"(d[22]), "+f"(d[23]),
          "+f"(d[24]), "+f"(d[25]), "+f"(d[26]), "+f"(d[27]), "+f"(d[28]), "+f"(d[29]), "+f"(d[30]), "+f"(d[31])
        : "r"(a0), "r"(a1), "r"(a2), "r"(a3), "r"(blo), "r"(scale_d), "n"(TB), "r"(DESC_HI));
}
template <int TB>
__device__ __forceinline__ void wgmma_rs_n128(float (&d)[64], uint32_t a0, uint32_t a1, uint32_t a2, uint32_t a3, uint32_t blo, int scale_d) {
    asm volatile("{\n.reg .pred p;\n.reg .b64 db;\nsetp.ne.b32 p, %69, 0;\n"
        "mov.b64 db, {%68, %71};\n"
        "wgmma.mma_async.sync.aligned.m64n128k16.f32.bf16.bf16 "
        "{%0, %1, %2, %3, %4, %5, %6, %7, %8, %9, %10, %11, %12, %13, %14, %15, %16, %17, %18, %19, %20, %21, %22, %23, %24, %25, %26, %27, %28, %29, %30, %31, %32, %33, %34, %35, %36, %37, %38, %39, %40, %41, %42, %43, %44, %45, %46, %47, %48, %49, %50, %51, %52, %53, %54, %55, %56, %57, %58, %59, %60, %61, %62, %63}, {%64, %65, %66, %67}, db, p, 1, 1, %70;\n}\n"
        :
          "+f"(d[0]), "+f"(d[1]), "+f"(d[2]), "+f"(d[3]), "+f"(d[4]), "+f"(d[5]), "+f"(d[6]), "+f"(d[7]),
          "+f"(d[8]), "+f"(d[9]), "+f"(d[10]), "+f"(d[11]), "+f"(d[12]), "+f"(d[13]), "+f"(d[14]), "+f"(d[15]),
          "+f"(d[16]), "+f"(d[17]), "+f"(d[18]), "+f"(d[19]), "+f"(d[20]), "+f"(d[21]), "+f"(d[22]), "+f"(d[23]),
          "+f"(d[24]), "+f"(d[25]), "+f"(d[26]), "+f"(d[27]), "+f"(d[28]), "+f"(d[29]), "+f"(d[30]), "+f"(d[31]),
          "+f"(d[32]), "+f"(d[33]), "+f"(d[34]), "+f"(d[35]), "+f"(d[36]), "+f"(d[37]), "+f"(d[38]), "+f"(d[39]),
          "+f"(d[40]), "+f"(d[41]), "+f"(d[42]), "+f"(d[43]), "+f"(d[44]), "+f"(d[45]), "+f"(d[46]), "+f"(d[47]),
          "+f"(d[48]), "+f"(d[49]), "+f"(d[50]), "+f"(d[51]), "+f"(d[52]), "+f"(d[53]), "+f"(d[54]), "+f"(d[55]),
          "+f"(d[56]), "+f"(d[57]), "+f"(d[58]), "+f"(d[59]), "+f"(d[60]), "+f"(d[61]), "+f"(d[62]), "+f"(d[63])
        : "r"(a0), "r"(a1), "r"(a2), "r"(a3), "r"(blo), "r"(scale_d), "n"(TB), "r"(DESC_HI));
}
template <int TB>
__device__ __forceinline__ void wgmma_rs_n128_z(float (&d)[64], uint32_t a0, uint32_t a1, uint32_t a2, uint32_t a3, uint32_t blo) {
    asm volatile("{\n.reg .pred p;\n.reg .b64 db;\nsetp.ne.b32 p, %69, 0;\n"
        "mov.b64 db, {%68, %71};\n"
        "wgmma.mma_async.sync.aligned.m64n128k16.f32.bf16.bf16 "
        "{%0, %1, %2, %3, %4, %5, %6, %7, %8, %9, %10, %11, %12, %13, %14, %15, %16, %17, %18, %19, %20, %21, %22, %23, %24, %25, %26, %27, %28, %29, %30, %31, %32, %33, %34, %35, %36, %37, %38, %39, %40, %41, %42, %43, %44, %45, %46, %47, %48, %49, %50, %51, %52, %53, %54, %55, %56, %57, %58, %59, %60, %61, %62, %63}, {%64, %65, %66, %67}, db, p, 1, 1, %70;\n}\n"
        :
          "=f"(d[0]), "=f"(d[1]), "=f"(d[2]), "=f"(d[3]), "=f"(d[4]), "=f"(d[5]), "=f"(d[6]), "=f"(d[7]),
          "=f"(d[8]), "=f"(d[9]), "=f"(d[10]), "=f"(d[11]), "=f"(d[12]), "=f"(d[13]), "=f"(d[14]), "=f"(d[15]),
          "=f"(d[16]), "=f"(d[17]), "=f"(d[18]), "=f"(d[19]), "=f"(d[20]), "=f"(d[21]), "=f"(d[22]), "=f"(d[23]),
          "=f"(d[24]), "=f"(d[25]), "=f"(d[26]), "=f"(d[27]), "=f"(d[28]), "=f"(d[29]), "=f"(d[30]), "=f"(d[31]),
          "=f"(d[32]), "=f"(d[33]), "=f"(d[34]), "=f"(d[35]), "=f"(d[36]), "=f"(d[37]), "=f"(d[38]), "=f"(d[39]),
          "=f"(d[40]), "=f"(d[41]), "=f"(d[42]), "=f"(d[43]), "=f"(d[44]), "=f"(d[45]), "=f"(d[46]), "=f"(d[47]),
          "=f"(d[48]), "=f"(d[49]), "=f"(d[50]), "=f"(d[51]), "=f"(d[52]), "=f"(d[53]), "=f"(d[54]), "=f"(d[55]),
          "=f"(d[56]), "=f"(d[57]), "=f"(d[58]), "=f"(d[59]), "=f"(d[60]), "=f"(d[61]), "=f"(d[62]), "=f"(d[63])
        : "r"(a0), "r"(a1), "r"(a2), "r"(a3), "r"(blo), "n"(0), "n"(TB), "r"(DESC_HI));
}
template <int TA, int TB>
__device__ __forceinline__ void wgmma_ss_n128_z(float (&d)[64], uint32_t alo, uint32_t blo) {
    asm volatile("{\n.reg .pred p;\n.reg .b64 da, db;\nsetp.ne.b32 p, %66, 0;\n"
        "mov.b64 da, {%64, %69};\nmov.b64 db, {%65, %69};\n"
        "wgmma.mma_async.sync.aligned.m64n128k16.f32.bf16.bf16 "
        "{%0, %1, %2, %3, %4, %5, %6, %7, %8, %9, %10, %11, %12, %13, %14, %15, %16, %17, %18, %19, %20, %21, %22, %23, %24, %25, %26, %27, %28, %29, %30, %31, %32, %33, %34, %35, %36, %37, %38, %39, %40, %41, %42, %43, %44, %45, %46, %47, %48, %49, %50, %51, %52, %53, %54, %55, %56, %57, %58, %59, %60, %61, %62, %63}, da, db, p, 1, 1, %67, %68;\n}\n"
        :
          "=f"(d[0]), "=f"(d[1]), "=f"(d[2]), "=f"(d[3]), "=f"(d[4]), "=f"(d[5]), "=f"(d[6]), "=f"(d[7]),
          "=f"(d[8]), "=f"(d[9]), "=f"(d[10]), "=f"(d[11]), "=f"(d[12]), "=f"(d[13]), "=f"(d[14]), "=f"(d[15]),
          "=f"(d[16]), "=f"(d[17]), "=f"(d[18]), "=f"(d[19]), "=f"(d[20]), "=f"(d[21]), "=f"(d[22]), "=f"(d[23]),
          "=f"(d[24]), "=f"(d[25]), "=f"(d[26]), "=f"(d[27]), "=f"(d[28]), "=f"(d[29]), "=f"(d[30]), "=f"(d[31]),
          "=f"(d[32]), "=f"(d[33]), "=f"(d[34]), "=f"(d[35]), "=f"(d[36]), "=f"(d[37]), "=f"(d[38]), "=f"(d[39]),
          "=f"(d[40]), "=f"(d[41]), "=f"(d[42]), "=f"(d[43]), "=f"(d[44]), "=f"(d[45]), "=f"(d[46]), "=f"(d[47]),
          "=f"(d[48]), "=f"(d[49]), "=f"(d[50]), "=f"(d[51]), "=f"(d[52]), "=f"(d[53]), "=f"(d[54]), "=f"(d[55]),
          "=f"(d[56]), "=f"(d[57]), "=f"(d[58]), "=f"(d[59]), "=f"(d[60]), "=f"(d[61]), "=f"(d[62]), "=f"(d[63])
        : "r"(alo), "r"(blo), "n"(0), "n"(TA), "n"(TB), "r"(DESC_HI));
}

__device__ __forceinline__ uint32_t pack_bf16(float lo, float hi) {
    uint32_t r;
    asm("cvt.rn.bf16x2.f32 %0, %1, %2;" : "=r"(r) : "f"(hi), "f"(lo));
    return r;
}
__device__ __forceinline__ uint32_t add_bf16x2(uint32_t a, uint32_t b) {
    uint32_t r;
    asm("add.rn.bf16x2 %0, %1, %2;" : "=r"(r) : "r"(a), "r"(b));
    return r;
}
__device__ __forceinline__ float bf_lo(uint32_t v) { return __uint_as_float(v << 16); }
__device__ __forceinline__ float bf_hi(uint32_t v) { return __uint_as_float(v & 0xffff0000u); }
__device__ __forceinline__ float round_bf16(float v) { return __bfloat162float(__float2bfloat16_rn(v)); }
__device__ __forceinline__ float ex2(float x) {
    float y;
    asm("ex2.approx.ftz.f32 %0, %1;" : "=f"(y) : "f"(x));
    return y;
}
__device__ __forceinline__ float rcp(float x) {
    float y;
    asm("rcp.approx.ftz.f32 %0, %1;" : "=f"(y) : "f"(x));
    return y;
}
__device__ __forceinline__ void stg128(void* p, uint32_t a, uint32_t b, uint32_t c, uint32_t d) {
    asm volatile("st.global.v4.b32 [%0], {%1, %2, %3, %4};" ::"l"(p), "r"(a), "r"(b), "r"(c), "r"(d) : "memory");
}
__device__ __forceinline__ void stg128p(void* p, uint32_t a, uint32_t b, uint32_t c, uint32_t d, uint64_t pol) {
    asm volatile("st.global.L2::cache_hint.v4.b32 [%0], {%1, %2, %3, %4}, %5;" ::"l"(p), "r"(a), "r"(b), "r"(c), "r"(d), "l"(pol) : "memory");
}
__device__ __forceinline__ uint64_t policy_sel(bool first) {
    uint64_t p;
    asm("createpolicy.fractional.L2::evict_normal.b64 %0, 1.0;" : "=l"(p));
    return first ? policy_evict_first() : p;
}
__device__ __forceinline__ int perm_row(int t) { return (t & ~255) | (((0x78 >> (((t >> 6) & 3) * 2)) & 3) << 6) | (t & 63); }
__device__ __forceinline__ int unperm_row(int t) { return (t & ~255) | (((0x9C >> (((t >> 6) & 3) * 2)) & 3) << 6) | (t & 63); }

#define PROF(i)
#define PROFG(i)
#define PROFDUMP()
#define TR(i)
#define OP(i)
#define BP(r, i)
#define LP(i)

template <int I>
__device__ __forceinline__ void store_chunk(const float (&a)[64], __nv_bfloat16* row0, __nv_bfloat16* row1, float s0, float s1) {
    stg128(row0 + 32 * I, pack_bf16(a[16 * I + 0] * s0, a[16 * I + 1] * s0), pack_bf16(a[16 * I + 4] * s0, a[16 * I + 5] * s0),
           pack_bf16(a[16 * I + 8] * s0, a[16 * I + 9] * s0), pack_bf16(a[16 * I + 12] * s0, a[16 * I + 13] * s0));
    stg128(row1 + 32 * I, pack_bf16(a[16 * I + 2] * s1, a[16 * I + 3] * s1), pack_bf16(a[16 * I + 6] * s1, a[16 * I + 7] * s1),
           pack_bf16(a[16 * I + 10] * s1, a[16 * I + 11] * s1), pack_bf16(a[16 * I + 14] * s1, a[16 * I + 15] * s1));
}
template <int I>
struct IntT { static constexpr int value = I; };
template <class F>
__device__ __forceinline__ void for4(F f) { f(IntT<0>{}); f(IntT<1>{}); f(IntT<2>{}); f(IntT<3>{}); }

struct Prod {
    uint32_t smem, bars;
    uint32_t bo, par;
    uint32_t dst, fb;
    __device__ __forceinline__ void acquire(uint32_t o, uint32_t parity, uint32_t bytes) {
        mbar_wait(bars + BAR_EMPTY + o, parity);
        fb = bars + BAR_FULL + o;
        dst = smem + o * (SLOT / 8);
        w_expect_tx(fb, bytes);
    }
    __device__ __forceinline__ void next(uint32_t bytes) {
        acquire(bo, par, bytes);
        const bool wrap = bo == (NSLOT - 1) * 8;
        bo = wrap ? 0u : bo + 8;
        par ^= wrap ? 1u : 0u;
    }
};

__device__ __forceinline__ int item_p(int ca, int rd) {
    const int v = (rd & 1) ? (ca + 4) & 7 : ca;
    return (rd & 2) ? 7 - v : v;
}
__device__ __forceinline__ int n_items(int ca, int cb) { return cb == 8 ? 8 : ((ca & 3) == 3) ? 3 : 4; }
__device__ __forceinline__ int item_rd(int ca, int cb, int j) { return cb == 8 ? 2 + ca : (ca == 7 && j == 2) ? 3 : j; }
__device__ __forceinline__ int item_h(int cb, int rd, int j) { return 8 * rd + (cb == 8 ? j : cb); }
__device__ __forceinline__ int item_q(int ca, int cb, int rd) { return cb == 8 ? 0 : item_p(ca, rd); }
__device__ __forceinline__ int out_p(int ca, int cb) { return (cb + 2 * (ca & 3)) & 7; }
__device__ __forceinline__ int kv_round(int i) { return (0x1023 >> (4 * i)) & 3; }
__device__ __forceinline__ int slot_a(int i) { return (0x5310 >> (4 * i)) & 15; }
__device__ __forceinline__ int slot_w(int m) { return (0x264 >> (4 * m)) & 15; }

__device__ __forceinline__ void producer(const Params& P, uint32_t smem, uint32_t bars, int ca, int cb, int rank) {
    Prod pr{smem, bars, 0u, cb == 8 ? 1u : 0u, 0u, 0u};
    if (cb < 8) {
        int m = 0;
        uint32_t lap = 1;
#pragma unroll 1
        for (int u = 0; u < 32; u++) {
            if (u >= 3) {
                const int v = (u == 3) ? 3 + ca : u + 7;
                if (v < 32 && (u == 3 || (v & 7) == ca)) w_tma_prefetch((v & 4) ? &P.wuv : &P.wuk, (cb + 8 * kv_round(v >> 3)) * 128 + rank * 64, (v & 3) * 128);
                if (u == 24) {
                    w_tma_prefetch(&P.wq, cb * 128 + rank * 64, ca * 64);
                    if (ca < 2) w_tma_prefetch(&P.wq, cb * 128 + rank * 64, (ca + 8) * 64);
                }
            }
            if (u == 2) mbar_wait(bars + BAR_FULL + slot_w(2) * 8, 0);
            if (u > 0) pr.acquire(slot_w(m) * 8, lap ^ (m >> 1), SLOT);
            lap ^= m >> 1;
            m = (m == 2) ? 0 : m + 1;
            TR(1 + u);
            if (u > 0) w_tma_load_mc(pr.dst + rank * 16384, (u & 4) ? &P.wuv : &P.wuk, (cb + 8 * kv_round(u >> 3)) * 128 + rank * 64, (u & 3) * 128, pr.fb);
            if (u < 3) {
                pr.acquire(slot_a(u + 1) * 8, 1, SLOT);
                w_tma_load(pr.dst, &P.ckv, u * 128 + 128, (2 * ca + rank) * 128, pr.fb);
                w_tma_load(pr.dst + 16384, &P.ckv, u * 128 + 192, (2 * ca + rank) * 128, pr.fb);
            }
        }
    }
    PROF(1);
    mbar_wait_sleep(bars + BAR_DEP, 0);
#pragma unroll 1
    for (int j = 0, pfs = 1; j < n_items(ca, cb); j++) {
        const int rd = item_rd(ca, cb, j), h = item_h(cb, rd, j), p = item_q(ca, cb, rd);
#pragma unroll 1
        for (int ks = 0; ks < 10; ks++) {
            pr.next(SLOT);
            w_tma_load_mc(pr.dst + 16384 + rank * 8192, &P.wq, h * 128 + rank * 64, ks * 64, pr.fb);
            w_tma_load(pr.dst, &P.xn, ks * 64, 256 * p + 128 * rank, pr.fb);
            if (cb == 8 && j < 7) w_tma_prefetch(&P.wq, (h + 1) * 128 + rank * 64, ks * 64);
        }
        PROF(8 + rd * 4);
        mbar_wait(bars + BAR_DEP + (1 + (cb == 8 ? j : rd)) * 8, 0);
        const int last = 4 * p + 3, top = h * 32 + last;
#pragma unroll 1
        for (int i = 0; i <= last; i++) {
            const int t = (i == 0) ? top - 1 : (i == last) ? h * 32 + 1 : (i & 1) ? top - 2 - i : top + 2 - i;
            pr.next(SLOT);
            const bool lastrd = (cb == 8 || rd == 3) ? false : (rd == 0) ? ca >= 6 : (rd == 1) ? (ca & 3) >= 2 : (ca == 3 || (ca < 3 && (t & 31) >= 4 * p));
            if (lastrd) w_tma_load_mc_last(pr.dst + rank * 16384, &P.kv, rank * 64, t * 128, pr.fb);
            else w_tma_load_mc(pr.dst + rank * 16384, &P.kv, rank * 64, t * 128, pr.fb);
            if (i == 2 && cb < 8) {
                const int upto = (j == n_items(ca, cb) - 1) ? 4 : item_rd(ca, cb, j + 1);
#pragma unroll 1
                for (; pfs <= upto; pfs++) {
                    if (pfs < 4) {
                        w_tma_prefetch(&P.wq, (8 * pfs + cb) * 128 + rank * 64, ca * 64);
                        if (ca < 2) w_tma_prefetch(&P.wq, (8 * pfs + cb) * 128 + rank * 64, (ca + 8) * 64);
                    } else {
#pragma unroll 1
                        for (int k = 0; k < 10; k++)
                            w_tma_prefetch(&P.wo, 320 * (ca >> 2) + 64 * (k >= 5 ? k - 5 : k), (cb * 4 + (ca & 3) + (k >= 5 ? 32 : 0)) * 64 + rank * 32);
                    }
                }
            }
        }
        PROF(9 + rd * 4);
    }
    if (cb < 8) {
        const int n0 = 320 * (ca >> 2), op = out_p(ca, cb);
        uint32_t* pool = g_flags + (F_POOL + op * 2 + (ca >> 2)) * 8;
        uint32_t nxt = 0;
        auto draw = [&]() {
            if (rank == 0) asm volatile(ELECT "atom.relaxed.gpu.global.add.u32 %0, [%1], 1;\n}\n" : "+r"(nxt) : "l"(pool) : "memory");
        };
        int fixed = -1;
#pragma unroll 1
        for (int i = -2; fixed < 4; i++) {
            int st = (ca & 3) + 4 * (i + 2);
            if (i == -1) draw();
            if (i >= 0 && fixed < 0) {
                const uint32_t mb = bars + BAR_MAIL + (i & 7) * 8, md = bars + MAIL_OFF + (i & 7) * 4;
                if (rank == 0) {
                    st = __reduce_add_sync(0xffffffffu, nxt);
                    asm volatile(ELECT "st.async.shared::cluster.mbarrier::complete_tx::bytes.b32 [%0], %1, [%2];\n}\n" ::"r"(mapa(md, 1)), "r"(st), "r"(mapa(mb, 1)) : "memory");
                    if (st < 48) draw();
                } else {
                    w_expect_tx(mb, 4);
                    mbar_wait(mb, (i >> 3) & 1);
                    asm volatile("ld.shared.u32 %0, [%1];" : "=r"(st) : "r"(md) : "memory");
                    st = __reduce_or_sync(0xffffffffu, st);
                }
                if (st >= 48) fixed = 0;
            }
            if (fixed >= 0) { st = 48 + (ca & 3) + 4 * fixed; fixed++; }
            const int krow = st * 64 + rank * 32;
            mbar_wait(bars + BAR_EMPTY + pr.bo, pr.par);
            asm volatile("st.shared.u32 [%0], %1;" ::"r"(bars + CTL_OFF + pr.bo), "r"((int)(fixed == 1)) : "memory");
            __syncwarp();
            pr.next(SLOT);
            w_tma_load_mc(pr.dst + 16384 + rank * 8192, &P.wo, n0, krow, pr.fb);
            w_tma_load_mc(pr.dst + 16384 + rank * 8192 + 4096, &P.wo, n0 + 64, krow, pr.fb);
            mbar_wait(bars + BAR_DEP + (5 + (st >> 4)) * 8, 0);
            w_tma_load(pr.dst, &P.ctx, (st & 1) * 64, (st >> 1) * SEQ + 256 * op + 128 * rank, pr.fb);
#pragma unroll 1
            for (int k = (fixed < 2) ? 0 : (fixed == 4) ? -2 : 1; k <= 0; k++) {
                pr.next(24576);
#pragma unroll
                for (int c = 0; c < 3; c++) w_tma_load_mc(pr.dst + rank * 12288 + c * 4096, &P.wo, n0 + 128 + 64 * c, krow + k * 256, pr.fb);
            }
        }
    }
}

struct Slot {
    uint32_t bo, dl, par;
};
struct Cons {
    uint32_t bars, rel;
    uint32_t dl0;
    uint32_t lane;
    Slot cur;
    __device__ __forceinline__ Slot slot(int s, uint32_t par) const { return Slot{(uint32_t)s * 8, dl0 + (uint32_t)s * (SLOT >> 4), par}; }
    __device__ __forceinline__ void wait(const Slot& s) const { mbar_wait(bars + BAR_FULL + s.bo, s.par); }
    __device__ __forceinline__ uint32_t peek() const { return mbar_peek(bars + BAR_FULL + cur.bo, cur.par); }
    __device__ __forceinline__ void wait(const Slot& s, uint32_t ok) const { mbar_wait_unless(ok, bars + BAR_FULL + s.bo, s.par); }
    __device__ __forceinline__ void release(uint32_t bo) const {
        asm volatile("{\n.reg .pred p;\nsetp.lt.u32 p, %1, 2;\n@p mbarrier.arrive.shared::cluster.b64 _, [%0];\n}\n" ::"r"(rel + bo), "r"(lane) : "memory");
    }
    __device__ __forceinline__ Slot next() {
        const Slot s = cur;
        const bool wrap = s.bo == (NSLOT - 1) * 8;
        cur.bo = wrap ? 0u : s.bo + 8;
        cur.dl = wrap ? dl0 : s.dl + (SLOT >> 4);
        cur.par = s.par ^ (wrap ? 1u : 0u);
        return s;
    }
};
__host__ __device__ constexpr uint32_t lbo(uint32_t bytes) { return (bytes >> 4) << 16; }

__device__ __forceinline__ float div640(float x) {
    const float q = x * (1.0f / DM);
    return fmaf(fmaf(-q, (float)DM, x), 1.0f / DM, q);
}
__device__ __forceinline__ float sqrt_approx(float x) {
    float y;
    asm("sqrt.approx.ftz.f32 %0, %1;" : "=f"(y) : "f"(x));
    return y;
}
struct LayerNorm {
    uint4 xv[5], wv[5];
    float mean, inv, r;
    uint32_t nmb;
    __nv_bfloat16 *pn, *po;
    static __device__ __forceinline__ float half_sum(float v) {
#pragma unroll
        for (int o = 8; o > 0; o >>= 1) v += __shfl_xor_sync(0xffffffffu, v, o);
        return v;
    }
    __device__ __forceinline__ void load(const __nv_bfloat16* x, const __nv_bfloat16* wr, __nv_bfloat16* out, int t, int l) {
        pn = g_xn + perm_row(t) * DM + 8 * l;
        po = out + t * DM + 8 * l;
        asm volatile("" : "+l"(pn), "+l"(po));
#pragma unroll
        for (int i = 0; i < 5; i++) {
            xv[i] = ldg_stream(reinterpret_cast<const uint4*>(x + t * DM) + l + 16 * i);
            wv[i] = __ldg(reinterpret_cast<const uint4*>(wr) + l + 16 * i);
        }
    }
    __device__ __forceinline__ void stat1() {
        float a[4] = {0.f, 0.f, 0.f, 0.f};
#pragma unroll
        for (int i = 0; i < 20; i++) { const uint32_t u = (&xv[i >> 2].x)[i & 3]; a[i & 3] += bf_lo(u) + bf_hi(u); }
        mean = div640(half_sum((a[0] + a[1]) + (a[2] + a[3])));
        r = 0.f;
    }
    template <int H>
    __device__ __forceinline__ void stat2() {
        float a[4] = {r, 0.f, 0.f, 0.f};
#pragma unroll
        for (int i = H ? 12 : 0; i < (H ? 20 : 12); i++) {
            uint32_t u = (&xv[i >> 2].x)[i & 3];
            asm volatile("" : "+r"(u));
            const float d0 = bf_lo(u) - mean, d1 = bf_hi(u) - mean;
            a[i & 3] = fmaf(d0, d0, fmaf(d1, d1, a[i & 3]));
        }
        r = (a[0] + a[1]) + (a[2] + a[3]);
        if (H) {
            inv = rcp(round_bf16(sqrt_approx(round_bf16(round_bf16(div640(half_sum(r))) + 1e-5f))));
            r = 0.f;
            nmb = pack_bf16(-mean, -mean);
        }
    }
    template <int I>
    __device__ __forceinline__ void piece(int t, int l) {
        uint32_t o[4], z[4];
        float a[4];
#pragma unroll
        for (int j = 0; j < 4; j++) {
            const uint32_t u = (&xv[I].x)[j], w = (&wv[I].x)[j];
            const uint32_t d = add_bf16x2(u, nmb);
            o[j] = pack_bf16(bf_lo(d) * inv, bf_hi(d) * inv);
            z[j] = add_bf16x2(u, o[j]);
            a[j] = fmaf(bf_hi(o[j]), bf_hi(w), bf_lo(o[j]) * bf_lo(w));
        }
        r += (a[0] + a[1]) + (a[2] + a[3]);
        stg128(pn + 128 * I, o[0], o[1], o[2], o[3]);
        stg128p(po + 128 * I, z[0], z[1], z[2], z[3], policy_evict_first());
        if (I == 4) {
            r = half_sum(r);
            if (l == 0) g_r[t] = round_bf16(r);
        }
    }
};

constexpr float SM_SCALE = 0.08838834764831845f * 1.4426950408889634f;

template <int J0, int J1>
__device__ __forceinline__ void exp_part(float (&s)[64], float n0, float n1, float& r0, float& r1) {
    float a1 = 0.f, b1 = 0.f;
#pragma unroll
    for (int j = J0; j < J1; j++) {
        s[4 * j + 0] = ex2(fmaf(s[4 * j + 0], SM_SCALE, n0));
        s[4 * j + 1] = ex2(fmaf(s[4 * j + 1], SM_SCALE, n0));
        s[4 * j + 2] = ex2(fmaf(s[4 * j + 2], SM_SCALE, n1));
        s[4 * j + 3] = ex2(fmaf(s[4 * j + 3], SM_SCALE, n1));
        r0 += s[4 * j + 0]; r1 += s[4 * j + 2];
        if (j == J0) { a1 = s[4 * j + 1]; b1 = s[4 * j + 3]; } else { a1 += s[4 * j + 1]; b1 += s[4 * j + 3]; }
    }
    r0 += a1;
    r1 += b1;
}
__device__ __forceinline__ void sched_barrier(float x, float y, uint32_t scratch) {
    asm volatile("{\n.reg .pred p;\nsetp.lt.f32 p, %0, 0f00000000;\n@p st.shared.f32 [%2], %1;\n}\n" ::"f"(x), "f"(y), "r"(scratch) : "memory");
}
__device__ __forceinline__ void pack_tile(const float (&s)[64], uint32_t (&p)[32]) {
#pragma unroll
    for (int i = 0; i < 32; i++) p[i] = pack_bf16(s[2 * i], s[2 * i + 1]);
}
template <bool ZERO>
__device__ __forceinline__ void gemm_rs(float (&d)[64], const uint32_t (&a)[32], uint32_t dl, int acc = 1) {
    const uint32_t b = dl + lbo(16384);
    if (ZERO) wgmma_rs_n128_z<1>(d, a[0], a[1], a[2], a[3], b);
#pragma unroll
    for (int k = ZERO ? 1 : 0; k < 8; k++) wgmma_rs_n128<1>(d, a[4 * k], a[4 * k + 1], a[4 * k + 2], a[4 * k + 3], b + k * 128, k ? 1 : acc);
}
__device__ __forceinline__ void gemm_pv(float (&d)[64], const uint32_t (&a)[32], uint32_t dl, int acc, int full) {
    const uint32_t b = dl + lbo(16384);
    wgmma_rs_n128<1>(d, a[0], a[1], a[2], a[3], b, acc);
    wgmma_commit();
    if (full) {
        wgmma_fence();
#pragma unroll
        for (int k = 4; k < 8; k++) wgmma_rs_n128<1>(d, a[4 * k], a[4 * k + 1], a[4 * k + 2], a[4 * k + 3], b + k * 128, 1);
        wgmma_commit();
    }
    wgmma_fence();
#pragma unroll
    for (int k = 1; k < 4; k++) wgmma_rs_n128<1>(d, a[4 * k], a[4 * k + 1], a[4 * k + 2], a[4 * k + 3], b + k * 128, 1);
}
template <int ZERO>
__device__ __forceinline__ void gemm_q(float (&d)[64], uint32_t dl, int role) {
    const uint32_t a = dl + role * 512 + lbo(16), b = dl + 1024 + lbo(8192);
    if (ZERO) wgmma_ss_n128_z<0, 1>(d, a, b);
#pragma unroll
    for (int k = ZERO ? 1 : 0; k < 4; k++) wgmma_ss_n128<0, 1>(d, a + k * 2, b + k * 128, 1);
}
template <bool KT, bool ZERO, int K0, int K1>
__device__ __forceinline__ void gemm_kv(float (&d)[64], uint32_t ckv, uint32_t wt, int wg) {
    if (KT) {
        const uint32_t a = wt + wg * 1024 + lbo(16), b = ckv + lbo(16);
        if (ZERO) wgmma_ss_n128_z<1, 0>(d, a, b);
#pragma unroll
        for (int k = ZERO ? 1 : K0; k < K1; k++) wgmma_ss_n128<1, 0>(d, a + k * 128, b + (k >> 2) * 1024 + (k & 3) * 2, 1);
    } else {
        const uint32_t a = ckv + wg * 512 + lbo(16), b = wt + lbo(16384);
        if (ZERO) wgmma_ss_n128_z<0, 1>(d, a, b);
#pragma unroll
        for (int k = ZERO ? 1 : K0; k < K1; k++) wgmma_ss_n128<0, 1>(d, a + (k >> 2) * 1024 + (k & 3) * 2, b + k * 128, 1);
    }
}
__device__ __forceinline__ void mma16816(float& d0, float& d1, float& d2, float& d3, uint32_t a0, uint32_t a1, uint32_t a2, uint32_t a3, uint32_t b0, uint32_t b1) {
    asm volatile("mma.sync.aligned.m16n8k16.row.col.f32.bf16.bf16.f32 {%0,%1,%2,%3}, {%4,%5,%6,%7}, {%8,%9}, {%0,%1,%2,%3};"
                 : "+f"(d0), "+f"(d1), "+f"(d2), "+f"(d3) : "r"(a0), "r"(a1), "r"(a2), "r"(a3), "r"(b0), "r"(b1));
}
__device__ __forceinline__ uint32_t ld_pair(const __nv_bfloat16* p) {
    const unsigned short* u = reinterpret_cast<const unsigned short*>(p);
    return (uint32_t)__ldcg(u) | ((uint32_t)__ldcg(u + 128) << 16);
}
__device__ __forceinline__ void attention_exact(float (&o)[64], const uint32_t (&qf)[32], float& l0, float& l1, int h, int nblk, int rr, int lane) {
    const int q = lane & 3, lr = lane >> 2;
    float m0 = -INFINITY, m1 = -INFINITY;
    l0 = 0.f; l1 = 0.f;
#pragma unroll 1
    for (int cidx = 0; cidx < nblk * 8; cidx++) {
        const int kc = cidx & 7;
        const __nv_bfloat16* kt = g_kv + (size_t)((h * 16 + (cidx >> 3)) * 2) * 16384;
        float sc[8];
#pragma unroll
        for (int i = 0; i < 8; i++) sc[i] = 0.f;
#pragma unroll
        for (int kk = 0; kk < 8; kk++)
#pragma unroll
            for (int nt = 0; nt < 2; nt++) {
                const __nv_bfloat16* b = kt + (16 * kk + 2 * q) * 128 + 16 * kc + 8 * nt + lr;
                mma16816(sc[4 * nt], sc[4 * nt + 1], sc[4 * nt + 2], sc[4 * nt + 3], qf[4 * kk], qf[4 * kk + 1], qf[4 * kk + 2], qf[4 * kk + 3],
                         ld_pair(b), ld_pair(b + 8 * 128));
            }
        const int lim = rr + ((nblk - 1) - (cidx >> 3)) * 128 - 32 * (kc >> 1) - 4 * (kc & 1);
#pragma unroll
        for (int i = 0; i < 8; i++)
            if (2 * (i >> 2) + (i & 1) > lim + 4 * (i & 2)) sc[i] = -INFINITY;
        float x0 = fmaxf(fmaxf(sc[0], sc[1]), fmaxf(sc[4], sc[5])), x1 = fmaxf(fmaxf(sc[2], sc[3]), fmaxf(sc[6], sc[7]));
        x0 = fmaxf(x0, __shfl_xor_sync(0xffffffffu, x0, 1)); x1 = fmaxf(x1, __shfl_xor_sync(0xffffffffu, x1, 1));
        x0 = fmaxf(x0, __shfl_xor_sync(0xffffffffu, x0, 2)); x1 = fmaxf(x1, __shfl_xor_sync(0xffffffffu, x1, 2));
        x0 = fmaxf(x0, m0); x1 = fmaxf(x1, m1);
        const float a0 = ex2((m0 - x0) * SM_SCALE), a1 = ex2((m1 - x1) * SM_SCALE);
        m0 = x0; m1 = x1;
#pragma unroll
        for (int i = 0; i < 8; i++) sc[i] = ex2((sc[i] - ((i & 2) ? m1 : m0)) * SM_SCALE);
        l0 = l0 * a0 + (sc[0] + sc[1]) + (sc[4] + sc[5]);
        l1 = l1 * a1 + (sc[2] + sc[3]) + (sc[6] + sc[7]);
        const uint32_t p0 = pack_bf16(sc[0], sc[1]), p1 = pack_bf16(sc[2], sc[3]), p2 = pack_bf16(sc[4], sc[5]), p3 = pack_bf16(sc[6], sc[7]);
        const __nv_bfloat16* vb = kt + 16384 + (16 * kc + 2 * q) * 128 + lr;
#pragma unroll
        for (int nt = 0; nt < 16; nt++) {
            o[4 * nt] *= a0; o[4 * nt + 1] *= a0; o[4 * nt + 2] *= a1; o[4 * nt + 3] *= a1;
            mma16816(o[4 * nt], o[4 * nt + 1], o[4 * nt + 2], o[4 * nt + 3], p0, p1, p2, p3, ld_pair(vb + 8 * nt), ld_pair(vb + 8 * nt + 8 * 128));
        }
    }
}

__device__ __forceinline__ void signal(uint32_t bars, int wg, int e, int lane) {
    __syncwarp();
    asm volatile("{\n.reg .pred p;\nsetp.eq.u32 p, %1, 0;\n@p mbarrier.arrive.shared::cta.b64 _, [%0];\n}\n" ::"r"(bars + BAR_SIG + (wg * 9 + e) * 8), "r"(lane) : "memory");
}

__device__ __forceinline__ void mod_ffn(const Params& P, uint32_t smem, int mc, int wg);

__device__ __forceinline__ void consumer(const Params& P, uint32_t smem, uint32_t bars, int ca, int cb, int rank, int wg) {
    const int lane = threadIdx.x & 31, w = (threadIdx.x >> 5) & 3, q = lane & 3, lr = lane >> 2;
    PROF(7);
    cluster_wait();
    Cons c{bars, mapa(bars + BAR_EMPTY, lane & 1), (smem & 0x3FFFF) >> 4, (uint32_t)lane, Slot{0u, (smem & 0x3FFFF) >> 4, cb == 8 ? 0u : 1u}};
    PROFG(180);
    PROF(1);
    float o[64], s[64];
    uint32_t pend;
    __nv_bfloat16* ep_ptr;
    int ep_step;
    if (cb == 8) {
        pend = 0;
        ep_ptr = g_ctx + (size_t)(item_h(cb, 2 + ca, 0) * SEQ + 128 * rank + 64 * wg + 16 * w + lr) * HD + 8 * q;
        ep_step = 8 * HD;
    } else {
        const int ln_t = blockIdx.x * 16 + wg * 8 + w * 2 + (lane >> 4);
        const int krow = 64 * wg + 16 * w + lr;
        const int vrow = 64 * wg + 32 * (w >> 1) + 8 * (lr >> 1) + 4 * (w & 1) + (lr & 1);
        ep_step = 2 * 128;
        int m = 0;
        uint32_t lap = 0;
        LayerNorm ln;
        auto step = [&](auto kt, auto kc, float (&d)[64], int hh) {
            const Slot sa = c.slot(slot_a(kc.value), 0), sw = c.slot(slot_w(m), lap ^ (m >> 1));
            lap ^= m >> 1;
            m = (m == 2) ? 0 : m + 1;
            TR(1 + (hh * 8 + (kt.value ? 0 : 4) + kc.value) * 2);
            if (kt.value && hh == 0) c.wait(sa);
            c.wait(sw);
            TR(2 + (hh * 8 + (kt.value ? 0 : 4) + kc.value) * 2);
            wgmma_fence();
            gemm_kv<kt.value, kc.value == 0, 0, KVSPLIT>(d, sa.dl, sw.dl, wg);
            wgmma_commit();
            wgmma_wait<1>();
            if (!(kt.value && kc.value == 0 && hh == 0)) c.release(pend);
            if (!kt.value && kc.value > 0 && hh == 3) c.release(slot_a(kc.value - 1) * 8);
            pend = sw.bo;
            wgmma_fence();
            gemm_kv<kt.value, false, KVSPLIT, 8>(d, sa.dl, sw.dl, wg);
            wgmma_commit();
        };
#pragma unroll 1
        for (int hh = 0; hh < 4; hh++) {
            __nv_bfloat16* base = g_kv + (size_t)(((cb + 8 * kv_round(hh)) * 16 + 2 * ca + rank) * 2) * 16384 + 8 * q;
            auto ln_stage = [&](auto pos) {
                constexpr int j = (pos.value + 8 - LNOFF % 8) % 8;
                if (hh == wg + (LNOFF + j) / 8) {
                    if (j == 0) ln.stat1();
                    if (j == 1) ln.template stat2<0>();
                    if (j == 2) ln.template stat2<1>();
                    if constexpr (j >= 3) ln.template piece<j - 3>(ln_t, lane & 15);
                    if (j == 7) signal(bars, wg, 0, lane);
                }
                if (pos.value == (LNOFF - LNLEAD) % 8 && hh == wg + (LNOFF - LNLEAD) / 8) ln.load(P.x, P.wr, P.out, ln_t, lane & 15);
            };
            for4([&](auto kc) {
                step(TrueT{}, kc, s, hh);
                if (hh > 0) {
                    if (kc.value == 0) fence_regs(o);
                    store_chunk<kc.value>(o, ep_ptr, ep_ptr + ep_step, 1.f, 1.f);
                    if (kc.value == 3) signal(bars, wg, hh, lane);
                }
                ln_stage(kc);
            });
            for4([&](auto kc) {
                step(FalseT{}, kc, o, hh);
                if (kc.value == 0) fence_regs(s);
                store_chunk<kc.value>(s, base + krow * 128, base + (krow + 8) * 128, 1.f, 1.f);
                ln_stage(IntT<kc.value + 4>{});
            });
            PROF(24 + hh);
            if (hh == 1) PROFG(181);
            ep_ptr = base + 16384 + vrow * 128;
        }
    }
    PROFG(182);
    PROF(2);
    uint32_t pf[32];
    {
        uint32_t qf[32];
        float l0 = 0.25f, l1 = 0.25f;
        const int bar_me = 2 + wg, bar_other = 3 - wg;
#pragma unroll 1
        for (int j = 0; j < n_items(ca, cb); j++) {
            const int rd = item_rd(ca, cb, j), h = item_h(cb, rd, j), p = item_q(ca, cb, rd);
            const int role = wg ^ (j & 1);
            const int nrest = 2 * p + role;
            Slot kfirst;
            const int lim = 64 * (role ^ rank) + 16 * w + lr - 8 * q;
            const uint64_t pol = policy_sel(j == 1 || j == 2);
            {
                auto qstep = [&](auto zero, int ks) {
                    const Slot sl = c.next();
                    c.wait(sl);
                    BP(2, 5 + 3 * ks);
                    wgmma_fence();
                    gemm_q<zero.value>(s, sl.dl, role);
                    wgmma_commit();
                    wgmma_wait<1>();
                    if (!zero.value || j > 0 || cb < 8) c.release(pend);
                    pend = sl.bo;
                };
                qstep(TrueT{}, 0);
                if (j == 0 && cb < 8) c.release(slot_a(3) * 8);
                fence_regs(o);
                l0 += __shfl_xor_sync(0xffffffffu, l0, 1); l1 += __shfl_xor_sync(0xffffffffu, l1, 1);
                l0 += __shfl_xor_sync(0xffffffffu, l0, 2); l1 += __shfl_xor_sync(0xffffffffu, l1, 2);
                l0 = rcp(l0); l1 = rcp(l1);
                for4([&](auto i) {
                    constexpr int B = 16 * i.value;
#pragma unroll
                    for (int r = 0; r < 2; r++) {
                        if (1 + 2 * i.value + r == 7 && !(role | rank)) named_sync(bar_me, 256);
                        qstep(FalseT{}, 1 + 2 * i.value + r);
                        const float f = r ? l1 : l0;
                        stg128p(ep_ptr + r * ep_step + 2 * B, pack_bf16(o[B + 2 * r] * f, o[B + 2 * r + 1] * f), pack_bf16(o[B + 2 * r + 4] * f, o[B + 2 * r + 5] * f),
                                pack_bf16(o[B + 2 * r + 8] * f, o[B + 2 * r + 9] * f), pack_bf16(o[B + 2 * r + 12] * f, o[B + 2 * r + 13] * f), pol);
#pragma unroll
                        for (int k = 0; k < 8; k++) {
                            float& v = o[B + 4 * (k >> 1) + 2 * r + (k & 1)];
                            v = (2 * B + k > lim + 8 * r) ? -1e30f : 0.f;
                            asm volatile("" : "+f"(v));
                        }
                    }
                });
                signal(bars, wg, (cb == 8 ? 0 : 4) + j, lane);
                PROF(11 + rd * 4);
                qstep(FalseT{}, 9);
                if (!role) { const Slot sl = c.next(); c.wait(sl); c.release(sl.bo); }
                kfirst = c.next();
                c.wait(kfirst);
                wgmma_wait<0>();
                BP(2, 34);
                c.release(pend);
                fence_regs(s);
                pack_tile(s, qf);
            }
            Slot vskip = c.cur;
            if (!role) vskip = c.next();
            PROF(8 + rd * 4);
            if (cb == 8) PROF(40 + 3 * j);
            fence_regs(qf); fence_regs(o);
            if (!role && rank) named_sync(bar_me, 256);
            BP(2, 36);
            auto first_qk = [&](auto half) {
                wgmma_fence();
#pragma unroll
                for (int k = 0; k < 8; k++) {
                    if (half.value) wgmma_rs_n64<1>(o, qf[4 * k], qf[4 * k + 1], qf[4 * k + 2], qf[4 * k + 3], kfirst.dl + lbo(16384) + k * 128, 1);
                    else wgmma_rs_n128<1>(o, qf[4 * k], qf[4 * k + 1], qf[4 * k + 2], qf[4 * k + 3], kfirst.dl + lbo(16384) + k * 128, 1);
                }
                wgmma_commit();
                named_arrive(bar_other, 256);
                if (!role) { c.wait(vskip); c.release(vskip.bo); }
                wgmma_wait<0>();
            };
            if (role == rank) first_qk(TrueT{});
            else first_qk(FalseT{});
            BP(2, 38);
            fence_regs(o);
            c.release(kfirst.bo);
            uint32_t ready = c.peek();
            float n0 = fmaxf(fmaxf(fmaxf(o[0], o[1]), fmaxf(o[4], o[5])), fmaxf(fmaxf(o[8], o[9]), fmaxf(o[12], o[13])));
            float n1 = fmaxf(fmaxf(fmaxf(o[2], o[3]), fmaxf(o[6], o[7])), fmaxf(fmaxf(o[10], o[11]), fmaxf(o[14], o[15])));
            n0 = __shfl_sync(0xffffffffu, n0, lane & 28); n1 = __shfl_sync(0xffffffffu, n1, lane & 28);
            n0 *= -SM_SCALE; n1 *= -SM_SCALE;
            l0 = 0.f; l1 = 0.f;
#pragma unroll
            for (int i = 0; i < 64; i++) s[i] = o[i];
            exp_part<0, 8>(s, n0, n1, l0, l1);
#pragma unroll
            for (int i = 0; i < 16; i++) pf[i] = pack_bf16(s[2 * i], s[2 * i + 1]);
            if (role != rank) {
                exp_part<8, 16>(s, n0, n1, l0, l1);
#pragma unroll
                for (int i = 16; i < 32; i++) pf[i] = pack_bf16(s[2 * i], s[2 * i + 1]);
            } else {
#pragma unroll
                for (int i = 16; i < 32; i++) pf[i] = 0u;
            }
            PROF(9 + rd * 4);
            if (cb == 8) PROF(41 + 3 * j);
#pragma unroll 1
            for (int it = 0; it < nrest; it++) {
                const Slot sk = c.next(), sv = c.next();
                LP(0);
                c.wait(sk, ready);
                fence_regs(o); fence_regs(pf);
                LP(1);
                named_sync(bar_me, 256);
                LP(2);
                if (it < 3) BP(2, 42 + 4 * it);
                if (it >= nrest - 2) BP(1, 62 + 4 * (it - nrest + 2));
                wgmma_fence();
                gemm_rs<true>(s, qf, sk.dl);
                wgmma_commit();
                c.wait(sv);
                wgmma_fence();
                gemm_pv(o, pf, sv.dl, it, it | (role ^ rank));
                wgmma_commit();
                named_arrive(bar_other, 256);
                LP(3);
                wgmma_wait<2>();
                LP(4);
                c.release(sk.bo);
                fence_regs(s);
                exp_part<0, SPLITJ>(s, n0, n1, l0, l1);
                sched_barrier(l0, l1, bars + MISC_OFF + 16);
                LP(5);
                wgmma_wait<0>();
                LP(6);
                c.release(sv.bo);
                ready = c.peek();
                fence_regs(o); fence_regs(pf);
                exp_part<SPLITJ, 16>(s, n0, n1, l0, l1);
                pack_tile(s, pf);
            }
            PROF(10 + rd * 4);
            if (cb == 8) PROF(42 + 3 * j);
            PROFG(183 + rd);
            const Slot sv = c.next();
            BP(1, 0);
            c.wait(sv, ready);
            const bool bad = __any_sync(0xffffffffu, !(l0 < 0x1p60f && l1 < 0x1p60f));
            if (__builtin_expect(bad || nrest == 0, 0)) {
#pragma unroll
                for (int i = 0; i < 64; i++) o[i] = 0.f;
                if (bad) {
                    attention_exact(o, qf, l0, l1, h, nrest + 1, lim, lane);
#pragma unroll
                    for (int i = 0; i < 32; i++) pf[i] = 0u;
                }
            }
            fence_regs(o); fence_regs(pf);
            if (!role) named_sync(bar_me, 256);
            BP(1, 2);
            wgmma_fence();
            gemm_rs<false>(o, pf, sv.dl);
            wgmma_commit();
            pend = sv.bo;
            ep_ptr = g_ctx + (size_t)(h * SEQ + 256 * p + 128 * rank + 64 * role + 16 * w + lr) * HD + 8 * q;
            ep_step = 8 * HD;
        }
        l0 += __shfl_xor_sync(0xffffffffu, l0, 1); l1 += __shfl_xor_sync(0xffffffffu, l1, 1);
        l0 += __shfl_xor_sync(0xffffffffu, l0, 2); l1 += __shfl_xor_sync(0xffffffffu, l1, 2);
        l0 = rcp(l0); l1 = rcp(l1);
        sched_barrier(l0, l1, bars + MISC_OFF + 16);
        wgmma_wait<0>();
        c.release(pend);
        fence_regs(o); fence_regs(pf);
#pragma unroll
        for (int i = 0; i < 32; i++) pf[i] = pack_bf16(o[2 * i] * ((i & 1) ? l1 : l0), o[2 * i + 1] * ((i & 1) ? l1 : l0));
    }
    PROFG(187);
    PROF(3);
    if (cb == 8) {
#pragma unroll
        for (int i = 0; i < 8; i++) stg128(ep_ptr + (i & 1) * 8 * HD + 32 * (i >> 1), pf[4 * (i & 6) + (i & 1)], pf[4 * (i & 6) + (i & 1) + 2], pf[4 * (i & 6) + (i & 1) + 4], pf[4 * (i & 6) + (i & 1) + 6]);
        signal(bars, wg, 8, lane);
        cluster_arrive();
        named_sync(1, 256);
        mod_ffn(P, smem, 2 * ca + rank, wg);
    } else
    {
        float a1[64], a2[96];
        uint32_t px = 0, py = 0;
        auto mma1 = [&](const Slot& x, int acc) {
#pragma unroll
            for (int k = 0; k < 4; k++) wgmma_ss_n128<0, 1>(a1, x.dl + wg * 512 + lbo(16) + k * 2, x.dl + 1024 + lbo(4096) + (k >> 1) * 512 + (k & 1) * 128, k ? 1 : acc);
        };
        auto mma2 = [&](const Slot& x, const Slot& y, int acc) {
#pragma unroll
            for (int k = 0; k < 4; k++) wgmma_ss_n192<0, 1>(a2, x.dl + wg * 512 + lbo(16) + k * 2, y.dl + lbo(4096) + (k >> 1) * 768 + (k & 1) * 128, k ? 1 : acc);
        };
#pragma unroll 1
        for (int t = 0, more = 1; more; t++) {
            const Slot sx = c.next(), sy = c.next();
            OP(2 * t);
            c.wait(sx);
            OP(2 * t + 1);
            wgmma_fence();
            mma1(sx, t);
            wgmma_commit();
            wgmma_wait<1>();
            asm volatile("ld.shared.u32 %0, [%1];" : "=r"(more) : "r"(bars + CTL_OFF + sx.bo) : "memory");
            if (t > 0) { c.release(px); c.release(py); }
            px = sx.bo; py = sy.bo;
            c.wait(sy);
            wgmma_fence();
            mma2(sx, sy, t);
            wgmma_commit();
            more = !__any_sync(0xffffffffu, more);
            if (t == 0) {
#pragma unroll
                for (int i = 0; i < 4; i++) stg128(ep_ptr + 32 * i, pf[8 * i], pf[8 * i + 2], pf[8 * i + 4], pf[8 * i + 6]);
            }
            if (t == 1) {
#pragma unroll
                for (int i = 0; i < 4; i++) stg128(ep_ptr + 8 * HD + 32 * i, pf[8 * i + 1], pf[8 * i + 3], pf[8 * i + 5], pf[8 * i + 7]);
                signal(bars, wg, 4 + n_items(ca, cb), lane);
            }
        }
        OP(60);
        const Slot x0 = c.next(), x1 = c.next(), x2 = c.next(), y0 = c.next(), y1 = c.next(), y2 = c.next(), fr = c.next();

        const int cw = __reduce_or_sync(0xffffffffu, wg * 4 + w);
        const int orow = unperm_row(256 * out_p(ca, cb) + 128 * rank + 16 * cw), ocol = 320 * (ca >> 2);
        const uint32_t sa = ((lane & 7) + (lane & 8)) * 128, sx = (lane >> 4) ^ (lane & 7);
        auto send = [&](auto chv, uint32_t box) {
            constexpr int ch = chv.value;
#pragma unroll
            for (int i = 0; i < 4; i++) {
                uint32_t r[4];
#pragma unroll
                for (int e = 0; e < 4; e++) {
                    const int k = 32 * ch + 8 * i + 2 * e;
                    r[e] = (ch < 2) ? pack_bf16(a1[k & 63], a1[(k & 63) + 1]) : pack_bf16(a2[ch < 2 ? 0 : k - 64], a2[ch < 2 ? 1 : k - 63]);
                }
                asm volatile("stmatrix.sync.aligned.m8n8.x4.shared.b16 [%0], {%1, %2, %3, %4};"
                             ::"r"(box + sa + ((sx ^ (2 * i)) << 4)), "r"(r[0]), "r"(r[1]), "r"(r[2]), "r"(r[3]) : "memory");
            }
            asm volatile("fence.proxy.async.shared::cta;" ::: "memory");
            __syncwarp();
            asm volatile(ELECT "cp.reduce.async.bulk.tensor.2d.global.shared::cta.add.bulk_group [%0, {%2, %3}], [%1];\n}\n"
                         ::"l"(&P.outm), "r"(box), "r"(ocol + 64 * ch), "r"(orow) : "memory");
        };
        auto addr = [&](const Slot& t) { return smem + t.bo * (SLOT / 8); };
        const bool follow = wg ^ ((n_items(ca, cb) - 1) & 1);
        c.wait(x0);
        c.wait(x1);
        c.wait(x2);
        if (follow) {
            wgmma_wait<0>();
            c.release(px); c.release(py);
            named_sync(2 + wg, 256);
        }
        wgmma_fence();
        mma1(x0, 1);
        wgmma_commit();
        wgmma_wait<1>();
        if (!follow) { c.release(px); c.release(py); }
        wgmma_fence();
        mma1(x1, 1);
        mma1(x2, 1);
        wgmma_commit();
        named_arrive(3 - wg, 256);
        mbar_wait(bars + BAR_DEP, 0);
        mbar_wait(bars + BAR_EMPTY + fr.bo, fr.par ^ 1);
        c.wait(y0);
        c.wait(y1);
        wgmma_wait<0>();
        fence_regs(a1);
        OP(61);
        send(IntT<0>{}, addr(fr) + cw * 4096);
        send(IntT<1>{}, addr(fr) + cw * 4096 + 2048);
        named_sync(2 + wg, 256);
        wgmma_fence();
        mma2(x0, y0, 1);
        mma2(x1, y1, 1);
        wgmma_commit();
        OP(62);
        c.wait(y2);
        wgmma_fence();
        mma2(x2, y2, 1);
        wgmma_commit();
        if (!follow) named_arrive(3 - wg, 256);
        wgmma_wait<0>();
        fence_regs(a2);
        PROFG(188);
        PROF(4);
        send(IntT<2>{}, addr(x0) + cw * 2048);
        send(IntT<3>{}, addr(x1) + cw * 2048);
        send(IntT<4>{}, addr(x2) + cw * 2048);
        PROF(5);
        asm volatile("cp.async.bulk.commit_group;\ncp.async.bulk.wait_group.read 0;" ::: "memory");
    }
    PROF(6);
}

__device__ __forceinline__ void mod_ffn(const Params& P, uint32_t smem, int mc  , int wg) {
    const int tid = threadIdx.x - 128, lane = tid & 31, cw = tid >> 5, q = lane & 3, lr = lane >> 2;
    const uint32_t xs = smem + 6 * SLOT, hs = xs + 10240 + wg * 1024, wmax = xs + 12288, sidx = wmax + 64, rbar = xs + 13312 + wg * 32;
    const uint32_t ring = smem + wg * 3 * SLOT;
    const int f0 = mc + 4 * wg, nunit = ((34 - f0) >> 3) * 8;
    const bool lead = __reduce_or_sync(0xffffffffu, cw & 3) == 0;
    auto lds = [](uint32_t a) { uint32_t v; asm volatile("ld.shared.u32 %0, [%1];" : "=r"(v) : "r"(a) : "memory"); return v; };
    auto sts = [](uint32_t a, uint32_t v) { asm volatile("st.shared.u32 [%0], %1;" ::"r"(a), "r"(v) : "memory"); };
    auto issue = [&](int u, int st) {
        if (lead && u < nunit) {
            const int fc = (f0 + (u & ~7)) * 64, k = u & 7;
            const uint32_t dst = ring + st * SLOT, bar = rbar + st * 8;
            w_expect_tx(bar, k == 7 ? 16384 : SLOT);
            if (k < 5) {
                w_tma_load_stream(dst, &P.wg, fc, k * 128, bar);
                w_tma_load_stream(dst + 16384, &P.wu, fc, k * 128, bar);
            } else {
#pragma unroll 1
                for (int b = 0; b < (k == 7 ? 2 : 4); b++) w_tma_load_stream(dst + b * 8192, &P.wd, (4 * (k - 5) + b) * 64, fc, bar);
            }
        }
    };
    if ((tid & 127) == 0) {
        mbar_init(rbar, 1); mbar_init(rbar + 8, 1); mbar_init(rbar + 16, 1);
        asm volatile("fence.mbarrier_init.release.cluster;" ::: "memory");
    }
    mbar_wait(smem + NSLOT * SLOT + BAR_DEP, 0);
    asm volatile("fence.proxy.async.shared::cta;" ::: "memory");
    named_sync(1, 256);
    PROF(1);
#pragma unroll 1
    for (int u = 0; u < 3; u++) issue(u, u);
    uint32_t key[8];
#pragma unroll
    for (int i = 0; i < 8; i++) {
        const int t = tid + 256 * i;
        uint32_t b = __float_as_uint(__ldcg(g_r + t) + 0.f) >> 16;
        b = (b & 0x8000u) ? (~b & 0xffffu) : (b | 0x8000u);
        key[i] = (b << 16) | (uint32_t)(0xffff - t);
    }
#pragma unroll 1
    for (int rnd = 0; rnd < 8; rnd++) {
        uint32_t mx = key[0];
#pragma unroll
        for (int i = 1; i < 8; i++) mx = max(mx, key[i]);
        sts(wmax + ((rnd & 1) * 8 + cw) * 4, __reduce_max_sync(0xffffffffu, mx));
        named_sync(1, 256);
        mx = __reduce_max_sync(0xffffffffu, lds(wmax + ((rnd & 1) * 8 + (lane & 7)) * 4));
#pragma unroll
        for (int i = 0; i < 8; i++) if (key[i] == mx) key[i] = 0;
        if (cw == rnd) sts(sidx + rnd * 4, 0xffff - (mx & 0xffffu));
    }
    __syncwarp();
    {
        const int t = lds(sidx + cw * 4);
        const uint4* src = reinterpret_cast<const uint4*>(g_xn + perm_row(t) * DM);
#pragma unroll
        for (int i = 0; i < 3; i++) {
            const int ch = lane + 32 * i;
            if (ch < 80) {
                const uint4 v = __ldcg(src + ch);
                asm volatile("st.shared.v4.b32 [%0], {%1, %2, %3, %4};" ::"r"(xs + (ch >> 3) * 1024 + cw * 128 + ((ch ^ cw) & 7) * 16), "r"(v.x), "r"(v.y), "r"(v.z), "r"(v.w) : "memory");
            }
        }
        asm volatile("fence.proxy.async.shared::cta;" ::: "memory");
    }
    named_sync(1, 256);
    PROF(3);
    float y[10][4];
#pragma unroll
    for (int i = 0; i < 10; i++) { y[i][0] = 0.f; y[i][1] = 0.f; y[i][2] = 0.f; y[i][3] = 0.f; }
    int st = 0, ph = 0, u = 0;
    auto begin = [&]() { mbar_wait(rbar + st * 8, ph); wgmma_fence(); return (((ring + st * SLOT) & 0x3FFFF) >> 4) + lbo(16); };
    auto end = [&]() {
        wgmma_commit();
        wgmma_wait<0>();
        named_sync(4 + wg, 128);
        issue(u + 3, st);
        u++;
        ph ^= st == 2;
        st = (st == 2) ? 0 : st + 1;
    };
    const uint32_t dx = ((xs & 0x3FFFF) >> 4) + lbo(16), dh = ((hs & 0x3FFFF) >> 4) + lbo(16);
#pragma unroll 1
    while (u < nunit) {
        float g[4], v[4];
#pragma unroll 1
        for (int kc = 0; kc < 5; kc++) {
            const uint32_t da = begin();
#pragma unroll
            for (int k = 0; k < 8; k++) {
                const uint32_t db = dx + (2 * kc + (k >> 2)) * 64 + (k & 3) * 2;
                wgmma_ss_n8<1, 0>(g, da + k * 128, db, k ? 1 : kc);
                wgmma_ss_n8<1, 0>(v, da + 1024 + k * 128, db, k ? 1 : kc);
            }
            end();
        }
        fence_regs(g); fence_regs(v);
#pragma unroll
        for (int e = 0; e < 4; e++) {
            const float gp = round_bf16(g[e]);
            const float hv = round_bf16(__fdividef(gp, 1.0f + __expf(fminf(-gp, 80.f)))) * round_bf16(v[e]);
            const int tok = 2 * q + (e & 1), ch = 2 * (cw & 3) + (e >> 1);
            asm volatile("st.shared.u16 [%0], %1;" ::"r"(hs + tok * 128 + ((ch ^ tok) * 16) + lr * 2), "h"((unsigned short)pack_bf16(hv, 0.f)) : "memory");
        }
        asm volatile("fence.proxy.async.shared::cta;" ::: "memory");
        named_sync(4 + wg, 128);
#pragma unroll
        for (int k3 = 0; k3 < 3; k3++) {
            const uint32_t da = begin();
#pragma unroll
            for (int b = 0; b < (k3 == 2 ? 2 : 4); b++)
#pragma unroll
                for (int k = 0; k < 4; k++) wgmma_ss_n8<1, 0>(y[4 * k3 + b], da + b * 512 + k * 128, dh + k * 2, 1);
            end();
        }
    }
    PROF(5);
#pragma unroll
    for (int i = 0; i < 10; i++) {
        fence_regs(y[i]);
#pragma unroll
        for (int e = 0; e < 4; e++) g_ypart[((mc * 2 + wg) * 8 + 2 * q + (e & 1)) * DM + 64 * i + 16 * (cw & 3) + lr + 8 * (e >> 1)] = y[i][e];
    }
    named_sync(1, 256);
    if (tid == 0) {
        flag_add(F_MODP);
        flag_wait<100>(F_MODP, 4u * (lds(smem + NSLOT * SLOT + MISC_OFF) + 1));
    }
    named_sync(1, 256);
    PROF(6);
    {
        const int c = 2 * mc + wg, t = lds(sidx + c * 4);
        const float rs = round_bf16(__fdividef(1.0f, 1.0f + __expf(fminf(-__ldcg(g_r + t), 80.f))));
#pragma unroll
        for (int i = 0; i < 3; i++) {
            const int c2 = (tid & 127) + 128 * i;
            if (c2 < DM / 2) {
                float y0 = 0.f, y1 = 0.f;
#pragma unroll
                for (int k = 0; k < 8; k++) {
                    const float2 v = __ldcg(reinterpret_cast<const float2*>(g_ypart + (k * 8 + c) * DM) + c2);
                    y0 += v.x; y1 += v.y;
                }
                asm volatile("red.relaxed.gpu.global.add.noftz.bf16x2 [%0], %1;" ::"l"(P.out + t * DM + 2 * c2), "r"(pack_bf16(round_bf16(y0) * rs, round_bf16(y1) * rs)) : "memory");
            }
        }
    }
    PROF(7);
}

__global__ void __cluster_dims__(2, 1, 1) __launch_bounds__(384, 1) fused_kernel(const __grid_constant__ Params P) {
    extern __shared__ __align__(1024) uint8_t smem_raw[];
    const uint32_t smem = (smem_u32(smem_raw) + 1023u) & ~1023u;
    const uint32_t bars = smem + NSLOT * SLOT;
    const int wgi = __reduce_or_sync(0xffffffffu, threadIdx.x >> 7);
    const int cl = blockIdx.x >> 1, rank = blockIdx.x & 1, ca = cl & 7, cb = cl >> 3;
    PROFG(30);
    PROF(0);
    if (threadIdx.x == 64) {
        const uint32_t fa = bars + BAR_FULL + slot_a(0) * 8, fw = bars + BAR_FULL + slot_w(0) * 8;
        mbar_init(fa, 1); mbar_init(fw, 1);
        asm volatile("fence.mbarrier_init.release.cluster;" ::: "memory");
        if (cb < 8) {
            mbar_expect_tx(fa, SLOT);
            mbar_expect_tx(fw, SLOT);
            tma_load(smem + slot_a(0) * SLOT, &P.ckv, 0, (2 * ca + rank) * 128, fa);
            tma_load(smem + slot_w(0) * SLOT, &P.wuk, (cb + 8 * kv_round(0)) * 128, 0, fw);
            tma_load(smem + slot_w(0) * SLOT + 16384, &P.wuk, (cb + 8 * kv_round(0)) * 128 + 64, 0, fw);
            tma_load(smem + slot_a(0) * SLOT + 16384, &P.ckv, 64, (2 * ca + rank) * 128, fa);
        }
    } else if (threadIdx.x == 0) {
#pragma unroll
        for (int i = 0; i < NSLOT; i++) {
            if (i != slot_a(0) && i != slot_w(0)) mbar_init(bars + BAR_FULL + i * 8, 1);
            mbar_init(bars + BAR_EMPTY + i * 8, 16);
        }
        if (cb < 8) {
            mbar_arrive(bars + BAR_FULL + 16);
            asm volatile("mbarrier.arrive.shared::cta.b64 _, [%0], 16;" ::"r"(bars + BAR_EMPTY + 16) : "memory");
        }
        asm volatile("fence.mbarrier_init.release.cluster;" ::: "memory");
        PROF(24);
    } else if (threadIdx.x == 32) {
#pragma unroll
        for (int i = 0; i < 18; i++) mbar_init(bars + BAR_SIG + i * 8, 4);
#pragma unroll
        for (int i = 0; i < 18; i++) mbar_init(bars + BAR_DEP + i * 8, 1);
        asm volatile("fence.mbarrier_init.release.cluster;" ::: "memory");
    }
    __syncthreads();
    PROF(29);
    cluster_arrive();
    if (wgi > 0) {
        asm volatile("setmaxnreg.inc.sync.aligned.u32 232;");
        consumer(P, smem, bars, ca, cb, rank, wgi - 1);
        PROFG(31);
        PROFDUMP();
    } else {
        asm volatile("setmaxnreg.dec.sync.aligned.u32 40;");
        const int w = __reduce_or_sync(0xffffffffu, threadIdx.x >> 5), lane = threadIdx.x & 31;
        if (threadIdx.x == 32) {
            prefetch_map(&P.wuv); prefetch_map(&P.xn); prefetch_map(&P.wq); prefetch_map(&P.kv); prefetch_map(&P.ctx); prefetch_map(&P.wo); prefetch_map(&P.outm);
        }
        __syncwarp();
        cluster_wait();
        PROF(27);
        {
            if (w == 0) {
                producer(P, smem, bars, ca, cb, rank);
            } else if (w < 3 && lane == 0) {
                const int wg = w - 1;
#pragma unroll 1
                for (int i = (cb == 8); i < (cb == 8 ? 9 : 5 + n_items(ca, cb)); i++) {
                    const int nb = wg + (LNOFF + 7 - 4) / 8;
                    const int e = (cb == 8) ? i : (i < nb) ? i + 1 : (i == nb) ? 0 : i;
                    mbar_wait_sleep(bars + BAR_SIG + (wg * 9 + e) * 8, 0);
                    int f;
                    if (cb == 8) f = F_CTX + (2 + ca) * 16 + rank;
                    else if (e == 0) {
                        f = F_LN;
                        if ((ca & 3) == 0 && rank == 0 && wg == 0) g_flags[(F_POOL + out_p(ca, cb) * 2 + (ca >> 2)) * 8] = 8;
                    }
                    else if (e < 5) f = F_KV + cb + 8 * kv_round(e - 1);
                    else { const int rd = item_rd(ca, cb, e - 5); f = F_CTX + rd * 16 + item_p(ca, rd) * 2 + rank; }
                    flag_add(f);
                }
            } else if (lane == 0) {
                const uint32_t epoch = read_epoch();
                asm volatile("st.shared.u32 [%0], %1;" ::"r"(bars + MISC_OFF), "r"(epoch) : "memory");
#pragma unroll 1
                for (int e = 0; e < 9; e++) {
                    int f;
                    uint32_t n;
                    if (e == 0) { f = F_LN; n = 256; }
                    else if (cb == 8) { f = F_KV + item_h(cb, 2 + ca, e - 1); n = 32; }
                    else if (e < 5) { f = F_KV + cb + 8 * (e - 1); n = 32; }
                    else { f = F_CTX + (e - 5) * 16 + out_p(ca, cb) * 2 + rank; n = 16; }
                    flag_wait<200>(f, n * (epoch + 1));
                    fence_proxy_async();
                    mbar_arrive(bars + BAR_DEP + e * 8);
                }
            }
        }
        if (cb == 8) { __syncwarp(); cluster_arrive(); cluster_wait(); }
        PROFG(31);
        PROFDUMP();
    }
}

typedef CUresult (*EncodeFn)(CUtensorMap*, CUtensorMapDataType, cuuint32_t, void*, const cuuint64_t*, const cuuint64_t*, const cuuint32_t*,
                             const cuuint32_t*, CUtensorMapInterleave, CUtensorMapSwizzle, CUtensorMapL2promotion, CUtensorMapFloatOOBfill);

void make_map(EncodeFn fn, CUtensorMap* m, const void* ptr, uint64_t rows, uint64_t cols, uint32_t box_rows) {
    cuuint64_t dims[2] = {cols, rows};
    cuuint64_t strides[1] = {cols * 2};
    cuuint32_t box[2] = {64, box_rows};
    cuuint32_t es[2] = {1, 1};
    fn(m, CU_TENSOR_MAP_DATA_TYPE_BFLOAT16, 2, const_cast<void*>(ptr), dims, strides, box, es, CU_TENSOR_MAP_INTERLEAVE_NONE,
       CU_TENSOR_MAP_SWIZZLE_128B, CU_TENSOR_MAP_L2_PROMOTION_L2_128B, CU_TENSOR_MAP_FLOAT_OOB_FILL_NONE);
}

}

extern "C" void kernel_launch(void* const* d_in, const int* in_sizes, int n_in, void* d_out, int out_size) {
    (void)in_sizes; (void)n_in; (void)out_size;
    void* fnp = nullptr;
    cudaDriverEntryPointQueryResult qr;
    cudaGetDriverEntryPoint("cuTensorMapEncodeTiled", &fnp, cudaEnableDefault, &qr);
    EncodeFn fn = (EncodeFn)fnp;
    void *xn, *kv, *ctx;
    cudaGetSymbolAddress(&xn, g_xn);
    cudaGetSymbolAddress(&kv, g_kv);
    cudaGetSymbolAddress(&ctx, g_ctx);
    Params P;
    make_map(fn, &P.ckv, d_in[1], SEQ, DC, 128);
    make_map(fn, &P.wq, d_in[2], DM, NH * HD, 64);
    make_map(fn, &P.wuk, d_in[3], DC, NH * HD, 128);
    make_map(fn, &P.wuv, d_in[4], DC, NH * HD, 128);
    make_map(fn, &P.wo, d_in[5], NH * HD, DM, 32);
    make_map(fn, &P.xn, xn, SEQ, DM, 128);
    make_map(fn, &P.kv, kv, NH * 16 * 2 * 128, 128, 128);
    make_map(fn, &P.ctx, ctx, NH * SEQ, HD, 128);
    P.x = (const __nv_bfloat16*)d_in[0];
    P.wr = (const __nv_bfloat16*)d_in[7];
    make_map(fn, &P.wg, d_in[8], DM, FF, 128);
    make_map(fn, &P.wu, d_in[9], DM, FF, 128);
    make_map(fn, &P.wd, d_in[10], FF, DM, 64);
    make_map(fn, &P.outm, d_out, SEQ, DM, 16);
    P.out = (__nv_bfloat16*)d_out;
    cudaFuncSetAttribute(fused_kernel, cudaFuncAttributeMaxDynamicSharedMemorySize, SMEM_BYTES);
    fused_kernel<<<NCTA, 384, SMEM_BYTES>>>(P);
}
```

```cpp
#include <cuda_runtime.h>
#include <cuda_bf16.h>
#include <cuda.h>
#include <stdint.h>

namespace {

constexpr int SEQ = 2048, DM = 640, DC = 512, NH = 32, HD = 128, FF = 1728;
constexpr int NSLOT = 7, SLOT = 32768;
constexpr int NCTA = 132;
constexpr int KVSPLIT = 1;
constexpr int LNOFF = 4, LNLEAD = 2;
constexpr int SPLITJ = 8;
constexpr uint32_t DESC_HI = (1024u >> 4) | (1u << 30);
constexpr int SMEM_BYTES = NSLOT * SLOT + 3072;

constexpr int BAR_FULL = 0, BAR_EMPTY = 64, BAR_SIG = 128  , BAR_DEP = 320  , BAR_MAIL = 400  ;
constexpr int MISC_OFF = 512  , MAIL_OFF = 544  , CTL_OFF = 576  ;

constexpr int F_EPOCH = 0, F_LN = 1, F_MODP = 3, F_KV = 4  , F_CTX = 36  , F_POOL = 100  , F_NUM = 116;

__device__ __align__(1024) __nv_bfloat16 g_xn[SEQ * DM];
__device__ __align__(1024) __nv_bfloat16 g_kv[NH * 16 * 2 * 128 * 128];
__device__ __align__(1024) __nv_bfloat16 g_ctx[NH * SEQ * HD];
__device__ __align__(16) float g_r[SEQ];
__device__ __align__(16) float g_ypart[8 * 8 * DM];
__device__ uint32_t g_flags[F_NUM * 8];

struct TrueT { static constexpr bool value = true; };
struct FalseT { static constexpr bool value = false; };

struct Params {
    CUtensorMap ckv, wuk, wuv, xn, wq, kv, ctx, wo, wg, wu, wd, outm;
    const __nv_bfloat16 *x, *wr;
    __nv_bfloat16* out;
};

__device__ __forceinline__ uint32_t smem_u32(const void* p) { return (uint32_t)__cvta_generic_to_shared(p); }
__device__ __forceinline__ void mbar_init(uint32_t bar, uint32_t cnt) {
    asm volatile("mbarrier.init.shared::cta.b64 [%0], %1;" ::"r"(bar), "r"(cnt) : "memory");
}
__device__ __forceinline__ void mbar_expect_tx(uint32_t bar, uint32_t bytes) {
    asm volatile("mbarrier.arrive.expect_tx.shared::cta.b64 _, [%0], %1;" ::"r"(bar), "r"(bytes) : "memory");
}
__device__ __forceinline__ void mbar_arrive(uint32_t bar) {
    asm volatile("mbarrier.arrive.shared::cta.b64 _, [%0];" ::"r"(bar) : "memory");
}
__device__ __forceinline__ uint32_t mapa(uint32_t addr, uint32_t cta) {
    uint32_t r;
    asm("mapa.shared::cluster.u32 %0, %1, %2;" : "=r"(r) : "r"(addr), "r"(cta));
    return r;
}
__device__ __forceinline__ void mbar_wait(uint32_t bar, uint32_t parity) {
    asm volatile(
        "{\n.reg .pred p;\n.reg .b32 c;\n"
        "mov.b32 c, 0;\n"
        "WLOOP:\n"
        "mbarrier.try_wait.parity.shared::cta.b64 p, [%0], %1;\n"
        "@p bra.uni WDONE;\n"
        "add.u32 c, c, 1;\n"
        "setp.lt.u32 p, c, 0x400000;\n"
        "@p bra.uni WLOOP;\n"
        "trap;\n"
        "WDONE:\n}\n" ::"r"(bar), "r"(parity) : "memory");
}
__device__ __forceinline__ uint32_t mbar_peek(uint32_t bar, uint32_t parity) {
    uint32_t ok;
    asm volatile("{\n.reg .pred p;\nmbarrier.test_wait.parity.shared::cta.b64 p, [%1], %2;\nselp.b32 %0, 1, 0, p;\n}\n" : "=r"(ok) : "r"(bar), "r"(parity) : "memory");
    return ok;
}
__device__ __forceinline__ void mbar_wait_unless(uint32_t ok, uint32_t bar, uint32_t parity) {
    asm volatile(
        "{\n.reg .pred p;\n.reg .b32 c;\n"
        "setp.ne.b32 p, %2, 0;\n"
        "@p bra.uni WDONE;\n"
        "mov.b32 c, 0;\n"
        "WLOOP:\n"
        "mbarrier.try_wait.parity.shared::cta.b64 p, [%0], %1;\n"
        "@p bra.uni WDONE;\n"
        "add.u32 c, c, 1;\n"
        "setp.lt.u32 p, c, 0x400000;\n"
        "@p bra.uni WLOOP;\n"
        "trap;\n"
        "WDONE:\n}\n" ::"r"(bar), "r"(parity), "r"(ok) : "memory");
}
__device__ __forceinline__ void mbar_wait_sleep(uint32_t bar, uint32_t parity) {
    asm volatile(
        "{\n.reg .pred p;\n.reg .b32 c;\n"
        "mov.b32 c, 0;\n"
        "WLOOP:\n"
        "mbarrier.try_wait.parity.shared::cta.b64 p, [%0], %1, 20000;\n"
        "@p bra.uni WDONE;\n"
        "add.u32 c, c, 1;\n"
        "setp.lt.u32 p, c, 0x40000;\n"
        "@p bra.uni WLOOP;\n"
        "trap;\n"
        "WDONE:\n}\n" ::"r"(bar), "r"(parity) : "memory");
}
__device__ __forceinline__ void tma_load(uint32_t dst, const CUtensorMap* m, int c0, int c1, uint32_t bar) {
    asm volatile("cp.async.bulk.tensor.2d.shared::cluster.global.mbarrier::complete_tx::bytes [%0], [%1, {%3, %4}], [%2];"
                 ::"r"(dst), "l"(m), "r"(bar), "r"(c0), "r"(c1) : "memory");
}
#define ELECT "{\n.reg .pred e;\nelect.sync _|e, 0xffffffff;\n@e "
__device__ __forceinline__ void w_expect_tx(uint32_t bar, uint32_t bytes) {
    asm volatile(ELECT "mbarrier.arrive.expect_tx.shared::cta.b64 _, [%0], %1;\n}\n" ::"r"(bar), "r"(bytes) : "memory");
}
__device__ __forceinline__ void w_tma_load(uint32_t dst, const CUtensorMap* m, int c0, int c1, uint32_t bar) {
    asm volatile(ELECT "cp.async.bulk.tensor.2d.shared::cluster.global.mbarrier::complete_tx::bytes [%0], [%1, {%3, %4}], [%2];\n}\n"
                 ::"r"(dst), "l"(m), "r"(bar), "r"(c0), "r"(c1) : "memory");
}
__device__ __forceinline__ void w_tma_load_mc(uint32_t dst, const CUtensorMap* m, int c0, int c1, uint32_t bar) {
    asm volatile(ELECT "cp.async.bulk.tensor.2d.shared::cluster.global.mbarrier::complete_tx::bytes.multicast::cluster [%0], [%1, {%3, %4}], [%2], %5;\n}\n"
                 ::"r"(dst), "l"(m), "r"(bar), "r"(c0), "r"(c1), "h"((uint16_t)3) : "memory");
}
__device__ __forceinline__ void w_tma_prefetch(const CUtensorMap* m, int c0, int c1) {
    asm volatile(ELECT "cp.async.bulk.prefetch.tensor.2d.L2.global [%0, {%1, %2}];\n}\n" ::"l"(m), "r"(c0), "r"(c1) : "memory");
}
__device__ __forceinline__ uint64_t policy_evict_first() {
    uint64_t p;
    asm("createpolicy.fractional.L2::evict_first.b64 %0, 1.0;" : "=l"(p));
    return p;
}
__device__ __forceinline__ void w_tma_load_mc_last(uint32_t dst, const CUtensorMap* m, int c0, int c1, uint32_t bar) {
    asm volatile(ELECT "cp.async.bulk.tensor.2d.shared::cluster.global.mbarrier::complete_tx::bytes.multicast::cluster.L2::cache_hint [%0], [%1, {%3, %4}], [%2], %5, %6;\n}\n"
                 ::"r"(dst), "l"(m), "r"(bar), "r"(c0), "r"(c1), "h"((uint16_t)3), "l"(policy_evict_first()) : "memory");
}
__device__ __forceinline__ void w_tma_load_stream(uint32_t dst, const CUtensorMap* m, int c0, int c1, uint32_t bar) {
    asm volatile(ELECT "cp.async.bulk.tensor.2d.shared::cluster.global.mbarrier::complete_tx::bytes.L2::cache_hint [%0], [%1, {%3, %4}], [%2], %5;\n}\n"
                 ::"r"(dst), "l"(m), "r"(bar), "r"(c0), "r"(c1), "l"(policy_evict_first()) : "memory");
}
__device__ __forceinline__ uint4 ldg_stream(const void* p) {
    uint4 v;
    asm volatile("ld.global.nc.L2::cache_hint.v4.b32 {%0, %1, %2, %3}, [%4], %5;" : "=r"(v.x), "=r"(v.y), "=r"(v.z), "=r"(v.w) : "l"(p), "l"(policy_evict_first()));
    return v;
}
__device__ __forceinline__ void prefetch_map(const CUtensorMap* m) {
    asm volatile("prefetch.tensormap [%0];" ::"l"(m) : "memory");
}
__device__ __forceinline__ void cluster_arrive() { asm volatile("barrier.cluster.arrive.relaxed.aligned;" ::: "memory"); }
__device__ __forceinline__ void cluster_wait() { asm volatile("barrier.cluster.wait.aligned;" ::: "memory"); }
__device__ __forceinline__ void named_sync(int id, int n) { asm volatile("bar.sync %0, %1;" ::"r"(id), "r"(n) : "memory"); }
__device__ __forceinline__ void named_arrive(int id, int n) { asm volatile("bar.arrive %0, %1;" ::"r"(id), "r"(n) : "memory"); }

__device__ __forceinline__ void flag_add(int f) {
    asm volatile("fence.acq_rel.gpu;\nred.relaxed.gpu.global.add.u32 [%0], 1;" ::"l"(g_flags + f * 8) : "memory");
}
template <int SLEEP>
__device__ __forceinline__ void flag_wait(int f, uint32_t target) {
    asm volatile(
        "{\n.reg .pred p;\n.reg .b32 c, v;\n"
        "mov.b32 c, 0;\n"
        "FLOOP:\n"
        "ld.acquire.gpu.global.u32 v, [%0];\n"
        "sub.u32 v, v, %1;\n"
        "setp.ge.s32 p, v, 0;\n"
        "@p bra FDONE;\n"
        "nanosleep.u32 %2;\n"
        "add.u32 c, c, 1;\n"
        "setp.lt.u32 p, c, 0x400000;\n"
        "@p bra FLOOP;\n"
        "trap;\n"
        "FDONE:\n}\n" ::"l"(g_flags + f * 8), "r"(target), "n"(SLEEP) : "memory");
}
__device__ __forceinline__ uint32_t read_epoch() { return atomicAdd(g_flags + F_EPOCH * 8, 1u) / NCTA; }
__device__ __forceinline__ void fence_proxy_async() { asm volatile("fence.proxy.async.global;" ::: "memory"); }

__device__ __forceinline__ void wgmma_fence() { asm volatile("wgmma.fence.sync.aligned;" ::: "memory"); }
__device__ __forceinline__ void wgmma_commit() { asm volatile("wgmma.commit_group.sync.aligned;" ::: "memory"); }
template <int N>
__device__ __forceinline__ void wgmma_wait() { asm volatile("wgmma.wait_group.sync.aligned %0;" ::"n"(N) : "memory"); }
template <int N>
__device__ __forceinline__ void fence_regs(float (&d)[N]) {
#pragma unroll
    for (int i = 0; i < N; i++) asm volatile("" : "+f"(d[i])::"memory");
}
template <int N>
__device__ __forceinline__ void fence_regs(uint32_t (&d)[N]) {
#pragma unroll
    for (int i = 0; i < N; i++) asm volatile("" : "+r"(d[i])::"memory");
}

template <int TA, int TB>
__device__ __forceinline__ void wgmma_ss_n128(float (&d)[64], uint32_t alo, uint32_t blo, int scale_d) {
    asm volatile("{\n.reg .pred p;\n.reg .b64 da, db;\nsetp.ne.b32 p, %66, 0;\n"
        "mov.b64 da, {%64, %69};\nmov.b64 db, {%65, %69};\n"
        "wgmma.mma_async.sync.aligned.m64n128k16.f32.bf16.bf16 "
        "{%0, %1, %2, %3, %4, %5, %6, %7, %8, %9, %10, %11, %12, %13, %14, %15, %16, %17, %18, %19, %20, %21, %22, %23, %24, %25, %26, %27, %28, %29, %30, %31, %32, %33, %34, %35, %36, %37, %38, %39, %40, %41, %42, %43, %44, %45, %46, %47, %48, %49, %50, %51, %52, %53, %54, %55, %56, %57, %58, %59, %60, %61, %62, %63}, da, db, p, 1, 1, %67, %68;\n}\n"
        :
          "+f"(d[0]), "+f"(d[1]), "+f"(d[2]), "+f"(d[3]), "+f"(d[4]), "+f"(d[5]), "+f"(d[6]), "+f"(d[7]),
          "+f"(d[8]), "+f"(d[9]), "+f"(d[10]), "+f"(d[11]), "+f"(d[12]), "+f"(d[13]), "+f"(d[14]), "+f"(d[15]),
          "+f"(d[16]), "+f"(d[17]), "+f"(d[18]), "+f"(d[19]), "+f"(d[20]), "+f"(d[21]), "+f"(d[22]), "+f"(d[23]),
          "+f"(d[24]), "+f"(d[25]), "+f"(d[26]), "+f"(d[27]), "+f"(d[28]), "+f"(d[29]), "+f"(d[30]), "+f"(d[31]),
          "+f"(d[32]), "+f"(d[33]), "+f"(d[34]), "+f"(d[35]), "+f"(d[36]), "+f"(d[37]), "+f"(d[38]), "+f"(d[39]),
          "+f"(d[40]), "+f"(d[41]), "+f"(d[42]), "+f"(d[43]), "+f"(d[44]), "+f"(d[45]), "+f"(d[46]), "+f"(d[47]),
          "+f"(d[48]), "+f"(d[49]), "+f"(d[50]), "+f"(d[51]), "+f"(d[52]), "+f"(d[53]), "+f"(d[54]), "+f"(d[55]),
          "+f"(d[56]), "+f"(d[57]), "+f"(d[58]), "+f"(d[59]), "+f"(d[60]), "+f"(d[61]), "+f"(d[62]), "+f"(d[63])
        : "r"(alo), "r"(blo), "r"(scale_d), "n"(TA), "n"(TB), "r"(DESC_HI));
}
template <int TA, int TB>
__device__ __forceinline__ void wgmma_ss_n192(float (&d)[96], uint32_t alo, uint32_t blo, int scale_d) {
    asm volatile("{\n.reg .pred p;\n.reg .b64 da, db;\nsetp.ne.b32 p, %98, 0;\n"
        "mov.b64 da, {%96, %101};\nmov.b64 db, {%97, %101};\n"
        "wgmma.mma_async.sync.aligned.m64n192k16.f32.bf16.bf16 "
        "{%0, %1, %2, %3, %4, %5, %6, %7, %8, %9, %10, %11, %12, %13, %14, %15, %16, %17, %18, %19, %20, %21, %22, %23, %24, %25, %26, %27, %28, %29, %30, %31, %32, %33, %34, %35, %36, %37, %38, %39, %40, %41, %42, %43, %44, %45, %46, %47, %48, %49, %50, %51, %52, %53, %54, %55, %56, %57, %58, %59, %60, %61, %62, %63, %64, %65, %66, %67, %68, %69, %70, %71, %72, %73, %74, %75, %76, %77, %78, %79, %80, %81, %82, %83, %84, %85, %86, %87, %88, %89, %90, %91, %92, %93, %94, %95}, da, db, p, 1, 1, %99, %100;\n}\n"
        :
          "+f"(d[0]), "+f"(d[1]), "+f"(d[2]), "+f"(d[3]), "+f"(d[4]), "+f"(d[5]), "+f"(d[6]), "+f"(d[7]),
          "+f"(d[8]), "+f"(d[9]), "+f"(d[10]), "+f"(d[11]), "+f"(d[12]), "+f"(d[13]), "+f"(d[14]), "+f"(d[15]),
          "+f"(d[16]), "+f"(d[17]), "+f"(d[18]), "+f"(d[19]), "+f"(d[20]), "+f"(d[21]), "+f"(d[22]), "+f"(d[23]),
          "+f"(d[24]), "+f"(d[25]), "+f"(d[26]), "+f"(d[27]), "+f"(d[28]), "+f"(d[29]), "+f"(d[30]), "+f"(d[31]),
          "+f"(d[32]), "+f"(d[33]), "+f"(d[34]), "+f"(d[35]), "+f"(d[36]), "+f"(d[37]), "+f"(d[38]), "+f"(d[39]),
          "+f"(d[40]), "+f"(d[41]), "+f"(d[42]), "+f"(d[43]), "+f"(d[44]), "+f"(d[45]), "+f"(d[46]), "+f"(d[47]),
          "+f"(d[48]), "+f"(d[49]), "+f"(d[50]), "+f"(d[51]), "+f"(d[52]), "+f"(d[53]), "+f"(d[54]), "+f"(d[55]),
          "+f"(d[56]), "+f"(d[57]), "+f"(d[58]), "+f"(d[59]), "+f"(d[60]), "+f"(d[61]), "+f"(d[62]), "+f"(d[63]),
          "+f"(d[64]), "+f"(d[65]), "+f"(d[66]), "+f"(d[67]), "+f"(d[68]), "+f"(d[69]), "+f"(d[70]), "+f"(d[71]),
          "+f"(d[72]), "+f"(d[73]), "+f"(d[74]), "+f"(d[75]), "+f"(d[76]), "+f"(d[77]), "+f"(d[78]), "+f"(d[79]),
          "+f"(d[80]), "+f"(d[81]), "+f"(d[82]), "+f"(d[83]), "+f"(d[84]), "+f"(d[85]), "+f"(d[86]), "+f"(d[87]),
          "+f"(d[88]), "+f"(d[89]), "+f"(d[90]), "+f"(d[91]), "+f"(d[92]), "+f"(d[93]), "+f"(d[94]), "+f"(d[95])
        : "r"(alo), "r"(blo), "r"(scale_d), "n"(TA), "n"(TB), "r"(DESC_HI));
}
template <int TA, int TB>
__device__ __forceinline__ void wgmma_ss_n8(float (&d)[4], uint32_t alo, uint32_t blo, int scale_d) {
    asm volatile("{\n.reg .pred p;\n.reg .b64 da, db;\nsetp.ne.b32 p, %6, 0;\n"
        "mov.b64 da, {%4, %9};\nmov.b64 db, {%5, %9};\n"
        "wgmma.mma_async.sync.aligned.m64n8k16.f32.bf16.bf16 "
        "{%0, %1, %2, %3}, da, db, p, 1, 1, %7, %8;\n}\n"
        :
          "+f"(d[0]), "+f"(d[1]), "+f"(d[2]), "+f"(d[3])
        : "r"(alo), "r"(blo), "r"(scale_d), "n"(TA), "n"(TB), "r"(DESC_HI));
}
template <int TB>
__device__ __forceinline__ void wgmma_rs_n64(float (&d)[64], uint32_t a0, uint32_t a1, uint32_t a2, uint32_t a3, uint32_t blo, int scale_d) {
    asm volatile("{\n.reg .pred p;\n.reg .b64 db;\nsetp.ne.b32 p, %37, 0;\n"
        "mov.b64 db, {%36, %39};\n"
        "wgmma.mma_async.sync.aligned.m64n64k16.f32.bf16.bf16 "
        "{%0, %1, %2, %3, %4, %5, %6, %7, %8, %9, %10, %11, %12, %13, %14, %15, %16, %17, %18, %19, %20, %21, %22, %23, %24, %25, %26, %27, %28, %29, %30, %31}, {%32, %33, %34, %35}, db, p, 1, 1, %38;\n}\n"
        :
          "+f"(d[0]), "+f"(d[1]), "+f"(d[2]), "+f"(d[3]), "+f"(d[4]), "+f"(d[5]), "+f"(d[6]), "+f"(d[7]),
          "+f"(d[8]), "+f"(d[9]), "+f"(d[10]), "+f"(d[11]), "+f"(d[12]), "+f"(d[13]), "+f"(d[14]), "+f"(d[15]),
          "+f"(d[16]), "+f"(d[17]), "+f"(d[18]), "+f"(d[19]), "+f"(d[20]), "+f"(d[21]), "+f"(d[22]), "+f"(d[23]),
          "+f"(d[24]), "+f"(d[25]), "+f"(d[26]), "+f"(d[27]), "+f"(d[28]), "+f"(d[29]), "+f"(d[30]), "+f"(d[31])
        : "r"(a0), "r"(a1), "r"(a2), "r"(a3), "r"(blo), "r"(scale_d), "n"(TB), "r"(DESC_HI));
}
template <int TB>
__device__ __forceinline__ void wgmma_rs_n128(float (&d)[64], uint32_t a0, uint32_t a1, uint32_t a2, uint32_t a3, uint32_t blo, int scale_d) {
    asm volatile("{\n.reg .pred p;\n.reg .b64 db;\nsetp.ne.b32 p, %69, 0;\n"
        "mov.b64 db, {%68, %71};\n"
        "wgmma.mma_async.sync.aligned.m64n128k16.f32.bf16.bf16 "
        "{%0, %1, %2, %3, %4, %5, %6, %7, %8, %9, %10, %11, %12, %13, %14, %15, %16, %17, %18, %19, %20, %21, %22, %23, %24, %25, %26, %27, %28, %29, %30, %31, %32, %33, %34, %35, %36, %37, %38, %39, %40, %41, %42, %43, %44, %45, %46, %47, %48, %49, %50, %51, %52, %53, %54, %55, %56, %57, %58, %59, %60, %61, %62, %63}, {%64, %65, %66, %67}, db, p, 1, 1, %70;\n}\n"
        :
          "+f"(d[0]), "+f"(d[1]), "+f"(d[2]), "+f"(d[3]), "+f"(d[4]), "+f"(d[5]), "+f"(d[6]), "+f"(d[7]),
          "+f"(d[8]), "+f"(d[9]), "+f"(d[10]), "+f"(d[11]), "+f"(d[12]), "+f"(d[13]), "+f"(d[14]), "+f"(d[15]),
          "+f"(d[16]), "+f"(d[17]), "+f"(d[18]), "+f"(d[19]), "+f"(d[20]), "+f"(d[21]), "+f"(d[22]), "+f"(d[23]),
          "+f"(d[24]), "+f"(d[25]), "+f"(d[26]), "+f"(d[27]), "+f"(d[28]), "+f"(d[29]), "+f"(d[30]), "+f"(d[31]),
          "+f"(d[32]), "+f"(d[33]), "+f"(d[34]), "+f"(d[35]), "+f"(d[36]), "+f"(d[37]), "+f"(d[38]), "+f"(d[39]),
          "+f"(d[40]), "+f"(d[41]), "+f"(d[42]), "+f"(d[43]), "+f"(d[44]), "+f"(d[45]), "+f"(d[46]), "+f"(d[47]),
          "+f"(d[48]), "+f"(d[49]), "+f"(d[50]), "+f"(d[51]), "+f"(d[52]), "+f"(d[53]), "+f"(d[54]), "+f"(d[55]),
          "+f"(d[56]), "+f"(d[57]), "+f"(d[58]), "+f"(d[59]), "+f"(d[60]), "+f"(d[61]), "+f"(d[62]), "+f"(d[63])
        : "r"(a0), "r"(a1), "r"(a2), "r"(a3), "r"(blo), "r"(scale_d), "n"(TB), "r"(DESC_HI));
}
template <int TB>
__device__ __forceinline__ void wgmma_rs_n128_z(float (&d)[64], uint32_t a0, uint32_t a1, uint32_t a2, uint32_t a3, uint32_t blo) {
    asm volatile("{\n.reg .pred p;\n.reg .b64 db;\nsetp.ne.b32 p, %69, 0;\n"
        "mov.b64 db, {%68, %71};\n"
        "wgmma.mma_async.sync.aligned.m64n128k16.f32.bf16.bf16 "
        "{%0, %1, %2, %3, %4, %5, %6, %7, %8, %9, %10, %11, %12, %13, %14, %15, %16, %17, %18, %19, %20, %21, %22, %23, %24, %25, %26, %27, %28, %29, %30, %31, %32, %33, %34, %35, %36, %37, %38, %39, %40, %41, %42, %43, %44, %45, %46, %47, %48, %49, %50, %51, %52, %53, %54, %55, %56, %57, %58, %59, %60, %61, %62, %63}, {%64, %65, %66, %67}, db, p, 1, 1, %70;\n}\n"
        :
          "=f"(d[0]), "=f"(d[1]), "=f"(d[2]), "=f"(d[3]), "=f"(d[4]), "=f"(d[5]), "=f"(d[6]), "=f"(d[7]),
          "=f"(d[8]), "=f"(d[9]), "=f"(d[10]), "=f"(d[11]), "=f"(d[12]), "=f"(d[13]), "=f"(d[14]), "=f"(d[15]),
          "=f"(d[16]), "=f"(d[17]), "=f"(d[18]), "=f"(d[19]), "=f"(d[20]), "=f"(d[21]), "=f"(d[22]), "=f"(d[23]),
          "=f"(d[24]), "=f"(d[25]), "=f"(d[26]), "=f"(d[27]), "=f"(d[28]), "=f"(d[29]), "=f"(d[30]), "=f"(d[31]),
          "=f"(d[32]), "=f"(d[33]), "=f"(d[34]), "=f"(d[35]), "=f"(d[36]), "=f"(d[37]), "=f"(d[38]), "=f"(d[39]),
          "=f"(d[40]), "=f"(d[41]), "=f"(d[42]), "=f"(d[43]), "=f"(d[44]), "=f"(d[45]), "=f"(d[46]), "=f"(d[47]),
          "=f"(d[48]), "=f"(d[49]), "=f"(d[50]), "=f"(d[51]), "=f"(d[52]), "=f"(d[53]), "=f"(d[54]), "=f"(d[55]),
          "=f"(d[56]), "=f"(d[57]), "=f"(d[58]), "=f"(d[59]), "=f"(d[60]), "=f"(d[61]), "=f"(d[62]), "=f"(d[63])
        : "r"(a0), "r"(a1), "r"(a2), "r"(a3), "r"(blo), "n"(0), "n"(TB), "r"(DESC_HI));
}
template <int TA, int TB>
__device__ __forceinline__ void wgmma_ss_n128_z(float (&d)[64], uint32_t alo, uint32_t blo) {
    asm volatile("{\n.reg .pred p;\n.reg .b64 da, db;\nsetp.ne.b32 p, %66, 0;\n"
        "mov.b64 da, {%64, %69};\nmov.b64 db, {%65, %69};\n"
        "wgmma.mma_async.sync.aligned.m64n128k16.f32.bf16.bf16 "
        "{%0, %1, %2, %3, %4, %5, %6, %7, %8, %9, %10, %11, %12, %13, %14, %15, %16, %17, %18, %19, %20, %21, %22, %23, %24, %25, %26, %27, %28, %29, %30, %31, %32, %33, %34, %35, %36, %37, %38, %39, %40, %41, %42, %43, %44, %45, %46, %47, %48, %49, %50, %51, %52, %53, %54, %55, %56, %57, %58, %59, %60, %61, %62, %63}, da, db, p, 1, 1, %67, %68;\n}\n"
        :
          "=f"(d[0]), "=f"(d[1]), "=f"(d[2]), "=f"(d[3]), "=f"(d[4]), "=f"(d[5]), "=f"(d[6]), "=f"(d[7]),
          "=f"(d[8]), "=f"(d[9]), "=f"(d[10]), "=f"(d[11]), "=f"(d[12]), "=f"(d[13]), "=f"(d[14]), "=f"(d[15]),
          "=f"(d[16]), "=f"(d[17]), "=f"(d[18]), "=f"(d[19]), "=f"(d[20]), "=f"(d[21]), "=f"(d[22]), "=f"(d[23]),
          "=f"(d[24]), "=f"(d[25]), "=f"(d[26]), "=f"(d[27]), "=f"(d[28]), "=f"(d[29]), "=f"(d[30]), "=f"(d[31]),
          "=f"(d[32]), "=f"(d[33]), "=f"(d[34]), "=f"(d[35]), "=f"(d[36]), "=f"(d[37]), "=f"(d[38]), "=f"(d[39]),
          "=f"(d[40]), "=f"(d[41]), "=f"(d[42]), "=f"(d[43]), "=f"(d[44]), "=f"(d[45]), "=f"(d[46]), "=f"(d[47]),
          "=f"(d[48]), "=f"(d[49]), "=f"(d[50]), "=f"(d[51]), "=f"(d[52]), "=f"(d[53]), "=f"(d[54]), "=f"(d[55]),
          "=f"(d[56]), "=f"(d[57]), "=f"(d[58]), "=f"(d[59]), "=f"(d[60]), "=f"(d[61]), "=f"(d[62]), "=f"(d[63])
        : "r"(alo), "r"(blo), "n"(0), "n"(TA), "n"(TB), "r"(DESC_HI));
}

__device__ __forceinline__ uint32_t pack_bf16(float lo, float hi) {
    uint32_t r;
    asm("cvt.rn.bf16x2.f32 %0, %1, %2;" : "=r"(r) : "f"(hi), "f"(lo));
    return r;
}
__device__ __forceinline__ uint32_t add_bf16x2(uint32_t a, uint32_t b) {
    uint32_t r;
    asm("add.rn.bf16x2 %0, %1, %2;" : "=r"(r) : "r"(a), "r"(b));
    return r;
}
__device__ __forceinline__ float bf_lo(uint32_t v) { return __uint_as_float(v << 16); }
__device__ __forceinline__ float bf_hi(uint32_t v) { return __uint_as_float(v & 0xffff0000u); }
__device__ __forceinline__ float round_bf16(float v) { return __bfloat162float(__float2bfloat16_rn(v)); }
__device__ __forceinline__ float ex2(float x) {
    float y;
    asm("ex2.approx.ftz.f32 %0, %1;" : "=f"(y) : "f"(x));
    return y;
}
__device__ __forceinline__ float rcp(float x) {
    float y;
    asm("rcp.approx.ftz.f32 %0, %1;" : "=f"(y) : "f"(x));
    return y;
}
__device__ __forceinline__ void stg128(void* p, uint32_t a, uint32_t b, uint32_t c, uint32_t d) {
    asm volatile("st.global.v4.b32 [%0], {%1, %2, %3, %4};" ::"l"(p), "r"(a), "r"(b), "r"(c), "r"(d) : "memory");
}
__device__ __forceinline__ void stg128p(void* p, uint32_t a, uint32_t b, uint32_t c, uint32_t d, uint64_t pol) {
    asm volatile("st.global.L2::cache_hint.v4.b32 [%0], {%1, %2, %3, %4}, %5;" ::"l"(p), "r"(a), "r"(b), "r"(c), "r"(d), "l"(pol) : "memory");
}
__device__ __forceinline__ uint64_t policy_sel(bool first) {
    uint64_t p;
    asm("createpolicy.fractional.L2::evict_normal.b64 %0, 1.0;" : "=l"(p));
    return first ? policy_evict_first() : p;
}
__device__ __forceinline__ int perm_row(int t) { return (t & ~255) | (((0x78 >> (((t >> 6) & 3) * 2)) & 3) << 6) | (t & 63); }
__device__ __forceinline__ int unperm_row(int t) { return (t & ~255) | (((0x9C >> (((t >> 6) & 3) * 2)) & 3) << 6) | (t & 63); }

#define PROF(i)
#define PROFG(i)
#define PROFDUMP()
#define TR(i)
#define OP(i)
#define BP(r, i)
#define LP(i)

template <int I>
__device__ __forceinline__ void store_chunk(const float (&a)[64], __nv_bfloat16* row0, __nv_bfloat16* row1, float s0, float s1) {
    stg128(row0 + 32 * I, pack_bf16(a[16 * I + 0] * s0, a[16 * I + 1] * s0), pack_bf16(a[16 * I + 4] * s0, a[16 * I + 5] * s0),
           pack_bf16(a[16 * I + 8] * s0, a[16 * I + 9] * s0), pack_bf16(a[16 * I + 12] * s0, a[16 * I + 13] * s0));
    stg128(row1 + 32 * I, pack_bf16(a[16 * I + 2] * s1, a[16 * I + 3] * s1), pack_bf16(a[16 * I + 6] * s1, a[16 * I + 7] * s1),
           pack_bf16(a[16 * I + 10] * s1, a[16 * I + 11] * s1), pack_bf16(a[16 * I + 14] * s1, a[16 * I + 15] * s1));
}
template <int I>
struct IntT { static constexpr int value = I; };
template <class F>
__device__ __forceinline__ void for4(F f) { f(IntT<0>{}); f(IntT<1>{}); f(IntT<2>{}); f(IntT<3>{}); }

struct Prod {
    uint32_t smem, bars;
    uint32_t bo, par;
    uint32_t dst, fb;
    __device__ __forceinline__ void acquire(uint32_t o, uint32_t parity, uint32_t bytes) {
        mbar_wait(bars + BAR_EMPTY + o, parity);
        fb = bars + BAR_FULL + o;
        dst = smem + o * (SLOT / 8);
        w_expect_tx(fb, bytes);
    }
    __device__ __forceinline__ void next(uint32_t bytes) {
        acquire(bo, par, bytes);
        const bool wrap = bo == (NSLOT - 1) * 8;
        bo = wrap ? 0u : bo + 8;
        par ^= wrap ? 1u : 0u;
    }
};

__device__ __forceinline__ int item_p(int ca, int rd) {
    const int v = (rd & 1) ? (ca + 4) & 7 : ca;
    return (rd & 2) ? 7 - v : v;
}
__device__ __forceinline__ int n_items(int ca, int cb) { return cb == 8 ? 8 : ((ca & 3) == 3) ? 3 : 4; }
__device__ __forceinline__ int item_rd(int ca, int cb, int j) { return cb == 8 ? 2 + ca : (ca == 7 && j == 2) ? 3 : j; }
__device__ __forceinline__ int item_h(int cb, int rd, int j) { return 8 * rd + (cb == 8 ? j : cb); }
__device__ __forceinline__ int item_q(int ca, int cb, int rd) { return cb == 8 ? 0 : item_p(ca, rd); }
__device__ __forceinline__ int out_p(int ca, int cb) { return (cb + 2 * (ca & 3)) & 7; }
__device__ __forceinline__ int kv_round(int i) { return (0x1023 >> (4 * i)) & 3; }
__device__ __forceinline__ int slot_a(int i) { return (0x5310 >> (4 * i)) & 15; }
__device__ __forceinline__ int slot_w(int m) { return (0x264 >> (4 * m)) & 15; }

__device__ __forceinline__ void producer(const Params& P, uint32_t smem, uint32_t bars, int ca, int cb, int rank) {
    Prod pr{smem, bars, 0u, cb == 8 ? 1u : 0u, 0u, 0u};
    if (cb < 8) {
        int m = 0;
        uint32_t lap = 1;
#pragma unroll 1
        for (int u = 0; u < 32; u++) {
            if (u >= 3) {
                const int v = (u == 3) ? 3 + ca : u + 7;
                if (v < 32 && (u == 3 || (v & 7) == ca)) w_tma_prefetch((v & 4) ? &P.wuv : &P.wuk, (cb + 8 * kv_round(v >> 3)) * 128 + rank * 64, (v & 3) * 128);
                if (u == 24) {
                    w_tma_prefetch(&P.wq, cb * 128 + rank * 64, ca * 64);
                    if (ca < 2) w_tma_prefetch(&P.wq, cb * 128 + rank * 64, (ca + 8) * 64);
                }
            }
            if (u == 2) mbar_wait(bars + BAR_FULL + slot_w(2) * 8, 0);
            if (u > 0) pr.acquire(slot_w(m) * 8, lap ^ (m >> 1), SLOT);
            lap ^= m >> 1;
            m = (m == 2) ? 0 : m + 1;
            TR(1 + u);
            if (u > 0) w_tma_load_mc(pr.dst + rank * 16384, (u & 4) ? &P.wuv : &P.wuk, (cb + 8 * kv_round(u >> 3)) * 128 + rank * 64, (u & 3) * 128, pr.fb);
            if (u < 3) {
                pr.acquire(slot_a(u + 1) * 8, 1, SLOT);
                w_tma_load(pr.dst, &P.ckv, u * 128 + 128, (2 * ca + rank) * 128, pr.fb);
                w_tma_load(pr.dst + 16384, &P.ckv, u * 128 + 192, (2 * ca + rank) * 128, pr.fb);
            }
        }
    }
    PROF(1);
    if (cb == 8) {
        mbar_wait_sleep(bars + BAR_DEP + 8, 0);
#pragma unroll 1
        for (int ks = 0; ks < 10; ks++) w_tma_prefetch(&P.wq, item_h(cb, 2 + ca, 0) * 128 + rank * 64, ks * 64);
    }
    mbar_wait_sleep(bars + BAR_DEP, 0);
#pragma unroll 1
    for (int j = 0, pfs = 1; j < n_items(ca, cb); j++) {
        const int rd = item_rd(ca, cb, j), h = item_h(cb, rd, j), p = item_q(ca, cb, rd);
#pragma unroll 1
        for (int ks = 0; ks < 10; ks++) {
            pr.next(SLOT);
            w_tma_load_mc(pr.dst + 16384 + rank * 8192, &P.wq, h * 128 + rank * 64, ks * 64, pr.fb);
            w_tma_load(pr.dst, &P.xn, ks * 64, 256 * p + 128 * rank, pr.fb);
            if (cb == 8 && j < 7) w_tma_prefetch(&P.wq, (h + 1) * 128 + rank * 64, ks * 64);
        }
        PROF(8 + rd * 4);
        mbar_wait(bars + BAR_DEP + (1 + (cb == 8 ? j : rd)) * 8, 0);
        const int last = 4 * p + 3, top = h * 32 + last;
#pragma unroll 1
        for (int i = 0; i <= last; i++) {
            const int t = (i == 0) ? top - 1 : (i == last) ? h * 32 + 1 : (i & 1) ? top - 2 - i : top + 2 - i;
            pr.next(SLOT);
            const bool lastrd = (cb == 8 || rd == 3) ? false : (rd == 0) ? ca >= 6 : (rd == 1) ? (ca & 3) >= 2 : (ca == 3 || (ca < 3 && (t & 31) >= 4 * p));
            if (lastrd) w_tma_load_mc_last(pr.dst + rank * 16384, &P.kv, rank * 64, t * 128, pr.fb);
            else w_tma_load_mc(pr.dst + rank * 16384, &P.kv, rank * 64, t * 128, pr.fb);
            if (i == 2 && cb < 8) {
                const int upto = (j == n_items(ca, cb) - 1) ? 4 : item_rd(ca, cb, j + 1);
#pragma unroll 1
                for (; pfs <= upto; pfs++) {
                    if (pfs < 4) {
                        w_tma_prefetch(&P.wq, (8 * pfs + cb) * 128 + rank * 64, ca * 64);
                        if (ca < 2) w_tma_prefetch(&P.wq, (8 * pfs + cb) * 128 + rank * 64, (ca + 8) * 64);
                    } else {
#pragma unroll 1
                        for (int k = 0; k < 10; k++)
                            w_tma_prefetch(&P.wo, 320 * (ca >> 2) + 64 * (k >= 5 ? k - 5 : k), (cb * 4 + (ca & 3) + (k >= 5 ? 32 : 0)) * 64 + rank * 32);
                    }
                }
            }
        }
        PROF(9 + rd * 4);
    }
    if (cb < 8) {
        const int n0 = 320 * (ca >> 2), op = out_p(ca, cb);
        uint32_t* pool = g_flags + (F_POOL + op * 2 + (ca >> 2)) * 8;
        uint32_t nxt = 0;
        auto draw = [&]() {
            if (rank == 0) asm volatile(ELECT "atom.relaxed.gpu.global.add.u32 %0, [%1], 1;\n}\n" : "+r"(nxt) : "l"(pool) : "memory");
        };
        int fixed = -1;
#pragma unroll 1
        for (int i = -2; fixed < 4; i++) {
            int st = (ca & 3) + 4 * (i + 2);
            if (i == -1) draw();
            if (i >= 0 && fixed < 0) {
                const uint32_t mb = bars + BAR_MAIL + (i & 7) * 8, md = bars + MAIL_OFF + (i & 7) * 4;
                if (rank == 0) {
                    st = __reduce_add_sync(0xffffffffu, nxt);
                    asm volatile(ELECT "st.async.shared::cluster.mbarrier::complete_tx::bytes.b32 [%0], %1, [%2];\n}\n" ::"r"(mapa(md, 1)), "r"(st), "r"(mapa(mb, 1)) : "memory");
                    if (st < 48) draw();
                } else {
                    w_expect_tx(mb, 4);
                    mbar_wait(mb, (i >> 3) & 1);
                    asm volatile("ld.shared.u32 %0, [%1];" : "=r"(st) : "r"(md) : "memory");
                    st = __reduce_or_sync(0xffffffffu, st);
                }
                if (st >= 48) fixed = 0;
            }
            if (fixed >= 0) { st = 48 + (ca & 3) + 4 * fixed; fixed++; }
            const int krow = st * 64 + rank * 32;
            mbar_wait(bars + BAR_EMPTY + pr.bo, pr.par);
            asm volatile("st.shared.u32 [%0], %1;" ::"r"(bars + CTL_OFF + pr.bo), "r"((int)(fixed == 1)) : "memory");
            __syncwarp();
            pr.next(SLOT);
            w_tma_load_mc(pr.dst + 16384 + rank * 8192, &P.wo, n0, krow, pr.fb);
            w_tma_load_mc(pr.dst + 16384 + rank * 8192 + 4096, &P.wo, n0 + 64, krow, pr.fb);
            mbar_wait(bars + BAR_DEP + (5 + (st >> 4)) * 8, 0);
            w_tma_load(pr.dst, &P.ctx, (st & 1) * 64, (st >> 1) * SEQ + 256 * op + 128 * rank, pr.fb);
#pragma unroll 1
            for (int k = (fixed < 2) ? 0 : (fixed == 4) ? -2 : 1; k <= 0; k++) {
                pr.next(24576);
#pragma unroll
                for (int c = 0; c < 3; c++) w_tma_load_mc(pr.dst + rank * 12288 + c * 4096, &P.wo, n0 + 128 + 64 * c, krow + k * 256, pr.fb);
            }
        }
    }
}

struct Slot {
    uint32_t bo, dl, par;
};
struct Cons {
    uint32_t bars, rel;
    uint32_t dl0;
    uint32_t lane;
    Slot cur;
    __device__ __forceinline__ Slot slot(int s, uint32_t par) const { return Slot{(uint32_t)s * 8, dl0 + (uint32_t)s * (SLOT >> 4), par}; }
    __device__ __forceinline__ void wait(const Slot& s) const { mbar_wait(bars + BAR_FULL + s.bo, s.par); }
    __device__ __forceinline__ uint32_t peek() const { return mbar_peek(bars + BAR_FULL + cur.bo, cur.par); }
    __device__ __forceinline__ void wait(const Slot& s, uint32_t ok) const { mbar_wait_unless(ok, bars + BAR_FULL + s.bo, s.par); }
    __device__ __forceinline__ void release(uint32_t bo) const {
        asm volatile("{\n.reg .pred p;\nsetp.lt.u32 p, %1, 2;\n@p mbarrier.arrive.shared::cluster.b64 _, [%0];\n}\n" ::"r"(rel + bo), "r"(lane) : "memory");
    }
    __device__ __forceinline__ Slot next() {
        const Slot s = cur;
        const bool wrap = s.bo == (NSLOT - 1) * 8;
        cur.bo = wrap ? 0u : s.bo + 8;
        cur.dl = wrap ? dl0 : s.dl + (SLOT >> 4);
        cur.par = s.par ^ (wrap ? 1u : 0u);
        return s;
    }
};
__host__ __device__ constexpr uint32_t lbo(uint32_t bytes) { return (bytes >> 4) << 16; }

__device__ __forceinline__ float div640(float x) {
    const float q = x * (1.0f / DM);
    return fmaf(fmaf(-q, (float)DM, x), 1.0f / DM, q);
}
__device__ __forceinline__ float sqrt_approx(float x) {
    float y;
    asm("sqrt.approx.ftz.f32 %0, %1;" : "=f"(y) : "f"(x));
    return y;
}
struct LayerNorm {
    uint4 xv[5], wv[5];
    float mean, inv, r;
    uint32_t nmb;
    __nv_bfloat16 *pn, *po;
    static __device__ __forceinline__ float half_sum(float v) {
#pragma unroll
        for (int o = 8; o > 0; o >>= 1) v += __shfl_xor_sync(0xffffffffu, v, o);
        return v;
    }
    __device__ __forceinline__ void load(const __nv_bfloat16* x, const __nv_bfloat16* wr, __nv_bfloat16* out, int t, int l) {
        pn = g_xn + perm_row(t) * DM + 8 * l;
        po = out + t * DM + 8 * l;
        asm volatile("" : "+l"(pn), "+l"(po));
#pragma unroll
        for (int i = 0; i < 5; i++) {
            xv[i] = ldg_stream(reinterpret_cast<const uint4*>(x + t * DM) + l + 16 * i);
            wv[i] = __ldg(reinterpret_cast<const uint4*>(wr) + l + 16 * i);
        }
    }
    __device__ __forceinline__ void stat1() {
        float a[4] = {0.f, 0.f, 0.f, 0.f};
#pragma unroll
        for (int i = 0; i < 20; i++) { const uint32_t u = (&xv[i >> 2].x)[i & 3]; a[i & 3] += bf_lo(u) + bf_hi(u); }
        mean = div640(half_sum((a[0] + a[1]) + (a[2] + a[3])));
        r = 0.f;
    }
    template <int H>
    __device__ __forceinline__ void stat2() {
        float a[4] = {r, 0.f, 0.f, 0.f};
#pragma unroll
        for (int i = H ? 12 : 0; i < (H ? 20 : 12); i++) {
            uint32_t u = (&xv[i >> 2].x)[i & 3];
            asm volatile("" : "+r"(u));
            const float d0 = bf_lo(u) - mean, d1 = bf_hi(u) - mean;
            a[i & 3] = fmaf(d0, d0, fmaf(d1, d1, a[i & 3]));
        }
        r = (a[0] + a[1]) + (a[2] + a[3]);
        if (H) {
            inv = rcp(round_bf16(sqrt_approx(round_bf16(round_bf16(div640(half_sum(r))) + 1e-5f))));
            r = 0.f;
            nmb = pack_bf16(-mean, -mean);
        }
    }
    template <int I>
    __device__ __forceinline__ void piece(int t, int l) {
        uint32_t o[4], z[4];
        float a[4];
#pragma unroll
        for (int j = 0; j < 4; j++) {
            const uint32_t u = (&xv[I].x)[j], w = (&wv[I].x)[j];
            const uint32_t d = add_bf16x2(u, nmb);
            o[j] = pack_bf16(bf_lo(d) * inv, bf_hi(d) * inv);
            z[j] = add_bf16x2(u, o[j]);
            a[j] = fmaf(bf_hi(o[j]), bf_hi(w), bf_lo(o[j]) * bf_lo(w));
        }
        r += (a[0] + a[1]) + (a[2] + a[3]);
        stg128(pn + 128 * I, o[0], o[1], o[2], o[3]);
        stg128p(po + 128 * I, z[0], z[1], z[2], z[3], policy_evict_first());
        if (I == 4) {
            r = half_sum(r);
            if (l == 0) g_r[t] = round_bf16(r);
        }
    }
};

constexpr float SM_SCALE = 0.08838834764831845f * 1.4426950408889634f;

template <int J0, int J1>
__device__ __forceinline__ void exp_part(float (&s)[64], float n0, float n1, float& r0, float& r1) {
    float a1 = 0.f, b1 = 0.f;
#pragma unroll
    for (int j = J0; j < J1; j++) {
        s[4 * j + 0] = ex2(fmaf(s[4 * j + 0], SM_SCALE, n0));
        s[4 * j + 1] = ex2(fmaf(s[4 * j + 1], SM_SCALE, n0));
        s[4 * j + 2] = ex2(fmaf(s[4 * j + 2], SM_SCALE, n1));
        s[4 * j + 3] = ex2(fmaf(s[4 * j + 3], SM_SCALE, n1));
        r0 += s[4 * j + 0]; r1 += s[4 * j + 2];
        if (j == J0) { a1 = s[4 * j + 1]; b1 = s[4 * j + 3]; } else { a1 += s[4 * j + 1]; b1 += s[4 * j + 3]; }
    }
    r0 += a1;
    r1 += b1;
}
__device__ __forceinline__ void sched_barrier(float x, float y, uint32_t scratch) {
    asm volatile("{\n.reg .pred p;\nsetp.lt.f32 p, %0, 0f00000000;\n@p st.shared.f32 [%2], %1;\n}\n" ::"f"(x), "f"(y), "r"(scratch) : "memory");
}
__device__ __forceinline__ void pack_tile(const float (&s)[64], uint32_t (&p)[32]) {
#pragma unroll
    for (int i = 0; i < 32; i++) p[i] = pack_bf16(s[2 * i], s[2 * i + 1]);
}
template <bool ZERO>
__device__ __forceinline__ void gemm_rs(float (&d)[64], const uint32_t (&a)[32], uint32_t dl, int acc = 1) {
    const uint32_t b = dl + lbo(16384);
    if (ZERO) wgmma_rs_n128_z<1>(d, a[0], a[1], a[2], a[3], b);
#pragma unroll
    for (int k = ZERO ? 1 : 0; k < 8; k++) wgmma_rs_n128<1>(d, a[4 * k], a[4 * k + 1], a[4 * k + 2], a[4 * k + 3], b + k * 128, k ? 1 : acc);
}
__device__ __forceinline__ void gemm_pv(float (&d)[64], const uint32_t (&a)[32], uint32_t dl, int acc, int full) {
    const uint32_t b = dl + lbo(16384);
    wgmma_rs_n128<1>(d, a[0], a[1], a[2], a[3], b, acc);
    wgmma_commit();
    if (full) {
        wgmma_fence();
#pragma unroll
        for (int k = 4; k < 8; k++) wgmma_rs_n128<1>(d, a[4 * k], a[4 * k + 1], a[4 * k + 2], a[4 * k + 3], b + k * 128, 1);
        wgmma_commit();
    }
    wgmma_fence();
#pragma unroll
    for (int k = 1; k < 4; k++) wgmma_rs_n128<1>(d, a[4 * k], a[4 * k + 1], a[4 * k + 2], a[4 * k + 3], b + k * 128, 1);
}
template <int ZERO>
__device__ __forceinline__ void gemm_q(float (&d)[64], uint32_t dl, int role) {
    const uint32_t a = dl + role * 512 + lbo(16), b = dl + 1024 + lbo(8192);
    if (ZERO) wgmma_ss_n128_z<0, 1>(d, a, b);
#pragma unroll
    for (int k = ZERO ? 1 : 0; k < 4; k++) wgmma_ss_n128<0, 1>(d, a + k * 2, b + k * 128, 1);
}
template <bool KT, bool ZERO, int K0, int K1>
__device__ __forceinline__ void gemm_kv(float (&d)[64], uint32_t ckv, uint32_t wt, int wg) {
    if (KT) {
        const uint32_t a = wt + wg * 1024 + lbo(16), b = ckv + lbo(16);
        if (ZERO) wgmma_ss_n128_z<1, 0>(d, a, b);
#pragma unroll
        for (int k = ZERO ? 1 : K0; k < K1; k++) wgmma_ss_n128<1, 0>(d, a + k * 128, b + (k >> 2) * 1024 + (k & 3) * 2, 1);
    } else {
        const uint32_t a = ckv + wg * 512 + lbo(16), b = wt + lbo(16384);
        if (ZERO) wgmma_ss_n128_z<0, 1>(d, a, b);
#pragma unroll
        for (int k = ZERO ? 1 : K0; k < K1; k++) wgmma_ss_n128<0, 1>(d, a + (k >> 2) * 1024 + (k & 3) * 2, b + k * 128, 1);
    }
}
__device__ __forceinline__ void mma16816(float& d0, float& d1, float& d2, float& d3, uint32_t a0, uint32_t a1, uint32_t a2, uint32_t a3, uint32_t b0, uint32_t b1) {
    asm volatile("mma.sync.aligned.m16n8k16.row.col.f32.bf16.bf16.f32 {%0,%1,%2,%3}, {%4,%5,%6,%7}, {%8,%9}, {%0,%1,%2,%3};"
                 : "+f"(d0), "+f"(d1), "+f"(d2), "+f"(d3) : "r"(a0), "r"(a1), "r"(a2), "r"(a3), "r"(b0), "r"(b1));
}
__device__ __forceinline__ uint32_t ld_pair(const __nv_bfloat16* p) {
    const unsigned short* u = reinterpret_cast<const unsigned short*>(p);
    return (uint32_t)__ldcg(u) | ((uint32_t)__ldcg(u + 128) << 16);
}
__device__ __forceinline__ void attention_exact(float (&o)[64], const uint32_t (&qf)[32], float& l0, float& l1, int h, int nblk, int rr, int lane) {
    const int q = lane & 3, lr = lane >> 2;
    float m0 = -INFINITY, m1 = -INFINITY;
    l0 = 0.f; l1 = 0.f;
#pragma unroll 1
    for (int cidx = 0; cidx < nblk * 8; cidx++) {
        const int kc = cidx & 7;
        const __nv_bfloat16* kt = g_kv + (size_t)((h * 16 + (cidx >> 3)) * 2) * 16384;
        float sc[8];
#pragma unroll
        for (int i = 0; i < 8; i++) sc[i] = 0.f;
#pragma unroll
        for (int kk = 0; kk < 8; kk++)
#pragma unroll
            for (int nt = 0; nt < 2; nt++) {
                const __nv_bfloat16* b = kt + (16 * kk + 2 * q) * 128 + 16 * kc + 8 * nt + lr;
                mma16816(sc[4 * nt], sc[4 * nt + 1], sc[4 * nt + 2], sc[4 * nt + 3], qf[4 * kk], qf[4 * kk + 1], qf[4 * kk + 2], qf[4 * kk + 3],
                         ld_pair(b), ld_pair(b + 8 * 128));
            }
        const int lim = rr + ((nblk - 1) - (cidx >> 3)) * 128 - 32 * (kc >> 1) - 4 * (kc & 1);
#pragma unroll
        for (int i = 0; i < 8; i++)
            if (2 * (i >> 2) + (i & 1) > lim + 4 * (i & 2)) sc[i] = -INFINITY;
        float x0 = fmaxf(fmaxf(sc[0], sc[1]), fmaxf(sc[4], sc[5])), x1 = fmaxf(fmaxf(sc[2], sc[3]), fmaxf(sc[6], sc[7]));
        x0 = fmaxf(x0, __shfl_xor_sync(0xffffffffu, x0, 1)); x1 = fmaxf(x1, __shfl_xor_sync(0xffffffffu, x1, 1));
        x0 = fmaxf(x0, __shfl_xor_sync(0xffffffffu, x0, 2)); x1 = fmaxf(x1, __shfl_xor_sync(0xffffffffu, x1, 2));
        x0 = fmaxf(x0, m0); x1 = fmaxf(x1, m1);
        const float a0 = ex2((m0 - x0) * SM_SCALE), a1 = ex2((m1 - x1) * SM_SCALE);
        m0 = x0; m1 = x1;
#pragma unroll
        for (int i = 0; i < 8; i++) sc[i] = ex2((sc[i] - ((i & 2) ? m1 : m0)) * SM_SCALE);
        l0 = l0 * a0 + (sc[0] + sc[1]) + (sc[4] + sc[5]);
        l1 = l1 * a1 + (sc[2] + sc[3]) + (sc[6] + sc[7]);
        const uint32_t p0 = pack_bf16(sc[0], sc[1]), p1 = pack_bf16(sc[2], sc[3]), p2 = pack_bf16(sc[4], sc[5]), p3 = pack_bf16(sc[6], sc[7]);
        const __nv_bfloat16* vb = kt + 16384 + (16 * kc + 2 * q) * 128 + lr;
#pragma unroll
        for (int nt = 0; nt < 16; nt++) {
            o[4 * nt] *= a0; o[4 * nt + 1] *= a0; o[4 * nt + 2] *= a1; o[4 * nt + 3] *= a1;
            mma16816(o[4 * nt], o[4 * nt + 1], o[4 * nt + 2], o[4 * nt + 3], p0, p1, p2, p3, ld_pair(vb + 8 * nt), ld_pair(vb + 8 * nt + 8 * 128));
        }
    }
}

__device__ __forceinline__ void signal(uint32_t bars, int wg, int e, int lane) {
    __syncwarp();
    asm volatile("{\n.reg .pred p;\nsetp.eq.u32 p, %1, 0;\n@p mbarrier.arrive.shared::cta.b64 _, [%0];\n}\n" ::"r"(bars + BAR_SIG + (wg * 9 + e) * 8), "r"(lane) : "memory");
}

__device__ __forceinline__ void mod_ffn(const Params& P, uint32_t smem, int mc, int wg);

__device__ __forceinline__ void consumer(const Params& P, uint32_t smem, uint32_t bars, int ca, int cb, int rank, int wg) {
    const int lane = threadIdx.x & 31, w = (threadIdx.x >> 5) & 3, q = lane & 3, lr = lane >> 2;
    PROF(7);
    cluster_wait();
    Cons c{bars, mapa(bars + BAR_EMPTY, lane & 1), (smem & 0x3FFFF) >> 4, (uint32_t)lane, Slot{0u, (smem & 0x3FFFF) >> 4, cb == 8 ? 0u : 1u}};
    PROFG(180);
    PROF(1);
    float o[64], s[64];
    uint32_t pend;
    __nv_bfloat16* ep_ptr;
    int ep_step;
    if (cb == 8) {
        pend = 0;
        ep_ptr = g_ctx + (size_t)(item_h(cb, 2 + ca, 0) * SEQ + 128 * rank + 64 * wg + 16 * w + lr) * HD + 8 * q;
        ep_step = 8 * HD;
    } else {
        const int ln_t = blockIdx.x * 16 + wg * 8 + w * 2 + (lane >> 4);
        const int krow = 64 * wg + 16 * w + lr;
        const int vrow = 64 * wg + 32 * (w >> 1) + 8 * (lr >> 1) + 4 * (w & 1) + (lr & 1);
        ep_step = 2 * 128;
        int m = 0;
        uint32_t lap = 0;
        LayerNorm ln;
        auto step = [&](auto kt, auto kc, float (&d)[64], int hh) {
            const Slot sa = c.slot(slot_a(kc.value), 0), sw = c.slot(slot_w(m), lap ^ (m >> 1));
            lap ^= m >> 1;
            m = (m == 2) ? 0 : m + 1;
            TR(1 + (hh * 8 + (kt.value ? 0 : 4) + kc.value) * 2);
            if (kt.value && hh == 0) c.wait(sa);
            c.wait(sw);
            TR(2 + (hh * 8 + (kt.value ? 0 : 4) + kc.value) * 2);
            wgmma_fence();
            gemm_kv<kt.value, kc.value == 0, 0, KVSPLIT>(d, sa.dl, sw.dl, wg);
            wgmma_commit();
            wgmma_wait<1>();
            if (!(kt.value && kc.value == 0 && hh == 0)) c.release(pend);
            if (!kt.value && kc.value > 0 && hh == 3) c.release(slot_a(kc.value - 1) * 8);
            pend = sw.bo;
            wgmma_fence();
            gemm_kv<kt.value, false, KVSPLIT, 8>(d, sa.dl, sw.dl, wg);
            wgmma_commit();
        };
#pragma unroll 1
        for (int hh = 0; hh < 4; hh++) {
            __nv_bfloat16* base = g_kv + (size_t)(((cb + 8 * kv_round(hh)) * 16 + 2 * ca + rank) * 2) * 16384 + 8 * q;
            auto ln_stage = [&](auto pos) {
                constexpr int j = (pos.value + 8 - LNOFF % 8) % 8;
                if (hh == wg + (LNOFF + j) / 8) {
                    if (j == 0) ln.stat1();
                    if (j == 1) ln.template stat2<0>();
                    if (j == 2) ln.template stat2<1>();
                    if constexpr (j >= 3) ln.template piece<j - 3>(ln_t, lane & 15);
                    if (j == 7) signal(bars, wg, 0, lane);
                }
                if (pos.value == (LNOFF - LNLEAD) % 8 && hh == wg + (LNOFF - LNLEAD) / 8) ln.load(P.x, P.wr, P.out, ln_t, lane & 15);
            };
            for4([&](auto kc) {
                step(TrueT{}, kc, s, hh);
                if (hh > 0) {
                    if (kc.value == 0) fence_regs(o);
                    store_chunk<kc.value>(o, ep_ptr, ep_ptr + ep_step, 1.f, 1.f);
                    if (kc.value == 3) signal(bars, wg, hh, lane);
                }
                ln_stage(kc);
            });
            for4([&](auto kc) {
                step(FalseT{}, kc, o, hh);
                if (kc.value == 0) fence_regs(s);
                store_chunk<kc.value>(s, base + krow * 128, base + (krow + 8) * 128, 1.f, 1.f);
                ln_stage(IntT<kc.value + 4>{});
            });
            PROF(24 + hh);
            if (hh == 1) PROFG(181);
            ep_ptr = base + 16384 + vrow * 128;
        }
    }
    PROFG(182);
    PROF(2);
    uint32_t pf[32];
    {
        uint32_t qf[32];
        float l0 = 0.25f, l1 = 0.25f;
        const int bar_me = 2 + wg, bar_other = 3 - wg;
#pragma unroll 1
        for (int j = 0; j < n_items(ca, cb); j++) {
            const int rd = item_rd(ca, cb, j), h = item_h(cb, rd, j), p = item_q(ca, cb, rd);
            const int role = wg ^ (j & 1);
            const int nrest = 2 * p + role;
            Slot kfirst;
            const int lim = 64 * (role ^ rank) + 16 * w + lr - 8 * q;
            const uint64_t pol = policy_sel(j == 1 || j == 2);
            {
                auto qstep = [&](auto zero, int ks) {
                    const Slot sl = c.next();
                    c.wait(sl);
                    BP(2, 5 + 3 * ks);
                    wgmma_fence();
                    gemm_q<zero.value>(s, sl.dl, role);
                    wgmma_commit();
                    wgmma_wait<1>();
                    if (!zero.value || j > 0 || cb < 8) c.release(pend);
                    pend = sl.bo;
                };
                qstep(TrueT{}, 0);
                if (j == 0 && cb < 8) c.release(slot_a(3) * 8);
                fence_regs(o);
                l0 += __shfl_xor_sync(0xffffffffu, l0, 1); l1 += __shfl_xor_sync(0xffffffffu, l1, 1);
                l0 += __shfl_xor_sync(0xffffffffu, l0, 2); l1 += __shfl_xor_sync(0xffffffffu, l1, 2);
                l0 = rcp(l0); l1 = rcp(l1);
                for4([&](auto i) {
                    constexpr int B = 16 * i.value;
#pragma unroll
                    for (int r = 0; r < 2; r++) {
                        if (1 + 2 * i.value + r == 7 && !(role | rank)) named_sync(bar_me, 256);
                        qstep(FalseT{}, 1 + 2 * i.value + r);
                        const float f = r ? l1 : l0;
                        stg128p(ep_ptr + r * ep_step + 2 * B, pack_bf16(o[B + 2 * r] * f, o[B + 2 * r + 1] * f), pack_bf16(o[B + 2 * r + 4] * f, o[B + 2 * r + 5] * f),
                                pack_bf16(o[B + 2 * r + 8] * f, o[B + 2 * r + 9] * f), pack_bf16(o[B + 2 * r + 12] * f, o[B + 2 * r + 13] * f), pol);
#pragma unroll
                        for (int k = 0; k < 8; k++) {
                            float& v = o[B + 4 * (k >> 1) + 2 * r + (k & 1)];
                            v = (2 * B + k > lim + 8 * r) ? -1e30f : 0.f;
                            asm volatile("" : "+f"(v));
                        }
                    }
                });
                signal(bars, wg, (cb == 8 ? 0 : 4) + j, lane);
                PROF(11 + rd * 4);
                qstep(FalseT{}, 9);
                if (!role) { const Slot sl = c.next(); c.wait(sl); c.release(sl.bo); }
                kfirst = c.next();
                c.wait(kfirst);
                wgmma_wait<0>();
                BP(2, 34);
                c.release(pend);
                fence_regs(s);
                pack_tile(s, qf);
            }
            Slot vskip = c.cur;
            if (!role) vskip = c.next();
            PROF(8 + rd * 4);
            if (cb == 8) PROF(40 + 3 * j);
            fence_regs(qf); fence_regs(o);
            if (!role && rank) named_sync(bar_me, 256);
            BP(2, 36);
            auto first_qk = [&](auto half) {
                wgmma_fence();
#pragma unroll
                for (int k = 0; k < 8; k++) {
                    if (half.value) wgmma_rs_n64<1>(o, qf[4 * k], qf[4 * k + 1], qf[4 * k + 2], qf[4 * k + 3], kfirst.dl + lbo(16384) + k * 128, 1);
                    else wgmma_rs_n128<1>(o, qf[4 * k], qf[4 * k + 1], qf[4 * k + 2], qf[4 * k + 3], kfirst.dl + lbo(16384) + k * 128, 1);
                }
                wgmma_commit();
                named_arrive(bar_other, 256);
                if (!role) { c.wait(vskip); c.release(vskip.bo); }
                wgmma_wait<0>();
            };
            if (role == rank) first_qk(TrueT{});
            else first_qk(FalseT{});
            BP(2, 38);
            fence_regs(o);
            c.release(kfirst.bo);
            uint32_t ready = c.peek();
            float n0 = fmaxf(fmaxf(fmaxf(o[0], o[1]), fmaxf(o[4], o[5])), fmaxf(fmaxf(o[8], o[9]), fmaxf(o[12], o[13])));
            float n1 = fmaxf(fmaxf(fmaxf(o[2], o[3]), fmaxf(o[6], o[7])), fmaxf(fmaxf(o[10], o[11]), fmaxf(o[14], o[15])));
            n0 = __shfl_sync(0xffffffffu, n0, lane & 28); n1 = __shfl_sync(0xffffffffu, n1, lane & 28);
            n0 *= -SM_SCALE; n1 *= -SM_SCALE;
            l0 = 0.f; l1 = 0.f;
#pragma unroll
            for (int i = 0; i < 64; i++) s[i] = o[i];
            exp_part<0, 8>(s, n0, n1, l0, l1);
#pragma unroll
            for (int i = 0; i < 16; i++) pf[i] = pack_bf16(s[2 * i], s[2 * i + 1]);
            if (role != rank) {
                exp_part<8, 16>(s, n0, n1, l0, l1);
#pragma unroll
                for (int i = 16; i < 32; i++) pf[i] = pack_bf16(s[2 * i], s[2 * i + 1]);
            } else {
#pragma unroll
                for (int i = 16; i < 32; i++) pf[i] = 0u;
            }
            PROF(9 + rd * 4);
            if (cb == 8) PROF(41 + 3 * j);
#pragma unroll 1
            for (int it = 0; it < nrest; it++) {
                const Slot sk = c.next(), sv = c.next();
                LP(0);
                c.wait(sk, ready);
                fence_regs(o); fence_regs(pf);
                LP(1);
                named_sync(bar_me, 256);
                LP(2);
                if (it < 3) BP(2, 42 + 4 * it);
                if (it >= nrest - 2) BP(1, 62 + 4 * (it - nrest + 2));
                wgmma_fence();
                gemm_rs<true>(s, qf, sk.dl);
                wgmma_commit();
                c.wait(sv);
                wgmma_fence();
                gemm_pv(o, pf, sv.dl, it, it | (role ^ rank));
                wgmma_commit();
                named_arrive(bar_other, 256);
                LP(3);
                wgmma_wait<2>();
                LP(4);
                c.release(sk.bo);
                fence_regs(s);
                exp_part<0, SPLITJ>(s, n0, n1, l0, l1);
                sched_barrier(l0, l1, bars + MISC_OFF + 16);
                LP(5);
                wgmma_wait<0>();
                LP(6);
                c.release(sv.bo);
                ready = c.peek();
                fence_regs(o); fence_regs(pf);
                exp_part<SPLITJ, 16>(s, n0, n1, l0, l1);
                pack_tile(s, pf);
            }
            PROF(10 + rd * 4);
            if (cb == 8) PROF(42 + 3 * j);
            PROFG(183 + rd);
            const Slot sv = c.next();
            BP(1, 0);
            c.wait(sv, ready);
            const bool bad = __any_sync(0xffffffffu, !(l0 < 0x1p60f && l1 < 0x1p60f));
            if (__builtin_expect(bad || nrest == 0, 0)) {
#pragma unroll
                for (int i = 0; i < 64; i++) o[i] = 0.f;
                if (bad) {
                    attention_exact(o, qf, l0, l1, h, nrest + 1, lim, lane);
#pragma unroll
                    for (int i = 0; i < 32; i++) pf[i] = 0u;
                }
            }
            fence_regs(o); fence_regs(pf);
            if (!role) named_sync(bar_me, 256);
            BP(1, 2);
            wgmma_fence();
            gemm_rs<false>(o, pf, sv.dl);
            wgmma_commit();
            pend = sv.bo;
            ep_ptr = g_ctx + (size_t)(h * SEQ + 256 * p + 128 * rank + 64 * role + 16 * w + lr) * HD + 8 * q;
            ep_step = 8 * HD;
        }
        l0 += __shfl_xor_sync(0xffffffffu, l0, 1); l1 += __shfl_xor_sync(0xffffffffu, l1, 1);
        l0 += __shfl_xor_sync(0xffffffffu, l0, 2); l1 += __shfl_xor_sync(0xffffffffu, l1, 2);
        l0 = rcp(l0); l1 = rcp(l1);
        sched_barrier(l0, l1, bars + MISC_OFF + 16);
        wgmma_wait<0>();
        c.release(pend);
        fence_regs(o); fence_regs(pf);
#pragma unroll
        for (int i = 0; i < 32; i++) pf[i] = pack_bf16(o[2 * i] * ((i & 1) ? l1 : l0), o[2 * i + 1] * ((i & 1) ? l1 : l0));
    }
    PROFG(187);
    PROF(3);
    if (cb == 8) {
#pragma unroll
        for (int i = 0; i < 8; i++) stg128(ep_ptr + (i & 1) * 8 * HD + 32 * (i >> 1), pf[4 * (i & 6) + (i & 1)], pf[4 * (i & 6) + (i & 1) + 2], pf[4 * (i & 6) + (i & 1) + 4], pf[4 * (i & 6) + (i & 1) + 6]);
        signal(bars, wg, 8, lane);
        cluster_arrive();
        named_sync(1, 256);
        mod_ffn(P, smem, 2 * ca + rank, wg);
    } else
    {
        float a1[64], a2[96];
        uint32_t px = 0, py = 0;
        auto mma1 = [&](const Slot& x, int acc) {
#pragma unroll
            for (int k = 0; k < 4; k++) wgmma_ss_n128<0, 1>(a1, x.dl + wg * 512 + lbo(16) + k * 2, x.dl + 1024 + lbo(4096) + (k >> 1) * 512 + (k & 1) * 128, k ? 1 : acc);
        };
        auto mma2 = [&](const Slot& x, const Slot& y, int acc) {
#pragma unroll
            for (int k = 0; k < 4; k++) wgmma_ss_n192<0, 1>(a2, x.dl + wg * 512 + lbo(16) + k * 2, y.dl + lbo(4096) + (k >> 1) * 768 + (k & 1) * 128, k ? 1 : acc);
        };
#pragma unroll 1
        for (int t = 0, more = 1; more; t++) {
            const Slot sx = c.next(), sy = c.next();
            OP(2 * t);
            c.wait(sx);
            OP(2 * t + 1);
            wgmma_fence();
            mma1(sx, t);
            wgmma_commit();
            wgmma_wait<1>();
            asm volatile("ld.shared.u32 %0, [%1];" : "=r"(more) : "r"(bars + CTL_OFF + sx.bo) : "memory");
            if (t > 0) { c.release(px); c.release(py); }
            px = sx.bo; py = sy.bo;
            c.wait(sy);
            wgmma_fence();
            mma2(sx, sy, t);
            wgmma_commit();
            more = !__any_sync(0xffffffffu, more);
            if (t == 0) {
#pragma unroll
                for (int i = 0; i < 4; i++) stg128(ep_ptr + 32 * i, pf[8 * i], pf[8 * i + 2], pf[8 * i + 4], pf[8 * i + 6]);
            }
            if (t == 1) {
#pragma unroll
                for (int i = 0; i < 4; i++) stg128(ep_ptr + 8 * HD + 32 * i, pf[8 * i + 1], pf[8 * i + 3], pf[8 * i + 5], pf[8 * i + 7]);
                signal(bars, wg, 4 + n_items(ca, cb), lane);
            }
        }
        OP(60);
        const Slot x0 = c.next(), x1 = c.next(), x2 = c.next(), y0 = c.next(), y1 = c.next(), y2 = c.next(), fr = c.next();

        const int cw = __reduce_or_sync(0xffffffffu, wg * 4 + w);
        const int orow = unperm_row(256 * out_p(ca, cb) + 128 * rank + 16 * cw), ocol = 320 * (ca >> 2);
        const uint32_t sa = ((lane & 7) + (lane & 8)) * 128, sx = (lane >> 4) ^ (lane & 7);
        auto send = [&](auto chv, uint32_t box) {
            constexpr int ch = chv.value;
#pragma unroll
            for (int i = 0; i < 4; i++) {
                uint32_t r[4];
#pragma unroll
                for (int e = 0; e < 4; e++) {
                    const int k = 32 * ch + 8 * i + 2 * e;
                    r[e] = (ch < 2) ? pack_bf16(a1[k & 63], a1[(k & 63) + 1]) : pack_bf16(a2[ch < 2 ? 0 : k - 64], a2[ch < 2 ? 1 : k - 63]);
                }
                asm volatile("stmatrix.sync.aligned.m8n8.x4.shared.b16 [%0], {%1, %2, %3, %4};"
                             ::"r"(box + sa + ((sx ^ (2 * i)) << 4)), "r"(r[0]), "r"(r[1]), "r"(r[2]), "r"(r[3]) : "memory");
            }
            asm volatile("fence.proxy.async.shared::cta;" ::: "memory");
            __syncwarp();
            asm volatile(ELECT "cp.reduce.async.bulk.tensor.2d.global.shared::cta.add.bulk_group [%0, {%2, %3}], [%1];\n}\n"
                         ::"l"(&P.outm), "r"(box), "r"(ocol + 64 * ch), "r"(orow) : "memory");
        };
        auto addr = [&](const Slot& t) { return smem + t.bo * (SLOT / 8); };
        const bool follow = wg ^ ((n_items(ca, cb) - 1) & 1);
        c.wait(x0);
        c.wait(x1);
        c.wait(x2);
        if (follow) {
            wgmma_wait<0>();
            c.release(px); c.release(py);
            named_sync(2 + wg, 256);
        }
        wgmma_fence();
        mma1(x0, 1);
        wgmma_commit();
        wgmma_wait<1>();
        if (!follow) { c.release(px); c.release(py); }
        wgmma_fence();
        mma1(x1, 1);
        mma1(x2, 1);
        wgmma_commit();
        named_arrive(3 - wg, 256);
        mbar_wait(bars + BAR_DEP, 0);
        mbar_wait(bars + BAR_EMPTY + fr.bo, fr.par ^ 1);
        c.wait(y0);
        c.wait(y1);
        wgmma_wait<0>();
        fence_regs(a1);
        OP(61);
        send(IntT<0>{}, addr(fr) + cw * 4096);
        send(IntT<1>{}, addr(fr) + cw * 4096 + 2048);
        named_sync(2 + wg, 256);
        wgmma_fence();
        mma2(x0, y0, 1);
        mma2(x1, y1, 1);
        wgmma_commit();
        OP(62);
        c.wait(y2);
        wgmma_fence();
        mma2(x2, y2, 1);
        wgmma_commit();
        if (!follow) named_arrive(3 - wg, 256);
        wgmma_wait<0>();
        fence_regs(a2);
        PROFG(188);
        PROF(4);
        send(IntT<2>{}, addr(x0) + cw * 2048);
        send(IntT<3>{}, addr(x1) + cw * 2048);
        send(IntT<4>{}, addr(x2) + cw * 2048);
        PROF(5);
        asm volatile("cp.async.bulk.commit_group;\ncp.async.bulk.wait_group.read 0;" ::: "memory");
    }
    PROF(6);
}

__device__ __forceinline__ void mod_ffn(const Params& P, uint32_t smem, int mc  , int wg) {
    const int tid = threadIdx.x - 128, lane = tid & 31, cw = tid >> 5, q = lane & 3, lr = lane >> 2;
    const uint32_t xs = smem + 6 * SLOT, hs = xs + 10240 + wg * 1024, wmax = xs + 12288, sidx = wmax + 64, rbar = xs + 13312 + wg * 32;
    const uint32_t ring = smem + wg * 3 * SLOT;
    const int f0 = mc + 4 * wg, nunit = ((34 - f0) >> 3) * 8;
    const bool lead = __reduce_or_sync(0xffffffffu, cw & 3) == 0;
    auto lds = [](uint32_t a) { uint32_t v; asm volatile("ld.shared.u32 %0, [%1];" : "=r"(v) : "r"(a) : "memory"); return v; };
    auto sts = [](uint32_t a, uint32_t v) { asm volatile("st.shared.u32 [%0], %1;" ::"r"(a), "r"(v) : "memory"); };
    auto issue = [&](int u, int st) {
        if (lead && u < nunit) {
            const int fc = (f0 + (u & ~7)) * 64, k = u & 7;
            const uint32_t dst = ring + st * SLOT, bar = rbar + st * 8;
            w_expect_tx(bar, k == 7 ? 16384 : SLOT);
            if (k < 5) {
                w_tma_load_stream(dst, &P.wg, fc, k * 128, bar);
                w_tma_load_stream(dst + 16384, &P.wu, fc, k * 128, bar);
            } else {
#pragma unroll 1
                for (int b = 0; b < (k == 7 ? 2 : 4); b++) w_tma_load_stream(dst + b * 8192, &P.wd, (4 * (k - 5) + b) * 64, fc, bar);
            }
        }
    };
    if ((tid & 127) == 0) {
        mbar_init(rbar, 1); mbar_init(rbar + 8, 1); mbar_init(rbar + 16, 1);
        asm volatile("fence.mbarrier_init.release.cluster;" ::: "memory");
    }
    mbar_wait(smem + NSLOT * SLOT + BAR_DEP, 0);
    asm volatile("fence.proxy.async.shared::cta;" ::: "memory");
    named_sync(1, 256);
    PROF(1);
#pragma unroll 1
    for (int u = 0; u < 3; u++) issue(u, u);
    uint32_t key[8];
#pragma unroll
    for (int i = 0; i < 8; i++) {
        const int t = tid + 256 * i;
        uint32_t b = __float_as_uint(__ldcg(g_r + t) + 0.f) >> 16;
        b = (b & 0x8000u) ? (~b & 0xffffu) : (b | 0x8000u);
        key[i] = (b << 16) | (uint32_t)(0xffff - t);
    }
#pragma unroll 1
    for (int rnd = 0; rnd < 8; rnd++) {
        uint32_t mx = key[0];
#pragma unroll
        for (int i = 1; i < 8; i++) mx = max(mx, key[i]);
        sts(wmax + ((rnd & 1) * 8 + cw) * 4, __reduce_max_sync(0xffffffffu, mx));
        named_sync(1, 256);
        mx = __reduce_max_sync(0xffffffffu, lds(wmax + ((rnd & 1) * 8 + (lane & 7)) * 4));
#pragma unroll
        for (int i = 0; i < 8; i++) if (key[i] == mx) key[i] = 0;
        if (cw == rnd) sts(sidx + rnd * 4, 0xffff - (mx & 0xffffu));
    }
    __syncwarp();
    {
        const int t = lds(sidx + cw * 4);
        const uint4* src = reinterpret_cast<const uint4*>(g_xn + perm_row(t) * DM);
#pragma unroll
        for (int i = 0; i < 3; i++) {
            const int ch = lane + 32 * i;
            if (ch < 80) {
                const uint4 v = __ldcg(src + ch);
                asm volatile("st.shared.v4.b32 [%0], {%1, %2, %3, %4};" ::"r"(xs + (ch >> 3) * 1024 + cw * 128 + ((ch ^ cw) & 7) * 16), "r"(v.x), "r"(v.y), "r"(v.z), "r"(v.w) : "memory");
            }
        }
        asm volatile("fence.proxy.async.shared::cta;" ::: "memory");
    }
    named_sync(1, 256);
    PROF(3);
    float y[10][4];
#pragma unroll
    for (int i = 0; i < 10; i++) { y[i][0] = 0.f; y[i][1] = 0.f; y[i][2] = 0.f; y[i][3] = 0.f; }
    int st = 0, ph = 0, u = 0;
    auto begin = [&]() { mbar_wait(rbar + st * 8, ph); wgmma_fence(); return (((ring + st * SLOT) & 0x3FFFF) >> 4) + lbo(16); };
    auto end = [&]() {
        wgmma_commit();
        wgmma_wait<0>();
        named_sync(4 + wg, 128);
        issue(u + 3, st);
        u++;
        ph ^= st == 2;
        st = (st == 2) ? 0 : st + 1;
    };
    const uint32_t dx = ((xs & 0x3FFFF) >> 4) + lbo(16), dh = ((hs & 0x3FFFF) >> 4) + lbo(16);
#pragma unroll 1
    while (u < nunit) {
        float g[4], v[4];
#pragma unroll 1
        for (int kc = 0; kc < 5; kc++) {
            const uint32_t da = begin();
#pragma unroll
            for (int k = 0; k < 8; k++) {
                const uint32_t db = dx + (2 * kc + (k >> 2)) * 64 + (k & 3) * 2;
                wgmma_ss_n8<1, 0>(g, da + k * 128, db, k ? 1 : kc);
                wgmma_ss_n8<1, 0>(v, da + 1024 + k * 128, db, k ? 1 : kc);
            }
            end();
        }
        fence_regs(g); fence_regs(v);
#pragma unroll
        for (int e = 0; e < 4; e++) {
            const float gp = round_bf16(g[e]);
            const float hv = round_bf16(__fdividef(gp, 1.0f + __expf(fminf(-gp, 80.f)))) * round_bf16(v[e]);
            const int tok = 2 * q + (e & 1), ch = 2 * (cw & 3) + (e >> 1);
            asm volatile("st.shared.u16 [%0], %1;" ::"r"(hs + tok * 128 + ((ch ^ tok) * 16) + lr * 2), "h"((unsigned short)pack_bf16(hv, 0.f)) : "memory");
        }
        asm volatile("fence.proxy.async.shared::cta;" ::: "memory");
        named_sync(4 + wg, 128);
#pragma unroll
        for (int k3 = 0; k3 < 3; k3++) {
            const uint32_t da = begin();
#pragma unroll
            for (int b = 0; b < (k3 == 2 ? 2 : 4); b++)
#pragma unroll
                for (int k = 0; k < 4; k++) wgmma_ss_n8<1, 0>(y[4 * k3 + b], da + b * 512 + k * 128, dh + k * 2, 1);
            end();
        }
    }
    PROF(5);
#pragma unroll
    for (int i = 0; i < 10; i++) {
        fence_regs(y[i]);
#pragma unroll
        for (int e = 0; e < 4; e++) g_ypart[((mc * 2 + wg) * 8 + 2 * q + (e & 1)) * DM + 64 * i + 16 * (cw & 3) + lr + 8 * (e >> 1)] = y[i][e];
    }
    named_sync(1, 256);
    if (tid == 0) {
        flag_add(F_MODP);
        flag_wait<100>(F_MODP, 4u * (lds(smem + NSLOT * SLOT + MISC_OFF) + 1));
    }
    named_sync(1, 256);
    PROF(6);
    {
        const int c = 2 * mc + wg, t = lds(sidx + c * 4);
        const float rs = round_bf16(__fdividef(1.0f, 1.0f + __expf(fminf(-__ldcg(g_r + t), 80.f))));
#pragma unroll
        for (int i = 0; i < 3; i++) {
            const int c2 = (tid & 127) + 128 * i;
            if (c2 < DM / 2) {
                float y0 = 0.f, y1 = 0.f;
#pragma unroll
                for (int k = 0; k < 8; k++) {
                    const float2 v = __ldcg(reinterpret_cast<const float2*>(g_ypart + (k * 8 + c) * DM) + c2);
                    y0 += v.x; y1 += v.y;
                }
                asm volatile("red.relaxed.gpu.global.add.noftz.bf16x2 [%0], %1;" ::"l"(P.out + t * DM + 2 * c2), "r"(pack_bf16(round_bf16(y0) * rs, round_bf16(y1) * rs)) : "memory");
            }
        }
    }
    PROF(7);
}

__global__ void __cluster_dims__(2, 1, 1) __launch_bounds__(384, 1) fused_kernel(const __grid_constant__ Params P) {
    extern __shared__ __align__(1024) uint8_t smem_raw[];
    const uint32_t smem = (smem_u32(smem_raw) + 1023u) & ~1023u;
    const uint32_t bars = smem + NSLOT * SLOT;
    const int wgi = __reduce_or_sync(0xffffffffu, threadIdx.x >> 7);
    const int cl = blockIdx.x >> 1, rank = blockIdx.x & 1, ca = cl & 7, cb = cl >> 3;
    PROFG(30);
    PROF(0);
    if (threadIdx.x == 64) {
        const uint32_t fa = bars + BAR_FULL + slot_a(0) * 8, fw = bars + BAR_FULL + slot_w(0) * 8;
        mbar_init(fa, 1); mbar_init(fw, 1);
        asm volatile("fence.mbarrier_init.release.cluster;" ::: "memory");
        if (cb < 8) {
            mbar_expect_tx(fa, SLOT);
            mbar_expect_tx(fw, SLOT);
            tma_load(smem + slot_a(0) * SLOT, &P.ckv, 0, (2 * ca + rank) * 128, fa);
            tma_load(smem + slot_w(0) * SLOT, &P.wuk, (cb + 8 * kv_round(0)) * 128, 0, fw);
            tma_load(smem + slot_w(0) * SLOT + 16384, &P.wuk, (cb + 8 * kv_round(0)) * 128 + 64, 0, fw);
            tma_load(smem + slot_a(0) * SLOT + 16384, &P.ckv, 64, (2 * ca + rank) * 128, fa);
        }
    } else if (threadIdx.x == 0) {
#pragma unroll
        for (int i = 0; i < NSLOT; i++) {
            if (i != slot_a(0) && i != slot_w(0)) mbar_init(bars + BAR_FULL + i * 8, 1);
            mbar_init(bars + BAR_EMPTY + i * 8, 16);
        }
        if (cb < 8) {
            mbar_arrive(bars + BAR_FULL + 16);
            asm volatile("mbarrier.arrive.shared::cta.b64 _, [%0], 16;" ::"r"(bars + BAR_EMPTY + 16) : "memory");
        }
        asm volatile("fence.mbarrier_init.release.cluster;" ::: "memory");
        PROF(24);
    } else if (threadIdx.x == 32) {
#pragma unroll
        for (int i = 0; i < 18; i++) mbar_init(bars + BAR_SIG + i * 8, 4);
#pragma unroll
        for (int i = 0; i < 18; i++) mbar_init(bars + BAR_DEP + i * 8, 1);
        asm volatile("fence.mbarrier_init.release.cluster;" ::: "memory");
    }
    __syncthreads();
    PROF(29);
    cluster_arrive();
    if (wgi > 0) {
        asm volatile("setmaxnreg.inc.sync.aligned.u32 232;");
        consumer(P, smem, bars, ca, cb, rank, wgi - 1);
        PROFG(31);
        PROFDUMP();
    } else {
        asm volatile("setmaxnreg.dec.sync.aligned.u32 40;");
        const int w = __reduce_or_sync(0xffffffffu, threadIdx.x >> 5), lane = threadIdx.x & 31;
        if (threadIdx.x == 32) {
            prefetch_map(&P.wuv); prefetch_map(&P.xn); prefetch_map(&P.wq); prefetch_map(&P.kv); prefetch_map(&P.ctx); prefetch_map(&P.wo); prefetch_map(&P.outm);
        }
        __syncwarp();
        cluster_wait();
        PROF(27);
        {
            if (w == 0) {
                producer(P, smem, bars, ca, cb, rank);
            } else if (w < 3 && lane == 0) {
                const int wg = w - 1;
#pragma unroll 1
                for (int i = (cb == 8); i < (cb == 8 ? 9 : 5 + n_items(ca, cb)); i++) {
                    const int nb = wg + (LNOFF + 7 - 4) / 8;
                    const int e = (cb == 8) ? i : (i < nb) ? i + 1 : (i == nb) ? 0 : i;
                    mbar_wait_sleep(bars + BAR_SIG + (wg * 9 + e) * 8, 0);
                    int f;
                    if (cb == 8) f = F_CTX + (2 + ca) * 16 + rank;
                    else if (e == 0) {
                        f = F_LN;
                        if ((ca & 3) == 0 && rank == 0 && wg == 0) g_flags[(F_POOL + out_p(ca, cb) * 2 + (ca >> 2)) * 8] = 8;
                    }
                    else if (e < 5) f = F_KV + cb + 8 * kv_round(e - 1);
                    else { const int rd = item_rd(ca, cb, e - 5); f = F_CTX + rd * 16 + item_p(ca, rd) * 2 + rank; }
                    flag_add(f);
                }
            } else if (lane == 0) {
                const uint32_t epoch = read_epoch();
                asm volatile("st.shared.u32 [%0], %1;" ::"r"(bars + MISC_OFF), "r"(epoch) : "memory");
#pragma unroll 1
                for (int i = 0; i < 9; i++) {
                    const int e = (cb == 8 && i < 2) ? 1 - i : i;
                    int f;
                    uint32_t n;
                    if (e == 0) { f = F_LN; n = 256; }
                    else if (cb == 8) { f = F_KV + item_h(cb, 2 + ca, e - 1); n = 32; }
                    else if (e < 5) { f = F_KV + cb + 8 * (e - 1); n = 32; }
                    else { f = F_CTX + (e - 5) * 16 + out_p(ca, cb) * 2 + rank; n = 16; }
                    flag_wait<200>(f, n * (epoch + 1));
                    fence_proxy_async();
                    mbar_arrive(bars + BAR_DEP + e * 8);
                }
            }
        }
        if (cb == 8) { __syncwarp(); cluster_arrive(); cluster_wait(); }
        PROFG(31);
        PROFDUMP();
    }
}

typedef CUresult (*EncodeFn)(CUtensorMap*, CUtensorMapDataType, cuuint32_t, void*, const cuuint64_t*, const cuuint64_t*, const cuuint32_t*,
                             const cuuint32_t*, CUtensorMapInterleave, CUtensorMapSwizzle, CUtensorMapL2promotion, CUtensorMapFloatOOBfill);

void make_map(EncodeFn fn, CUtensorMap* m, const void* ptr, uint64_t rows, uint64_t cols, uint32_t box_rows) {
    cuuint64_t dims[2] = {cols, rows};
    cuuint64_t strides[1] = {cols * 2};
    cuuint32_t box[2] = {64, box_rows};
    cuuint32_t es[2] = {1, 1};
    fn(m, CU_TENSOR_MAP_DATA_TYPE_BFLOAT16, 2, const_cast<void*>(ptr), dims, strides, box, es, CU_TENSOR_MAP_INTERLEAVE_NONE,
       CU_TENSOR_MAP_SWIZZLE_128B, CU_TENSOR_MAP_L2_PROMOTION_L2_128B, CU_TENSOR_MAP_FLOAT_OOB_FILL_NONE);
}

}

extern "C" void kernel_launch(void* const* d_in, const int* in_sizes, int n_in, void* d_out, int out_size) {
    (void)in_sizes; (void)n_in; (void)out_size;
    void* fnp = nullptr;
    cudaDriverEntryPointQueryResult qr;
    cudaGetDriverEntryPoint("cuTensorMapEncodeTiled", &fnp, cudaEnableDefault, &qr);
    EncodeFn fn = (EncodeFn)fnp;
    void *xn, *kv, *ctx;
    cudaGetSymbolAddress(&xn, g_xn);
    cudaGetSymbolAddress(&kv, g_kv);
    cudaGetSymbolAddress(&ctx, g_ctx);
    Params P;
    make_map(fn, &P.ckv, d_in[1], SEQ, DC, 128);
    make_map(fn, &P.wq, d_in[2], DM, NH * HD, 64);
    make_map(fn, &P.wuk, d_in[3], DC, NH * HD, 128);
    make_map(fn, &P.wuv, d_in[4], DC, NH * HD, 128);
    make_map(fn, &P.wo, d_in[5], NH * HD, DM, 32);
    make_map(fn, &P.xn, xn, SEQ, DM, 128);
    make_map(fn, &P.kv, kv, NH * 16 * 2 * 128, 128, 128);
    make_map(fn, &P.ctx, ctx, NH * SEQ, HD, 128);
    P.x = (const __nv_bfloat16*)d_in[0];
    P.wr = (const __nv_bfloat16*)d_in[7];
    make_map(fn, &P.wg, d_in[8], DM, FF, 128);
    make_map(fn, &P.wu, d_in[9], DM, FF, 128);
    make_map(fn, &P.wd, d_in[10], FF, DM, 64);
    make_map(fn, &P.outm, d_out, SEQ, DM, 16);
    P.out = (__nv_bfloat16*)d_out;
    cudaFuncSetAttribute(fused_kernel, cudaFuncAttributeMaxDynamicSharedMemorySize, SMEM_BYTES);
    fused_kernel<<<NCTA, 384, SMEM_BYTES>>>(P);
}
```

```cpp
#include <cuda_runtime.h>
#include <cuda_bf16.h>
#include <cuda.h>
#include <stdint.h>

namespace {

constexpr int SEQ = 2048, DM = 640, DC = 512, NH = 32, HD = 128, FF = 1728;
constexpr int NSLOT = 7, SLOT = 32768;
constexpr int NCTA = 132;
constexpr int KVSPLIT = 1;
constexpr int LNOFF = 4, LNLEAD = 2;
constexpr int SPLITJ = 8;
constexpr uint32_t DESC_HI = (1024u >> 4) | (1u << 30);
constexpr int SMEM_BYTES = NSLOT * SLOT + 3072;

constexpr int BAR_FULL = 0, BAR_EMPTY = 64, BAR_SIG = 128  , BAR_DEP = 320  , BAR_MAIL = 400  ;
constexpr int MISC_OFF = 512  , MAIL_OFF = 544  , CTL_OFF = 576  ;

constexpr int F_EPOCH = 0, F_LN = 1, F_MODP = 3, F_KV = 4  , F_CTX = 36  , F_POOL = 100  , F_NUM = 116;

__device__ __align__(1024) __nv_bfloat16 g_xn[SEQ * DM];
__device__ __align__(1024) __nv_bfloat16 g_kv[NH * 16 * 2 * 128 * 128];
__device__ __align__(1024) __nv_bfloat16 g_ctx[NH * SEQ * HD];
__device__ __align__(16) float g_r[SEQ];
__device__ __align__(16) float g_ypart[8 * 8 * DM];
__device__ uint32_t g_flags[F_NUM * 8];

struct TrueT { static constexpr bool value = true; };
struct FalseT { static constexpr bool value = false; };

struct Params {
    CUtensorMap ckv, wuk, wuv, xn, wq, kv, ctx, wo, wg, wu, wd, outm;
    const __nv_bfloat16 *x, *wr;
    __nv_bfloat16* out;
};

__device__ __forceinline__ uint32_t smem_u32(const void* p) { return (uint32_t)__cvta_generic_to_shared(p); }
__device__ __forceinline__ void mbar_init(uint32_t bar, uint32_t cnt) {
    asm volatile("mbarrier.init.shared::cta.b64 [%0], %1;" ::"r"(bar), "r"(cnt) : "memory");
}
__device__ __forceinline__ void mbar_expect_tx(uint32_t bar, uint32_t bytes) {
    asm volatile("mbarrier.arrive.expect_tx.shared::cta.b64 _, [%0], %1;" ::"r"(bar), "r"(bytes) : "memory");
}
__device__ __forceinline__ void mbar_arrive(uint32_t bar) {
    asm volatile("mbarrier.arrive.shared::cta.b64 _, [%0];" ::"r"(bar) : "memory");
}
__device__ __forceinline__ uint32_t mapa(uint32_t addr, uint32_t cta) {
    uint32_t r;
    asm("mapa.shared::cluster.u32 %0, %1, %2;" : "=r"(r) : "r"(addr), "r"(cta));
    return r;
}
__device__ __forceinline__ void mbar_wait(uint32_t bar, uint32_t parity) {
    asm volatile(
        "{\n.reg .pred p;\n.reg .b32 c;\n"
        "mov.b32 c, 0;\n"
        "WLOOP:\n"
        "mbarrier.try_wait.parity.shared::cta.b64 p, [%0], %1;\n"
        "@p bra.uni WDONE;\n"
        "add.u32 c, c, 1;\n"
        "setp.lt.u32 p, c, 0x400000;\n"
        "@p bra.uni WLOOP;\n"
        "trap;\n"
        "WDONE:\n}\n" ::"r"(bar), "r"(parity) : "memory");
}
__device__ __forceinline__ uint32_t mbar_peek(uint32_t bar, uint32_t parity) {
    uint32_t ok;
    asm volatile("{\n.reg .pred p;\nmbarrier.test_wait.parity.shared::cta.b64 p, [%1], %2;\nselp.b32 %0, 1, 0, p;\n}\n" : "=r"(ok) : "r"(bar), "r"(parity) : "memory");
    return ok;
}
__device__ __forceinline__ void mbar_wait_unless(uint32_t ok, uint32_t bar, uint32_t parity) {
    asm volatile(
        "{\n.reg .pred p;\n.reg .b32 c;\n"
        "setp.ne.b32 p, %2, 0;\n"
        "@p bra.uni WDONE;\n"
        "mov.b32 c, 0;\n"
        "WLOOP:\n"
        "mbarrier.try_wait.parity.shared::cta.b64 p, [%0], %1;\n"
        "@p bra.uni WDONE;\n"
        "add.u32 c, c, 1;\n"
        "setp.lt.u32 p, c, 0x400000;\n"
        "@p bra.uni WLOOP;\n"
        "trap;\n"
        "WDONE:\n}\n" ::"r"(bar), "r"(parity), "r"(ok) : "memory");
}
__device__ __forceinline__ void mbar_wait_sleep(uint32_t bar, uint32_t parity) {
    asm volatile(
        "{\n.reg .pred p;\n.reg .b32 c;\n"
        "mov.b32 c, 0;\n"
        "WLOOP:\n"
        "mbarrier.try_wait.parity.shared::cta.b64 p, [%0], %1, 20000;\n"
        "@p bra.uni WDONE;\n"
        "add.u32 c, c, 1;\n"
        "setp.lt.u32 p, c, 0x40000;\n"
        "@p bra.uni WLOOP;\n"
        "trap;\n"
        "WDONE:\n}\n" ::"r"(bar), "r"(parity) : "memory");
}
__device__ __forceinline__ void tma_load(uint32_t dst, const CUtensorMap* m, int c0, int c1, uint32_t bar) {
    asm volatile("cp.async.bulk.tensor.2d.shared::cluster.global.mbarrier::complete_tx::bytes [%0], [%1, {%3, %4}], [%2];"
                 ::"r"(dst), "l"(m), "r"(bar), "r"(c0), "r"(c1) : "memory");
}
#define ELECT "{\n.reg .pred e;\nelect.sync _|e, 0xffffffff;\n@e "
__device__ __forceinline__ void w_expect_tx(uint32_t bar, uint32_t bytes) {
    asm volatile(ELECT "mbarrier.arrive.expect_tx.shared::cta.b64 _, [%0], %1;\n}\n" ::"r"(bar), "r"(bytes) : "memory");
}
__device__ __forceinline__ void w_tma_load(uint32_t dst, const CUtensorMap* m, int c0, int c1, uint32_t bar) {
    asm volatile(ELECT "cp.async.bulk.tensor.2d.shared::cluster.global.mbarrier::complete_tx::bytes [%0], [%1, {%3, %4}], [%2];\n}\n"
                 ::"r"(dst), "l"(m), "r"(bar), "r"(c0), "r"(c1) : "memory");
}
__device__ __forceinline__ void w_tma_load_mc(uint32_t dst, const CUtensorMap* m, int c0, int c1, uint32_t bar) {
    asm volatile(ELECT "cp.async.bulk.tensor.2d.shared::cluster.global.mbarrier::complete_tx::bytes.multicast::cluster [%0], [%1, {%3, %4}], [%2], %5;\n}\n"
                 ::"r"(dst), "l"(m), "r"(bar), "r"(c0), "r"(c1), "h"((uint16_t)3) : "memory");
}
__device__ __forceinline__ void w_tma_prefetch(const CUtensorMap* m, int c0, int c1) {
    asm volatile(ELECT "cp.async.bulk.prefetch.tensor.2d.L2.global [%0, {%1, %2}];\n}\n" ::"l"(m), "r"(c0), "r"(c1) : "memory");
}
__device__ __forceinline__ uint64_t policy_evict_first() {
    uint64_t p;
    asm("createpolicy.fractional.L2::evict_first.b64 %0, 1.0;" : "=l"(p));
    return p;
}
__device__ __forceinline__ void w_tma_load_mc_last(uint32_t dst, const CUtensorMap* m, int c0, int c1, uint32_t bar) {
    asm volatile(ELECT "cp.async.bulk.tensor.2d.shared::cluster.global.mbarrier::complete_tx::bytes.multicast::cluster.L2::cache_hint [%0], [%1, {%3, %4}], [%2], %5, %6;\n}\n"
                 ::"r"(dst), "l"(m), "r"(bar), "r"(c0), "r"(c1), "h"((uint16_t)3), "l"(policy_evict_first()) : "memory");
}
__device__ __forceinline__ void w_tma_load_stream(uint32_t dst, const CUtensorMap* m, int c0, int c1, uint32_t bar) {
    asm volatile(ELECT "cp.async.bulk.tensor.2d.shared::cluster.global.mbarrier::complete_tx::bytes.L2::cache_hint [%0], [%1, {%3, %4}], [%2], %5;\n}\n"
                 ::"r"(dst), "l"(m), "r"(bar), "r"(c0), "r"(c1), "l"(policy_evict_first()) : "memory");
}
__device__ __forceinline__ uint4 ldg_stream(const void* p) {
    uint4 v;
    asm volatile("ld.global.nc.L2::cache_hint.v4.b32 {%0, %1, %2, %3}, [%4], %5;" : "=r"(v.x), "=r"(v.y), "=r"(v.z), "=r"(v.w) : "l"(p), "l"(policy_evict_first()));
    return v;
}
__device__ __forceinline__ void prefetch_map(const CUtensorMap* m) {
    asm volatile("prefetch.tensormap [%0];" ::"l"(m) : "memory");
}
__device__ __forceinline__ void cluster_arrive() { asm volatile("barrier.cluster.arrive.relaxed.aligned;" ::: "memory"); }
__device__ __forceinline__ void cluster_wait() { asm volatile("barrier.cluster.wait.aligned;" ::: "memory"); }
__device__ __forceinline__ void named_sync(int id, int n) { asm volatile("bar.sync %0, %1;" ::"r"(id), "r"(n) : "memory"); }
__device__ __forceinline__ void named_arrive(int id, int n) { asm volatile("bar.arrive %0, %1;" ::"r"(id), "r"(n) : "memory"); }

__device__ __forceinline__ void flag_add(int f) {
    asm volatile("fence.acq_rel.gpu;\nred.relaxed.gpu.global.add.u32 [%0], 1;" ::"l"(g_flags + f * 8) : "memory");
}
template <int SLEEP>
__device__ __forceinline__ void flag_wait(int f, uint32_t target) {
    asm volatile(
        "{\n.reg .pred p;\n.reg .b32 c, v;\n"
        "mov.b32 c, 0;\n"
        "FLOOP:\n"
        "ld.acquire.gpu.global.u32 v, [%0];\n"
        "sub.u32 v, v, %1;\n"
        "setp.ge.s32 p, v, 0;\n"
        "@p bra FDONE;\n"
        "nanosleep.u32 %2;\n"
        "add.u32 c, c, 1;\n"
        "setp.lt.u32 p, c, 0x400000;\n"
        "@p bra FLOOP;\n"
        "trap;\n"
        "FDONE:\n}\n" ::"l"(g_flags + f * 8), "r"(target), "n"(SLEEP) : "memory");
}
__device__ __forceinline__ uint32_t read_epoch() { return atomicAdd(g_flags + F_EPOCH * 8, 1u) / NCTA; }
__device__ __forceinline__ void fence_proxy_async() { asm volatile("fence.proxy.async.global;" ::: "memory"); }

__device__ __forceinline__ void wgmma_fence() { asm volatile("wgmma.fence.sync.aligned;" ::: "memory"); }
__device__ __forceinline__ void wgmma_commit() { asm volatile("wgmma.commit_group.sync.aligned;" ::: "memory"); }
template <int N>
__device__ __forceinline__ void wgmma_wait() { asm volatile("wgmma.wait_group.sync.aligned %0;" ::"n"(N) : "memory"); }
template <int N>
__device__ __forceinline__ void fence_regs(float (&d)[N]) {
#pragma unroll
    for (int i = 0; i < N; i++) asm volatile("" : "+f"(d[i])::"memory");
}
template <int N>
__device__ __forceinline__ void fence_regs(uint32_t (&d)[N]) {
#pragma unroll
    for (int i = 0; i < N; i++) asm volatile("" : "+r"(d[i])::"memory");
}

template <int TA, int TB>
__device__ __forceinline__ void wgmma_ss_n128(float (&d)[64], uint32_t alo, uint32_t blo, int scale_d) {
    asm volatile("{\n.reg .pred p;\n.reg .b64 da, db;\nsetp.ne.b32 p, %66, 0;\n"
        "mov.b64 da, {%64, %69};\nmov.b64 db, {%65, %69};\n"
        "wgmma.mma_async.sync.aligned.m64n128k16.f32.bf16.bf16 "
        "{%0, %1, %2, %3, %4, %5, %6, %7, %8, %9, %10, %11, %12, %13, %14, %15, %16, %17, %18, %19, %20, %21, %22, %23, %24, %25, %26, %27, %28, %29, %30, %31, %32, %33, %34, %35, %36, %37, %38, %39, %40, %41, %42, %43, %44, %45, %46, %47, %48, %49, %50, %51, %52, %53, %54, %55, %56, %57, %58, %59, %60, %61, %62, %63}, da, db, p, 1, 1, %67, %68;\n}\n"
        :
          "+f"(d[0]), "+f"(d[1]), "+f"(d[2]), "+f"(d[3]), "+f"(d[4]), "+f"(d[5]), "+f"(d[6]), "+f"(d[7]),
          "+f"(d[8]), "+f"(d[9]), "+f"(d[10]), "+f"(d[11]), "+f"(d[12]), "+f"(d[13]), "+f"(d[14]), "+f"(d[15]),
          "+f"(d[16]), "+f"(d[17]), "+f"(d[18]), "+f"(d[19]), "+f"(d[20]), "+f"(d[21]), "+f"(d[22]), "+f"(d[23]),
          "+f"(d[24]), "+f"(d[25]), "+f"(d[26]), "+f"(d[27]), "+f"(d[28]), "+f"(d[29]), "+f"(d[30]), "+f"(d[31]),
          "+f"(d[32]), "+f"(d[33]), "+f"(d[34]), "+f"(d[35]), "+f"(d[36]), "+f"(d[37]), "+f"(d[38]), "+f"(d[39]),
          "+f"(d[40]), "+f"(d[41]), "+f"(d[42]), "+f"(d[43]), "+f"(d[44]), "+f"(d[45]), "+f"(d[46]), "+f"(d[47]),
          "+f"(d[48]), "+f"(d[49]), "+f"(d[50]), "+f"(d[51]), "+f"(d[52]), "+f"(d[53]), "+f"(d[54]), "+f"(d[55]),
          "+f"(d[56]), "+f"(d[57]), "+f"(d[58]), "+f"(d[59]), "+f"(d[60]), "+f"(d[61]), "+f"(d[62]), "+f"(d[63])
        : "r"(alo), "r"(blo), "r"(scale_d), "n"(TA), "n"(TB), "r"(DESC_HI));
}
template <int TA, int TB>
__device__ __forceinline__ void wgmma_ss_n192(float (&d)[96], uint32_t alo, uint32_t blo, int scale_d) {
    asm volatile("{\n.reg .pred p;\n.reg .b64 da, db;\nsetp.ne.b32 p, %98, 0;\n"
        "mov.b64 da, {%96, %101};\nmov.b64 db, {%97, %101};\n"
        "wgmma.mma_async.sync.aligned.m64n192k16.f32.bf16.bf16 "
        "{%0, %1, %2, %3, %4, %5, %6, %7, %8, %9, %10, %11, %12, %13, %14, %15, %16, %17, %18, %19, %20, %21, %22, %23, %24, %25, %26, %27, %28, %29, %30, %31, %32, %33, %34, %35, %36, %37, %38, %39, %40, %41, %42, %43, %44, %45, %46, %47, %48, %49, %50, %51, %52, %53, %54, %55, %56, %57, %58, %59, %60, %61, %62, %63, %64, %65, %66, %67, %68, %69, %70, %71, %72, %73, %74, %75, %76, %77, %78, %79, %80, %81, %82, %83, %84, %85, %86, %87, %88, %89, %90, %91, %92, %93, %94, %95}, da, db, p, 1, 1, %99, %100;\n}\n"
        :
          "+f"(d[0]), "+f"(d[1]), "+f"(d[2]), "+f"(d[3]), "+f"(d[4]), "+f"(d[5]), "+f"(d[6]), "+f"(d[7]),
          "+f"(d[8]), "+f"(d[9]), "+f"(d[10]), "+f"(d[11]), "+f"(d[12]), "+f"(d[13]), "+f"(d[14]), "+f"(d[15]),
          "+f"(d[16]), "+f"(d[17]), "+f"(d[18]), "+f"(d[19]), "+f"(d[20]), "+f"(d[21]), "+f"(d[22]), "+f"(d[23]),
          "+f"(d[24]), "+f"(d[25]), "+f"(d[26]), "+f"(d[27]), "+f"(d[28]), "+f"(d[29]), "+f"(d[30]), "+f"(d[31]),
          "+f"(d[32]), "+f"(d[33]), "+f"(d[34]), "+f"(d[35]), "+f"(d[36]), "+f"(d[37]), "+f"(d[38]), "+f"(d[39]),
          "+f"(d[40]), "+f"(d[41]), "+f"(d[42]), "+f"(d[43]), "+f"(d[44]), "+f"(d[45]), "+f"(d[46]), "+f"(d[47]),
          "+f"(d[48]), "+f"(d[49]), "+f"(d[50]), "+f"(d[51]), "+f"(d[52]), "+f"(d[53]), "+f"(d[54]), "+f"(d[55]),
          "+f"(d[56]), "+f"(d[57]), "+f"(d[58]), "+f"(d[59]), "+f"(d[60]), "+f"(d[61]), "+f"(d[62]), "+f"(d[63]),
          "+f"(d[64]), "+f"(d[65]), "+f"(d[66]), "+f"(d[67]), "+f"(d[68]), "+f"(d[69]), "+f"(d[70]), "+f"(d[71]),
          "+f"(d[72]), "+f"(d[73]), "+f"(d[74]), "+f"(d[75]), "+f"(d[76]), "+f"(d[77]), "+f"(d[78]), "+f"(d[79]),
          "+f"(d[80]), "+f"(d[81]), "+f"(d[82]), "+f"(d[83]), "+f"(d[84]), "+f"(d[85]), "+f"(d[86]), "+f"(d[87]),
          "+f"(d[88]), "+f"(d[89]), "+f"(d[90]), "+f"(d[91]), "+f"(d[92]), "+f"(d[93]), "+f"(d[94]), "+f"(d[95])
        : "r"(alo), "r"(blo), "r"(scale_d), "n"(TA), "n"(TB), "r"(DESC_HI));
}
template <int TA, int TB>
__device__ __forceinline__ void wgmma_ss_n8(float (&d)[4], uint32_t alo, uint32_t blo, int scale_d) {
    asm volatile("{\n.reg .pred p;\n.reg .b64 da, db;\nsetp.ne.b32 p, %6, 0;\n"
        "mov.b64 da, {%4, %9};\nmov.b64 db, {%5, %9};\n"
        "wgmma.mma_async.sync.aligned.m64n8k16.f32.bf16.bf16 "
        "{%0, %1, %2, %3}, da, db, p, 1, 1, %7, %8;\n}\n"
        :
          "+f"(d[0]), "+f"(d[1]), "+f"(d[2]), "+f"(d[3])
        : "r"(alo), "r"(blo), "r"(scale_d), "n"(TA), "n"(TB), "r"(DESC_HI));
}
template <int TB>
__device__ __forceinline__ void wgmma_rs_n64(float (&d)[64], uint32_t a0, uint32_t a1, uint32_t a2, uint32_t a3, uint32_t blo, int scale_d) {
    asm volatile("{\n.reg .pred p;\n.reg .b64 db;\nsetp.ne.b32 p, %37, 0;\n"
        "mov.b64 db, {%36, %39};\n"
        "wgmma.mma_async.sync.aligned.m64n64k16.f32.bf16.bf16 "
        "{%0, %1, %2, %3, %4, %5, %6, %7, %8, %9, %10, %11, %12, %13, %14, %15, %16, %17, %18, %19, %20, %21, %22, %23, %24, %25, %26, %27, %28, %29, %30, %31}, {%32, %33, %34, %35}, db, p, 1, 1, %38;\n}\n"
        :
          "+f"(d[0]), "+f"(d[1]), "+f"(d[2]), "+f"(d[3]), "+f"(d[4]), "+f"(d[5]), "+f"(d[6]), "+f"(d[7]),
          "+f"(d[8]), "+f"(d[9]), "+f"(d[10]), "+f"(d[11]), "+f"(d[12]), "+f"(d[13]), "+f"(d[14]), "+f"(d[15]),
          "+f"(d[16]), "+f"(d[17]), "+f"(d[18]), "+f"(d[19]), "+f"(d[20]), "+f"(d[21]), "+f"(d[22]), "+f"(d[23]),
          "+f"(d[24]), "+f"(d[25]), "+f"(d[26]), "+f"(d[27]), "+f"(d[28]), "+f"(d[29]), "+f"(d[30]), "+f"(d[31])
        : "r"(a0), "r"(a1), "r"(a2), "r"(a3), "r"(blo), "r"(scale_d), "n"(TB), "r"(DESC_HI));
}
template <int TB>
__device__ __forceinline__ void wgmma_rs_n128(float (&d)[64], uint32_t a0, uint32_t a1, uint32_t a2, uint32_t a3, uint32_t blo, int scale_d) {
    asm volatile("{\n.reg .pred p;\n.reg .b64 db;\nsetp.ne.b32 p, %69, 0;\n"
        "mov.b64 db, {%68, %71};\n"
        "wgmma.mma_async.sync.aligned.m64n128k16.f32.bf16.bf16 "
        "{%0, %1, %2, %3, %4, %5, %6, %7, %8, %9, %10, %11, %12, %13, %14, %15, %16, %17, %18, %19, %20, %21, %22, %23, %24, %25, %26, %27, %28, %29, %30, %31, %32, %33, %34, %35, %36, %37, %38, %39, %40, %41, %42, %43, %44, %45, %46, %47, %48, %49, %50, %51, %52, %53, %54, %55, %56, %57, %58, %59, %60, %61, %62, %63}, {%64, %65, %66, %67}, db, p, 1, 1, %70;\n}\n"
        :
          "+f"(d[0]), "+f"(d[1]), "+f"(d[2]), "+f"(d[3]), "+f"(d[4]), "+f"(d[5]), "+f"(d[6]), "+f"(d[7]),
          "+f"(d[8]), "+f"(d[9]), "+f"(d[10]), "+f"(d[11]), "+f"(d[12]), "+f"(d[13]), "+f"(d[14]), "+f"(d[15]),
          "+f"(d[16]), "+f"(d[17]), "+f"(d[18]), "+f"(d[19]), "+f"(d[20]), "+f"(d[21]), "+f"(d[22]), "+f"(d[23]),
          "+f"(d[24]), "+f"(d[25]), "+f"(d[26]), "+f"(d[27]), "+f"(d[28]), "+f"(d[29]), "+f"(d[30]), "+f"(d[31]),
          "+f"(d[32]), "+f"(d[33]), "+f"(d[34]), "+f"(d[35]), "+f"(d[36]), "+f"(d[37]), "+f"(d[38]), "+f"(d[39]),
          "+f"(d[40]), "+f"(d[41]), "+f"(d[42]), "+f"(d[43]), "+f"(d[44]), "+f"(d[45]), "+f"(d[46]), "+f"(d[47]),
          "+f"(d[48]), "+f"(d[49]), "+f"(d[50]), "+f"(d[51]), "+f"(d[52]), "+f"(d[53]), "+f"(d[54]), "+f"(d[55]),
          "+f"(d[56]), "+f"(d[57]), "+f"(d[58]), "+f"(d[59]), "+f"(d[60]), "+f"(d[61]), "+f"(d[62]), "+f"(d[63])
        : "r"(a0), "r"(a1), "r"(a2), "r"(a3), "r"(blo), "r"(scale_d), "n"(TB), "r"(DESC_HI));
}
template <int TB>
__device__ __forceinline__ void wgmma_rs_n128_z(float (&d)[64], uint32_t a0, uint32_t a1, uint32_t a2, uint32_t a3, uint32_t blo) {
    asm volatile("{\n.reg .pred p;\n.reg .b64 db;\nsetp.ne.b32 p, %69, 0;\n"
        "mov.b64 db, {%68, %71};\n"
        "wgmma.mma_async.sync.aligned.m64n128k16.f32.bf16.bf16 "
        "{%0, %1, %2, %3, %4, %5, %6, %7, %8, %9, %10, %11, %12, %13, %14, %15, %16, %17, %18, %19, %20, %21, %22, %23, %24, %25, %26, %27, %28, %29, %30, %31, %32, %33, %34, %35, %36, %37, %38, %39, %40, %41, %42, %43, %44, %45, %46, %47, %48, %49, %50, %51, %52, %53, %54, %55, %56, %57, %58, %59, %60, %61, %62, %63}, {%64, %65, %66, %67}, db, p, 1, 1, %70;\n}\n"
        :
          "=f"(d[0]), "=f"(d[1]), "=f"(d[2]), "=f"(d[3]), "=f"(d[4]), "=f"(d[5]), "=f"(d[6]), "=f"(d[7]),
          "=f"(d[8]), "=f"(d[9]), "=f"(d[10]), "=f"(d[11]), "=f"(d[12]), "=f"(d[13]), "=f"(d[14]), "=f"(d[15]),
          "=f"(d[16]), "=f"(d[17]), "=f"(d[18]), "=f"(d[19]), "=f"(d[20]), "=f"(d[21]), "=f"(d[22]), "=f"(d[23]),
          "=f"(d[24]), "=f"(d[25]), "=f"(d[26]), "=f"(d[27]), "=f"(d[28]), "=f"(d[29]), "=f"(d[30]), "=f"(d[31]),
          "=f"(d[32]), "=f"(d[33]), "=f"(d[34]), "=f"(d[35]), "=f"(d[36]), "=f"(d[37]), "=f"(d[38]), "=f"(d[39]),
          "=f"(d[40]), "=f"(d[41]), "=f"(d[42]), "=f"(d[43]), "=f"(d[44]), "=f"(d[45]), "=f"(d[46]), "=f"(d[47]),
          "=f"(d[48]), "=f"(d[49]), "=f"(d[50]), "=f"(d[51]), "=f"(d[52]), "=f"(d[53]), "=f"(d[54]), "=f"(d[55]),
          "=f"(d[56]), "=f"(d[57]), "=f"(d[58]), "=f"(d[59]), "=f"(d[60]), "=f"(d[61]), "=f"(d[62]), "=f"(d[63])
        : "r"(a0), "r"(a1), "r"(a2), "r"(a3), "r"(blo), "n"(0), "n"(TB), "r"(DESC_HI));
}
template <int TA, int TB>
__device__ __forceinline__ void wgmma_ss_n128_z(float (&d)[64], uint32_t alo, uint32_t blo) {
    asm volatile("{\n.reg .pred p;\n.reg .b64 da, db;\nsetp.ne.b32 p, %66, 0;\n"
        "mov.b64 da, {%64, %69};\nmov.b64 db, {%65, %69};\n"
        "wgmma.mma_async.sync.aligned.m64n128k16.f32.bf16.bf16 "
        "{%0, %1, %2, %3, %4, %5, %6, %7, %8, %9, %10, %11, %12, %13, %14, %15, %16, %17, %18, %19, %20, %21, %22, %23, %24, %25, %26, %27, %28, %29, %30, %31, %32, %33, %34, %35, %36, %37, %38, %39, %40, %41, %42, %43, %44, %45, %46, %47, %48, %49, %50, %51, %52, %53, %54, %55, %56, %57, %58, %59, %60, %61, %62, %63}, da, db, p, 1, 1, %67, %68;\n}\n"
        :
          "=f"(d[0]), "=f"(d[1]), "=f"(d[2]), "=f"(d[3]), "=f"(d[4]), "=f"(d[5]), "=f"(d[6]), "=f"(d[7]),
          "=f"(d[8]), "=f"(d[9]), "=f"(d[10]), "=f"(d[11]), "=f"(d[12]), "=f"(d[13]), "=f"(d[14]), "=f"(d[15]),
          "=f"(d[16]), "=f"(d[17]), "=f"(d[18]), "=f"(d[19]), "=f"(d[20]), "=f"(d[21]), "=f"(d[22]), "=f"(d[23]),
          "=f"(d[24]), "=f"(d[25]), "=f"(d[26]), "=f"(d[27]), "=f"(d[28]), "=f"(d[29]), "=f"(d[30]), "=f"(d[31]),
          "=f"(d[32]), "=f"(d[33]), "=f"(d[34]), "=f"(d[35]), "=f"(d[36]), "=f"(d[37]), "=f"(d[38]), "=f"(d[39]),
          "=f"(d[40]), "=f"(d[41]), "=f"(d[42]), "=f"(d[43]), "=f"(d[44]), "=f"(d[45]), "=f"(d[46]), "=f"(d[47]),
          "=f"(d[48]), "=f"(d[49]), "=f"(d[50]), "=f"(d[51]), "=f"(d[52]), "=f"(d[53]), "=f"(d[54]), "=f"(d[55]),
          "=f"(d[56]), "=f"(d[57]), "=f"(d[58]), "=f"(d[59]), "=f"(d[60]), "=f"(d[61]), "=f"(d[62]), "=f"(d[63])
        : "r"(alo), "r"(blo), "n"(0), "n"(TA), "n"(TB), "r"(DESC_HI));
}

__device__ __forceinline__ uint32_t pack_bf16(float lo, float hi) {
    uint32_t r;
    asm("cvt.rn.bf16x2.f32 %0, %1, %2;" : "=r"(r) : "f"(hi), "f"(lo));
    return r;
}
__device__ __forceinline__ uint32_t add_bf16x2(uint32_t a, uint32_t b) {
    uint32_t r;
    asm("add.rn.bf16x2 %0, %1, %2;" : "=r"(r) : "r"(a), "r"(b));
    return r;
}
__device__ __forceinline__ float bf_lo(uint32_t v) { return __uint_as_float(v << 16); }
__device__ __forceinline__ float bf_hi(uint32_t v) { return __uint_as_float(v & 0xffff0000u); }
__device__ __forceinline__ float round_bf16(float v) { return __bfloat162float(__float2bfloat16_rn(v)); }
__device__ __forceinline__ float ex2(float x) {
    float y;
    asm("ex2.approx.ftz.f32 %0, %1;" : "=f"(y) : "f"(x));
    return y;
}
__device__ __forceinline__ float rcp(float x) {
    float y;
    asm("rcp.approx.ftz.f32 %0, %1;" : "=f"(y) : "f"(x));
    return y;
}
__device__ __forceinline__ void stg128(void* p, uint32_t a, uint32_t b, uint32_t c, uint32_t d) {
    asm volatile("st.global.v4.b32 [%0], {%1, %2, %3, %4};" ::"l"(p), "r"(a), "r"(b), "r"(c), "r"(d) : "memory");
}
__device__ __forceinline__ void stg128p(void* p, uint32_t a, uint32_t b, uint32_t c, uint32_t d, uint64_t pol) {
    asm volatile("st.global.L2::cache_hint.v4.b32 [%0], {%1, %2, %3, %4}, %5;" ::"l"(p), "r"(a), "r"(b), "r"(c), "r"(d), "l"(pol) : "memory");
}
__device__ __forceinline__ uint64_t policy_sel(bool first) {
    uint64_t p;
    asm("createpolicy.fractional.L2::evict_normal.b64 %0, 1.0;" : "=l"(p));
    return first ? policy_evict_first() : p;
}
__device__ __forceinline__ int perm_row(int t) { return (t & ~255) | (((0x78 >> (((t >> 6) & 3) * 2)) & 3) << 6) | (t & 63); }
__device__ __forceinline__ int unperm_row(int t) { return (t & ~255) | (((0x9C >> (((t >> 6) & 3) * 2)) & 3) << 6) | (t & 63); }

#define PROF(i)
#define PROFG(i)
#define PROFDUMP()
#define TR(i)
#define OP(i)
#define BP(r, i)
#define LP(i)

template <int I>
__device__ __forceinline__ void store_chunk(const float (&a)[64], __nv_bfloat16* row0, __nv_bfloat16* row1, float s0, float s1) {
    stg128(row0 + 32 * I, pack_bf16(a[16 * I + 0] * s0, a[16 * I + 1] * s0), pack_bf16(a[16 * I + 4] * s0, a[16 * I + 5] * s0),
           pack_bf16(a[16 * I + 8] * s0, a[16 * I + 9] * s0), pack_bf16(a[16 * I + 12] * s0, a[16 * I + 13] * s0));
    stg128(row1 + 32 * I, pack_bf16(a[16 * I + 2] * s1, a[16 * I + 3] * s1), pack_bf16(a[16 * I + 6] * s1, a[16 * I + 7] * s1),
           pack_bf16(a[16 * I + 10] * s1, a[16 * I + 11] * s1), pack_bf16(a[16 * I + 14] * s1, a[16 * I + 15] * s1));
}
template <int I>
struct IntT { static constexpr int value = I; };
template <class F>
__device__ __forceinline__ void for4(F f) { f(IntT<0>{}); f(IntT<1>{}); f(IntT<2>{}); f(IntT<3>{}); }

struct Prod {
    uint32_t smem, bars;
    uint32_t bo, par;
    uint32_t dst, fb;
    __device__ __forceinline__ void acquire(uint32_t o, uint32_t parity, uint32_t bytes) {
        mbar_wait(bars + BAR_EMPTY + o, parity);
        fb = bars + BAR_FULL + o;
        dst = smem + o * (SLOT / 8);
        w_expect_tx(fb, bytes);
    }
    __device__ __forceinline__ void next(uint32_t bytes) {
        acquire(bo, par, bytes);
        const bool wrap = bo == (NSLOT - 1) * 8;
        bo = wrap ? 0u : bo + 8;
        par ^= wrap ? 1u : 0u;
    }
};

__device__ __forceinline__ int item_p(int ca, int rd) {
    const int v = (rd & 1) ? (ca + 4) & 7 : ca;
    return (rd & 2) ? 7 - v : v;
}
__device__ __forceinline__ int n_items(int ca, int cb) { return cb == 8 ? 8 : ((ca & 3) == 3) ? 3 : 4; }
__device__ __forceinline__ int item_rd(int ca, int cb, int j) { return cb == 8 ? 2 + ca : (ca == 7 && j == 2) ? 3 : j; }
__device__ __forceinline__ int item_h(int cb, int rd, int j) { return 8 * rd + (cb == 8 ? j : cb); }
__device__ __forceinline__ int item_q(int ca, int cb, int rd) { return cb == 8 ? 0 : item_p(ca, rd); }
__device__ __forceinline__ int out_p(int ca, int cb) { return (cb + 2 * (ca & 3)) & 7; }
__device__ __forceinline__ int kv_round(int i) { return (0x1023 >> (4 * i)) & 3; }
__device__ __forceinline__ int slot_a(int i) { return (0x5310 >> (4 * i)) & 15; }
__device__ __forceinline__ int slot_w(int m) { return (0x264 >> (4 * m)) & 15; }

__device__ __forceinline__ void producer(const Params& P, uint32_t smem, uint32_t bars, int ca, int cb, int rank) {
    Prod pr{smem, bars, 0u, cb == 8 ? 1u : 0u, 0u, 0u};
    if (cb < 8) {
        int m = 0;
        uint32_t lap = 1;
#pragma unroll 1
        for (int u = 0; u < 32; u++) {
            if (u >= 3) {
                const int v = (u == 3) ? 3 + ca : u + 7;
                if (v < 32 && (u == 3 || (v & 7) == ca)) w_tma_prefetch((v & 4) ? &P.wuv : &P.wuk, (cb + 8 * kv_round(v >> 3)) * 128 + rank * 64, (v & 3) * 128);
                if (u == 24) {
                    w_tma_prefetch(&P.wq, cb * 128 + rank * 64, ca * 64);
                    if (ca < 2) w_tma_prefetch(&P.wq, cb * 128 + rank * 64, (ca + 8) * 64);
                }
            }
            if (u == 2) mbar_wait(bars + BAR_FULL + slot_w(2) * 8, 0);
            if (u > 0) pr.acquire(slot_w(m) * 8, lap ^ (m >> 1), SLOT);
            lap ^= m >> 1;
            m = (m == 2) ? 0 : m + 1;
            TR(1 + u);
            if (u > 0) w_tma_load_mc(pr.dst + rank * 16384, (u & 4) ? &P.wuv : &P.wuk, (cb + 8 * kv_round(u >> 3)) * 128 + rank * 64, (u & 3) * 128, pr.fb);
            if (u < 3) {
                pr.acquire(slot_a(u + 1) * 8, 1, SLOT);
                w_tma_load(pr.dst, &P.ckv, u * 128 + 128, (2 * ca + rank) * 128, pr.fb);
                w_tma_load(pr.dst + 16384, &P.ckv, u * 128 + 192, (2 * ca + rank) * 128, pr.fb);
            }
        }
    }
    PROF(1);
    if (cb == 8) {
        mbar_wait_sleep(bars + BAR_DEP + 8, 0);
#pragma unroll 1
        for (int ks = 0; ks < 10; ks++) w_tma_prefetch(&P.wq, item_h(cb, 2 + ca, 0) * 128 + rank * 64, ks * 64);
    }
    mbar_wait_sleep(bars + BAR_DEP, 0);
#pragma unroll 1
    for (int j = 0, pfs = 1; j < n_items(ca, cb); j++) {
        const int rd = item_rd(ca, cb, j), h = item_h(cb, rd, j), p = item_q(ca, cb, rd);
#pragma unroll 1
        for (int ks = 0; ks < 10; ks++) {
            pr.next(SLOT);
            w_tma_load_mc(pr.dst + 16384 + rank * 8192, &P.wq, h * 128 + rank * 64, ks * 64, pr.fb);
            w_tma_load(pr.dst, &P.xn, ks * 64, 256 * p + 128 * rank, pr.fb);
            if (cb == 8 && j < 7) w_tma_prefetch(&P.wq, (h + 1) * 128 + rank * 64, ks * 64);
        }
        PROF(8 + rd * 4);
        mbar_wait(bars + BAR_DEP + (1 + (cb == 8 ? j : rd)) * 8, 0);
        const int last = 4 * p + 3, top = h * 32 + last;
#pragma unroll 1
        for (int i = 0; i <= last; i++) {
            const int t = (i == 0) ? top - 1 : (i == last) ? h * 32 + 1 : (i & 1) ? top - 2 - i : top + 2 - i;
            pr.next(SLOT);
            const bool lastrd = (cb == 8 || rd == 3) ? false : (rd == 0) ? ca >= 6 : (rd == 1) ? (ca & 3) >= 2 : (ca == 3 || (ca < 3 && (t & 31) >= 4 * p));
            if (lastrd) w_tma_load_mc_last(pr.dst + rank * 16384, &P.kv, rank * 64, t * 128, pr.fb);
            else w_tma_load_mc(pr.dst + rank * 16384, &P.kv, rank * 64, t * 128, pr.fb);
            if (i == 2 && cb < 8) {
                const int upto = (j == n_items(ca, cb) - 1) ? 4 : item_rd(ca, cb, j + 1);
#pragma unroll 1
                for (; pfs <= upto; pfs++) {
                    if (pfs < 4) {
                        w_tma_prefetch(&P.wq, (8 * pfs + cb) * 128 + rank * 64, ca * 64);
                        if (ca < 2) w_tma_prefetch(&P.wq, (8 * pfs + cb) * 128 + rank * 64, (ca + 8) * 64);
                    } else {
#pragma unroll 1
                        for (int k = 0; k < 10; k++)
                            w_tma_prefetch(&P.wo, 320 * (ca >> 2) + 64 * (k >= 5 ? k - 5 : k), (cb * 4 + (ca & 3) + (k >= 5 ? 32 : 0)) * 64 + rank * 32);
                    }
                }
            }
        }
        PROF(9 + rd * 4);
    }
    if (cb < 8) {
        const int n0 = 320 * (ca >> 2), op = out_p(ca, cb);
        uint32_t* pool = g_flags + (F_POOL + op * 2 + (ca >> 2)) * 8;
        uint32_t nxt = 0;
        auto draw = [&]() {
            if (rank == 0) asm volatile(ELECT "atom.relaxed.gpu.global.add.u32 %0, [%1], 1;\n}\n" : "+r"(nxt) : "l"(pool) : "memory");
        };
        int fixed = -1;
#pragma unroll 1
        for (int i = -2; fixed < 4; i++) {
            int st = (ca & 3) + 4 * (i + 2);
            if (i == -1) draw();
            if (i >= 0 && fixed < 0) {
                const uint32_t mb = bars + BAR_MAIL + (i & 7) * 8, md = bars + MAIL_OFF + (i & 7) * 4;
                if (rank == 0) {
                    st = __reduce_add_sync(0xffffffffu, nxt);
                    asm volatile(ELECT "st.async.shared::cluster.mbarrier::complete_tx::bytes.b32 [%0], %1, [%2];\n}\n" ::"r"(mapa(md, 1)), "r"(st), "r"(mapa(mb, 1)) : "memory");
                    if (st < 48) draw();
                } else {
                    w_expect_tx(mb, 4);
                    mbar_wait(mb, (i >> 3) & 1);
                    asm volatile("ld.shared.u32 %0, [%1];" : "=r"(st) : "r"(md) : "memory");
                    st = __reduce_or_sync(0xffffffffu, st);
                }
                if (st >= 48) fixed = 0;
            }
            if (fixed >= 0) { st = 48 + (ca & 3) + 4 * fixed; fixed++; }
            const int krow = st * 64 + rank * 32;
            mbar_wait(bars + BAR_EMPTY + pr.bo, pr.par);
            asm volatile("st.shared.u32 [%0], %1;" ::"r"(bars + CTL_OFF + pr.bo), "r"((int)(fixed == 1)) : "memory");
            __syncwarp();
            pr.next(SLOT);
            w_tma_load_mc(pr.dst + 16384 + rank * 8192, &P.wo, n0, krow, pr.fb);
            w_tma_load_mc(pr.dst + 16384 + rank * 8192 + 4096, &P.wo, n0 + 64, krow, pr.fb);
            mbar_wait(bars + BAR_DEP + (5 + (st >> 4)) * 8, 0);
            w_tma_load(pr.dst, &P.ctx, (st & 1) * 64, (st >> 1) * SEQ + 256 * op + 128 * rank, pr.fb);
#pragma unroll 1
            for (int k = (fixed < 2) ? 0 : (fixed == 4) ? -2 : 1; k <= 0; k++) {
                pr.next(24576);
#pragma unroll
                for (int c = 0; c < 3; c++) w_tma_load_mc(pr.dst + rank * 12288 + c * 4096, &P.wo, n0 + 128 + 64 * c, krow + k * 256, pr.fb);
            }
        }
    }
}

struct Slot {
    uint32_t bo, dl, par;
};
struct Cons {
    uint32_t bars, rel;
    uint32_t dl0;
    uint32_t lane;
    Slot cur;
    __device__ __forceinline__ Slot slot(int s, uint32_t par) const { return Slot{(uint32_t)s * 8, dl0 + (uint32_t)s * (SLOT >> 4), par}; }
    __device__ __forceinline__ void wait(const Slot& s) const { mbar_wait(bars + BAR_FULL + s.bo, s.par); }
    __device__ __forceinline__ uint32_t peek() const { return mbar_peek(bars + BAR_FULL + cur.bo, cur.par); }
    __device__ __forceinline__ void wait(const Slot& s, uint32_t ok) const { mbar_wait_unless(ok, bars + BAR_FULL + s.bo, s.par); }
    __device__ __forceinline__ void release(uint32_t bo) const {
        asm volatile("{\n.reg .pred p;\nsetp.lt.u32 p, %1, 2;\n@p mbarrier.arrive.shared::cluster.b64 _, [%0];\n}\n" ::"r"(rel + bo), "r"(lane) : "memory");
    }
    __device__ __forceinline__ Slot next() {
        const Slot s = cur;
        const bool wrap = s.bo == (NSLOT - 1) * 8;
        cur.bo = wrap ? 0u : s.bo + 8;
        cur.dl = wrap ? dl0 : s.dl + (SLOT >> 4);
        cur.par = s.par ^ (wrap ? 1u : 0u);
        return s;
    }
};
__host__ __device__ constexpr uint32_t lbo(uint32_t bytes) { return (bytes >> 4) << 16; }

__device__ __forceinline__ float div640(float x) {
    const float q = x * (1.0f / DM);
    return fmaf(fmaf(-q, (float)DM, x), 1.0f / DM, q);
}
__device__ __forceinline__ float sqrt_approx(float x) {
    float y;
    asm("sqrt.approx.ftz.f32 %0, %1;" : "=f"(y) : "f"(x));
    return y;
}
struct LayerNorm {
    uint4 xv[5], wv[5];
    float mean, inv, r;
    uint32_t nmb;
    __nv_bfloat16 *pn, *po;
    static __device__ __forceinline__ float half_sum(float v) {
#pragma unroll
        for (int o = 8; o > 0; o >>= 1) v += __shfl_xor_sync(0xffffffffu, v, o);
        return v;
    }
    __device__ __forceinline__ void load(const __nv_bfloat16* x, const __nv_bfloat16* wr, __nv_bfloat16* out, int t, int l) {
        pn = g_xn + perm_row(t) * DM + 8 * l;
        po = out + t * DM + 8 * l;
        asm volatile("" : "+l"(pn), "+l"(po));
#pragma unroll
        for (int i = 0; i < 5; i++) {
            xv[i] = ldg_stream(reinterpret_cast<const uint4*>(x + t * DM) + l + 16 * i);
            wv[i] = __ldg(reinterpret_cast<const uint4*>(wr) + l + 16 * i);
        }
    }
    __device__ __forceinline__ void stat1() {
        float a[4] = {0.f, 0.f, 0.f, 0.f};
#pragma unroll
        for (int i = 0; i < 20; i++) { const uint32_t u = (&xv[i >> 2].x)[i & 3]; a[i & 3] += bf_lo(u) + bf_hi(u); }
        mean = div640(half_sum((a[0] + a[1]) + (a[2] + a[3])));
        r = 0.f;
    }
    template <int H>
    __device__ __forceinline__ void stat2() {
        float a[4] = {r, 0.f, 0.f, 0.f};
#pragma unroll
        for (int i = H ? 12 : 0; i < (H ? 20 : 12); i++) {
            uint32_t u = (&xv[i >> 2].x)[i & 3];
            asm volatile("" : "+r"(u));
            const float d0 = bf_lo(u) - mean, d1 = bf_hi(u) - mean;
            a[i & 3] = fmaf(d0, d0, fmaf(d1, d1, a[i & 3]));
        }
        r = (a[0] + a[1]) + (a[2] + a[3]);
        if (H) {
            inv = rcp(round_bf16(sqrt_approx(round_bf16(round_bf16(div640(half_sum(r))) + 1e-5f))));
            r = 0.f;
            nmb = pack_bf16(-mean, -mean);
        }
    }
    template <int I>
    __device__ __forceinline__ void piece(int t, int l) {
        uint32_t o[4], z[4];
        float a[4];
#pragma unroll
        for (int j = 0; j < 4; j++) {
            const uint32_t u = (&xv[I].x)[j], w = (&wv[I].x)[j];
            const uint32_t d = add_bf16x2(u, nmb);
            o[j] = pack_bf16(bf_lo(d) * inv, bf_hi(d) * inv);
            z[j] = add_bf16x2(u, o[j]);
            a[j] = fmaf(bf_hi(o[j]), bf_hi(w), bf_lo(o[j]) * bf_lo(w));
        }
        r += (a[0] + a[1]) + (a[2] + a[3]);
        stg128(pn + 128 * I, o[0], o[1], o[2], o[3]);
        stg128p(po + 128 * I, z[0], z[1], z[2], z[3], policy_evict_first());
        if (I == 4) {
            r = half_sum(r);
            if (l == 0) g_r[t] = round_bf16(r);
        }
    }
};

constexpr float SM_SCALE = 0.08838834764831845f * 1.4426950408889634f;

template <int J0, int J1>
__device__ __forceinline__ void exp_part(float (&s)[64], float n0, float n1, float& r0, float& r1) {
    float a1 = 0.f, b1 = 0.f;
#pragma unroll
    for (int j = J0; j < J1; j++) {
        s[4 * j + 0] = ex2(fmaf(s[4 * j + 0], SM_SCALE, n0));
        s[4 * j + 1] = ex2(fmaf(s[4 * j + 1], SM_SCALE, n0));
        s[4 * j + 2] = ex2(fmaf(s[4 * j + 2], SM_SCALE, n1));
        s[4 * j + 3] = ex2(fmaf(s[4 * j + 3], SM_SCALE, n1));
        r0 += s[4 * j + 0]; r1 += s[4 * j + 2];
        if (j == J0) { a1 = s[4 * j + 1]; b1 = s[4 * j + 3]; } else { a1 += s[4 * j + 1]; b1 += s[4 * j + 3]; }
    }
    r0 += a1;
    r1 += b1;
}
__device__ __forceinline__ void sched_barrier(float x, float y, uint32_t scratch) {
    asm volatile("{\n.reg .pred p;\nsetp.lt.f32 p, %0, 0f00000000;\n@p st.shared.f32 [%2], %1;\n}\n" ::"f"(x), "f"(y), "r"(scratch) : "memory");
}
__device__ __forceinline__ void pack_tile(const float (&s)[64], uint32_t (&p)[32]) {
#pragma unroll
    for (int i = 0; i < 32; i++) p[i] = pack_bf16(s[2 * i], s[2 * i + 1]);
}
template <bool ZERO>
__device__ __forceinline__ void gemm_rs(float (&d)[64], const uint32_t (&a)[32], uint32_t dl, int acc = 1) {
    const uint32_t b = dl + lbo(16384);
    if (ZERO) wgmma_rs_n128_z<1>(d, a[0], a[1], a[2], a[3], b);
#pragma unroll
    for (int k = ZERO ? 1 : 0; k < 8; k++) wgmma_rs_n128<1>(d, a[4 * k], a[4 * k + 1], a[4 * k + 2], a[4 * k + 3], b + k * 128, k ? 1 : acc);
}
__device__ __forceinline__ void gemm_pv(float (&d)[64], const uint32_t (&a)[32], uint32_t dl, int acc, int full) {
    const uint32_t b = dl + lbo(16384);
    wgmma_rs_n128<1>(d, a[0], a[1], a[2], a[3], b, acc);
    wgmma_commit();
    if (full) {
        wgmma_fence();
#pragma unroll
        for (int k = 4; k < 8; k++) wgmma_rs_n128<1>(d, a[4 * k], a[4 * k + 1], a[4 * k + 2], a[4 * k + 3], b + k * 128, 1);
        wgmma_commit();
    }
    wgmma_fence();
#pragma unroll
    for (int k = 1; k < 4; k++) wgmma_rs_n128<1>(d, a[4 * k], a[4 * k + 1], a[4 * k + 2], a[4 * k + 3], b + k * 128, 1);
}
template <int ZERO>
__device__ __forceinline__ void gemm_q(float (&d)[64], uint32_t dl, int role) {
    const uint32_t a = dl + role * 512 + lbo(16), b = dl + 1024 + lbo(8192);
    if (ZERO) wgmma_ss_n128_z<0, 1>(d, a, b);
#pragma unroll
    for (int k = ZERO ? 1 : 0; k < 4; k++) wgmma_ss_n128<0, 1>(d, a + k * 2, b + k * 128, 1);
}
template <bool KT, bool ZERO, int K0, int K1>
__device__ __forceinline__ void gemm_kv(float (&d)[64], uint32_t ckv, uint32_t wt, int wg) {
    if (KT) {
        const uint32_t a = wt + wg * 1024 + lbo(16), b = ckv + lbo(16);
        if (ZERO) wgmma_ss_n128_z<1, 0>(d, a, b);
#pragma unroll
        for (int k = ZERO ? 1 : K0; k < K1; k++) wgmma_ss_n128<1, 0>(d, a + k * 128, b + (k >> 2) * 1024 + (k & 3) * 2, 1);
    } else {
        const uint32_t a = ckv + wg * 512 + lbo(16), b = wt + lbo(16384);
        if (ZERO) wgmma_ss_n128_z<0, 1>(d, a, b);
#pragma unroll
        for (int k = ZERO ? 1 : K0; k < K1; k++) wgmma_ss_n128<0, 1>(d, a + (k >> 2) * 1024 + (k & 3) * 2, b + k * 128, 1);
    }
}
__device__ __forceinline__ void mma16816(float& d0, float& d1, float& d2, float& d3, uint32_t a0, uint32_t a1, uint32_t a2, uint32_t a3, uint32_t b0, uint32_t b1) {
    asm volatile("mma.sync.aligned.m16n8k16.row.col.f32.bf16.bf16.f32 {%0,%1,%2,%3}, {%4,%5,%6,%7}, {%8,%9}, {%0,%1,%2,%3};"
                 : "+f"(d0), "+f"(d1), "+f"(d2), "+f"(d3) : "r"(a0), "r"(a1), "r"(a2), "r"(a3), "r"(b0), "r"(b1));
}
__device__ __forceinline__ uint32_t ld_pair(const __nv_bfloat16* p) {
    const unsigned short* u = reinterpret_cast<const unsigned short*>(p);
    return (uint32_t)__ldcg(u) | ((uint32_t)__ldcg(u + 128) << 16);
}
__device__ __forceinline__ void attention_exact(float (&o)[64], const uint32_t (&qf)[32], float& l0, float& l1, int h, int nblk, int rr, int lane) {
    const int q = lane & 3, lr = lane >> 2;
    float m0 = -INFINITY, m1 = -INFINITY;
    l0 = 0.f; l1 = 0.f;
#pragma unroll 1
    for (int cidx = 0; cidx < nblk * 8; cidx++) {
        const int kc = cidx & 7;
        const __nv_bfloat16* kt = g_kv + (size_t)((h * 16 + (cidx >> 3)) * 2) * 16384;
        float sc[8];
#pragma unroll
        for (int i = 0; i < 8; i++) sc[i] = 0.f;
#pragma unroll
        for (int kk = 0; kk < 8; kk++)
#pragma unroll
            for (int nt = 0; nt < 2; nt++) {
                const __nv_bfloat16* b = kt + (16 * kk + 2 * q) * 128 + 16 * kc + 8 * nt + lr;
                mma16816(sc[4 * nt], sc[4 * nt + 1], sc[4 * nt + 2], sc[4 * nt + 3], qf[4 * kk], qf[4 * kk + 1], qf[4 * kk + 2], qf[4 * kk + 3],
                         ld_pair(b), ld_pair(b + 8 * 128));
            }
        const int lim = rr + ((nblk - 1) - (cidx >> 3)) * 128 - 32 * (kc >> 1) - 4 * (kc & 1);
#pragma unroll
        for (int i = 0; i < 8; i++)
            if (2 * (i >> 2) + (i & 1) > lim + 4 * (i & 2)) sc[i] = -INFINITY;
        float x0 = fmaxf(fmaxf(sc[0], sc[1]), fmaxf(sc[4], sc[5])), x1 = fmaxf(fmaxf(sc[2], sc[3]), fmaxf(sc[6], sc[7]));
        x0 = fmaxf(x0, __shfl_xor_sync(0xffffffffu, x0, 1)); x1 = fmaxf(x1, __shfl_xor_sync(0xffffffffu, x1, 1));
        x0 = fmaxf(x0, __shfl_xor_sync(0xffffffffu, x0, 2)); x1 = fmaxf(x1, __shfl_xor_sync(0xffffffffu, x1, 2));
        x0 = fmaxf(x0, m0); x1 = fmaxf(x1, m1);
        const float a0 = ex2((m0 - x0) * SM_SCALE), a1 = ex2((m1 - x1) * SM_SCALE);
        m0 = x0; m1 = x1;
#pragma unroll
        for (int i = 0; i < 8; i++) sc[i] = ex2((sc[i] - ((i & 2) ? m1 : m0)) * SM_SCALE);
        l0 = l0 * a0 + (sc[0] + sc[1]) + (sc[4] + sc[5]);
        l1 = l1 * a1 + (sc[2] + sc[3]) + (sc[6] + sc[7]);
        const uint32_t p0 = pack_bf16(sc[0], sc[1]), p1 = pack_bf16(sc[2], sc[3]), p2 = pack_bf16(sc[4], sc[5]), p3 = pack_bf16(sc[6], sc[7]);
        const __nv_bfloat16* vb = kt + 16384 + (16 * kc + 2 * q) * 128 + lr;
#pragma unroll
        for (int nt = 0; nt < 16; nt++) {
            o[4 * nt] *= a0; o[4 * nt + 1] *= a0; o[4 * nt + 2] *= a1; o[4 * nt + 3] *= a1;
            mma16816(o[4 * nt], o[4 * nt + 1], o[4 * nt + 2], o[4 * nt + 3], p0, p1, p2, p3, ld_pair(vb + 8 * nt), ld_pair(vb + 8 * nt + 8 * 128));
        }
    }
}

__device__ __forceinline__ void signal(uint32_t bars, int wg, int e, int lane) {
    __syncwarp();
    asm volatile("{\n.reg .pred p;\nsetp.eq.u32 p, %1, 0;\n@p mbarrier.arrive.shared::cta.b64 _, [%0];\n}\n" ::"r"(bars + BAR_SIG + (wg * 9 + e) * 8), "r"(lane) : "memory");
}

__device__ __forceinline__ void mod_ffn(const Params& P, uint32_t smem, int mc, int wg);

__device__ __forceinline__ void consumer(const Params& P, uint32_t smem, uint32_t bars, int ca, int cb, int rank, int wg) {
    const int lane = threadIdx.x & 31, w = (threadIdx.x >> 5) & 3, q = lane & 3, lr = lane >> 2;
    PROF(7);
    cluster_wait();
    Cons c{bars, mapa(bars + BAR_EMPTY, lane & 1), (smem & 0x3FFFF) >> 4, (uint32_t)lane, Slot{0u, (smem & 0x3FFFF) >> 4, cb == 8 ? 0u : 1u}};
    PROFG(180);
    PROF(1);
    float o[64], s[64];
    uint32_t pend;
    __nv_bfloat16* ep_ptr;
    int ep_step;
    if (cb == 8) {
        pend = 0;
        ep_ptr = g_ctx + (size_t)(item_h(cb, 2 + ca, 0) * SEQ + 128 * rank + 64 * wg + 16 * w + lr) * HD + 8 * q;
        ep_step = 8 * HD;
    } else {
        const int ln_t = blockIdx.x * 16 + wg * 8 + w * 2 + (lane >> 4);
        const int krow = 64 * wg + 16 * w + lr;
        const int vrow = 64 * wg + 32 * (w >> 1) + 8 * (lr >> 1) + 4 * (w & 1) + (lr & 1);
        ep_step = 2 * 128;
        int m = 0;
        uint32_t lap = 0;
        LayerNorm ln;
        auto step = [&](auto kt, auto kc, float (&d)[64], int hh) {
            const Slot sa = c.slot(slot_a(kc.value), 0), sw = c.slot(slot_w(m), lap ^ (m >> 1));
            lap ^= m >> 1;
            m = (m == 2) ? 0 : m + 1;
            TR(1 + (hh * 8 + (kt.value ? 0 : 4) + kc.value) * 2);
            if (kt.value && hh == 0) c.wait(sa);
            c.wait(sw);
            TR(2 + (hh * 8 + (kt.value ? 0 : 4) + kc.value) * 2);
            wgmma_fence();
            gemm_kv<kt.value, kc.value == 0, 0, KVSPLIT>(d, sa.dl, sw.dl, wg);
            wgmma_commit();
            wgmma_wait<1>();
            if (!(kt.value && kc.value == 0 && hh == 0)) c.release(pend);
            if (!kt.value && kc.value > 0 && hh == 3) c.release(slot_a(kc.value - 1) * 8);
            pend = sw.bo;
            wgmma_fence();
            gemm_kv<kt.value, false, KVSPLIT, 8>(d, sa.dl, sw.dl, wg);
            wgmma_commit();
        };
#pragma unroll 1
        for (int hh = 0; hh < 4; hh++) {
            __nv_bfloat16* base = g_kv + (size_t)(((cb + 8 * kv_round(hh)) * 16 + 2 * ca + rank) * 2) * 16384 + 8 * q;
            auto ln_stage = [&](auto pos) {
                constexpr int j = (pos.value + 8 - LNOFF % 8) % 8;
                if (hh == wg + (LNOFF + j) / 8) {
                    if (j == 0) ln.stat1();
                    if (j == 1) ln.template stat2<0>();
                    if (j == 2) ln.template stat2<1>();
                    if constexpr (j >= 3) ln.template piece<j - 3>(ln_t, lane & 15);
                    if (j == 7) signal(bars, wg, 0, lane);
                }
                if (pos.value == (LNOFF - LNLEAD) % 8 && hh == wg + (LNOFF - LNLEAD) / 8) ln.load(P.x, P.wr, P.out, ln_t, lane & 15);
            };
            for4([&](auto kc) {
                step(TrueT{}, kc, s, hh);
                if (hh > 0) {
                    if (kc.value == 0) fence_regs(o);
                    store_chunk<kc.value>(o, ep_ptr, ep_ptr + ep_step, 1.f, 1.f);
                    if (kc.value == 3) signal(bars, wg, hh, lane);
                }
                ln_stage(kc);
            });
            for4([&](auto kc) {
                step(FalseT{}, kc, o, hh);
                if (kc.value == 0) fence_regs(s);
                store_chunk<kc.value>(s, base + krow * 128, base + (krow + 8) * 128, 1.f, 1.f);
                ln_stage(IntT<kc.value + 4>{});
            });
            PROF(24 + hh);
            if (hh == 1) PROFG(181);
            ep_ptr = base + 16384 + vrow * 128;
        }
    }
    PROFG(182);
    PROF(2);
    uint32_t pf[32];
    {
        uint32_t qf[32];
        float l0 = 0.25f, l1 = 0.25f;
        const int bar_me = 2 + wg, bar_other = 3 - wg;
#pragma unroll 1
        for (int j = 0; j < n_items(ca, cb); j++) {
            const int rd = item_rd(ca, cb, j), h = item_h(cb, rd, j), p = item_q(ca, cb, rd);
            const int role = wg ^ (j & 1);
            const int nrest = 2 * p + role;
            Slot kfirst;
            const int lim = 64 * (role ^ rank) + 16 * w + lr - 8 * q;
            const uint64_t pol = policy_sel(j == 1 || j == 2);
            {
                auto qstep = [&](auto zero, int ks) {
                    const Slot sl = c.next();
                    c.wait(sl);
                    BP(2, 5 + 3 * ks);
                    wgmma_fence();
                    gemm_q<zero.value>(s, sl.dl, role);
                    wgmma_commit();
                    wgmma_wait<1>();
                    if (!zero.value || j > 0 || cb < 8) c.release(pend);
                    pend = sl.bo;
                };
                qstep(TrueT{}, 0);
                if (j == 0 && cb < 8) c.release(slot_a(3) * 8);
                fence_regs(o);
                l0 += __shfl_xor_sync(0xffffffffu, l0, 1); l1 += __shfl_xor_sync(0xffffffffu, l1, 1);
                l0 += __shfl_xor_sync(0xffffffffu, l0, 2); l1 += __shfl_xor_sync(0xffffffffu, l1, 2);
                l0 = rcp(l0); l1 = rcp(l1);
                for4([&](auto i) {
                    constexpr int B = 16 * i.value;
#pragma unroll
                    for (int r = 0; r < 2; r++) {
                        if (1 + 2 * i.value + r == 7 && !(role | rank)) named_sync(bar_me, 256);
                        qstep(FalseT{}, 1 + 2 * i.value + r);
                        const float f = r ? l1 : l0;
                        stg128p(ep_ptr + r * ep_step + 2 * B, pack_bf16(o[B + 2 * r] * f, o[B + 2 * r + 1] * f), pack_bf16(o[B + 2 * r + 4] * f, o[B + 2 * r + 5] * f),
                                pack_bf16(o[B + 2 * r + 8] * f, o[B + 2 * r + 9] * f), pack_bf16(o[B + 2 * r + 12] * f, o[B + 2 * r + 13] * f), pol);
#pragma unroll
                        for (int k = 0; k < 8; k++) {
                            float& v = o[B + 4 * (k >> 1) + 2 * r + (k & 1)];
                            v = (2 * B + k > lim + 8 * r) ? -1e30f : 0.f;
                            asm volatile("" : "+f"(v));
                        }
                    }
                });
                signal(bars, wg, (cb == 8 ? 0 : 4) + j, lane);
                PROF(11 + rd * 4);
                qstep(FalseT{}, 9);
                if (!role) { const Slot sl = c.next(); c.wait(sl); c.release(sl.bo); }
                kfirst = c.next();
                c.wait(kfirst);
                wgmma_wait<0>();
                BP(2, 34);
                c.release(pend);
                fence_regs(s);
                pack_tile(s, qf);
            }
            Slot vskip = c.cur;
            if (!role) vskip = c.next();
            PROF(8 + rd * 4);
            if (cb == 8) PROF(40 + 3 * j);
            fence_regs(qf); fence_regs(o);
            if (!role && rank) named_sync(bar_me, 256);
            BP(2, 36);
            auto first_qk = [&](auto half) {
                wgmma_fence();
#pragma unroll
                for (int k = 0; k < 8; k++) {
                    if (half.value) wgmma_rs_n64<1>(o, qf[4 * k], qf[4 * k + 1], qf[4 * k + 2], qf[4 * k + 3], kfirst.dl + lbo(16384) + k * 128, 1);
                    else wgmma_rs_n128<1>(o, qf[4 * k], qf[4 * k + 1], qf[4 * k + 2], qf[4 * k + 3], kfirst.dl + lbo(16384) + k * 128, 1);
                }
                wgmma_commit();
                named_arrive(bar_other, 256);
                if (!role) { c.wait(vskip); c.release(vskip.bo); }
                wgmma_wait<0>();
            };
            if (role == rank) first_qk(TrueT{});
            else first_qk(FalseT{});
            BP(2, 38);
            fence_regs(o);
            c.release(kfirst.bo);
            uint32_t ready = c.peek();
            float n0 = fmaxf(fmaxf(fmaxf(o[0], o[1]), fmaxf(o[4], o[5])), fmaxf(fmaxf(o[8], o[9]), fmaxf(o[12], o[13])));
            float n1 = fmaxf(fmaxf(fmaxf(o[2], o[3]), fmaxf(o[6], o[7])), fmaxf(fmaxf(o[10], o[11]), fmaxf(o[14], o[15])));
            n0 = __shfl_sync(0xffffffffu, n0, lane & 28); n1 = __shfl_sync(0xffffffffu, n1, lane & 28);
            n0 *= -SM_SCALE; n1 *= -SM_SCALE;
            l0 = 0.f; l1 = 0.f;
#pragma unroll
            for (int i = 0; i < 64; i++) s[i] = o[i];
            exp_part<0, 8>(s, n0, n1, l0, l1);
#pragma unroll
            for (int i = 0; i < 16; i++) pf[i] = pack_bf16(s[2 * i], s[2 * i + 1]);
            if (role != rank) {
                exp_part<8, 16>(s, n0, n1, l0, l1);
#pragma unroll
                for (int i = 16; i < 32; i++) pf[i] = pack_bf16(s[2 * i], s[2 * i + 1]);
            } else {
#pragma unroll
                for (int i = 16; i < 32; i++) pf[i] = 0u;
            }
            PROF(9 + rd * 4);
            if (cb == 8) PROF(41 + 3 * j);
#pragma unroll 1
            for (int it = 0; it < nrest; it++) {
                const Slot sk = c.next(), sv = c.next();
                LP(0);
                c.wait(sk, ready);
                fence_regs(o); fence_regs(pf);
                LP(1);
                named_sync(bar_me, 256);
                LP(2);
                if (it < 3) BP(2, 42 + 4 * it);
                if (it >= nrest - 2) BP(1, 62 + 4 * (it - nrest + 2));
                wgmma_fence();
                gemm_rs<true>(s, qf, sk.dl);
                wgmma_commit();
                c.wait(sv);
                wgmma_fence();
                gemm_pv(o, pf, sv.dl, it, it | (role ^ rank));
                wgmma_commit();
                named_arrive(bar_other, 256);
                LP(3);
                wgmma_wait<2>();
                LP(4);
                c.release(sk.bo);
                fence_regs(s);
                exp_part<0, SPLITJ>(s, n0, n1, l0, l1);
                sched_barrier(l0, l1, bars + MISC_OFF + 16);
                LP(5);
                wgmma_wait<0>();
                LP(6);
                c.release(sv.bo);
                ready = c.peek();
                fence_regs(o); fence_regs(pf);
                exp_part<SPLITJ, 16>(s, n0, n1, l0, l1);
                pack_tile(s, pf);
            }
            PROF(10 + rd * 4);
            if (cb == 8) PROF(42 + 3 * j);
            PROFG(183 + rd);
            const Slot sv = c.next();
            BP(1, 0);
            c.wait(sv, ready);
            const bool bad = __any_sync(0xffffffffu, !(l0 < 0x1p60f && l1 < 0x1p60f));
            if (__builtin_expect(bad || nrest == 0, 0)) {
#pragma unroll
                for (int i = 0; i < 64; i++) o[i] = 0.f;
                if (bad) {
                    attention_exact(o, qf, l0, l1, h, nrest + 1, lim, lane);
#pragma unroll
                    for (int i = 0; i < 32; i++) pf[i] = 0u;
                }
            }
            fence_regs(o); fence_regs(pf);
            if (!role) named_sync(bar_me, 256);
            BP(1, 2);
            wgmma_fence();
            gemm_rs<false>(o, pf, sv.dl);
            wgmma_commit();
            pend = sv.bo;
            ep_ptr = g_ctx + (size_t)(h * SEQ + 256 * p + 128 * rank + 64 * role + 16 * w + lr) * HD + 8 * q;
            ep_step = 8 * HD;
        }
        l0 += __shfl_xor_sync(0xffffffffu, l0, 1); l1 += __shfl_xor_sync(0xffffffffu, l1, 1);
        l0 += __shfl_xor_sync(0xffffffffu, l0, 2); l1 += __shfl_xor_sync(0xffffffffu, l1, 2);
        l0 = rcp(l0); l1 = rcp(l1);
        sched_barrier(l0, l1, bars + MISC_OFF + 16);
        wgmma_wait<0>();
        c.release(pend);
        fence_regs(o); fence_regs(pf);
#pragma unroll
        for (int i = 0; i < 32; i++) pf[i] = pack_bf16(o[2 * i] * ((i & 1) ? l1 : l0), o[2 * i + 1] * ((i & 1) ? l1 : l0));
    }
    PROFG(187);
    PROF(3);
    if (cb == 8) {
#pragma unroll
        for (int i = 0; i < 8; i++) stg128(ep_ptr + (i & 1) * 8 * HD + 32 * (i >> 1), pf[4 * (i & 6) + (i & 1)], pf[4 * (i & 6) + (i & 1) + 2], pf[4 * (i & 6) + (i & 1) + 4], pf[4 * (i & 6) + (i & 1) + 6]);
        signal(bars, wg, 8, lane);
        cluster_arrive();
        named_sync(1, 256);
        mod_ffn(P, smem, 2 * ca + rank, wg);
    } else
    {
        float a1[64], a2[96];
        uint32_t px = 0, py = 0;
        auto mma1 = [&](const Slot& x, int acc) {
#pragma unroll
            for (int k = 0; k < 4; k++) wgmma_ss_n128<0, 1>(a1, x.dl + wg * 512 + lbo(16) + k * 2, x.dl + 1024 + lbo(4096) + (k >> 1) * 512 + (k & 1) * 128, k ? 1 : acc);
        };
        auto mma2 = [&](const Slot& x, const Slot& y, int acc) {
#pragma unroll
            for (int k = 0; k < 4; k++) wgmma_ss_n192<0, 1>(a2, x.dl + wg * 512 + lbo(16) + k * 2, y.dl + lbo(4096) + (k >> 1) * 768 + (k & 1) * 128, k ? 1 : acc);
        };
#pragma unroll 1
        for (int t = 0, more = 1; more; t++) {
            const Slot sx = c.next(), sy = c.next();
            OP(2 * t);
            c.wait(sx);
            OP(2 * t + 1);
            wgmma_fence();
            mma1(sx, t);
            wgmma_commit();
            wgmma_wait<1>();
            asm volatile("ld.shared.u32 %0, [%1];" : "=r"(more) : "r"(bars + CTL_OFF + sx.bo) : "memory");
            if (t > 0) { c.release(px); c.release(py); }
            px = sx.bo; py = sy.bo;
            c.wait(sy);
            wgmma_fence();
            mma2(sx, sy, t);
            wgmma_commit();
            more = !__any_sync(0xffffffffu, more);
            if (t == 0) {
#pragma unroll
                for (int i = 0; i < 4; i++) stg128(ep_ptr + 32 * i, pf[8 * i], pf[8 * i + 2], pf[8 * i + 4], pf[8 * i + 6]);
            }
            if (t == 1) {
#pragma unroll
                for (int i = 0; i < 4; i++) stg128(ep_ptr + 8 * HD + 32 * i, pf[8 * i + 1], pf[8 * i + 3], pf[8 * i + 5], pf[8 * i + 7]);
                signal(bars, wg, 4 + n_items(ca, cb), lane);
            }
        }
        OP(60);
        const Slot x0 = c.next(), x1 = c.next(), x2 = c.next(), y0 = c.next(), y1 = c.next(), y2 = c.next(), fr = c.next();

        const int cw = __reduce_or_sync(0xffffffffu, wg * 4 + w);
        const int orow = unperm_row(256 * out_p(ca, cb) + 128 * rank + 16 * cw), ocol = 320 * (ca >> 2);
        const uint32_t sa = ((lane & 7) + (lane & 8)) * 128, sx = (lane >> 4) ^ (lane & 7);
        auto send = [&](auto chv, uint32_t box) {
            constexpr int ch = chv.value;
#pragma unroll
            for (int i = 0; i < 4; i++) {
                uint32_t r[4];
#pragma unroll
                for (int e = 0; e < 4; e++) {
                    const int k = 32 * ch + 8 * i + 2 * e;
                    r[e] = (ch < 2) ? pack_bf16(a1[k & 63], a1[(k & 63) + 1]) : pack_bf16(a2[ch < 2 ? 0 : k - 64], a2[ch < 2 ? 1 : k - 63]);
                }
                asm volatile("stmatrix.sync.aligned.m8n8.x4.shared.b16 [%0], {%1, %2, %3, %4};"
                             ::"r"(box + sa + ((sx ^ (2 * i)) << 4)), "r"(r[0]), "r"(r[1]), "r"(r[2]), "r"(r[3]) : "memory");
            }
            asm volatile("fence.proxy.async.shared::cta;" ::: "memory");
            __syncwarp();
            asm volatile(ELECT "cp.reduce.async.bulk.tensor.2d.global.shared::cta.add.bulk_group [%0, {%2, %3}], [%1];\n}\n"
                         ::"l"(&P.outm), "r"(box), "r"(ocol + 64 * ch), "r"(orow) : "memory");
        };
        auto addr = [&](const Slot& t) { return smem + t.bo * (SLOT / 8); };
        const bool follow = wg ^ ((n_items(ca, cb) - 1) & 1);
        c.wait(x0);
        c.wait(x1);
        c.wait(x2);
        if (follow) {
            wgmma_wait<0>();
            c.release(px); c.release(py);
            named_sync(2 + wg, 256);
        }
        wgmma_fence();
        mma1(x0, 1);
        wgmma_commit();
        wgmma_wait<1>();
        if (!follow) { c.release(px); c.release(py); }
        wgmma_fence();
        mma1(x1, 1);
        mma1(x2, 1);
        wgmma_commit();
        named_arrive(3 - wg, 256);
        mbar_wait(bars + BAR_DEP, 0);
        mbar_wait(bars + BAR_EMPTY + fr.bo, fr.par ^ 1);
        c.wait(y0);
        c.wait(y1);
        wgmma_wait<0>();
        fence_regs(a1);
        OP(61);
        send(IntT<0>{}, addr(fr) + cw * 4096);
        send(IntT<1>{}, addr(fr) + cw * 4096 + 2048);
        named_sync(2 + wg, 256);
        wgmma_fence();
        mma2(x0, y0, 1);
        mma2(x1, y1, 1);
        wgmma_commit();
        OP(62);
        c.wait(y2);
        wgmma_fence();
        mma2(x2, y2, 1);
        wgmma_commit();
        if (!follow) named_arrive(3 - wg, 256);
        wgmma_wait<0>();
        fence_regs(a2);
        PROFG(188);
        PROF(4);
        send(IntT<2>{}, addr(x0) + cw * 2048);
        send(IntT<3>{}, addr(x1) + cw * 2048);
        send(IntT<4>{}, addr(x2) + cw * 2048);
        PROF(5);
        asm volatile("cp.async.bulk.commit_group;\ncp.async.bulk.wait_group.read 0;" ::: "memory");
    }
    PROF(6);
}

__device__ __forceinline__ void select_top8(uint32_t bars, int lane) {
    uint32_t last = 0xffffffffu;
#pragma unroll 1
    for (int rnd = 0; rnd < 8; rnd++) {
        uint32_t mx = 0;
#pragma unroll 4
        for (int i = 0; i < 16; i++) {
            const float4 v = __ldcg(reinterpret_cast<const float4*>(g_r) + lane + 32 * i);
#pragma unroll
            for (int e = 0; e < 4; e++) {
                uint32_t b = __float_as_uint((&v.x)[e] + 0.f);
                b = (b & 0x80000000u) ? ~b : (b | 0x80000000u);
                const uint32_t key = (b & 0xffff0000u) | (uint32_t)(0xfffe - (4 * (lane + 32 * i) + e));
                if (key < last) mx = max(mx, key);
            }
        }
        last = __reduce_max_sync(0xffffffffu, mx);
        asm volatile("st.shared.u32 [%0], %1;" ::"r"(bars + MAIL_OFF + rnd * 4), "r"(0xfffe - (last & 0xffffu)) : "memory");
    }
    __syncwarp();
    if (lane == 0) mbar_arrive(bars + BAR_DEP + 9 * 8);
    __syncwarp();
}

__device__ __forceinline__ void mod_ffn(const Params& P, uint32_t smem, int mc  , int wg) {
    const int tid = threadIdx.x - 128, lane = tid & 31, cw = tid >> 5, q = lane & 3, lr = lane >> 2;
    const uint32_t xs = smem + 6 * SLOT, hs = xs + 10240 + wg * 1024, sidx = smem + NSLOT * SLOT + MAIL_OFF, rbar = xs + 13312 + wg * 32;
    const uint32_t ring = smem + wg * 3 * SLOT;
    const int f0 = mc + 4 * wg, nunit = ((34 - f0) >> 3) * 8;
    const bool lead = __reduce_or_sync(0xffffffffu, cw & 3) == 0;
    auto lds = [](uint32_t a) { uint32_t v; asm volatile("ld.shared.u32 %0, [%1];" : "=r"(v) : "r"(a) : "memory"); return v; };
    auto issue = [&](int u, int st) {
        if (lead && u < nunit) {
            const int fc = (f0 + (u & ~7)) * 64, k = u & 7;
            const uint32_t dst = ring + st * SLOT, bar = rbar + st * 8;
            w_expect_tx(bar, k == 7 ? 16384 : SLOT);
            if (k < 5) {
                w_tma_load_stream(dst, &P.wg, fc, k * 128, bar);
                w_tma_load_stream(dst + 16384, &P.wu, fc, k * 128, bar);
            } else {
#pragma unroll 1
                for (int b = 0; b < (k == 7 ? 2 : 4); b++) w_tma_load_stream(dst + b * 8192, &P.wd, (4 * (k - 5) + b) * 64, fc, bar);
            }
        }
    };
    if ((tid & 127) == 0) {
        mbar_init(rbar, 1); mbar_init(rbar + 8, 1); mbar_init(rbar + 16, 1);
        asm volatile("fence.mbarrier_init.release.cluster;" ::: "memory");
    }
    mbar_wait(smem + NSLOT * SLOT + BAR_DEP + 9 * 8, 0);
    asm volatile("fence.proxy.async.shared::cta;" ::: "memory");
    named_sync(1, 256);
    PROF(1);
#pragma unroll 1
    for (int u = 0; u < 3; u++) issue(u, u);
    {
        const int t = lds(sidx + cw * 4);
        const uint4* src = reinterpret_cast<const uint4*>(g_xn + perm_row(t) * DM);
#pragma unroll
        for (int i = 0; i < 3; i++) {
            const int ch = lane + 32 * i;
            if (ch < 80) {
                const uint4 v = __ldcg(src + ch);
                asm volatile("st.shared.v4.b32 [%0], {%1, %2, %3, %4};" ::"r"(xs + (ch >> 3) * 1024 + cw * 128 + ((ch ^ cw) & 7) * 16), "r"(v.x), "r"(v.y), "r"(v.z), "r"(v.w) : "memory");
            }
        }
        asm volatile("fence.proxy.async.shared::cta;" ::: "memory");
    }
    named_sync(1, 256);
    PROF(3);
    float y[10][4];
#pragma unroll
    for (int i = 0; i < 10; i++) { y[i][0] = 0.f; y[i][1] = 0.f; y[i][2] = 0.f; y[i][3] = 0.f; }
    int st = 0, ph = 0, u = 0;
    auto begin = [&]() { mbar_wait(rbar + st * 8, ph); wgmma_fence(); return (((ring + st * SLOT) & 0x3FFFF) >> 4) + lbo(16); };
    auto end = [&]() {
        wgmma_commit();
        wgmma_wait<0>();
        named_sync(4 + wg, 128);
        issue(u + 3, st);
        u++;
        ph ^= st == 2;
        st = (st == 2) ? 0 : st + 1;
    };
    const uint32_t dx = ((xs & 0x3FFFF) >> 4) + lbo(16), dh = ((hs & 0x3FFFF) >> 4) + lbo(16);
#pragma unroll 1
    while (u < nunit) {
        float g[4], v[4];
#pragma unroll 1
        for (int kc = 0; kc < 5; kc++) {
            const uint32_t da = begin();
#pragma unroll
            for (int k = 0; k < 8; k++) {
                const uint32_t db = dx + (2 * kc + (k >> 2)) * 64 + (k & 3) * 2;
                wgmma_ss_n8<1, 0>(g, da + k * 128, db, k ? 1 : kc);
                wgmma_ss_n8<1, 0>(v, da + 1024 + k * 128, db, k ? 1 : kc);
            }
            end();
        }
        fence_regs(g); fence_regs(v);
#pragma unroll
        for (int e = 0; e < 4; e++) {
            const float gp = round_bf16(g[e]);
            const float hv = round_bf16(__fdividef(gp, 1.0f + __expf(fminf(-gp, 80.f)))) * round_bf16(v[e]);
            const int tok = 2 * q + (e & 1), ch = 2 * (cw & 3) + (e >> 1);
            asm volatile("st.shared.u16 [%0], %1;" ::"r"(hs + tok * 128 + ((ch ^ tok) * 16) + lr * 2), "h"((unsigned short)pack_bf16(hv, 0.f)) : "memory");
        }
        asm volatile("fence.proxy.async.shared::cta;" ::: "memory");
        named_sync(4 + wg, 128);
#pragma unroll
        for (int k3 = 0; k3 < 3; k3++) {
            const uint32_t da = begin();
#pragma unroll
            for (int b = 0; b < (k3 == 2 ? 2 : 4); b++)
#pragma unroll
                for (int k = 0; k < 4; k++) wgmma_ss_n8<1, 0>(y[4 * k3 + b], da + b * 512 + k * 128, dh + k * 2, 1);
            end();
        }
    }
    PROF(5);
#pragma unroll
    for (int i = 0; i < 10; i++) {
        fence_regs(y[i]);
#pragma unroll
        for (int e = 0; e < 4; e++) g_ypart[((mc * 2 + wg) * 8 + 2 * q + (e & 1)) * DM + 64 * i + 16 * (cw & 3) + lr + 8 * (e >> 1)] = y[i][e];
    }
    named_sync(1, 256);
    if (tid == 0) {
        flag_add(F_MODP);
        flag_wait<100>(F_MODP, 4u * (lds(smem + NSLOT * SLOT + MISC_OFF) + 1));
    }
    named_sync(1, 256);
    PROF(6);
    {
        const int c = 2 * mc + wg, t = lds(sidx + c * 4);
        const float rs = round_bf16(__fdividef(1.0f, 1.0f + __expf(fminf(-__ldcg(g_r + t), 80.f))));
#pragma unroll
        for (int i = 0; i < 3; i++) {
            const int c2 = (tid & 127) + 128 * i;
            if (c2 < DM / 2) {
                float y0 = 0.f, y1 = 0.f;
#pragma unroll
                for (int k = 0; k < 8; k++) {
                    const float2 v = __ldcg(reinterpret_cast<const float2*>(g_ypart + (k * 8 + c) * DM) + c2);
                    y0 += v.x; y1 += v.y;
                }
                asm volatile("red.relaxed.gpu.global.add.noftz.bf16x2 [%0], %1;" ::"l"(P.out + t * DM + 2 * c2), "r"(pack_bf16(round_bf16(y0) * rs, round_bf16(y1) * rs)) : "memory");
            }
        }
    }
    PROF(7);
}

__global__ void __cluster_dims__(2, 1, 1) __launch_bounds__(384, 1) fused_kernel(const __grid_constant__ Params P) {
    extern __shared__ __align__(1024) uint8_t smem_raw[];
    const uint32_t smem = (smem_u32(smem_raw) + 1023u) & ~1023u;
    const uint32_t bars = smem + NSLOT * SLOT;
    const int wgi = __reduce_or_sync(0xffffffffu, threadIdx.x >> 7);
    const int cl = blockIdx.x >> 1, rank = blockIdx.x & 1, ca = cl & 7, cb = cl >> 3;
    PROFG(30);
    PROF(0);
    if (threadIdx.x == 64) {
        const uint32_t fa = bars + BAR_FULL + slot_a(0) * 8, fw = bars + BAR_FULL + slot_w(0) * 8;
        mbar_init(fa, 1); mbar_init(fw, 1);
        asm volatile("fence.mbarrier_init.release.cluster;" ::: "memory");
        if (cb < 8) {
            mbar_expect_tx(fa, SLOT);
            mbar_expect_tx(fw, SLOT);
            tma_load(smem + slot_a(0) * SLOT, &P.ckv, 0, (2 * ca + rank) * 128, fa);
            tma_load(smem + slot_w(0) * SLOT, &P.wuk, (cb + 8 * kv_round(0)) * 128, 0, fw);
            tma_load(smem + slot_w(0) * SLOT + 16384, &P.wuk, (cb + 8 * kv_round(0)) * 128 + 64, 0, fw);
            tma_load(smem + slot_a(0) * SLOT + 16384, &P.ckv, 64, (2 * ca + rank) * 128, fa);
        }
    } else if (threadIdx.x == 0) {
#pragma unroll
        for (int i = 0; i < NSLOT; i++) {
            if (i != slot_a(0) && i != slot_w(0)) mbar_init(bars + BAR_FULL + i * 8, 1);
            mbar_init(bars + BAR_EMPTY + i * 8, 16);
        }
        if (cb < 8) {
            mbar_arrive(bars + BAR_FULL + 16);
            asm volatile("mbarrier.arrive.shared::cta.b64 _, [%0], 16;" ::"r"(bars + BAR_EMPTY + 16) : "memory");
        }
        asm volatile("fence.mbarrier_init.release.cluster;" ::: "memory");
        PROF(24);
    } else if (threadIdx.x == 32) {
#pragma unroll
        for (int i = 0; i < 18; i++) mbar_init(bars + BAR_SIG + i * 8, 4);
#pragma unroll
        for (int i = 0; i < 18; i++) mbar_init(bars + BAR_DEP + i * 8, 1);
        asm volatile("fence.mbarrier_init.release.cluster;" ::: "memory");
    }
    __syncthreads();
    PROF(29);
    cluster_arrive();
    if (wgi > 0) {
        asm volatile("setmaxnreg.inc.sync.aligned.u32 232;");
        consumer(P, smem, bars, ca, cb, rank, wgi - 1);
        PROFG(31);
        PROFDUMP();
    } else {
        asm volatile("setmaxnreg.dec.sync.aligned.u32 40;");
        const int w = __reduce_or_sync(0xffffffffu, threadIdx.x >> 5), lane = threadIdx.x & 31;
        if (threadIdx.x == 32) {
            prefetch_map(&P.wuv); prefetch_map(&P.xn); prefetch_map(&P.wq); prefetch_map(&P.kv); prefetch_map(&P.ctx); prefetch_map(&P.wo); prefetch_map(&P.outm);
        }
        __syncwarp();
        cluster_wait();
        PROF(27);
        {
            if (w == 0) {
                producer(P, smem, bars, ca, cb, rank);
            } else if (w < 3 && lane == 0) {
                const int wg = w - 1;
#pragma unroll 1
                for (int i = (cb == 8); i < (cb == 8 ? 9 : 5 + n_items(ca, cb)); i++) {
                    const int nb = wg + (LNOFF + 7 - 4) / 8;
                    const int e = (cb == 8) ? i : (i < nb) ? i + 1 : (i == nb) ? 0 : i;
                    mbar_wait_sleep(bars + BAR_SIG + (wg * 9 + e) * 8, 0);
                    int f;
                    if (cb == 8) f = F_CTX + (2 + ca) * 16 + rank;
                    else if (e == 0) {
                        f = F_LN;
                        if ((ca & 3) == 0 && rank == 0 && wg == 0) g_flags[(F_POOL + out_p(ca, cb) * 2 + (ca >> 2)) * 8] = 8;
                    }
                    else if (e < 5) f = F_KV + cb + 8 * kv_round(e - 1);
                    else { const int rd = item_rd(ca, cb, e - 5); f = F_CTX + rd * 16 + item_p(ca, rd) * 2 + rank; }
                    flag_add(f);
                }
            } else if (lane == 0) {
                const uint32_t epoch = read_epoch();
                asm volatile("st.shared.u32 [%0], %1;" ::"r"(bars + MISC_OFF), "r"(epoch) : "memory");
#pragma unroll 1
                for (int i = 0; i < 9; i++) {
                    const int e = (cb == 8 && i < 2) ? 1 - i : i;
                    int f;
                    uint32_t n;
                    if (e == 0) { f = F_LN; n = 256; }
                    else if (cb == 8) { f = F_KV + item_h(cb, 2 + ca, e - 1); n = 32; }
                    else if (e < 5) { f = F_KV + cb + 8 * (e - 1); n = 32; }
                    else { f = F_CTX + (e - 5) * 16 + out_p(ca, cb) * 2 + rank; n = 16; }
                    flag_wait<200>(f, n * (epoch + 1));
                    fence_proxy_async();
                    mbar_arrive(bars + BAR_DEP + e * 8);
                }
            }
        }
        if (cb == 8) {
            __syncwarp();
            if (w == 3) select_top8(bars, lane);
            cluster_arrive();
            cluster_wait();
        }
        PROFG(31);
        PROFDUMP();
    }
}

typedef CUresult (*EncodeFn)(CUtensorMap*, CUtensorMapDataType, cuuint32_t, void*, const cuuint64_t*, const cuuint64_t*, const cuuint32_t*,
                             const cuuint32_t*, CUtensorMapInterleave, CUtensorMapSwizzle, CUtensorMapL2promotion, CUtensorMapFloatOOBfill);

void make_map(EncodeFn fn, CUtensorMap* m, const void* ptr, uint64_t rows, uint64_t cols, uint32_t box_rows) {
    cuuint64_t dims[2] = {cols, rows};
    cuuint64_t strides[1] = {cols * 2};
    cuuint32_t box[2] = {64, box_rows};
    cuuint32_t es[2] = {1, 1};
    fn(m, CU_TENSOR_MAP_DATA_TYPE_BFLOAT16, 2, const_cast<void*>(ptr), dims, strides, box, es, CU_TENSOR_MAP_INTERLEAVE_NONE,
       CU_TENSOR_MAP_SWIZZLE_128B, CU_TENSOR_MAP_L2_PROMOTION_L2_128B, CU_TENSOR_MAP_FLOAT_OOB_FILL_NONE);
}

}

extern "C" void kernel_launch(void* const* d_in, const int* in_sizes, int n_in, void* d_out, int out_size) {
    (void)in_sizes; (void)n_in; (void)out_size;
    void* fnp = nullptr;
    cudaDriverEntryPointQueryResult qr;
    cudaGetDriverEntryPoint("cuTensorMapEncodeTiled", &fnp, cudaEnableDefault, &qr);
    EncodeFn fn = (EncodeFn)fnp;
    void *xn, *kv, *ctx;
    cudaGetSymbolAddress(&xn, g_xn);
    cudaGetSymbolAddress(&kv, g_kv);
    cudaGetSymbolAddress(&ctx, g_ctx);
    Params P;
    make_map(fn, &P.ckv, d_in[1], SEQ, DC, 128);
    make_map(fn, &P.wq, d_in[2], DM, NH * HD, 64);
    make_map(fn, &P.wuk, d_in[3], DC, NH * HD, 128);
    make_map(fn, &P.wuv, d_in[4], DC, NH * HD, 128);
    make_map(fn, &P.wo, d_in[5], NH * HD, DM, 32);
    make_map(fn, &P.xn, xn, SEQ, DM, 128);
    make_map(fn, &P.kv, kv, NH * 16 * 2 * 128, 128, 128);
    make_map(fn, &P.ctx, ctx, NH * SEQ, HD, 128);
    P.x = (const __nv_bfloat16*)d_in[0];
    P.wr = (const __nv_bfloat16*)d_in[7];
    make_map(fn, &P.wg, d_in[8], DM, FF, 128);
    make_map(fn, &P.wu, d_in[9], DM, FF, 128);
    make_map(fn, &P.wd, d_in[10], FF, DM, 64);
    make_map(fn, &P.outm, d_out, SEQ, DM, 16);
    P.out = (__nv_bfloat16*)d_out;
    cudaFuncSetAttribute(fused_kernel, cudaFuncAttributeMaxDynamicSharedMemorySize, SMEM_BYTES);
    fused_kernel<<<NCTA, 384, SMEM_BYTES>>>(P);
}
```
